```python
import torch

def _softmax(x, axis=-1):
    return torch.softmax(x, dim=axis)

def _gelu(x):
    return torch.nn.functional.gelu(x, approximate='tanh')

def _silu(x):
    return torch.nn.functional.silu(x)

def _sigmoid(x):
    return torch.sigmoid(x)

def _layernorm(x, axis=-1, eps=1e-05):
    m = x.mean(dim=axis, keepdim=True)
    v = x.var(dim=axis, keepdim=True, unbiased=False)
    return (x - m) / torch.sqrt(v + eps)

def _scatter_add(tgt, idx, src, axis=0):
    return tgt.clone().index_add_(axis, idx, src)

def _segment_sum(src, seg, n):
    out = torch.zeros((n,) + src.shape[1:], dtype=src.dtype)
    return out.index_add_(0, seg, src)

def _pad(x, pw):
    flat = tuple((v for pair in reversed(pw) for v in pair))
    return torch.nn.functional.pad(x, flat)
kernel_name = 'interleave_layers__memory_aug_recurrent_mem_tr__spectral_gfnet__prompt'

def setup_inputs():

    _w = lambda a: (lambda t: t.to(torch.bfloat16) if t.is_floating_point() else t)(torch.as_tensor(a))

    def _A_setup():
        B, S, Dm = (1, 2048, 640)
        H, Dh = (32, 128)
        M, seg = (8, 32)
        seg = min(seg, S)
        S = S // seg * seg
        return {'x': _w((lambda *s: torch.randn(*s, dtype=torch.bfloat16) * 0.05)(B, S, Dm)), 'mem0': _w((lambda *s: torch.randn(*s, dtype=torch.bfloat16) * 0.2)(B, M, Dm)), 'Wq': _w((lambda *s: torch.randn(*s, dtype=torch.bfloat16) * 1.6)(Dm, H, Dh) * Dm ** (-0.5)), 'Wk': _w((lambda *s: torch.randn(*s, dtype=torch.bfloat16) * 1.6)(Dm, H, Dh) * Dm ** (-0.5)), 'Wv': _w((lambda *s: torch.randn(*s, dtype=torch.bfloat16) * 0.2)(Dm, H, Dh) * Dm ** (-0.5)), 'Wo': _w((lambda *s: torch.randn(*s, dtype=torch.bfloat16) * 0.2)(H, Dh, Dm) * (H * Dh) ** (-0.5)), 'seg_len': seg}
    _A_in = _A_setup()

    def _B_setup():
        B, S, D = (1, 2048, 640)
        Df = D // 2 + 1
        return {'x': _w((lambda *s: torch.randn(*s, dtype=torch.bfloat16) * 0.05)(B, S, D)), 'w_r': _w((lambda *s: torch.randn(*s, dtype=torch.bfloat16) * 0.4)(S, Df) * 0.02), 'w_i': _w((lambda *s: torch.randn(*s, dtype=torch.bfloat16) * 0.4)(S, Df) * 0.02)}
    _B_in = _B_setup()
    return {'A_x': _A_in['x'], 'A_mem0': _A_in['mem0'], 'A_Wq': _A_in['Wq'], 'A_Wk': _A_in['Wk'], 'A_Wv': _A_in['Wv'], 'A_Wo': _A_in['Wo'], 'A_seg_len': _A_in['seg_len'], 'B_x': _B_in['x'], 'B_w_r': _B_in['w_r'], 'B_w_i': _B_in['w_i']}

def reference(A_x, A_mem0, A_Wq, A_Wk, A_Wv, A_Wo, A_seg_len, B_x, B_w_r, B_w_i):

    def _A_ref(x, mem0, Wq, Wk, Wv, Wo, seg_len):
        B, S, Dm = x.shape
        H, Dh = (Wq.shape[1], Wq.shape[2])
        M = mem0.shape[1]
        scale = Dh ** (-0.5)
        n_seg = S // seg_len
        L = M + seg_len
        idx = torch.arange(L)
        mask = (idx[:, None] < M) | (idx[:, None] >= idx[None, :])
        mem = mem0
        outs = []
        for s in range(n_seg):
            xs = x[:, s * seg_len:(s + 1) * seg_len, :].clone()
            h = torch.concatenate([mem, xs], axis=1)
            q = torch.einsum('btd,dhe->bhte', h, Wq)
            k = torch.einsum('btd,dhe->bhte', h, Wk)
            v = torch.einsum('btd,dhe->bhte', h, Wv)
            scores = torch.einsum('bhqe,bhke->bhqk', q, k) * scale
            scores = torch.where(mask[None, None], scores, -1000000000.0)
            p = _softmax(scores, axis=-1)
            o = torch.einsum('bhqk,bhke->bhqe', p, v)
            o = torch.einsum('bhte,hed->btd', o, Wo)
            mem = o[:, :M, :].clone()
            outs.append(o[:, M:, :])
        return torch.concatenate(outs, axis=1)

    def _B_ref(x, w_r, w_i):
        B, S, D = x.shape
        X = (lambda x, axes=(-2, -1): torch.fft.rfft2(x.float(), dim=axes))(x, axes=(-2, -1))
        W = w_r + 1j * w_i
        X = X * W
        y = (lambda x, s, axes=(-2, -1): torch.fft.irfft2(x, s=s, dim=axes).to(torch.bfloat16))(X, (S, D), axes=(-2, -1))
        return y
    x = A_x
    x = x + _A_ref(_layernorm(x, axis=-1), A_mem0, A_Wq, A_Wk, A_Wv, A_Wo, A_seg_len)
    x = x + _B_ref(_layernorm(x, axis=-1), B_w_r, B_w_i)
    x = x + _A_ref(_layernorm(x, axis=-1), A_mem0, A_Wq, A_Wk, A_Wv, A_Wo, A_seg_len)
    x = x + _B_ref(_layernorm(x, axis=-1), B_w_r, B_w_i)
    return x
```

```cpp
#include <cuda_runtime.h>
#include <cuda_bf16.h>
#include <stdint.h>

#define DEV __device__ __forceinline__
typedef unsigned long long u64;
typedef __nv_bfloat16 bf16;

namespace {

constexpr int S_ = 2048, D_ = 640, H_ = 32, E_ = 128, NSEG = 64;

__device__ __align__(1024) unsigned char g_xn[S_ * D_ * 2];
__device__ __align__(1024) unsigned char g_o[S_ * H_ * E_ * 2];
constexpr int ACC_LAYER = 32 * 5120;
__device__ __align__(4096) u64 g_acc[2 * ACC_LAYER];
__device__ __align__(16) float g_nrm[256];
__device__ __align__(1024) unsigned char g_wop[H_ * E_ * D_ * 2];
__device__ __align__(1024) bf16 g_x1[S_ * D_];
__device__ __align__(1024) bf16 g_x2[S_ * D_];
constexpr int NCOL = 321;
__device__ __align__(1024) unsigned char g_z[NCOL * 8192];
__device__ __align__(1024) unsigned char g_wt[NCOL * 8192];
__device__ __align__(1024) uint4 g_f128[2 * 8 * 256];
__device__ __align__(1024) uint4 g_f64[2 * 4 * 128];
__device__ __align__(1024) bf16 g_g32[2 * 4096];

DEV uint32_t s2u(const void* p) { return (uint32_t)__cvta_generic_to_shared(p); }
DEV uint32_t clk() { uint32_t c; asm volatile("mov.u32 %0,%%clock;" : "=r"(c)::"memory"); return c; }
DEV uint32_t mapa(uint32_t a, uint32_t r) { uint32_t o; asm("mapa.shared::cluster.u32 %0,%1,%2;" : "=r"(o) : "r"(a), "r"(r)); return o; }
DEV void mbar_init(uint32_t b, uint32_t n) { asm volatile("mbarrier.init.shared::cta.b64 [%0],%1;" ::"r"(b), "r"(n) : "memory"); }
DEV bool mbar_try(uint32_t b, uint32_t par) {
    uint32_t ok;
    asm volatile("{.reg .pred p; mbarrier.try_wait.parity.shared::cta.b64 p,[%1],%2; selp.u32 %0,1,0,p;}" : "=r"(ok) : "r"(b), "r"(par) : "memory");
    return ok;
}
constexpr uint32_t SPIN_LIMIT = 1u << 18;
DEV void mbar_wait(uint32_t b, uint32_t par) {
    uint32_t n = 0;
    while (!mbar_try(b, par)) if (++n > SPIN_LIMIT) __trap();
}
DEV uint32_t opaque(uint32_t x) { return __shfl_xor_sync(~0u, x, 0); }
#define SFENCE() asm volatile("{.reg .pred p; setp.ne.u32 p,%1,0; @p mov.u32 %0,%%clock;}" : "+r"(sfd) : "r"((uint32_t)never) : "memory")
DEV void mbar_arrive(uint32_t b) { asm volatile("mbarrier.arrive.shared::cta.b64 _,[%0];" ::"r"(b) : "memory"); }
DEV void mbar_arrive_remote(uint32_t b) { asm volatile("mbarrier.arrive.shared::cluster.b64 _,[%0];" ::"r"(b) : "memory"); }
DEV void mbar_expect(uint32_t b, uint32_t tx) { asm volatile("mbarrier.arrive.expect_tx.shared::cta.b64 _,[%0],%1;" ::"r"(b), "r"(tx) : "memory"); }
DEV void bar_sync(int id, int n) { asm volatile("bar.sync %0,%1;" ::"r"(id), "r"(n) : "memory"); }
DEV void bar_arrive(int id, int n) { asm volatile("bar.arrive %0,%1;" ::"r"(id), "r"(n) : "memory"); }
DEV void st_async1(uint32_t a, uint32_t x, uint32_t b) {
    asm volatile("st.async.shared::cluster.mbarrier::complete_tx::bytes.u32 [%0],%1,[%2];" ::"r"(a), "r"(x), "r"(b) : "memory");
}
DEV void st_async2(uint32_t a, uint32_t x, uint32_t y, uint32_t b) {
    asm volatile("st.async.shared::cluster.mbarrier::complete_tx::bytes.v2.u32 [%0],{%1,%2},[%3];" ::"r"(a), "r"(x), "r"(y), "r"(b) : "memory");
}
DEV void st_async4(uint32_t a, uint32_t x, uint32_t y, uint32_t z, uint32_t w, uint32_t b) {
    asm volatile("st.async.shared::cluster.mbarrier::complete_tx::bytes.v4.u32 [%0],{%1,%2,%3,%4},[%5];" ::"r"(a), "r"(x), "r"(y), "r"(z), "r"(w), "r"(b) : "memory");
}
DEV void bulk_g2s(uint32_t dst, const void* src, uint32_t bytes, uint32_t b) {
    asm volatile("cp.async.bulk.shared::cluster.global.mbarrier::complete_tx::bytes [%0],[%1],%2,[%3];" ::"r"(dst), "l"(src), "r"(bytes), "r"(b) : "memory");
}
DEV void bulk_s2s(uint32_t dst, uint32_t src, uint32_t bytes, uint32_t b) {
    asm volatile("cp.async.bulk.shared::cluster.shared::cta.mbarrier::complete_tx::bytes [%0],[%1],%2,[%3];" ::"r"(dst), "r"(src), "r"(bytes), "r"(b) : "memory");
}
DEV void bulk_s2g(void* dst, uint32_t src, uint32_t bytes) {
    asm volatile("cp.async.bulk.global.shared::cta.bulk_group [%0],[%1],%2;" ::"l"(dst), "r"(src), "r"(bytes) : "memory");
}
DEV void fence_async() { asm volatile("fence.proxy.async.shared::cta;" ::: "memory"); }
DEV uint32_t pack2(float lo, float hi) { uint32_t r; asm("cvt.rn.bf16x2.f32 %0,%1,%2;" : "=r"(r) : "f"(hi), "f"(lo)); return r; }
DEV uint32_t prmt(uint32_t a, uint32_t b, uint32_t s) { uint32_t r; asm("prmt.b32 %0,%1,%2,%3;" : "=r"(r) : "r"(a), "r"(b), "r"(s)); return r; }
DEV float ex2(float x) { float r; asm("ex2.approx.ftz.f32 %0,%1;" : "=f"(r) : "f"(x)); return r; }
DEV float rcp(float x) { float r; asm("rcp.approx.ftz.f32 %0,%1;" : "=f"(r) : "f"(x)); return r; }
DEV void lds128(uint32_t* r, uint32_t a) { asm volatile("ld.shared.v4.u32 {%0,%1,%2,%3},[%4];" : "=r"(r[0]), "=r"(r[1]), "=r"(r[2]), "=r"(r[3]) : "r"(a) : "memory"); }
DEV void lds64(uint32_t* r, uint32_t a) { asm volatile("ld.shared.v2.u32 {%0,%1},[%2];" : "=r"(r[0]), "=r"(r[1]) : "r"(a) : "memory"); }
DEV void lds64f(float& x, float& y, uint32_t a) { asm volatile("ld.shared.v2.f32 {%0,%1},[%2];" : "=f"(x), "=f"(y) : "r"(a) : "memory"); }
DEV void lds128f(float* r, uint32_t a) { asm volatile("ld.shared.v4.f32 {%0,%1,%2,%3},[%4];" : "=f"(r[0]), "=f"(r[1]), "=f"(r[2]), "=f"(r[3]) : "r"(a) : "memory"); }
DEV void sts128(uint32_t a, uint32_t x, uint32_t y, uint32_t z, uint32_t w) { asm volatile("st.shared.v4.u32 [%0],{%1,%2,%3,%4};" ::"r"(a), "r"(x), "r"(y), "r"(z), "r"(w) : "memory"); }
DEV void sts64(uint32_t a, uint32_t x, uint32_t y) { asm volatile("st.shared.v2.u32 [%0],{%1,%2};" ::"r"(a), "r"(x), "r"(y) : "memory"); }
DEV void sts32(uint32_t a, uint32_t x) { asm volatile("st.shared.u32 [%0],%1;" ::"r"(a), "r"(x) : "memory"); }
DEV void ldsm4(uint32_t* r, uint32_t a) { asm volatile("ldmatrix.sync.aligned.m8n8.x4.shared.b16 {%0,%1,%2,%3},[%4];" : "=r"(r[0]), "=r"(r[1]), "=r"(r[2]), "=r"(r[3]) : "r"(a) : "memory"); }
DEV void stsm4t(uint32_t a, uint32_t x, uint32_t y, uint32_t z, uint32_t w) { asm volatile("stmatrix.sync.aligned.m8n8.x4.trans.shared.b16 [%0],{%1,%2,%3,%4};" ::"r"(a), "r"(x), "r"(y), "r"(z), "r"(w) : "memory"); }
DEV void stsm4(uint32_t a, uint32_t x, uint32_t y, uint32_t z, uint32_t w) { asm volatile("stmatrix.sync.aligned.m8n8.x4.shared.b16 [%0],{%1,%2,%3,%4};" ::"r"(a), "r"(x), "r"(y), "r"(z), "r"(w) : "memory"); }
DEV void stsm2(uint32_t a, uint32_t x, uint32_t y) { asm volatile("stmatrix.sync.aligned.m8n8.x2.shared.b16 [%0],{%1,%2};" ::"r"(a), "r"(x), "r"(y) : "memory"); }
DEV void stsm2t(uint32_t a, uint32_t x, uint32_t y) { asm volatile("stmatrix.sync.aligned.m8n8.x2.trans.shared.b16 [%0],{%1,%2};" ::"r"(a), "r"(x), "r"(y) : "memory"); }
DEV void mma16(float* d, uint32_t a0, uint32_t a1, uint32_t a2, uint32_t a3, uint32_t b0, uint32_t b1) {
    asm volatile("mma.sync.aligned.m16n8k16.row.col.f32.bf16.bf16.f32 {%0,%1,%2,%3},{%4,%5,%6,%7},{%8,%9},{%0,%1,%2,%3};"
                 : "+f"(d[0]), "+f"(d[1]), "+f"(d[2]), "+f"(d[3]) : "r"(a0), "r"(a1), "r"(a2), "r"(a3), "r"(b0), "r"(b1));
}
DEV void mma8(float* d, uint32_t a0, uint32_t a1, uint32_t b0) {
    asm volatile("mma.sync.aligned.m16n8k8.row.col.f32.bf16.bf16.f32 {%0,%1,%2,%3},{%4,%5},{%6},{%0,%1,%2,%3};"
                 : "+f"(d[0]), "+f"(d[1]), "+f"(d[2]), "+f"(d[3]) : "r"(a0), "r"(a1), "r"(b0));
}
DEV u64 mkdesc(uint32_t a, uint32_t lbo, uint32_t sbo) { return (u64)((a & 0x3ffff) >> 4) | ((u64)(lbo >> 4) << 16) | ((u64)(sbo >> 4) << 32); }
DEV void wg_fence() { asm volatile("wgmma.fence.sync.aligned;" ::: "memory"); }
DEV void wg_commit() { asm volatile("wgmma.commit_group.sync.aligned;" ::: "memory"); }
template <int N> DEV void wg_wait() { asm volatile("wgmma.wait_group.sync.aligned %0;" ::"n"(N) : "memory"); }
template <int ACC> DEV void wgmma_n32_rs(float* d, const uint32_t* a, u64 desc) {
    asm volatile("wgmma.mma_async.sync.aligned.m64n32k16.f32.bf16.bf16 {%0,%1,%2,%3,%4,%5,%6,%7,%8,%9,%10,%11,%12,%13,%14,%15},{%16,%17,%18,%19},%20,%21,1,1,0;"
                 : "+f"(d[0]), "+f"(d[1]), "+f"(d[2]), "+f"(d[3]), "+f"(d[4]), "+f"(d[5]), "+f"(d[6]), "+f"(d[7]),
                   "+f"(d[8]), "+f"(d[9]), "+f"(d[10]), "+f"(d[11]), "+f"(d[12]), "+f"(d[13]), "+f"(d[14]), "+f"(d[15])
                 : "r"(a[0]), "r"(a[1]), "r"(a[2]), "r"(a[3]), "l"(desc), "n"(ACC));
}
template <int ACC> DEV void wgmma_n32_ss(float* d, u64 da, u64 desc) {
    asm volatile("wgmma.mma_async.sync.aligned.m64n32k16.f32.bf16.bf16 {%0,%1,%2,%3,%4,%5,%6,%7,%8,%9,%10,%11,%12,%13,%14,%15},%16,%17,%18,1,1,0,0;"
                 : "+f"(d[0]), "+f"(d[1]), "+f"(d[2]), "+f"(d[3]), "+f"(d[4]), "+f"(d[5]), "+f"(d[6]), "+f"(d[7]),
                   "+f"(d[8]), "+f"(d[9]), "+f"(d[10]), "+f"(d[11]), "+f"(d[12]), "+f"(d[13]), "+f"(d[14]), "+f"(d[15])
                 : "l"(da), "l"(desc), "n"(ACC));
}
template <int ACC> DEV void wgmma_n16_ss(float* d, u64 da, u64 desc) {
    asm volatile("wgmma.mma_async.sync.aligned.m64n16k16.f32.bf16.bf16 {%0,%1,%2,%3,%4,%5,%6,%7},%8,%9,%10,1,1,0,0;"
                 : "+f"(d[0]), "+f"(d[1]), "+f"(d[2]), "+f"(d[3]), "+f"(d[4]), "+f"(d[5]), "+f"(d[6]), "+f"(d[7])
                 : "l"(da), "l"(desc), "n"(ACC));
}
#define ACC8(o) "+f"(d[o]), "+f"(d[o + 1]), "+f"(d[o + 2]), "+f"(d[o + 3]), "+f"(d[o + 4]), "+f"(d[o + 5]), "+f"(d[o + 6]), "+f"(d[o + 7])
template <int ACC, int TB> DEV void wgmma_n64_rs(float* d, const uint32_t* a, u64 desc) {
    asm volatile("wgmma.mma_async.sync.aligned.m64n64k16.f32.bf16.bf16 {%0,%1,%2,%3,%4,%5,%6,%7,%8,%9,%10,%11,%12,%13,%14,%15,"
                 "%16,%17,%18,%19,%20,%21,%22,%23,%24,%25,%26,%27,%28,%29,%30,%31},{%32,%33,%34,%35},%36,%37,1,1,%38;"
                 : ACC8(0), ACC8(8), ACC8(16), ACC8(24) : "r"(a[0]), "r"(a[1]), "r"(a[2]), "r"(a[3]), "l"(desc), "n"(ACC), "n"(TB));
}
template <int ACC, int TB> DEV void wgmma_n80_rs(float* d, const uint32_t* a, u64 desc) {
    asm volatile("wgmma.mma_async.sync.aligned.m64n80k16.f32.bf16.bf16 {%0,%1,%2,%3,%4,%5,%6,%7,%8,%9,%10,%11,%12,%13,%14,%15,"
                 "%16,%17,%18,%19,%20,%21,%22,%23,%24,%25,%26,%27,%28,%29,%30,%31,%32,%33,%34,%35,%36,%37,%38,%39},{%40,%41,%42,%43},%44,%45,1,1,%46;"
                 : ACC8(0), ACC8(8), ACC8(16), ACC8(24), ACC8(32) : "r"(a[0]), "r"(a[1]), "r"(a[2]), "r"(a[3]), "l"(desc), "n"(ACC), "n"(TB));
}
template <int TB> DEV void wgmma_n80_ss(float* d, u64 da, u64 desc) {
    asm volatile("wgmma.mma_async.sync.aligned.m64n80k16.f32.bf16.bf16 {%0,%1,%2,%3,%4,%5,%6,%7,%8,%9,%10,%11,%12,%13,%14,%15,"
                 "%16,%17,%18,%19,%20,%21,%22,%23,%24,%25,%26,%27,%28,%29,%30,%31,%32,%33,%34,%35,%36,%37,%38,%39},%40,%41,1,1,1,0,%42;"
                 : ACC8(0), ACC8(8), ACC8(16), ACC8(24), ACC8(32) : "l"(da), "l"(desc), "n"(TB));
}
DEV void pdl_wait() { asm volatile("griddepcontrol.wait;" ::: "memory"); }
DEV void pdl_launch() { asm volatile("griddepcontrol.launch_dependents;" ::: "memory"); }
DEV uint32_t ldg32(const void* p) { uint32_t v; asm volatile("ld.global.nc.u32 %0,[%1];" : "=r"(v) : "l"(p)); return v; }
DEV void ld_acc(u64& a, u64& b, const void* p) {
    const uint32_t done = (uint32_t)a & (uint32_t)b & 32u;
    asm volatile("{.reg .pred p; setp.eq.u32 p,%3,0;\n"
                 "@p ld.relaxed.gpu.global.v2.u64 {%0,%1},[%2];}" : "+l"(a), "+l"(b) : "l"(p), "r"(done) : "memory");
}
DEV void ld_acc0(u64& a, u64& b, const void* p) {
    asm volatile("ld.relaxed.gpu.global.v2.u64 {%0,%1},[%2];" : "=l"(a), "=l"(b) : "l"(p) : "memory");
}
DEV uint32_t absmax2(uint32_t a, uint32_t b) { uint32_t r; asm("max.xorsign.abs.bf16x2 %0,%1,%2;" : "=r"(r) : "r"(a), "r"(b)); return r; }
DEV float lds32f(uint32_t a) { float x; asm volatile("ld.shared.f32 %0,[%1];" : "=f"(x) : "r"(a) : "memory"); return x; }
DEV void red_add64(u64* p, uint32_t lo, uint32_t hi) {
    asm volatile("{.reg .b64 v; mov.b64 v,{%1,%2}; red.relaxed.gpu.global.add.u64 [%0],v;}" ::"l"(p), "r"(lo), "r"(hi) : "memory");
}
DEV float bf_round(float x) { return __bfloat162float(__float2bfloat16_rn(x)); }
DEV float bf_lo(uint32_t u) { return __uint_as_float(u << 16); }
DEV float bf_hi(uint32_t u) { return __uint_as_float(u & 0xffff0000u); }

#define PROFT(i)

DEV void ln_row(float (&v)[3][8], int lane) {
    float s = 0.f;
#pragma unroll
    for (int c = 0; c < 3; c++)
#pragma unroll
        for (int j = 0; j < 8; j++) s += v[c][j];
#pragma unroll
    for (int o = 16; o; o >>= 1) s += __shfl_xor_sync(~0u, s, o);
    float mean = s * (1.f / D_), q = 0.f;
#pragma unroll
    for (int c = 0; c < 3; c++)
        if (c < 2 || lane < 16)
#pragma unroll
            for (int j = 0; j < 8; j++) { float d = v[c][j] - mean; q += d * d; }
#pragma unroll
    for (int o = 16; o; o >>= 1) q += __shfl_xor_sync(~0u, q, o);
    float mb = bf_round(mean);
    float sd = bf_round(sqrtf(bf_round(bf_round(q * (1.f / D_)) + 1e-5f)));
#pragma unroll
    for (int c = 0; c < 3; c++)
#pragma unroll
        for (int j = 0; j < 8; j++) v[c][j] = bf_round(v[c][j] - mb) / sd;
}

__global__ void __launch_bounds__(512) prep_kernel(const bf16* __restrict__ x, const bf16* __restrict__ Wv, const bf16* __restrict__ Wo) {
    __shared__ float red[32];
    const int tid = threadIdx.x, lane = tid & 31, warp = tid >> 5, b = blockIdx.x;
    {
        int row = b * 16 + warp;
        float v[3][8];
#pragma unroll
        for (int c = 0; c < 3; c++) {
            uint4 u = make_uint4(0, 0, 0, 0);
            if (c < 2 || lane < 16) u = *(const uint4*)(x + row * D_ + (c * 32 + lane) * 8);
            v[c][0] = bf_lo(u.x); v[c][1] = bf_hi(u.x); v[c][2] = bf_lo(u.y); v[c][3] = bf_hi(u.y);
            v[c][4] = bf_lo(u.z); v[c][5] = bf_hi(u.z); v[c][6] = bf_lo(u.w); v[c][7] = bf_hi(u.w);
        }
        ln_row(v, lane);
#pragma unroll
        for (int c = 0; c < 3; c++)
            if (c < 2 || lane < 16)
                *(uint4*)(g_xn + (row >> 5) * 40960 + (c * 32 + lane) * 512 + (row & 31) * 16) =
                    make_uint4(pack2(v[c][0], v[c][1]), pack2(v[c][2], v[c][3]), pack2(v[c][4], v[c][5]), pack2(v[c][6], v[c][7]));
    }
    for (int i = b * 512 + tid; i < ACC_LAYER; i += 128 * 512) ((uint4*)g_acc)[i] = make_uint4(0, 0, 0, 0);
    float sv = 0.f;
#pragma unroll
    for (int i = 0; i < 5; i++) {
        uint4 u = *(const uint4*)(Wv + (size_t)((b & 3) * 160 + i * 32 + (tid >> 4)) * 4096 + (b >> 2) * E_ + (tid & 15) * 8);
        uint32_t w[4] = {u.x, u.y, u.z, u.w};
#pragma unroll
        for (int j = 0; j < 4; j++) { float a = bf_lo(w[j]), c = bf_hi(w[j]); sv += a * a + c * c; }
    }
    float so = 0.f;
    if (tid < 320) {
        float s0 = 0.f, s1 = 0.f;
#pragma unroll 8
        for (int r = 0; r < 32; r++) { uint32_t u = *(const uint32_t*)(Wo + (size_t)(b * 32 + r) * D_ + tid * 2); float a = bf_lo(u), c = bf_hi(u); s0 += a * a; s1 += c * c; }
        so = fmaxf(s0, s1);
    }
#pragma unroll
    for (int o = 16; o; o >>= 1) { sv += __shfl_xor_sync(~0u, sv, o); so = fmaxf(so, __shfl_xor_sync(~0u, so, o)); }
    if (lane == 0) { red[warp] = sv; red[16 + warp] = so; }
    __syncthreads();
    if (tid == 0) {
        float a = 0.f, c = 0.f;
        for (int i = 0; i < 16; i++) { a += red[i]; c = fmaxf(c, red[16 + i]); }
        g_nrm[b] = a; g_nrm[128 + b] = c;
    }
}

__host__ __device__ constexpr int col_freq(int c) {
    return c == 320 ? 320 : c < 192 ? (c >> 6) * 128 + (c & 63) : c == 192 ? 192 : c < 256 ? 448 - c : c == 256 ? 64 : 384 - c;
}
DEV float rdft(int n, int k, int sn, int N) {
    float s, c;
    sincospif((float)((n * k) & (N - 1)) * (2.f / N), &s, &c);
    return !sn ? c : k ? s : (n & 1 ? -1.f : 1.f);
}
__global__ void __launch_bounds__(512) tables_kernel(const bf16* __restrict__ Wo, const bf16* __restrict__ wr, const bf16* __restrict__ wi) {
    const int tid = threadIdx.x, b = blockIdx.x;
#pragma unroll
    for (int i = 0; i < 5; i++) {
        const int idx = i * 512 + tid, r = (idx & 7) + 8 * (idx / 640), cg = (idx % 640) >> 3, e = (b & 3) * 32 + r;
        const uint4 v = *(const uint4*)(Wo + (size_t)(b * 32 + r) * D_ + cg * 8);
        *(uint4*)(g_wop + (size_t)((cg / 10) * H_ + (b >> 2)) * 20480 + (e >> 3) * 1280 + (cg % 10) * 128 + (e & 7) * 16) = v;
    }
    if (tid < NCOL) {
        const int ka = b >> 2, i = b & 3, kn = ka ? 2048 - ka : 32, kc = col_freq(tid);
        const unsigned short* pr = (const unsigned short*)wr + kc;
        const unsigned short* pi = (const unsigned short*)wi + kc;
#pragma unroll
        for (int q = 0; q < 4; q++) {
            uint32_t v[4];
#pragma unroll
            for (int j = 0; j < 4; j++) {
                const int k = ((j & 1 ? kn : ka) + 64 * (4 * (2 * i + (j >> 1)) + q)) & 2047;
                v[j] = pr[k * NCOL] | ((uint32_t)pi[k * NCOL] << 16);
            }
            *(uint4*)(g_wt + tid * 8192 + i * 2048 + (ka * 4 + q) * 16) = make_uint4(v[0], v[1], v[2], v[3]);
        }
    }
    const int gid = b * 512 + tid;
    if (gid < 4096) {
        const int inv = gid >> 11, ks = (gid >> 8) & 7, t = gid & 255, g = (t & 31) >> 2, q = t & 3, tile = t >> 5;
        uint32_t v[4];
#pragma unroll
        for (int j = 0; j < 4; j++) {
            float x[2];
#pragma unroll
            for (int u = 0; u < 2; u++) {
                const int m = inv ? 16 * tile + 2 * g + (j & 1) : 16 * ks + 8 * (j >> 1) + 2 * q + u;
                const int k2 = inv ? 8 * ks + 2 * q + u : 8 * tile + g, sn = inv ? j >> 1 : j & 1;
                x[u] = rdft(m, k2, sn, 128);
                if (sn && k2) x[u] = -x[u];
            }
            v[j] = pack2(x[0], x[1]);
        }
        g_f128[gid] = make_uint4(v[0], v[1], v[2], v[3]);
    } else if (gid < 5120) {
        const int id = gid - 4096, inv = id >> 9, ks = (id >> 7) & 3, t = id & 127, g = (t & 31) >> 2, q = t & 3, tile = t >> 5;
        uint32_t v[4];
#pragma unroll
        for (int j = 0; j < 4; j++) {
            float x[2];
#pragma unroll
            for (int u = 0; u < 2; u++) {
                const int a = inv ? 16 * tile + g + 8 * (j & 1) : 16 * ks + 8 * (j >> 1) + 2 * q + u;
                const int ka = inv ? 8 * ks + 2 * q + u : 8 * tile + g, sn = inv ? j >> 1 : j & 1;
                x[u] = rdft(a, ka, sn, 64);
            }
            v[j] = pack2(x[0], x[1]);
        }
        g_f64[id] = make_uint4(v[0], v[1], v[2], v[3]);
    } else if (gid < 5120 + 8192) {
        const int id = gid - 5120, inv = id >> 12, n = ((id >> 9) & 7) * 8 + ((id >> 3) & 7), k = ((id >> 6) & 7) * 8 + (id & 7);
        float s, c;
        sincospif((float)(((n >> 1) * (k >> 1)) & 31) * (1.f / 16), &s, &c);
        if (inv) s = -s;
        g_g32[id] = __float2bfloat16_rn((n & 1) == (k & 1) ? c : (k & 1) ? s : -s);
    }
}

namespace op {
constexpr int STAGE = 32768 + 20480, NST = 4, SMEM = NST * STAGE + 128;
}
__global__ void __launch_bounds__(288, 1) outproj_kernel(const bf16* __restrict__ x, bf16* __restrict__ x1) {
    using namespace op;
    extern __shared__ __align__(1024) unsigned char smem[];
    const uint32_t sb = s2u(smem), bar = sb + NST * STAGE;
    const int tid = threadIdx.x, lane = tid & 31, warp = __shfl_sync(~0u, tid >> 5, 0), mt = blockIdx.x >> 3, nt = blockIdx.x & 7;
    if (tid == 0) {
        for (int i = 0; i < NST; i++) { mbar_init(bar + 8 * i, 1); mbar_init(bar + 8 * (NST + i), 8); }
        asm volatile("fence.mbarrier_init.release.cluster;" ::: "memory");
    }
    __syncthreads();
    pdl_wait();
    pdl_launch();
    if (warp == 8) {
        if (lane == 0) {
            for (int h = 0; h < H_; h++) {
                const int st = h % NST;
                if (h >= NST) mbar_wait(bar + 8 * (NST + st), (h / NST - 1) & 1);
                mbar_expect(bar + 8 * st, STAGE);
                for (int i = 0; i < 4; i++) bulk_g2s(sb + st * STAGE + i * 8192, g_o + (size_t)((mt * 4 + i) * H_ + h) * 8192, 8192, bar + 8 * st);
                bulk_g2s(sb + st * STAGE + 32768, g_wop + (size_t)(nt * H_ + h) * 20480, 20480, bar + 8 * st);
            }
        }
    } else {
        float acc[40];
#pragma unroll
        for (int i = 0; i < 40; i++) acc[i] = 0.f;
        for (int h = 0; h < H_; h++) {
            const int st = h % NST;
            mbar_wait(bar + 8 * st, (h / NST) & 1);
            const u64 da = mkdesc(sb + st * STAGE + (warp >> 2) * 16384, 128, 2048), db = mkdesc(sb + st * STAGE + 32768, 1280, 128);
            wg_fence();
#pragma unroll
            for (int ks = 0; ks < 8; ks++) wgmma_n80_ss<1>(acc, da + ks * 16, db + ks * 160);
            wg_commit();
            if (h > 0) {
                wg_wait<1>();
                if (lane == 0) mbar_arrive(bar + 8 * (NST + (h - 1) % NST));
            }
        }
        wg_wait<0>();
        const int row = mt * 128 + warp * 16 + (lane >> 2), col = nt * 80 + 2 * (lane & 3);
#pragma unroll
        for (int t = 0; t < 10; t++)
#pragma unroll
            for (int j = 0; j < 2; j++) {
                const size_t o = (size_t)(row + 8 * j) * D_ + col + 8 * t;
                const uint32_t u = *(const uint32_t*)(x + o);
                *(uint32_t*)(x1 + o) = pack2(bf_lo(u) + bf_round(acc[4 * t + 2 * j]), bf_hi(u) + bf_round(acc[4 * t + 2 * j + 1]));
            }
    }
}

constexpr float C5A = 0.30901699437494742f, C5B = -0.80901699437494742f, S5A = 0.95105651629515357f, S5B = 0.58778525229247313f;
template <int SGN> DEV void dft5(const float (&tr)[5], const float (&ti)[5], float (&zr)[5], float (&zi)[5]) {
    const float ar = tr[1] + tr[4], ai = ti[1] + ti[4], br = tr[2] + tr[3], bi = ti[2] + ti[3];
    const float cr = tr[1] - tr[4], ci = ti[1] - ti[4], dr = tr[2] - tr[3], di = ti[2] - ti[3];
    zr[0] = tr[0] + ar + br; zi[0] = ti[0] + ai + bi;
    const float m1r = tr[0] + C5A * ar + C5B * br, m1i = ti[0] + C5A * ai + C5B * bi;
    const float m2r = tr[0] + C5B * ar + C5A * br, m2i = ti[0] + C5B * ai + C5A * bi;
    const float n1r = SGN * (S5A * cr + S5B * dr), n1i = SGN * (S5A * ci + S5B * di);
    const float n2r = SGN * (S5B * cr - S5A * dr), n2i = SGN * (S5B * ci - S5A * di);
    zr[1] = m1r + n1i; zi[1] = m1i - n1r; zr[4] = m1r - n1i; zi[4] = m1i + n1r;
    zr[2] = m2r + n2i; zi[2] = m2i - n2r; zr[3] = m2r - n2i; zi[3] = m2i + n2r;
}
DEV void ln40(float (&v)[40]) {
    float s = 0.f;
#pragma unroll
    for (int i = 0; i < 40; i++) s += v[i];
#pragma unroll
    for (int o = 8; o; o >>= 1) s += __shfl_xor_sync(~0u, s, o);
    const float mean = s * (1.f / D_);
    float q = 0.f;
#pragma unroll
    for (int i = 0; i < 40; i++) { const float d = v[i] - mean; q += d * d; }
#pragma unroll
    for (int o = 8; o; o >>= 1) q += __shfl_xor_sync(~0u, q, o);
    const float mb = bf_round(mean);
    const float inv = 1.f / bf_round(sqrtf(bf_round(bf_round(q * (1.f / D_)) + 1e-5f)));
#pragma unroll
    for (int i = 0; i < 40; i++) v[i] = bf_round(v[i] - mb) * inv;
}
DEV void unpack8(float* v, uint4 u) {
    v[0] = bf_lo(u.x); v[1] = bf_hi(u.x); v[2] = bf_lo(u.y); v[3] = bf_hi(u.y);
    v[4] = bf_lo(u.z); v[5] = bf_hi(u.z); v[6] = bf_lo(u.w); v[7] = bf_hi(u.w);
}

__global__ void __launch_bounds__(256) rowfft_kernel(const bf16* __restrict__ x) {
    __shared__ __align__(128) unsigned char sm[10 * 2304];
    const uint32_t sb = s2u(sm);
    const int tid = threadIdx.x, lane = tid & 31, q = lane & 3, blk = blockIdx.x, k2 = tid >> 2;
    float twr[5], twi[5];
#pragma unroll
    for (int r = 1; r < 5; r++) { sincospif((float)(r * k2) * (-1.f / 320), &twi[r], &twr[r]); }
    pdl_wait();
    pdl_launch();
    uint32_t f[8][4];
#pragma unroll
    for (int ks = 0; ks < 8; ks++) { const uint4 u = g_f128[ks * 256 + tid]; f[ks][0] = u.x; f[ks][1] = u.y; f[ks][2] = u.z; f[ks][3] = u.w; }
    {
        const int rho = tid >> 4, j = tid & 15;
        float v[40];
#pragma unroll
        for (int i = 0; i < 5; i++) unpack8(v + 8 * i, *(const uint4*)(x + (size_t)(blk * 16 + rho) * D_ + j * 40 + i * 8));
        ln40(v);
        const uint32_t a = sb + ((rho >> 1) & 1) * 2304 + j * 144 + (2 * (rho >> 2) + (rho & 1)) * 16;
#pragma unroll
        for (int r = 0; r < 5; r++)
            sts128(a + r * 4608, pack2(v[r], v[5 + r]), pack2(v[10 + r], v[15 + r]), pack2(v[20 + r], v[25 + r]), pack2(v[30 + r], v[35 + r]));
    }
    fence_async();
    __syncthreads();
    float acc[40];
    const u64 db = mkdesc(sb, 144, 2304);
    wg_fence();
    wgmma_n80_rs<0, 0>(acc, f[0], db);
#pragma unroll
    for (int ks = 1; ks < 8; ks++) wgmma_n80_rs<1, 0>(acc, f[ks], db + ks * 18);
    wg_commit();
    wg_wait<0>();
    unsigned char* zp = g_z + (blk >> 1) * 128 + ((((blk & 1) * 4 + q) ^ ((blk >> 1) & 7)) << 4);
    uint32_t o[5][4];
#pragma unroll
    for (int u = 0; u < 4; u++) {
        float tr[5], ti[5], zr[5], zi[5];
#pragma unroll
        for (int r = 0; r < 5; r++) {
            const float yr = acc[8 * r + 4 * (u >> 1) + (u & 1)], yi = k2 ? acc[8 * r + 4 * (u >> 1) + 2 + (u & 1)] : 0.f;
            tr[r] = r ? yr * twr[r] - yi * twi[r] : yr;
            ti[r] = r ? yr * twi[r] + yi * twr[r] : yi;
        }
        dft5<1>(tr, ti, zr, zi);
#pragma unroll
        for (int j = 0; j < 5; j++) o[j][u] = pack2(zr[j], j < 3 ? zi[j] : -zi[j]);
    }
#pragma unroll
    for (int j = 0; j < 5; j++)
        if (j < 3 || k2) *(uint4*)(zp + (64 * j + k2) * 8192) = make_uint4(o[j][0], o[j][1], o[j][2], o[j][3]);
    if (k2 == 0) {
#pragma unroll
        for (int u = 0; u < 4; u++) {
            float tr[5], ti[5], zr[5], zi[5];
            const float cr[5] = {1.f, -C5B, C5A, -C5A, C5B}, ci[5] = {0.f, -S5B, -S5A, -S5A, -S5B};
#pragma unroll
            for (int r = 0; r < 5; r++) { const float y = acc[8 * r + 4 * (u >> 1) + 2 + (u & 1)]; tr[r] = y * cr[r]; ti[r] = y * ci[r]; }
            dft5<1>(tr, ti, zr, zi);
            o[0][u] = pack2(zr[0], zi[0]); o[1][u] = pack2(zr[1], zi[1]); o[2][u] = pack2(zr[2], 0.f);
        }
        *(uint4*)(zp + 256 * 8192) = make_uint4(o[0][0], o[0][1], o[0][2], o[0][3]);
        *(uint4*)(zp + 192 * 8192) = make_uint4(o[1][0], o[1][1], o[1][2], o[1][3]);
        *(uint4*)(zp + 320 * 8192) = make_uint4(o[2][0], o[2][1], o[2][2], o[2][3]);
    }
}

constexpr int CF_SMEM = 16384 + 3 * 16384 + 64;
__global__ void __launch_bounds__(384) colfft_kernel() {
    extern __shared__ __align__(1024) unsigned char smem[];
    const uint32_t sb = s2u(smem), bar = sb + 65536;
    const int tid = threadIdx.x, lane = tid & 31, q = lane & 3, wg = __shfl_sync(~0u, tid >> 7, 0), t = tid & 127, ka = t >> 2;
    const int col = blockIdx.x * 3 + wg;
    const uint32_t d0 = sb + 16384 + wg * 16384, d1 = d0 + 8192;
    if (tid == 0) {
        for (int i = 0; i < 4; i++) mbar_init(bar + 8 * i, 1);
        asm volatile("fence.mbarrier_init.release.cluster;" ::: "memory");
    }
    float twr[8], twi[8];
#pragma unroll
    for (int i = 0; i < 8; i++) sincospif((float)((4 * i + q) * (ka ? ka : -32)) * (1.f / 1024), &twi[i], &twr[i]);
    __syncthreads();
    pdl_wait();
    pdl_launch();
    if (t == 0) {
        mbar_expect(bar + 8 * wg, 8192);
        bulk_g2s(d0, g_z + col * 8192, 8192, bar + 8 * wg);
        if (wg == 0) { mbar_expect(bar + 24, 16384); bulk_g2s(sb, g_g32, 16384, bar + 24); }
    }
    uint32_t f[4][4], w[16];
#pragma unroll
    for (int ks = 0; ks < 4; ks++) { const uint4 u = g_f64[ks * 128 + t]; f[ks][0] = u.x; f[ks][1] = u.y; f[ks][2] = u.z; f[ks][3] = u.w; }
#pragma unroll
    for (int i = 0; i < 4; i++) { const uint4 u = *(const uint4*)(g_wt + col * 8192 + i * 2048 + t * 16); w[4 * i] = u.x; w[4 * i + 1] = u.y; w[4 * i + 2] = u.z; w[4 * i + 3] = u.w; }
    float acc[32];
    uint32_t a[4][4];
    const u64 SW128 = 1ull << 62;
    mbar_wait(bar + 8 * wg, 0);
    {
        const u64 db = mkdesc(d0, 0, 1024) | SW128;
        wg_fence();
        wgmma_n64_rs<0, 1>(acc, f[0], db);
#pragma unroll
        for (int ks = 1; ks < 4; ks++) wgmma_n64_rs<1, 1>(acc, f[ks], db + ks * 128);
        wg_commit();
        wg_wait<0>();
    }
#pragma unroll
    for (int ks = 0; ks < 4; ks++) { const uint4 u = g_f64[512 + ks * 128 + t]; f[ks][0] = u.x; f[ks][1] = u.y; f[ks][2] = u.z; f[ks][3] = u.w; }
#pragma unroll
    for (int i = 0; i < 8; i++) {
        const float c0 = acc[4 * i], c1 = acc[4 * i + 1], c2 = acc[4 * i + 2], c3 = acc[4 * i + 3];
        const float pr = c0 + c3, pi = c1 - c2, nr = ka ? c0 - c3 : c2, ni = ka ? c1 + c2 : c3;
        a[i >> 1][2 * (i & 1)] = ka ? pack2(pr * twr[i] + pi * twi[i], pi * twr[i] - pr * twi[i]) : pack2(c0, c1);
        a[i >> 1][2 * (i & 1) + 1] = pack2(nr * twr[i] - ni * twi[i], ni * twr[i] + nr * twi[i]);
    }
    mbar_wait(bar + 24, 0);
    {
        const u64 db = mkdesc(sb, 128, 1024);
        wg_fence();
        wgmma_n64_rs<0, 0>(acc, a[0], db);
#pragma unroll
        for (int ks = 1; ks < 4; ks++) wgmma_n64_rs<1, 0>(acc, a[ks], db + ks * 16);
        wg_commit();
        wg_wait<0>();
    }
    constexpr float NORM = 1.f / (2048.f * 640.f);
#pragma unroll
    for (int i = 0; i < 16; i++) {
        const float zr = acc[2 * i] * NORM, zi = acc[2 * i + 1] * NORM, wr = bf_lo(w[i]), wi = bf_hi(w[i]);
        a[i >> 2][i & 3] = pack2(zr * wr - zi * wi, zr * wi + zi * wr);
    }
    {
        const u64 db = mkdesc(sb + 8192, 128, 1024);
        wg_fence();
        wgmma_n64_rs<0, 0>(acc, a[0], db);
#pragma unroll
        for (int ks = 1; ks < 4; ks++) wgmma_n64_rs<1, 0>(acc, a[ks], db + ks * 16);
        wg_commit();
        wg_wait<0>();
    }
    const uint32_t row = (t >> 5) * 2048 + (lane & 15) * 128;
#pragma unroll
    for (int i = 0; i < 8; i++) {
        const float c0 = acc[4 * i], c1 = acc[4 * i + 1], c2 = acc[4 * i + 2], c3 = acc[4 * i + 3];
        const float pr = c0 * twr[i] - c1 * twi[i], pi = c1 * twr[i] + c0 * twi[i];
        const float nr = c2 * twr[i] + c3 * twi[i], ni = c3 * twr[i] - c2 * twi[i];
        a[i >> 1][2 * (i & 1)] = ka ? pack2(pr + nr, pi + ni) : pack2(c0, c1);
        a[i >> 1][2 * (i & 1) + 1] = ka ? pack2(ni - pi, pr - nr) : pack2(nr, ni);
    }
#pragma unroll
    for (int i = 0; i < 4; i++) stsm4(d1 + row + (((2 * i + (lane >> 4)) ^ (lane & 7)) << 4), a[i][0], a[i][1], a[i][2], a[i][3]);
    fence_async();
    bar_sync(1 + wg, 128);
    {
        const u64 db = mkdesc(d1, 0, 1024) | SW128;
        wg_fence();
        wgmma_n64_rs<0, 1>(acc, f[0], db);
#pragma unroll
        for (int ks = 1; ks < 4; ks++) wgmma_n64_rs<1, 1>(acc, f[ks], db + ks * 128);
        wg_commit();
        wg_wait<0>();
    }
#pragma unroll
    for (int i = 0; i < 4; i++)
        stsm4(d0 + row + (((2 * i + (lane >> 4)) ^ (lane & 7)) << 4), pack2(acc[8 * i], acc[8 * i + 1]), pack2(acc[8 * i + 2], acc[8 * i + 3]),
              pack2(acc[8 * i + 4], acc[8 * i + 5]), pack2(acc[8 * i + 6], acc[8 * i + 7]));
    fence_async();
    bar_sync(1 + wg, 128);
    if (t == 0) {
        bulk_s2g(g_z + col * 8192, d0, 8192);
        asm volatile("cp.async.bulk.commit_group;" ::: "memory");
        asm volatile("cp.async.bulk.wait_group 0;" ::: "memory");
    }
}

__global__ void __launch_bounds__(256) rowifft_kernel(const bf16* __restrict__ x, bf16* __restrict__ out, int last) {
    __shared__ __align__(128) unsigned char sm[20480 + 16 * 1296];
    const uint32_t sb = s2u(sm), sy = sb + 20480;
    const int tid = threadIdx.x, lane = tid & 31, q = lane & 3, blk = blockIdx.x, k2 = tid >> 2, warp = tid >> 5;
    float twr[5], twi[5];
#pragma unroll
    for (int r = 1; r < 5; r++) { sincospif((float)(r * k2) * (1.f / 320), &twi[r], &twr[r]); twr[r] *= 2.f; twi[r] *= 2.f; }
    pdl_wait();
    pdl_launch();
    const unsigned char* zp = g_z + (blk >> 1) * 128 + ((((blk & 1) * 4 + q) ^ ((blk >> 1) & 7)) << 4);
    uint4 z[6];
#pragma unroll
    for (int j = 0; j < 5; j++) z[j] = *(const uint4*)(zp + (64 * j + k2) * 8192);
    z[5] = k2 ? make_uint4(0, 0, 0, 0) : *(const uint4*)(zp + 320 * 8192);
    uint32_t f[8][4];
#pragma unroll
    for (int ks = 0; ks < 8; ks++) { const uint4 u = g_f128[2048 + ks * 256 + tid]; f[ks][0] = u.x; f[ks][1] = u.y; f[ks][2] = u.z; f[ks][3] = u.w; }
    uint4 xr[5];
#pragma unroll
    for (int i = 0; i < 5; i++) xr[i] = *(const uint4*)(x + (size_t)(blk * 16 + (tid >> 4)) * D_ + (tid & 15) * 40 + i * 8);
    float acc[40];
#pragma unroll
    for (int u = 0; u < 4; u++) {
        float yr[6], yi[6], tr[5], ti[5], zr[5], zi[5];
#pragma unroll
        for (int j = 0; j < 6; j++) { const uint32_t v = u == 0 ? z[j].x : u == 1 ? z[j].y : u == 2 ? z[j].z : z[j].w; yr[j] = bf_lo(v); yi[j] = bf_hi(v); }
#pragma unroll
        for (int j = 0; j < 5; j++) { tr[j] = yr[j]; ti[j] = j < 3 ? yi[j] : -yi[j]; }
        dft5<-1>(tr, ti, zr, zi);
        const float c1[5] = {1.f, C5A, C5B, C5B, C5A}, s1[5] = {0.f, S5A, S5B, -S5B, -S5A};
        const float c2[5] = {1.f, C5B, C5A, C5A, C5B}, s2[5] = {0.f, S5B, -S5A, S5A, -S5B};
        const float c3[5] = {1.f, -C5B, C5A, -C5A, C5B}, s3[5] = {0.f, S5B, S5A, S5A, S5B};
        const float c4[5] = {1.f, -C5A, C5B, -C5B, C5A}, s4[5] = {0.f, S5A, -S5B, -S5B, S5A};
#pragma unroll
        for (int r = 0; r < 5; r++) {
            float er = r ? zr[r] * twr[r] - zi[r] * twi[r] : 2.f * zr[0], ei = r ? zr[r] * twi[r] + zi[r] * twr[r] : 2.f * zi[0];
            if (k2 == 0) {
                er = yr[0] + 2.f * (yr[1] * c1[r] - yi[1] * s1[r] + yr[2] * c2[r] - yi[2] * s2[r]);
                ei = (r & 1 ? -yr[5] : yr[5]) + 2.f * (yr[4] * c3[r] - yi[4] * s3[r] + yr[3] * c4[r] - yi[3] * s4[r]);
            }
            acc[8 * r + 4 * (u >> 1) + (u & 1)] = er;
            acc[8 * r + 4 * (u >> 1) + 2 + (u & 1)] = ei;
        }
    }
#pragma unroll
    for (int r = 0; r < 5; r++)
        stsm4(sb + (2 * warp + ((lane >> 3) & 1)) * 1280 + (2 * r + (lane >> 4)) * 128 + (lane & 7) * 16, pack2(acc[8 * r], acc[8 * r + 1]),
              pack2(acc[8 * r + 2], acc[8 * r + 3]), pack2(acc[8 * r + 4], acc[8 * r + 5]), pack2(acc[8 * r + 6], acc[8 * r + 7]));
    fence_async();
    __syncthreads();
    const u64 db = mkdesc(sb, 1280, 128);
    wg_fence();
    wgmma_n80_rs<0, 1>(acc, f[0], db);
#pragma unroll
    for (int ks = 1; ks < 8; ks++) wgmma_n80_rs<1, 1>(acc, f[ks], db + ks * 160);
    wg_commit();
    wg_wait<0>();
#pragma unroll
    for (int u = 0; u < 4; u++) {
        float e[10];
#pragma unroll
        for (int r = 0; r < 5; r++) { e[r] = acc[8 * r + 4 * (u >> 1) + (u & 1)]; e[5 + r] = acc[8 * r + 4 * (u >> 1) + 2 + (u & 1)]; }
#pragma unroll
        for (int i = 0; i < 5; i++) sts32(sy + (4 * q + u) * 1296 + k2 * 20 + i * 4, pack2(e[2 * i], e[2 * i + 1]));
    }
    __syncthreads();
    const int rho = tid >> 4, j = tid & 15, row = blk * 16 + rho;
    float v[40];
#pragma unroll
    for (int i = 0; i < 5; i++) {
        uint32_t y[4];
        float a[8], b[8];
        lds128(y, sy + rho * 1296 + j * 80 + i * 16);
        unpack8(a, xr[i]); unpack8(b, make_uint4(y[0], y[1], y[2], y[3]));
        const uint4 o = make_uint4(pack2(a[0] + b[0], a[1] + b[1]), pack2(a[2] + b[2], a[3] + b[3]), pack2(a[4] + b[4], a[5] + b[5]), pack2(a[6] + b[6], a[7] + b[7]));
        *(uint4*)(out + (size_t)row * D_ + j * 40 + i * 8) = o;
        unpack8(v + 8 * i, o);
    }
    if (!last) {
        ln40(v);
#pragma unroll
        for (int i = 0; i < 5; i++)
            *(uint4*)(g_xn + (row >> 5) * 40960 + (j * 5 + i) * 512 + (row & 31) * 16) =
                make_uint4(pack2(v[8 * i], v[8 * i + 1]), pack2(v[8 * i + 2], v[8 * i + 3]), pack2(v[8 * i + 4], v[8 * i + 5]), pack2(v[8 * i + 6], v[8 * i + 7]));
    }
}

namespace rec {
constexpr int NS = 5;
constexpr int OFF_X = 0;
constexpr int OFF_WO = 81920;
constexpr int OFF_WS = OFF_WO + 57344;
constexpr int OFF_MEMB = OFF_WS + NS * 4096;
constexpr int OFF_VX = OFF_MEMB + 10240;
constexpr int OFF_VM = OFF_VX + 16384;
constexpr int OFF_Q = OFF_VM + 4096;
constexpr int OFF_K = OFF_Q + 10240;
constexpr int OFF_PX = OFF_K + 10240;
constexpr int OFF_OST = OFF_PX + 5120;
constexpr int OFF_PT = OFF_OST + 4096;
constexpr int OFF_PS = OFF_PT + 1536;
constexpr int OFF_OB = OFF_PS + 2560;
constexpr int OFF_MX = OFF_OB + 2048;
constexpr int OFF_BAR = OFF_MX + 64;
constexpr int OFF_PROF = OFF_BAR + 256;
constexpr int SMEM = OFF_PROF;
enum { B_FIN = 0, B_XT = 1, B_KX = 3, B_VX = 5, B_KM = 7, B_XD = 9, B_X1 = 11, B_WN = 13, B_PXF = 15, B_PXE = 16 };
enum { NB_MEM = 1, NB_QK = 2, NB_WIN = 3, NB_ATT = 4, NB_X = 5, NB_PRO = 6, NB_W1 = 7 };
#define NOX 0
#define NW1 8
#define NW1B 4
constexpr float SM_SCALE = 0.08838834764831845f * 1.4426950408889634f;
}

__global__ void __launch_bounds__(512, 1) rec_kernel(const bf16* __restrict__ mem0, const bf16* __restrict__ Wq, const bf16* __restrict__ Wk,
                                                     const bf16* __restrict__ Wv, const bf16* __restrict__ Wo, int layer, int delay) {
    using namespace rec;
    extern __shared__ __align__(1024) unsigned char smem[];
    const uint32_t sb = s2u(smem);
    const int tid = threadIdx.x, lane = tid & 31, warp = __shfl_sync(~0u, tid >> 5, 0);
    const int g = lane >> 2, q = lane & 3;
    uint32_t rank; asm("mov.u32 %0,%%cluster_ctarank;" : "=r"(rank));
    const int h = blockIdx.x / 3;
    const uint32_t bar = sb + OFF_BAR;
    if (tid == 0) {
        for (int i = 0; i < 2; i++) {
            mbar_init(bar + 8 * (B_XT + i), 1); mbar_init(bar + 8 * (B_KX + i), 8); mbar_init(bar + 8 * (B_VX + i), 1);
            mbar_init(bar + 8 * (B_KM + i), 8); mbar_init(bar + 8 * (B_XD + i), rank < 2 ? 4 : 8);
            mbar_init(bar + 8 * (B_X1 + i), 1); mbar_init(bar + 8 * (B_WN + i), 1);
        }
        mbar_init(bar + 8 * B_PXF, 1); mbar_init(bar + 8 * B_PXE, 2);
        mbar_init(bar + 8 * B_FIN, 48);
        asm volatile("fence.mbarrier_init.release.cluster;" ::: "memory");
    }
    asm volatile("barrier.cluster.arrive.aligned; barrier.cluster.wait.aligned;" ::: "memory");
    const bool never = delay < 0;

    if (warp < 8) {
        asm volatile("setmaxnreg.inc.sync.aligned.u32 184;");
        uint32_t a[40 - NS][4];
        const uint32_t l16 = opaque(sb + lane * 16);
        uint32_t wsa = opaque(sb + OFF_WS + warp * 512 + (lane & 7) * 16 + ((lane >> 3) & 1) * 256 + (lane >> 4) * 128);
        const uint32_t dst = opaque(rank < 2 ? sb + OFF_Q + (warp >> 2) * 10240 + (warp & 3) * 256 + (lane & 15) * 16 + (lane >> 4) * 1024
                                             : sb + OFF_VM + warp * 256 + lane * 4);
        const bool l0 = lane == 0;
        uint32_t& sfd = wsa;
        {
            const bf16* W = rank == 2 ? Wv : (warp < 4 ? Wq : Wk);
            const int eb = rank == 2 ? warp * 16 : rank * 64 + (warp & 3) * 16;
            const bf16* p = W + h * E_ + eb + 2 * g + (size_t)(2 * q) * 4096;
            uint32_t t[NS][4];
#pragma unroll
            for (int ks = 0; ks < 40; ks++) {
                uint32_t* u = ks < NS ? t[ks] : a[ks - NS];
                u[0] = ldg32(p + (size_t)(16 * ks) * 4096); u[1] = ldg32(p + (size_t)(16 * ks + 1) * 4096);
                u[2] = ldg32(p + (size_t)(16 * ks + 8) * 4096); u[3] = ldg32(p + (size_t)(16 * ks + 9) * 4096);
            }
#pragma unroll
            for (int ks = 0; ks < 40; ks++) {
                uint32_t* u = ks < NS ? t[ks] : a[ks - NS];
                uint32_t u0 = u[0], u1 = u[1], u2 = u[2], u3 = u[3];
                u[0] = prmt(u0, u1, 0x5410); u[1] = prmt(u0, u1, 0x7632);
                u[2] = prmt(u2, u3, 0x5410); u[3] = prmt(u2, u3, 0x7632);
                if (ks < NS) stsm4(wsa + ks * 4096, u[0], u[1], u[2], u[3]);
            }
            fence_async();
            bar_sync(NB_PRO, 256);
        }
        for (int s = -1; s < NSEG; s++) {
            if (s >= 0) {
                float d0[4] = {0.f, 0.f, 0.f, 0.f}, d1[4] = {0.f, 0.f, 0.f, 0.f};
                uint32_t t[NS][4], b[20][4];
#pragma unroll
                for (int ks = 0; ks < NS; ks++) ldsm4(t[ks], wsa + ks * 4096);
                bar_sync(NB_MEM, 384);
                lds128(b[0], l16 + OFF_MEMB); lds128(b[1], l16 + OFF_MEMB + 512);
#pragma unroll
                for (int kp = 0; kp < 20; kp++) {
#pragma unroll
                    for (int j = 0; j < 2; j++) {
                        const int ks = 2 * kp + j;
                        const uint32_t* f = ks < NS ? t[ks] : a[ks - NS];
                        mma16(j ? d1 : d0, f[0], f[1], f[2], f[3], b[kp][2 * j], b[kp][2 * j + 1]);
                    }
                    if (kp == 0 && warp == 0) PROFT(0);
                    if (kp < 2) { lds128(b[2 * kp + 2], l16 + OFF_MEMB + (2 * kp + 2) * 512); lds128(b[2 * kp + 3], l16 + OFF_MEMB + (2 * kp + 3) * 512); }
                    else if (kp + 4 < 20) lds128(b[kp + 4], l16 + OFF_MEMB + (kp + 4) * 512);
                    if (kp < 16) SFENCE();
                }
                const float is = lds32f(sb + OFF_MX + 16);
                const uint32_t p0 = pack2((d0[0] + d1[0]) * is, (d0[1] + d1[1]) * is), p1 = pack2((d0[2] + d1[2]) * is, (d0[3] + d1[3]) * is);
                if (rank < 2) {
                    stsm2t(dst + (s & 1) * 5120, p0, p1);
                } else {
                    const uint32_t la = dst + (s & 1) * 2048, vb = bar + 8 * (B_VX + (s & 1));
                    st_async1(mapa(la, 0), p0, mapa(vb, 0)); st_async1(mapa(la, 1), p0, mapa(vb, 1));
                    st_async1(mapa(la + 128, 0), p1, mapa(vb, 0)); st_async1(mapa(la + 128, 1), p1, mapa(vb, 1));
                    sts32(la, p0); sts32(la + 128, p1);
                }
                if (s < NSEG - 1) bar_arrive(NB_QK, 384);
                __syncwarp();
                if (l0) mbar_arrive(bar + 8 * (B_KM + (s & 1)));
                if (warp == 0) PROFT(1);
                if (s == NSEG - 1) break;
            }
            const int n = s + 1, pb = n & 1;
            float acc[16];
            mbar_wait(bar + 8 * (B_XT + pb), (n >> 1) & 1);
            const u64 desc = mkdesc(sb + OFF_X + pb * 40960, 512, 128);
            const u64 da = mkdesc(sb + OFF_WS + (warp >> 2) * 2048, 128, 256);
            if (s >= 0) bar_sync(NB_W1, 384);
            wg_fence();
            wgmma_n32_rs<0>(acc, a[39 - NS], desc + 39 * 64);
#pragma unroll
            for (int ks = 38; ks >= 40 - (NOX ? 1 : NW1); ks--) wgmma_n32_rs<1>(acc, a[ks - NS], desc + ks * 64);
            wg_commit();
            if (s >= 0 && rank < 2) {
                wg_wait<0>();
                if (warp == 0) PROFT(15);
                bar_sync(NB_WIN, 384);
                if (warp == 0 && l0) mbar_arrive(bar + 8 * (B_WN + (s & 1)));
            }
            wg_fence();
#pragma unroll
            for (int ks = 39 - NW1; ks >= 40 - NW1 - (NOX ? 0 : NW1B); ks--) wgmma_n32_rs<1>(acc, a[ks - NS], desc + ks * 64);
            wg_commit();
            if (s >= 0 && rank == 2) {
                wg_wait<0>();
                if (warp == 0) PROFT(15);
                bar_sync(NB_WIN, 384);
            }
            if (s >= 0 && warp == 0) PROFT(2);
            wg_fence();
#pragma unroll
            for (int ks = 0; ks < (NOX ? 0 : 40 - NW1 - NW1B); ks++) {
                if (ks < NS) wgmma_n32_ss<1>(acc, da + ks * 256, desc + ks * 64);
                else wgmma_n32_rs<1>(acc, a[ks - NS], desc + ks * 64);
            }
            wg_commit();
            if (n >= 2) mbar_wait(bar + 8 * (B_XD + pb), ((n >> 1) - 1) & 1);
            wg_wait<0>();
            uint32_t pk[8];
#pragma unroll
            for (int i = 0; i < 8; i++) pk[i] = pack2(acc[2 * i], acc[2 * i + 1]);
            if (rank < 2) {
                const uint32_t la = dst + pb * 5120 + 1024;
                stsm4t(la, pk[0], pk[1], pk[2], pk[3]);
                stsm4t(la + 2048, pk[4], pk[5], pk[6], pk[7]);
            } else {
                const uint32_t la = l16 + OFF_VX + pb * 8192 + warp * 1024;
                stsm4(la, pk[0], pk[2], pk[4], pk[6]);
                stsm4(la + 512, pk[1], pk[3], pk[5], pk[7]);
                fence_async();
            }
            __syncwarp();
            if (l0) mbar_arrive(bar + 8 * (B_KX + pb));
            if (s >= 0 && warp == 0) PROFT(3);
        }
    } else if (warp < 12) {
        asm volatile("setmaxnreg.dec.sync.aligned.u32 104;");
        const int w = warp - 8;
        const bool four = w == 0 || (w == 1 && rank == 0);
        const int tile3 = rank == 0 ? 36 + w : 37 + rank;
        uint32_t amax = 0;
#pragma unroll
        for (int it = 0; it < 5; it++) {
            const int kp = it * 4 + w;
            const bf16* p = mem0 + g * D_ + kp * 32 + 2 * q;
            uint32_t b0 = ldg32(p), b1 = ldg32(p + 8), b2 = ldg32(p + 16), b3 = ldg32(p + 24);
            sts128(sb + OFF_MEMB + kp * 512 + lane * 16, b0, b1, b2, b3);
            amax = absmax2(amax, absmax2(absmax2(b0, b1), absmax2(b2, b3)));
        }
        if (tid == 256) sts32(sb + OFF_MX + 16, 0x3f800000u);
        bar_arrive(NB_MEM, 384);
        for (int r = 0; r < (four ? 4 : 3); r++) {
            const int T = r < 3 ? 12 * r + 4 * rank + w : tile3;
            const bf16* p = Wo + (size_t)(h * E_ + 4 * q) * D_ + 16 * T + 8 * (g & 1) + 2 * (g >> 1);
            uint32_t u[8][4];
#pragma unroll
            for (int ks = 0; ks < 8; ks++)
#pragma unroll
                for (int j = 0; j < 4; j++) u[ks][j] = ldg32(p + (16 * ks + j) * D_);
#pragma unroll
            for (int ks = 0; ks < 8; ks++)
                sts128(sb + OFF_WO + (r * 4 + w) * 4096 + ks * 512 + lane * 16, prmt(u[ks][0], u[ks][2], 0x5410), prmt(u[ks][0], u[ks][2], 0x7632),
                       prmt(u[ks][1], u[ks][3], 0x5410), prmt(u[ks][1], u[ks][3], 0x7632));
        }
        float cw;
        {
            const float4 a = ((const float4*)g_nrm)[lane], c = ((const float4*)g_nrm)[32 + lane];
            float sm = sqrtf((a.x + a.y) + (a.z + a.w)) * sqrtf((c.x + c.y) + (c.z + c.w)), mxv = sm;
#pragma unroll
            for (int o = 16; o; o >>= 1) { sm += __shfl_xor_sync(~0u, sm, o); mxv = fmaxf(mxv, __shfl_xor_sync(~0u, mxv, o)); }
            cw = 26.5f * fmaxf(sm, 8.f * mxv);
        }
        const uint32_t l16 = opaque(sb + lane * 16), l8 = opaque(sb + lane * 8);
        uint32_t lq = opaque(sb + OFF_Q + (lane & 7) * 16 + ((lane >> 3) & 1) * 256 + (lane >> 4) * 128);
        const uint32_t lv = opaque(sb + OFF_VX + w * 2048 + (lane & 7) * 16 + ((lane >> 3) & 1) * 512 + (lane >> 4) * 128);
        uint32_t& sfd = lq;
        const uint32_t q8 = opaque(8 * q);
        const bool l0 = lane == 0, t0 = tid == 256;
        const char* rp = (const char*)(g_acc + layer * ACC_LAYER) + (4 * rank + w) * 1024 + opaque(((q >> 1) * 32 + (q & 1) * 8 + g) * 8);
        const char* lp = (const char*)(g_acc + layer * ACC_LAYER) + opaque((w * 256 + (2 * (g & 1) + (g >> 2)) * 32 + ((g >> 1) & 1) * 8 + 2 * q) * 8);
        const int t3off = (tile3 - 4 * rank - w) * 1024;
        float isig = 1.f;
        for (int s = 0; s < NSEG - 1; s++) {
            const int pb = s & 1;
            const uint32_t x1 = bar + 8 * (B_X1 + pb);
            {
                uint32_t m = max(amax & 0x7fffu, (amax >> 16) & 0x7fffu);
                m = __reduce_max_sync(~0u, m);
                if (l0) sts32(sb + OFF_MX + w * 4, m << 16);
            }
            if (t0) {
                mbar_expect(x1, 2560);
                if (rank < 2) mbar_expect(bar + 8 * (B_VX + pb), 10240);
            }
            mbar_wait(bar + 8 * (B_KX + pb), (s >> 1) & 1);
            if (rank < 2) {
                uint32_t kf[8], qf[8];
                const uint32_t ka = l16 + OFF_K + pb * 5120, qa = lq + pb * 5120;
                ldsm4(kf, ka + (1 + w) * 1024); ldsm4(kf + 4, ka + (1 + w) * 1024 + 512);
                const uint32_t pa = l8 + OFF_PS + rank * 1280 + w * 256;
                const uint32_t pa0 = mapa(pa, rank ^ 1), pa1 = mapa(pa, 2), pa2 = mapa(pa, rank);
                const uint32_t xb0 = mapa(x1, rank ^ 1), xb1 = mapa(x1, 2), xb2 = mapa(x1, rank);
                bar_sync(NB_QK, 384);
                ldsm4(qf, qa); ldsm4(qf + 4, qa + 512);
                float c0[4] = {0.f, 0.f, 0.f, 0.f}, c1[4] = {0.f, 0.f, 0.f, 0.f}, c2[4] = {0.f, 0.f, 0.f, 0.f}, c3[4] = {0.f, 0.f, 0.f, 0.f};
                if (w == 3) {
                    uint32_t mf[8];
                    ldsm4(mf, ka); ldsm4(mf + 4, ka + 512);
                    mma16(c0, qf[0], qf[1], qf[2], qf[3], kf[0], kf[1]); mma16(c1, qf[0], qf[1], qf[2], qf[3], kf[2], kf[3]);
                    mma16(c2, qf[0], qf[1], qf[2], qf[3], mf[0], mf[1]); mma16(c3, qf[0], qf[1], qf[2], qf[3], mf[2], mf[3]);
                    mma16(c0, qf[4], qf[5], qf[6], qf[7], kf[4], kf[5]); mma16(c1, qf[4], qf[5], qf[6], qf[7], kf[6], kf[7]);
                    mma16(c2, qf[4], qf[5], qf[6], qf[7], mf[4], mf[5]); mma16(c3, qf[4], qf[5], qf[6], qf[7], mf[6], mf[7]);
                    const uint32_t y0 = __float_as_uint(c0[0] + c1[2]), y1 = __float_as_uint(c0[1] + c1[3]);
                    const uint32_t z0 = __float_as_uint(c2[0] + c3[2]), z1 = __float_as_uint(c2[1] + c3[3]);
                    st_async2(pa0, y0, y1, xb0); st_async2(pa1, y0, y1, xb1);
                    st_async2(pa0 + 256, z0, z1, xb0); st_async2(pa1 + 256, z0, z1, xb1);
                    st_async2(pa2, y0, y1, xb2); st_async2(pa2 + 256, z0, z1, xb2);
                } else {
                    mma16(c0, qf[0], qf[1], qf[2], qf[3], kf[0], kf[1]); mma16(c1, qf[0], qf[1], qf[2], qf[3], kf[2], kf[3]);
                    mma16(c2, qf[4], qf[5], qf[6], qf[7], kf[4], kf[5]); mma16(c3, qf[4], qf[5], qf[6], qf[7], kf[6], kf[7]);
                    const uint32_t y0 = __float_as_uint((c0[0] + c1[2]) + (c2[0] + c3[2])), y1 = __float_as_uint((c0[1] + c1[3]) + (c2[1] + c3[3]));
                    st_async2(pa0, y0, y1, xb0); st_async2(pa1, y0, y1, xb1); st_async2(pa2, y0, y1, xb2);
                }
                if (w == 0) PROFT(4);
            } else {
                bar_sync(NB_QK, 384);
            }
            uint32_t wf[12][4], vf[2][2][4], vm[4];
#pragma unroll
            for (int ks = 0; ks < 8; ks++) lds128(wf[ks], l16 + OFF_WO + w * 4096 + ks * 512);
            bar_arrive(NB_W1, 384);
            float sig;
            {
                float m4[4];
                lds128f(m4, sb + OFF_MX);
                float bound = cw * fmaxf(fmaxf(fmaxf(m4[0], m4[1]), fmaxf(m4[2], m4[3])) * isig, 1.f);
                uint32_t e = max((__float_as_uint(bound) >> 23) & 255u, 31u);
                sig = __uint_as_float((278u - e) << 23);
                isig = __uint_as_float((e - 30u) << 23);
                if (t0) sts32(sb + OFF_MX + 16, __float_as_uint(isig));
            }
            if (rank < 2) mbar_wait(bar + 8 * (B_VX + pb), (s >> 1) & 1);
#pragma unroll
            for (int t = 0; t < 2; t++)
#pragma unroll
                for (int j = 0; j < 2; j++) ldsm4(vf[t][j], lv + pb * 8192 + t * 1024 + j * 256);
            ldsm4(vm, l16 + OFF_VM + pb * 2048 + w * 512);
            if (w == 0) PROFT(5);
            mbar_wait(x1, (s >> 1) & 1);
            if (w == 0) PROFT(6);
            float sc[10], sd[10];
#pragma unroll
            for (int nt = 0; nt < 5; nt++) {
                lds64f(sc[2 * nt], sc[2 * nt + 1], l8 + OFF_PS + nt * 256);
                lds64f(sd[2 * nt], sd[2 * nt + 1], l8 + OFF_PS + 1280 + nt * 256);
            }
            SFENCE();
#pragma unroll
            for (int i = 0; i < 10; i++) sc[i] += sd[i];
            float mx = fmaxf(fmaxf(fmaxf(fmaxf(sc[0], sc[1]), fmaxf(sc[2], sc[3])), fmaxf(fmaxf(sc[4], sc[5]), fmaxf(sc[6], sc[7]))), fmaxf(sc[8], sc[9]));
            {
                float m1 = __shfl_xor_sync(~0u, mx, 1), m2 = __shfl_xor_sync(~0u, mx, 2), m3 = __shfl_xor_sync(~0u, mx, 3);
                SFENCE();
                mx = fmaxf(fmaxf(mx, m1), fmaxf(m2, m3)) * SM_SCALE;
            }
            float o0[4] = {0.f, 0.f, 0.f, 0.f}, o1[4] = {0.f, 0.f, 0.f, 0.f};
            sc[8] = ex2(fmaf(sc[8], SM_SCALE, -mx)); sc[9] = ex2(fmaf(sc[9], SM_SCALE, -mx));
#pragma unroll
            for (int i = 0; i < 4; i++) sc[i] = ex2(fmaf(sc[i], SM_SCALE, -mx));
            SFENCE();
            {
                const uint32_t p = pack2(sc[8], sc[9]);
                mma8(o0, vm[0], vm[1], p);
                mma8(o1, vm[2], vm[3], p);
            }
#pragma unroll
            for (int i = 4; i < 8; i++) sc[i] = ex2(fmaf(sc[i], SM_SCALE, -mx));
            SFENCE();
#pragma unroll
            for (int j = 0; j < 2; j++) {
                const uint32_t p0 = pack2(sc[4 * j], sc[4 * j + 1]), p1 = pack2(sc[4 * j + 2], sc[4 * j + 3]);
                mma16(o0, vf[0][j][0], vf[0][j][1], vf[0][j][2], vf[0][j][3], p0, p1);
                mma16(o1, vf[1][j][0], vf[1][j][1], vf[1][j][2], vf[1][j][3], p0, p1);
            }
            SFENCE();
#pragma unroll
            for (int ks = 0; ks < 4; ks++) lds128(wf[8 + ks], l16 + OFF_WO + (4 + w) * 4096 + ks * 512);
            float sum = ((sc[0] + sc[1]) + (sc[2] + sc[3])) + ((sc[4] + sc[5]) + (sc[6] + sc[7])) + (sc[8] + sc[9]);
            const float s1 = __shfl_xor_sync(~0u, sum, 1), s2 = __shfl_xor_sync(~0u, sum, 2), s3 = __shfl_xor_sync(~0u, sum, 3);
            stsm4t(l16 + OFF_OB + w * 512, pack2(o0[0], o0[1]), pack2(o0[2], o0[3]), pack2(o1[0], o1[1]), pack2(o1[2], o1[3]));
            bar_sync(NB_ATT, 128);
            uint32_t ob[16];
#pragma unroll
            for (int j = 0; j < 4; j++) ldsm4(ob + 4 * j, l16 + OFF_OB + j * 512);
            SFENCE();
            sum = rcp((sum + s1) + (s2 + s3)) * sig;
            const float sg0 = __shfl_sync(~0u, sum, q8), sg1 = __shfl_sync(~0u, sum, q8 + 4);
            auto emit = [&](const char* p, float v0, float v1, float v2, float v3) {
                red_add64((u64*)p, (__float_as_uint(fmaf(v0, sg0, 12582912.f)) << 6) + 1, __float_as_uint(fmaf(v2, sg0, 12582912.f)) << 6);
                red_add64((u64*)(p + 512), (__float_as_uint(fmaf(v1, sg1, 12582912.f)) << 6) + 1, __float_as_uint(fmaf(v3, sg1, 12582912.f)) << 6);
            };
            auto tile = [&](int r, float (&c)[2][4], float (&e)[2][4]) {
#pragma unroll
                for (int i = 0; i < 4; i++) c[0][i] = c[1][i] = e[0][i] = e[1][i] = 0.f;
#pragma unroll
                for (int ks = 0; ks < 8; ks++) {
                    uint32_t* f = wf[(8 * r + ks) % 12];
                    mma16(ks & 2 ? e[ks & 1] : c[ks & 1], f[0], f[1], f[2], f[3], ob[2 * ks], ob[2 * ks + 1]);
                    const int nx = 8 * r + ks + 12;
                    if (nx < 24 || (nx < 32 && four)) lds128(f, l16 + OFF_WO + ((nx >> 3) * 4 + w) * 4096 + (nx & 7) * 512);
                }
            };
            float c[2][4], e[2][4];
            SFENCE();
            tile(0, c, e);
            SFENCE();
            emit(rp, (c[0][0] + c[1][0]) + (e[0][0] + e[1][0]), (c[0][1] + c[1][1]) + (e[0][1] + e[1][1]),
                 (c[0][2] + c[1][2]) + (e[0][2] + e[1][2]), (c[0][3] + c[1][3]) + (e[0][3] + e[1][3]));
            if (w == 0) PROFT(7);
            SFENCE();
            tile(1, c, c);
            SFENCE();
            tile(2, e, e);
            emit(rp + 12288, c[0][0] + c[1][0], c[0][1] + c[1][1], c[0][2] + c[1][2], c[0][3] + c[1][3]);
            if (four) tile(3, c, c);
            emit(rp + 24576, e[0][0] + e[1][0], e[0][1] + e[1][1], e[0][2] + e[1][2], e[0][3] + e[1][3]);
            if (four) emit(rp + t3off, c[0][0] + c[1][0], c[0][1] + c[1][1], c[0][2] + c[1][2], c[0][3] + c[1][3]);
            const uint32_t tr = clk();
            bar_arrive(NB_WIN, 384);
            if (w == 0) PROFT(8);
            u64 y[20];
            uint32_t b[20];
            while (clk() - tr < (uint32_t)delay) {}
#pragma unroll
            for (int i = 0; i < 10; i++) ld_acc0(y[2 * i], y[2 * i + 1], lp + (i >> 1) * 8192 + (i & 1) * 1024);
            if (w == 0) PROFT(9);
            for (uint32_t n = 0;; n++) {
                uint32_t ok = 32u;
#pragma unroll
                for (int it = 0; it < 5; it++) {
#pragma unroll
                    for (int j = 0; j < 4; j++) {
                        const u64 z = y[4 * it + j];
                        b[4 * it + j] = pack2((float)(int)(uint32_t)z, (float)(int)(uint32_t)(z >> 32));
                        ok &= (uint32_t)z;
                    }
                    sts128(l16 + OFF_MEMB + (it * 4 + w) * 512, b[4 * it], b[4 * it + 1], b[4 * it + 2], b[4 * it + 3]);
                    SFENCE();
                }
                if (__all_sync(~0u, ok)) break;
                if (n > SPIN_LIMIT) __trap();
#pragma unroll
                for (int i = 0; i < 10; i++) ld_acc(y[2 * i], y[2 * i + 1], lp + (i >> 1) * 8192 + (i & 1) * 1024);
            }
            bar_arrive(NB_MEM, 384);
            if (w == 0) PROFT(11);
            amax = b[0];
#pragma unroll
            for (int i = 1; i < 20; i++) amax = absmax2(amax, b[i]);
            const int adv = pb ? 40960 - 128 : 128;
            rp += adv; lp += adv;
        }
        if (t0 && rank < 2) mbar_expect(bar + 8 * (B_VX + 1), 10240);
    } else {
        asm volatile("setmaxnreg.dec.sync.aligned.u32 40;");
        const int w = warp - 12;
        const bool t0 = tid == 384;
        if (t0) {
            for (int n = 0; n < 2; n++) {
                mbar_expect(bar + 8 * (B_XT + n), 40960);
                bulk_g2s(sb + OFF_X + n * 40960, g_xn + n * 40960, 40960, bar + 8 * (B_XT + n));
            }
        }
        if (rank == 2) {
            if (w == 0) {
                for (int s = 0; s < NSEG; s++) {
                    const int pb = s & 1, ph = (s >> 1) & 1;
                    mbar_wait(bar + 8 * (B_KX + pb), ph);
                    if (lane < 2) bulk_s2s(mapa(sb + OFF_VX + pb * 8192, lane), sb + OFF_VX + pb * 8192, 8192, mapa(bar + 8 * (B_VX + pb), lane));
                    mbar_wait(bar + 8 * (B_KM + pb), ph);
                    if (t0 && s + 2 < NSEG) {
                        mbar_expect(bar + 8 * (B_XT + pb), 40960);
                        bulk_g2s(sb + OFF_X + pb * 40960, g_xn + (s + 2) * 40960, 40960, bar + 8 * (B_XT + pb));
                    }
                }
            }
        } else {
            const uint32_t l16 = sb + lane * 16;
            if (w < 2) sts32(sb + OFF_PT + w * 768 + 640 + lane * 4, 0u);
            for (int s = 0; s < NSEG; s++) {
                const int pb = s & 1, ph = (s >> 1) & 1;
                if (t0) mbar_expect(bar + 8 * B_PXF, rank ? 5120 : 3072);
                mbar_wait(bar + 8 * (B_KM + pb), ph);
                if (w == 0) PROFT(12);
                float c[2][4];
#pragma unroll
                for (int t = 0; t < 2; t++) {
                    const int mt = w == 0 ? 0 : (w == 1 ? t : 1);
                    const int tg = w == 1 ? 0 : (w == 3 ? 3 + t : 1 + t);
                    const uint32_t qa = l16 + OFF_Q + pb * 5120 + (1 + 2 * mt) * 1024;
                    const uint32_t ka = l16 + OFF_K + pb * 5120 + tg * 1024;
                    c[t][0] = c[t][1] = c[t][2] = c[t][3] = 0.f;
#pragma unroll
                    for (int j = 0; j < 2; j++) {
                        uint32_t f0[4], f1[4], kf[4];
                        ldsm4(f0, qa + j * 512); ldsm4(f1, qa + 1024 + j * 512); ldsm4(kf, ka + j * 512);
                        mma16(c[t], f0[0], f1[0], f0[1], f1[1], kf[0], kf[1]);
                        mma16(c[t], f0[2], f1[2], f0[3], f1[3], kf[2], kf[3]);
                    }
                }
                if (t0) {
                    if (s + 2 < NSEG) {
                        mbar_expect(bar + 8 * (B_XT + pb), 40960);
                        bulk_g2s(sb + OFF_X + pb * 40960, g_xn + (s + 2) * 40960, 40960, bar + 8 * (B_XT + pb));
                    }
                    asm volatile("cp.async.bulk.wait_group.read 0;" ::: "memory");
                }
                if (s >= 1) mbar_wait(bar + 8 * B_PXE, pb ^ 1);
                if (s < NSEG - 1) mbar_wait(bar + 8 * (B_X1 + pb), ph);
#pragma unroll
                for (int t = 0; t < 2; t++) {
                    const int mt = w == 0 ? 0 : (w == 1 ? t : 1);
                    const int nt = w == 1 ? 4 : (w == 3 ? 2 + t : t);
                    st_async4(mapa(l16 + OFF_PX + rank * 2560 + nt * 512, mt), __float_as_uint(c[t][0]), __float_as_uint(c[t][1]),
                              __float_as_uint(c[t][2]), __float_as_uint(c[t][3]), mapa(bar + 8 * B_PXF, mt));
                }
                if (w < 2) {
                    mbar_wait(bar + 8 * B_PXF, pb);
                    if (w == 0) PROFT(13);
                    const int tq = 16 * rank + 8 * w + g;
                    float sc[10];
#pragma unroll
                    for (int nt = 0; nt < 5; nt++) {
                        float u0, u1, v0, v1;
                        lds64f(u0, u1, l16 + OFF_PX + nt * 512 + w * 8);
                        lds64f(v0, v1, l16 + OFF_PX + 2560 + nt * 512 + w * 8);
                        sc[2 * nt] = (nt == 4 || 8 * nt + 2 * q <= tq) ? (u0 + v0) * SM_SCALE : -INFINITY;
                        sc[2 * nt + 1] = (nt == 4 || 8 * nt + 2 * q + 1 <= tq) ? (u1 + v1) * SM_SCALE : -INFINITY;
                    }
                    float mx = sc[0];
#pragma unroll
                    for (int i = 1; i < 10; i++) mx = fmaxf(mx, sc[i]);
                    mx = fmaxf(mx, __shfl_xor_sync(~0u, mx, 1));
                    mx = fmaxf(mx, __shfl_xor_sync(~0u, mx, 2));
                    if (lane == 0) mbar_arrive_remote(mapa(bar + 8 * B_PXE, rank ^ 1));
                    float sum = 0.f;
#pragma unroll
                    for (int i = 0; i < 10; i++) { sc[i] = ex2(sc[i] - mx); sum += sc[i]; }
                    sum += __shfl_xor_sync(~0u, sum, 1);
                    sum += __shfl_xor_sync(~0u, sum, 2);
                    sum = rcp(sum);
#pragma unroll
                    for (int nt = 0; nt < 5; nt++) sts32(sb + OFF_PT + w * 768 + nt * 128 + lane * 4, pack2(sc[2 * nt] * sum, sc[2 * nt + 1] * sum));
                }
                mbar_wait(bar + 8 * (B_VX + pb), ph);
                fence_async();
                bar_sync(NB_X, 128);
                if (s < NSEG - 1) mbar_wait(bar + 8 * (B_WN + pb), ph);
#pragma unroll 1
                for (int m = 0; m < 2; m++) {
                    float acc[8];
                    const u64 dv = mkdesc(sb + OFF_VX + pb * 8192 + m * 4096, 128, 512), dp = mkdesc(sb + OFF_PT, 128, 768);
                    wg_fence();
                    wgmma_n16_ss<0>(acc, dv, dp);
                    wgmma_n16_ss<1>(acc, dv + 16, dp + 16);
                    wgmma_n16_ss<1>(acc, mkdesc(sb + OFF_VM + pb * 2048 + m * 1024, 0, 128), dp + 32);
                    wg_commit();
                    wg_wait<0>();
                    const uint32_t oa = sb + OFF_OST + (8 * m + 2 * w + (g >> 2)) * 128 + q * 32 + (g & 3) * 4;
#pragma unroll
                    for (int nt = 0; nt < 2; nt++) {
                        sts32(oa + nt * 2048, pack2(acc[4 * nt], acc[4 * nt + 2]));
                        sts32(oa + nt * 2048 + 16, pack2(acc[4 * nt + 1], acc[4 * nt + 3]));
                    }
                }
                fence_async();
                bar_sync(NB_X, 128);
                if (t0) {
                    bulk_s2g(g_o + (size_t)(s * H_ + h) * 8192 + rank * 4096, sb + OFF_OST, 4096);
                    asm volatile("cp.async.bulk.commit_group;" ::: "memory");
                }
                if (lane < 2) mbar_arrive_remote(mapa(bar + 8 * (B_XD + pb), lane ? 2 : rank));
                if (w == 0) PROFT(14);
            }
            if (t0) asm volatile("cp.async.bulk.wait_group 0;" ::: "memory");
        }
    }
    __syncwarp();
    if (lane < 3) mbar_arrive_remote(mapa(bar + 8 * B_FIN, lane));
    mbar_wait(bar + 8 * B_FIN, 0);
}

int g_delay = 700, g_layers = 2;

void launch_rec(const bf16* mem0, const bf16* Wq, const bf16* Wk, const bf16* Wv, const bf16* Wo, int layer) {
    cudaLaunchConfig_t c = {};
    c.gridDim = dim3(96); c.blockDim = dim3(512); c.dynamicSmemBytes = rec::SMEM; c.stream = cudaStreamPerThread;
    cudaLaunchAttribute at[1];
    at[0].id = cudaLaunchAttributeClusterDimension; at[0].val.clusterDim.x = 3; at[0].val.clusterDim.y = 1; at[0].val.clusterDim.z = 1;
    c.attrs = at; c.numAttrs = 1;
    cudaLaunchKernelEx(&c, rec_kernel, mem0, Wq, Wk, Wv, Wo, layer, g_delay);
}

}

extern "C" void kernel_launch(void* const* d_in, const int* in_sizes, int n_in, void* d_out, int out_size) {
    const bf16* x = (const bf16*)d_in[0];
    const bf16* mem0 = (const bf16*)d_in[1];
    const bf16* Wq = (const bf16*)d_in[2];
    const bf16* Wk = (const bf16*)d_in[3];
    const bf16* Wv = (const bf16*)d_in[4];
    const bf16* Wo = (const bf16*)d_in[5];
    const bf16* wr = (const bf16*)d_in[8];
    const bf16* wi = (const bf16*)d_in[9];
    cudaFuncSetAttribute(rec_kernel, cudaFuncAttributeMaxDynamicSharedMemorySize, rec::SMEM);
    cudaFuncSetAttribute(outproj_kernel, cudaFuncAttributeMaxDynamicSharedMemorySize, op::SMEM);
    cudaFuncSetAttribute(colfft_kernel, cudaFuncAttributeMaxDynamicSharedMemorySize, CF_SMEM);
    bf16 *x1, *x2;
    cudaGetSymbolAddress((void**)&x1, g_x1);
    cudaGetSymbolAddress((void**)&x2, g_x2);
    cudaStream_t st = cudaStreamPerThread;
    prep_kernel<<<128, 512, 0, st>>>(x, Wv, Wo);
    tables_kernel<<<128, 512, 0, st>>>(Wo, wr, wi);
    for (int layer = 0; layer < g_layers; layer++) {
        launch_rec(mem0, Wq, Wk, Wv, Wo, layer);
        outproj_kernel<<<128, 288, op::SMEM, st>>>(layer ? x2 : x, x1);
        rowfft_kernel<<<128, 256, 0, st>>>(x1);
        colfft_kernel<<<107, 384, CF_SMEM, st>>>();
        rowifft_kernel<<<128, 256, 0, st>>>(x1, layer ? (bf16*)d_out : x2, layer);
    }
}
```

```cpp
#include <cuda_runtime.h>
#include <cuda_bf16.h>
#include <stdint.h>

#define DEV __device__ __forceinline__
typedef unsigned long long u64;
typedef __nv_bfloat16 bf16;

namespace {

constexpr int S_ = 2048, D_ = 640, H_ = 32, E_ = 128, NSEG = 64;

__device__ __align__(1024) unsigned char g_xn[S_ * D_ * 2];
__device__ __align__(1024) unsigned char g_o[S_ * H_ * E_ * 2];
constexpr int ACC_LAYER = 32 * 5120;
__device__ __align__(4096) u64 g_acc[2 * ACC_LAYER];
__device__ __align__(16) float g_nrm[256];
__device__ __align__(1024) unsigned char g_wop[H_ * E_ * D_ * 2];
__device__ __align__(1024) bf16 g_x1[S_ * D_];
__device__ __align__(1024) bf16 g_x2[S_ * D_];
constexpr int NCOL = 321;
__device__ __align__(1024) unsigned char g_z[NCOL * 8192];
__device__ __align__(1024) unsigned char g_wt[NCOL * 8192];
__device__ __align__(1024) uint4 g_f128[2 * 8 * 256];
__device__ __align__(1024) uint4 g_f64[2 * 4 * 128];
__device__ __align__(1024) bf16 g_g32[2 * 4096];

DEV uint32_t s2u(const void* p) { return (uint32_t)__cvta_generic_to_shared(p); }
DEV uint32_t clk() { uint32_t c; asm volatile("mov.u32 %0,%%clock;" : "=r"(c)::"memory"); return c; }
DEV uint32_t mapa(uint32_t a, uint32_t r) { uint32_t o; asm("mapa.shared::cluster.u32 %0,%1,%2;" : "=r"(o) : "r"(a), "r"(r)); return o; }
DEV void mbar_init(uint32_t b, uint32_t n) { asm volatile("mbarrier.init.shared::cta.b64 [%0],%1;" ::"r"(b), "r"(n) : "memory"); }
DEV bool mbar_try(uint32_t b, uint32_t par) {
    uint32_t ok;
    asm volatile("{.reg .pred p; mbarrier.try_wait.parity.shared::cta.b64 p,[%1],%2; selp.u32 %0,1,0,p;}" : "=r"(ok) : "r"(b), "r"(par) : "memory");
    return ok;
}
constexpr uint32_t SPIN_LIMIT = 1u << 18;
DEV void mbar_wait(uint32_t b, uint32_t par) {
    uint32_t n = 0;
    while (!mbar_try(b, par)) if (++n > SPIN_LIMIT) __trap();
}
DEV uint32_t opaque(uint32_t x) { return __shfl_xor_sync(~0u, x, 0); }
#define SFENCE() asm volatile("{.reg .pred p; setp.ne.u32 p,%1,0; @p mov.u32 %0,%%clock;}" : "+r"(sfd) : "r"((uint32_t)never) : "memory")
DEV void mbar_arrive(uint32_t b) { asm volatile("mbarrier.arrive.shared::cta.b64 _,[%0];" ::"r"(b) : "memory"); }
DEV void mbar_arrive_elect(uint32_t b) { asm volatile("{.reg .pred p; elect.sync _|p, 0xffffffff; @p mbarrier.arrive.shared::cta.b64 _,[%0];}" ::"r"(b) : "memory"); }
DEV void mbar_arrive_remote(uint32_t b) { asm volatile("mbarrier.arrive.shared::cluster.b64 _,[%0];" ::"r"(b) : "memory"); }
DEV void mbar_expect(uint32_t b, uint32_t tx) { asm volatile("mbarrier.arrive.expect_tx.shared::cta.b64 _,[%0],%1;" ::"r"(b), "r"(tx) : "memory"); }
DEV void bar_sync(int id, int n) { asm volatile("bar.sync %0,%1;" ::"r"(id), "r"(n) : "memory"); }
DEV void bar_arrive(int id, int n) { asm volatile("bar.arrive %0,%1;" ::"r"(id), "r"(n) : "memory"); }
template <int ID, int N> DEV void bar_arrive_if(bool p) {
    asm volatile("{.reg .pred p; setp.ne.u32 p,%0,0; @p bar.arrive %1,%2;}" ::"r"((uint32_t)p), "n"(ID), "n"(N) : "memory");
}
DEV void st_async1(uint32_t a, uint32_t x, uint32_t b) {
    asm volatile("st.async.shared::cluster.mbarrier::complete_tx::bytes.u32 [%0],%1,[%2];" ::"r"(a), "r"(x), "r"(b) : "memory");
}
DEV void st_async2(uint32_t a, uint32_t x, uint32_t y, uint32_t b) {
    asm volatile("st.async.shared::cluster.mbarrier::complete_tx::bytes.v2.u32 [%0],{%1,%2},[%3];" ::"r"(a), "r"(x), "r"(y), "r"(b) : "memory");
}
DEV void st_async4(uint32_t a, uint32_t x, uint32_t y, uint32_t z, uint32_t w, uint32_t b) {
    asm volatile("st.async.shared::cluster.mbarrier::complete_tx::bytes.v4.u32 [%0],{%1,%2,%3,%4},[%5];" ::"r"(a), "r"(x), "r"(y), "r"(z), "r"(w), "r"(b) : "memory");
}
DEV void bulk_g2s(uint32_t dst, const void* src, uint32_t bytes, uint32_t b) {
    asm volatile("cp.async.bulk.shared::cluster.global.mbarrier::complete_tx::bytes [%0],[%1],%2,[%3];" ::"r"(dst), "l"(src), "r"(bytes), "r"(b) : "memory");
}
DEV void bulk_s2s(uint32_t dst, uint32_t src, uint32_t bytes, uint32_t b) {
    asm volatile("cp.async.bulk.shared::cluster.shared::cta.mbarrier::complete_tx::bytes [%0],[%1],%2,[%3];" ::"r"(dst), "r"(src), "r"(bytes), "r"(b) : "memory");
}
DEV void bulk_s2g(void* dst, uint32_t src, uint32_t bytes) {
    asm volatile("cp.async.bulk.global.shared::cta.bulk_group [%0],[%1],%2;" ::"l"(dst), "r"(src), "r"(bytes) : "memory");
}
DEV void cp16(uint32_t dst, const void* src) { asm volatile("cp.async.cg.shared.global [%0],[%1],16;" ::"r"(dst), "l"(src) : "memory"); }
DEV void cp_commit() { asm volatile("cp.async.commit_group;" ::: "memory"); }
template <int N> DEV void cp_wait() { asm volatile("cp.async.wait_group %0;" ::"n"(N) : "memory"); }
DEV uint32_t lds32(uint32_t a) { uint32_t x; asm volatile("ld.shared.u32 %0,[%1];" : "=r"(x) : "r"(a) : "memory"); return x; }
DEV void fence_async() { asm volatile("fence.proxy.async.shared::cta;" ::: "memory"); }
DEV uint32_t pack2(float lo, float hi) { uint32_t r; asm("cvt.rn.bf16x2.f32 %0,%1,%2;" : "=r"(r) : "f"(hi), "f"(lo)); return r; }
DEV uint32_t prmt(uint32_t a, uint32_t b, uint32_t s) { uint32_t r; asm("prmt.b32 %0,%1,%2,%3;" : "=r"(r) : "r"(a), "r"(b), "r"(s)); return r; }
DEV float ex2(float x) { float r; asm("ex2.approx.ftz.f32 %0,%1;" : "=f"(r) : "f"(x)); return r; }
DEV float rcp(float x) { float r; asm("rcp.approx.ftz.f32 %0,%1;" : "=f"(r) : "f"(x)); return r; }
DEV void lds128(uint32_t* r, uint32_t a) { asm volatile("ld.shared.v4.u32 {%0,%1,%2,%3},[%4];" : "=r"(r[0]), "=r"(r[1]), "=r"(r[2]), "=r"(r[3]) : "r"(a) : "memory"); }
DEV void lds64(uint32_t* r, uint32_t a) { asm volatile("ld.shared.v2.u32 {%0,%1},[%2];" : "=r"(r[0]), "=r"(r[1]) : "r"(a) : "memory"); }
DEV void lds64f(float& x, float& y, uint32_t a) { asm volatile("ld.shared.v2.f32 {%0,%1},[%2];" : "=f"(x), "=f"(y) : "r"(a) : "memory"); }
DEV void lds128f(float* r, uint32_t a) { asm volatile("ld.shared.v4.f32 {%0,%1,%2,%3},[%4];" : "=f"(r[0]), "=f"(r[1]), "=f"(r[2]), "=f"(r[3]) : "r"(a) : "memory"); }
DEV void sts128(uint32_t a, uint32_t x, uint32_t y, uint32_t z, uint32_t w) { asm volatile("st.shared.v4.u32 [%0],{%1,%2,%3,%4};" ::"r"(a), "r"(x), "r"(y), "r"(z), "r"(w) : "memory"); }
DEV void sts64(uint32_t a, uint32_t x, uint32_t y) { asm volatile("st.shared.v2.u32 [%0],{%1,%2};" ::"r"(a), "r"(x), "r"(y) : "memory"); }
DEV void sts32(uint32_t a, uint32_t x) { asm volatile("st.shared.u32 [%0],%1;" ::"r"(a), "r"(x) : "memory"); }
DEV void ldsm4(uint32_t* r, uint32_t a) { asm volatile("ldmatrix.sync.aligned.m8n8.x4.shared.b16 {%0,%1,%2,%3},[%4];" : "=r"(r[0]), "=r"(r[1]), "=r"(r[2]), "=r"(r[3]) : "r"(a) : "memory"); }
DEV void ldsm2(uint32_t* r, uint32_t a) { asm volatile("ldmatrix.sync.aligned.m8n8.x2.shared.b16 {%0,%1},[%2];" : "=r"(r[0]), "=r"(r[1]) : "r"(a) : "memory"); }
DEV void stsm4t(uint32_t a, uint32_t x, uint32_t y, uint32_t z, uint32_t w) { asm volatile("stmatrix.sync.aligned.m8n8.x4.trans.shared.b16 [%0],{%1,%2,%3,%4};" ::"r"(a), "r"(x), "r"(y), "r"(z), "r"(w) : "memory"); }
DEV void stsm4(uint32_t a, uint32_t x, uint32_t y, uint32_t z, uint32_t w) { asm volatile("stmatrix.sync.aligned.m8n8.x4.shared.b16 [%0],{%1,%2,%3,%4};" ::"r"(a), "r"(x), "r"(y), "r"(z), "r"(w) : "memory"); }
DEV void stsm2(uint32_t a, uint32_t x, uint32_t y) { asm volatile("stmatrix.sync.aligned.m8n8.x2.shared.b16 [%0],{%1,%2};" ::"r"(a), "r"(x), "r"(y) : "memory"); }
DEV void stsm2t(uint32_t a, uint32_t x, uint32_t y) { asm volatile("stmatrix.sync.aligned.m8n8.x2.trans.shared.b16 [%0],{%1,%2};" ::"r"(a), "r"(x), "r"(y) : "memory"); }
DEV void mma16(float* d, uint32_t a0, uint32_t a1, uint32_t a2, uint32_t a3, uint32_t b0, uint32_t b1) {
    asm volatile("mma.sync.aligned.m16n8k16.row.col.f32.bf16.bf16.f32 {%0,%1,%2,%3},{%4,%5,%6,%7},{%8,%9},{%0,%1,%2,%3};"
                 : "+f"(d[0]), "+f"(d[1]), "+f"(d[2]), "+f"(d[3]) : "r"(a0), "r"(a1), "r"(a2), "r"(a3), "r"(b0), "r"(b1));
}
DEV void mma8(float* d, uint32_t a0, uint32_t a1, uint32_t b0) {
    asm volatile("mma.sync.aligned.m16n8k8.row.col.f32.bf16.bf16.f32 {%0,%1,%2,%3},{%4,%5},{%6},{%0,%1,%2,%3};"
                 : "+f"(d[0]), "+f"(d[1]), "+f"(d[2]), "+f"(d[3]) : "r"(a0), "r"(a1), "r"(b0));
}
DEV u64 mkdesc(uint32_t a, uint32_t lbo, uint32_t sbo) { return (u64)((a & 0x3ffff) >> 4) | ((u64)(lbo >> 4) << 16) | ((u64)(sbo >> 4) << 32); }
DEV void wg_fence() { asm volatile("wgmma.fence.sync.aligned;" ::: "memory"); }
DEV void wg_commit() { asm volatile("wgmma.commit_group.sync.aligned;" ::: "memory"); }
template <int N> DEV void wg_wait() { asm volatile("wgmma.wait_group.sync.aligned %0;" ::"n"(N) : "memory"); }
template <int ACC> DEV void wgmma_n32_rs(float* d, const uint32_t* a, u64 desc) {
    asm volatile("wgmma.mma_async.sync.aligned.m64n32k16.f32.bf16.bf16 {%0,%1,%2,%3,%4,%5,%6,%7,%8,%9,%10,%11,%12,%13,%14,%15},{%16,%17,%18,%19},%20,%21,1,1,0;"
                 : "+f"(d[0]), "+f"(d[1]), "+f"(d[2]), "+f"(d[3]), "+f"(d[4]), "+f"(d[5]), "+f"(d[6]), "+f"(d[7]),
                   "+f"(d[8]), "+f"(d[9]), "+f"(d[10]), "+f"(d[11]), "+f"(d[12]), "+f"(d[13]), "+f"(d[14]), "+f"(d[15])
                 : "r"(a[0]), "r"(a[1]), "r"(a[2]), "r"(a[3]), "l"(desc), "n"(ACC));
}
template <int ACC> DEV void wgmma_n32_ss(float* d, u64 da, u64 desc) {
    asm volatile("wgmma.mma_async.sync.aligned.m64n32k16.f32.bf16.bf16 {%0,%1,%2,%3,%4,%5,%6,%7,%8,%9,%10,%11,%12,%13,%14,%15},%16,%17,%18,1,1,0,0;"
                 : "+f"(d[0]), "+f"(d[1]), "+f"(d[2]), "+f"(d[3]), "+f"(d[4]), "+f"(d[5]), "+f"(d[6]), "+f"(d[7]),
                   "+f"(d[8]), "+f"(d[9]), "+f"(d[10]), "+f"(d[11]), "+f"(d[12]), "+f"(d[13]), "+f"(d[14]), "+f"(d[15])
                 : "l"(da), "l"(desc), "n"(ACC));
}
template <int ACC> DEV void wgmma_n16_ss(float* d, u64 da, u64 desc) {
    asm volatile("wgmma.mma_async.sync.aligned.m64n16k16.f32.bf16.bf16 {%0,%1,%2,%3,%4,%5,%6,%7},%8,%9,%10,1,1,0,0;"
                 : "+f"(d[0]), "+f"(d[1]), "+f"(d[2]), "+f"(d[3]), "+f"(d[4]), "+f"(d[5]), "+f"(d[6]), "+f"(d[7])
                 : "l"(da), "l"(desc), "n"(ACC));
}
#define ACC8(o) "+f"(d[o]), "+f"(d[o + 1]), "+f"(d[o + 2]), "+f"(d[o + 3]), "+f"(d[o + 4]), "+f"(d[o + 5]), "+f"(d[o + 6]), "+f"(d[o + 7])
template <int ACC, int TB> DEV void wgmma_n64_rs(float* d, const uint32_t* a, u64 desc) {
    asm volatile("wgmma.mma_async.sync.aligned.m64n64k16.f32.bf16.bf16 {%0,%1,%2,%3,%4,%5,%6,%7,%8,%9,%10,%11,%12,%13,%14,%15,"
                 "%16,%17,%18,%19,%20,%21,%22,%23,%24,%25,%26,%27,%28,%29,%30,%31},{%32,%33,%34,%35},%36,%37,1,1,%38;"
                 : ACC8(0), ACC8(8), ACC8(16), ACC8(24) : "r"(a[0]), "r"(a[1]), "r"(a[2]), "r"(a[3]), "l"(desc), "n"(ACC), "n"(TB));
}
template <int ACC, int TB> DEV void wgmma_n80_rs(float* d, const uint32_t* a, u64 desc) {
    asm volatile("wgmma.mma_async.sync.aligned.m64n80k16.f32.bf16.bf16 {%0,%1,%2,%3,%4,%5,%6,%7,%8,%9,%10,%11,%12,%13,%14,%15,"
                 "%16,%17,%18,%19,%20,%21,%22,%23,%24,%25,%26,%27,%28,%29,%30,%31,%32,%33,%34,%35,%36,%37,%38,%39},{%40,%41,%42,%43},%44,%45,1,1,%46;"
                 : ACC8(0), ACC8(8), ACC8(16), ACC8(24), ACC8(32) : "r"(a[0]), "r"(a[1]), "r"(a[2]), "r"(a[3]), "l"(desc), "n"(ACC), "n"(TB));
}
template <int TB> DEV void wgmma_n80_ss(float* d, u64 da, u64 desc) {
    asm volatile("wgmma.mma_async.sync.aligned.m64n80k16.f32.bf16.bf16 {%0,%1,%2,%3,%4,%5,%6,%7,%8,%9,%10,%11,%12,%13,%14,%15,"
                 "%16,%17,%18,%19,%20,%21,%22,%23,%24,%25,%26,%27,%28,%29,%30,%31,%32,%33,%34,%35,%36,%37,%38,%39},%40,%41,1,1,1,0,%42;"
                 : ACC8(0), ACC8(8), ACC8(16), ACC8(24), ACC8(32) : "l"(da), "l"(desc), "n"(TB));
}
template <int ACC> DEV void wgmma_n40_ss(float* d, u64 da, u64 desc) {
    asm volatile("wgmma.mma_async.sync.aligned.m64n40k16.f32.bf16.bf16 {%0,%1,%2,%3,%4,%5,%6,%7,%8,%9,%10,%11,%12,%13,%14,%15,%16,%17,%18,%19},%20,%21,%22,1,1,0,0;"
                 : ACC8(0), ACC8(8), "+f"(d[16]), "+f"(d[17]), "+f"(d[18]), "+f"(d[19]) : "l"(da), "l"(desc), "n"(ACC));
}
DEV void pdl_wait() { asm volatile("griddepcontrol.wait;" ::: "memory"); }
DEV void pdl_launch() { asm volatile("griddepcontrol.launch_dependents;" ::: "memory"); }
DEV uint32_t ldg32(const void* p) { uint32_t v; asm volatile("ld.global.nc.u32 %0,[%1];" : "=r"(v) : "l"(p)); return v; }
DEV void ld_acc(u64& a, u64& b, const void* p) {
    const uint32_t done = (uint32_t)a & (uint32_t)b & 32u;
    asm volatile("{.reg .pred p; setp.eq.u32 p,%3,0;\n"
                 "@p ld.relaxed.gpu.global.v2.u64 {%0,%1},[%2];}" : "+l"(a), "+l"(b) : "l"(p), "r"(done) : "memory");
}
DEV void ld_acc0(u64& a, u64& b, const void* p) {
    asm volatile("ld.relaxed.gpu.global.v2.u64 {%0,%1},[%2];" : "=l"(a), "=l"(b) : "l"(p) : "memory");
}
DEV uint32_t and3(uint32_t a, uint32_t b, uint32_t c) { uint32_t r; asm volatile("lop3.b32 %0,%1,%2,%3,0x80;" : "=r"(r) : "r"(a), "r"(b), "r"(c)); return r; }
DEV uint32_t absmax2(uint32_t a, uint32_t b) { uint32_t r; asm("max.xorsign.abs.bf16x2 %0,%1,%2;" : "=r"(r) : "r"(a), "r"(b)); return r; }
DEV float lds32f(uint32_t a) { float x; asm volatile("ld.shared.f32 %0,[%1];" : "=f"(x) : "r"(a) : "memory"); return x; }
DEV void red_add64(u64* p, uint32_t lo, uint32_t hi) {
    asm volatile("{.reg .b64 v; mov.b64 v,{%1,%2}; red.relaxed.gpu.global.add.u64 [%0],v;}" ::"l"(p), "r"(lo), "r"(hi) : "memory");
}
DEV float bf_round(float x) { return __bfloat162float(__float2bfloat16_rn(x)); }
DEV float bf_lo(uint32_t u) { return __uint_as_float(u << 16); }
DEV float bf_hi(uint32_t u) { return __uint_as_float(u & 0xffff0000u); }

#define GPROF(i, n)
#define PROFT(i)
#define STAMP(i)

DEV void ln_row(float (&v)[3][8], int lane) {
    float s = 0.f;
#pragma unroll
    for (int c = 0; c < 3; c++)
#pragma unroll
        for (int j = 0; j < 8; j++) s += v[c][j];
#pragma unroll
    for (int o = 16; o; o >>= 1) s += __shfl_xor_sync(~0u, s, o);
    float mean = s * (1.f / D_), q = 0.f;
#pragma unroll
    for (int c = 0; c < 3; c++)
        if (c < 2 || lane < 16)
#pragma unroll
            for (int j = 0; j < 8; j++) { float d = v[c][j] - mean; q += d * d; }
#pragma unroll
    for (int o = 16; o; o >>= 1) q += __shfl_xor_sync(~0u, q, o);
    float mb = bf_round(mean);
    float sd = bf_round(sqrtf(bf_round(bf_round(q * (1.f / D_)) + 1e-5f)));
#pragma unroll
    for (int c = 0; c < 3; c++)
#pragma unroll
        for (int j = 0; j < 8; j++) v[c][j] = bf_round(v[c][j] - mb) / sd;
}

__global__ void __launch_bounds__(512) prep_kernel(const bf16* __restrict__ x, const bf16* __restrict__ Wv, const bf16* __restrict__ Wo) {
    __shared__ float red[32];
    const int tid = threadIdx.x, lane = tid & 31, warp = tid >> 5, b = blockIdx.x;
    {
        int row = b * 16 + warp;
        float v[3][8];
#pragma unroll
        for (int c = 0; c < 3; c++) {
            uint4 u = make_uint4(0, 0, 0, 0);
            if (c < 2 || lane < 16) u = *(const uint4*)(x + row * D_ + (c * 32 + lane) * 8);
            v[c][0] = bf_lo(u.x); v[c][1] = bf_hi(u.x); v[c][2] = bf_lo(u.y); v[c][3] = bf_hi(u.y);
            v[c][4] = bf_lo(u.z); v[c][5] = bf_hi(u.z); v[c][6] = bf_lo(u.w); v[c][7] = bf_hi(u.w);
        }
        ln_row(v, lane);
#pragma unroll
        for (int c = 0; c < 3; c++)
            if (c < 2 || lane < 16)
                *(uint4*)(g_xn + (row >> 5) * 40960 + (c * 32 + lane) * 512 + (row & 31) * 16) =
                    make_uint4(pack2(v[c][0], v[c][1]), pack2(v[c][2], v[c][3]), pack2(v[c][4], v[c][5]), pack2(v[c][6], v[c][7]));
    }
    for (int i = b * 512 + tid; i < ACC_LAYER; i += 128 * 512) ((uint4*)g_acc)[i] = make_uint4(0, 0, 0, 0);
    float sv = 0.f;
#pragma unroll
    for (int i = 0; i < 5; i++) {
        uint4 u = *(const uint4*)(Wv + (size_t)((b & 3) * 160 + i * 32 + (tid >> 4)) * 4096 + (b >> 2) * E_ + (tid & 15) * 8);
        uint32_t w[4] = {u.x, u.y, u.z, u.w};
#pragma unroll
        for (int j = 0; j < 4; j++) { float a = bf_lo(w[j]), c = bf_hi(w[j]); sv += a * a + c * c; }
    }
    float so = 0.f;
    if (tid < 320) {
        float s0 = 0.f, s1 = 0.f;
#pragma unroll 8
        for (int r = 0; r < 32; r++) { uint32_t u = *(const uint32_t*)(Wo + (size_t)(b * 32 + r) * D_ + tid * 2); float a = bf_lo(u), c = bf_hi(u); s0 += a * a; s1 += c * c; }
        so = fmaxf(s0, s1);
    }
#pragma unroll
    for (int o = 16; o; o >>= 1) { sv += __shfl_xor_sync(~0u, sv, o); so = fmaxf(so, __shfl_xor_sync(~0u, so, o)); }
    if (lane == 0) { red[warp] = sv; red[16 + warp] = so; }
    __syncthreads();
    if (tid == 0) {
        float a = 0.f, c = 0.f;
        for (int i = 0; i < 16; i++) { a += red[i]; c = fmaxf(c, red[16 + i]); }
        g_nrm[b] = a; g_nrm[128 + b] = c;
    }
}

__host__ __device__ constexpr int col_freq(int c) {
    return c == 320 ? 320 : c < 192 ? (c >> 6) * 128 + (c & 63) : c == 192 ? 192 : c < 256 ? 448 - c : c == 256 ? 64 : 384 - c;
}
DEV float rdft(int n, int k, int sn, int N) {
    float s, c;
    sincospif((float)((n * k) & (N - 1)) * (2.f / N), &s, &c);
    return !sn ? c : k ? s : (n & 1 ? -1.f : 1.f);
}
__global__ void __launch_bounds__(512) tables_kernel(const bf16* __restrict__ Wo, const bf16* __restrict__ wr, const bf16* __restrict__ wi) {
    const int tid = threadIdx.x, b = blockIdx.x;
#pragma unroll
    for (int i = 0; i < 5; i++) {
        const int idx = i * 512 + tid, r = (idx & 7) + 8 * (idx / 640), cg = (idx % 640) >> 3, e = (b & 3) * 32 + r;
        const uint4 v = *(const uint4*)(Wo + (size_t)(b * 32 + r) * D_ + cg * 8);
        *(uint4*)(g_wop + (size_t)((cg / 10) * H_ + (b >> 2)) * 20480 + (e >> 3) * 1280 + (cg % 10) * 128 + (e & 7) * 16) = v;
    }
    if (tid < NCOL) {
        const int ka = b >> 2, i = b & 3, kn = ka ? 2048 - ka : 32, kc = col_freq(tid);
        const unsigned short* pr = (const unsigned short*)wr + kc;
        const unsigned short* pi = (const unsigned short*)wi + kc;
#pragma unroll
        for (int q = 0; q < 4; q++) {
            uint32_t v[4];
#pragma unroll
            for (int j = 0; j < 4; j++) {
                const int k = ((j & 1 ? kn : ka) + 64 * (4 * (2 * i + (j >> 1)) + q)) & 2047;
                v[j] = pr[k * NCOL] | ((uint32_t)pi[k * NCOL] << 16);
            }
            *(uint4*)(g_wt + tid * 8192 + i * 2048 + (ka * 4 + q) * 16) = make_uint4(v[0], v[1], v[2], v[3]);
        }
    }
    const int gid = b * 512 + tid;
    if (gid < 4096) {
        const int inv = gid >> 11, ks = (gid >> 8) & 7, t = gid & 255, g = (t & 31) >> 2, q = t & 3, tile = t >> 5;
        uint32_t v[4];
#pragma unroll
        for (int j = 0; j < 4; j++) {
            float x[2];
#pragma unroll
            for (int u = 0; u < 2; u++) {
                const int m = inv ? 16 * tile + 2 * g + (j & 1) : 16 * ks + 8 * (j >> 1) + 2 * q + u;
                const int k2 = inv ? 8 * ks + 2 * q + u : 8 * tile + g, sn = inv ? j >> 1 : j & 1;
                x[u] = rdft(m, k2, sn, 128);
                if (sn && k2) x[u] = -x[u];
            }
            v[j] = pack2(x[0], x[1]);
        }
        g_f128[gid] = make_uint4(v[0], v[1], v[2], v[3]);
    } else if (gid < 5120) {
        const int id = gid - 4096, inv = id >> 9, ks = (id >> 7) & 3, t = id & 127, g = (t & 31) >> 2, q = t & 3, tile = t >> 5;
        uint32_t v[4];
#pragma unroll
        for (int j = 0; j < 4; j++) {
            float x[2];
#pragma unroll
            for (int u = 0; u < 2; u++) {
                const int a = inv ? 16 * tile + g + 8 * (j & 1) : 16 * ks + 8 * (j >> 1) + 2 * q + u;
                const int ka = inv ? 8 * ks + 2 * q + u : 8 * tile + g, sn = inv ? j >> 1 : j & 1;
                x[u] = rdft(a, ka, sn, 64);
            }
            v[j] = pack2(x[0], x[1]);
        }
        g_f64[id] = make_uint4(v[0], v[1], v[2], v[3]);
    } else if (gid < 5120 + 8192) {
        const int id = gid - 5120, inv = id >> 12, n = ((id >> 9) & 7) * 8 + ((id >> 3) & 7), k = ((id >> 6) & 7) * 8 + (id & 7);
        float s, c;
        sincospif((float)(((n >> 1) * (k >> 1)) & 31) * (1.f / 16), &s, &c);
        if (inv) s = -s;
        g_g32[id] = __float2bfloat16_rn((n & 1) == (k & 1) ? c : (k & 1) ? s : -s);
    }
}

namespace op {
constexpr int STAGE = 32768 + 20480, NST = 4, SMEM = NST * STAGE + 128;
}
__global__ void __launch_bounds__(288, 1) outproj_kernel(const bf16* __restrict__ x, bf16* __restrict__ x1) {
    using namespace op;
    extern __shared__ __align__(1024) unsigned char smem[];
    const uint32_t sb = s2u(smem), bar = sb + NST * STAGE;
    const int tid = threadIdx.x, lane = tid & 31, warp = __shfl_sync(~0u, tid >> 5, 0), mt = blockIdx.x >> 3, nt = blockIdx.x & 7;
    if (tid == 0) {
        for (int i = 0; i < NST; i++) { mbar_init(bar + 8 * i, 1); mbar_init(bar + 8 * (NST + i), 8); }
        asm volatile("fence.mbarrier_init.release.cluster;" ::: "memory");
    }
    __syncthreads();
    pdl_wait();
    pdl_launch();
    if (warp == 8) {
        if (lane == 0) {
            for (int h = 0; h < H_; h++) {
                const int st = h % NST;
                if (h >= NST) mbar_wait(bar + 8 * (NST + st), (h / NST - 1) & 1);
                mbar_expect(bar + 8 * st, STAGE);
                for (int i = 0; i < 4; i++) bulk_g2s(sb + st * STAGE + i * 8192, g_o + (size_t)((mt * 4 + i) * H_ + h) * 8192, 8192, bar + 8 * st);
                bulk_g2s(sb + st * STAGE + 32768, g_wop + (size_t)(nt * H_ + h) * 20480, 20480, bar + 8 * st);
            }
        }
    } else {
        float acc[40];
#pragma unroll
        for (int i = 0; i < 40; i++) acc[i] = 0.f;
        for (int h = 0; h < H_; h++) {
            const int st = h % NST;
            mbar_wait(bar + 8 * st, (h / NST) & 1);
            const u64 da = mkdesc(sb + st * STAGE + (warp >> 2) * 16384, 128, 2048), db = mkdesc(sb + st * STAGE + 32768, 1280, 128);
            wg_fence();
#pragma unroll
            for (int ks = 0; ks < 8; ks++) wgmma_n80_ss<1>(acc, da + ks * 16, db + ks * 160);
            wg_commit();
            if (h > 0) {
                wg_wait<1>();
                if (lane == 0) mbar_arrive(bar + 8 * (NST + (h - 1) % NST));
            }
        }
        wg_wait<0>();
        const int row = mt * 128 + warp * 16 + (lane >> 2), col = nt * 80 + 2 * (lane & 3);
#pragma unroll
        for (int t = 0; t < 10; t++)
#pragma unroll
            for (int j = 0; j < 2; j++) {
                const size_t o = (size_t)(row + 8 * j) * D_ + col + 8 * t;
                const uint32_t u = *(const uint32_t*)(x + o);
                *(uint32_t*)(x1 + o) = pack2(bf_lo(u) + bf_round(acc[4 * t + 2 * j]), bf_hi(u) + bf_round(acc[4 * t + 2 * j + 1]));
            }
    }
}

constexpr float C5A = 0.30901699437494742f, C5B = -0.80901699437494742f, S5A = 0.95105651629515357f, S5B = 0.58778525229247313f;
template <int SGN> DEV void dft5(const float (&tr)[5], const float (&ti)[5], float (&zr)[5], float (&zi)[5]) {
    const float ar = tr[1] + tr[4], ai = ti[1] + ti[4], br = tr[2] + tr[3], bi = ti[2] + ti[3];
    const float cr = tr[1] - tr[4], ci = ti[1] - ti[4], dr = tr[2] - tr[3], di = ti[2] - ti[3];
    zr[0] = tr[0] + ar + br; zi[0] = ti[0] + ai + bi;
    const float m1r = tr[0] + C5A * ar + C5B * br, m1i = ti[0] + C5A * ai + C5B * bi;
    const float m2r = tr[0] + C5B * ar + C5A * br, m2i = ti[0] + C5B * ai + C5A * bi;
    const float n1r = SGN * (S5A * cr + S5B * dr), n1i = SGN * (S5A * ci + S5B * di);
    const float n2r = SGN * (S5B * cr - S5A * dr), n2i = SGN * (S5B * ci - S5A * di);
    zr[1] = m1r + n1i; zi[1] = m1i - n1r; zr[4] = m1r - n1i; zi[4] = m1i + n1r;
    zr[2] = m2r + n2i; zi[2] = m2i - n2r; zr[3] = m2r - n2i; zi[3] = m2i + n2r;
}
DEV void ln40(float (&v)[40]) {
    float s = 0.f;
#pragma unroll
    for (int i = 0; i < 40; i++) s += v[i];
#pragma unroll
    for (int o = 8; o; o >>= 1) s += __shfl_xor_sync(~0u, s, o);
    const float mean = s * (1.f / D_);
    float q = 0.f;
#pragma unroll
    for (int i = 0; i < 40; i++) { const float d = v[i] - mean; q += d * d; }
#pragma unroll
    for (int o = 8; o; o >>= 1) q += __shfl_xor_sync(~0u, q, o);
    const float mb = bf_round(mean);
    const float inv = 1.f / bf_round(sqrtf(bf_round(bf_round(q * (1.f / D_)) + 1e-5f)));
#pragma unroll
    for (int i = 0; i < 40; i++) v[i] = bf_round(v[i] - mb) * inv;
}
DEV void unpack8(float* v, uint4 u) {
    v[0] = bf_lo(u.x); v[1] = bf_hi(u.x); v[2] = bf_lo(u.y); v[3] = bf_hi(u.y);
    v[4] = bf_lo(u.z); v[5] = bf_hi(u.z); v[6] = bf_lo(u.w); v[7] = bf_hi(u.w);
}

__global__ void __launch_bounds__(256) rowfft_kernel(const bf16* __restrict__ x) {
    __shared__ __align__(128) unsigned char sm[10 * 2304];
    const uint32_t sb = s2u(sm);
    const int tid = threadIdx.x, lane = tid & 31, q = lane & 3, blk = blockIdx.x, k2 = tid >> 2;
    float twr[5], twi[5];
#pragma unroll
    for (int r = 1; r < 5; r++) { sincospif((float)(r * k2) * (-1.f / 320), &twi[r], &twr[r]); }
    pdl_wait();
    pdl_launch();
    uint32_t f[8][4];
#pragma unroll
    for (int ks = 0; ks < 8; ks++) { const uint4 u = g_f128[ks * 256 + tid]; f[ks][0] = u.x; f[ks][1] = u.y; f[ks][2] = u.z; f[ks][3] = u.w; }
    {
        const int rho = tid >> 4, j = tid & 15;
        float v[40];
#pragma unroll
        for (int i = 0; i < 5; i++) unpack8(v + 8 * i, *(const uint4*)(x + (size_t)(blk * 16 + rho) * D_ + j * 40 + i * 8));
        ln40(v);
        const uint32_t a = sb + ((rho >> 1) & 1) * 2304 + j * 144 + (2 * (rho >> 2) + (rho & 1)) * 16;
#pragma unroll
        for (int r = 0; r < 5; r++)
            sts128(a + r * 4608, pack2(v[r], v[5 + r]), pack2(v[10 + r], v[15 + r]), pack2(v[20 + r], v[25 + r]), pack2(v[30 + r], v[35 + r]));
    }
    fence_async();
    __syncthreads();
    float acc[40];
    const u64 db = mkdesc(sb, 144, 2304);
    wg_fence();
    wgmma_n80_rs<0, 0>(acc, f[0], db);
#pragma unroll
    for (int ks = 1; ks < 8; ks++) wgmma_n80_rs<1, 0>(acc, f[ks], db + ks * 18);
    wg_commit();
    wg_wait<0>();
    unsigned char* zp = g_z + (blk >> 1) * 128 + ((((blk & 1) * 4 + q) ^ ((blk >> 1) & 7)) << 4);
    uint32_t o[5][4];
#pragma unroll
    for (int u = 0; u < 4; u++) {
        float tr[5], ti[5], zr[5], zi[5];
#pragma unroll
        for (int r = 0; r < 5; r++) {
            const float yr = acc[8 * r + 4 * (u >> 1) + (u & 1)], yi = k2 ? acc[8 * r + 4 * (u >> 1) + 2 + (u & 1)] : 0.f;
            tr[r] = r ? yr * twr[r] - yi * twi[r] : yr;
            ti[r] = r ? yr * twi[r] + yi * twr[r] : yi;
        }
        dft5<1>(tr, ti, zr, zi);
#pragma unroll
        for (int j = 0; j < 5; j++) o[j][u] = pack2(zr[j], j < 3 ? zi[j] : -zi[j]);
    }
#pragma unroll
    for (int j = 0; j < 5; j++)
        if (j < 3 || k2) *(uint4*)(zp + (64 * j + k2) * 8192) = make_uint4(o[j][0], o[j][1], o[j][2], o[j][3]);
    if (k2 == 0) {
#pragma unroll
        for (int u = 0; u < 4; u++) {
            float tr[5], ti[5], zr[5], zi[5];
            const float cr[5] = {1.f, -C5B, C5A, -C5A, C5B}, ci[5] = {0.f, -S5B, -S5A, -S5A, -S5B};
#pragma unroll
            for (int r = 0; r < 5; r++) { const float y = acc[8 * r + 4 * (u >> 1) + 2 + (u & 1)]; tr[r] = y * cr[r]; ti[r] = y * ci[r]; }
            dft5<1>(tr, ti, zr, zi);
            o[0][u] = pack2(zr[0], zi[0]); o[1][u] = pack2(zr[1], zi[1]); o[2][u] = pack2(zr[2], 0.f);
        }
        *(uint4*)(zp + 256 * 8192) = make_uint4(o[0][0], o[0][1], o[0][2], o[0][3]);
        *(uint4*)(zp + 192 * 8192) = make_uint4(o[1][0], o[1][1], o[1][2], o[1][3]);
        *(uint4*)(zp + 320 * 8192) = make_uint4(o[2][0], o[2][1], o[2][2], o[2][3]);
    }
}

constexpr int CF_SMEM = 16384 + 3 * 16384 + 64;
__global__ void __launch_bounds__(384) colfft_kernel() {
    extern __shared__ __align__(1024) unsigned char smem[];
    const uint32_t sb = s2u(smem), bar = sb + 65536;
    const int tid = threadIdx.x, lane = tid & 31, q = lane & 3, wg = __shfl_sync(~0u, tid >> 7, 0), t = tid & 127, ka = t >> 2;
    const int col = blockIdx.x * 3 + wg;
    const uint32_t d0 = sb + 16384 + wg * 16384, d1 = d0 + 8192;
    if (tid == 0) {
        for (int i = 0; i < 4; i++) mbar_init(bar + 8 * i, 1);
        asm volatile("fence.mbarrier_init.release.cluster;" ::: "memory");
    }
    float twr[8], twi[8];
#pragma unroll
    for (int i = 0; i < 8; i++) sincospif((float)((4 * i + q) * (ka ? ka : -32)) * (1.f / 1024), &twi[i], &twr[i]);
    __syncthreads();
    pdl_wait();
    pdl_launch();
    if (t == 0) {
        mbar_expect(bar + 8 * wg, 8192);
        bulk_g2s(d0, g_z + col * 8192, 8192, bar + 8 * wg);
        if (wg == 0) { mbar_expect(bar + 24, 16384); bulk_g2s(sb, g_g32, 16384, bar + 24); }
    }
    uint32_t f[4][4], w[16];
#pragma unroll
    for (int ks = 0; ks < 4; ks++) { const uint4 u = g_f64[ks * 128 + t]; f[ks][0] = u.x; f[ks][1] = u.y; f[ks][2] = u.z; f[ks][3] = u.w; }
#pragma unroll
    for (int i = 0; i < 4; i++) { const uint4 u = *(const uint4*)(g_wt + col * 8192 + i * 2048 + t * 16); w[4 * i] = u.x; w[4 * i + 1] = u.y; w[4 * i + 2] = u.z; w[4 * i + 3] = u.w; }
    float acc[32];
    uint32_t a[4][4];
    const u64 SW128 = 1ull << 62;
    mbar_wait(bar + 8 * wg, 0);
    {
        const u64 db = mkdesc(d0, 0, 1024) | SW128;
        wg_fence();
        wgmma_n64_rs<0, 1>(acc, f[0], db);
#pragma unroll
        for (int ks = 1; ks < 4; ks++) wgmma_n64_rs<1, 1>(acc, f[ks], db + ks * 128);
        wg_commit();
        wg_wait<0>();
    }
#pragma unroll
    for (int ks = 0; ks < 4; ks++) { const uint4 u = g_f64[512 + ks * 128 + t]; f[ks][0] = u.x; f[ks][1] = u.y; f[ks][2] = u.z; f[ks][3] = u.w; }
#pragma unroll
    for (int i = 0; i < 8; i++) {
        const float c0 = acc[4 * i], c1 = acc[4 * i + 1], c2 = acc[4 * i + 2], c3 = acc[4 * i + 3];
        const float pr = c0 + c3, pi = c1 - c2, nr = ka ? c0 - c3 : c2, ni = ka ? c1 + c2 : c3;
        a[i >> 1][2 * (i & 1)] = ka ? pack2(pr * twr[i] + pi * twi[i], pi * twr[i] - pr * twi[i]) : pack2(c0, c1);
        a[i >> 1][2 * (i & 1) + 1] = pack2(nr * twr[i] - ni * twi[i], ni * twr[i] + nr * twi[i]);
    }
    mbar_wait(bar + 24, 0);
    {
        const u64 db = mkdesc(sb, 128, 1024);
        wg_fence();
        wgmma_n64_rs<0, 0>(acc, a[0], db);
#pragma unroll
        for (int ks = 1; ks < 4; ks++) wgmma_n64_rs<1, 0>(acc, a[ks], db + ks * 16);
        wg_commit();
        wg_wait<0>();
    }
    constexpr float NORM = 1.f / (2048.f * 640.f);
#pragma unroll
    for (int i = 0; i < 16; i++) {
        const float zr = acc[2 * i] * NORM, zi = acc[2 * i + 1] * NORM, wr = bf_lo(w[i]), wi = bf_hi(w[i]);
        a[i >> 2][i & 3] = pack2(zr * wr - zi * wi, zr * wi + zi * wr);
    }
    {
        const u64 db = mkdesc(sb + 8192, 128, 1024);
        wg_fence();
        wgmma_n64_rs<0, 0>(acc, a[0], db);
#pragma unroll
        for (int ks = 1; ks < 4; ks++) wgmma_n64_rs<1, 0>(acc, a[ks], db + ks * 16);
        wg_commit();
        wg_wait<0>();
    }
    const uint32_t row = (t >> 5) * 2048 + (lane & 15) * 128;
#pragma unroll
    for (int i = 0; i < 8; i++) {
        const float c0 = acc[4 * i], c1 = acc[4 * i + 1], c2 = acc[4 * i + 2], c3 = acc[4 * i + 3];
        const float pr = c0 * twr[i] - c1 * twi[i], pi = c1 * twr[i] + c0 * twi[i];
        const float nr = c2 * twr[i] + c3 * twi[i], ni = c3 * twr[i] - c2 * twi[i];
        a[i >> 1][2 * (i & 1)] = ka ? pack2(pr + nr, pi + ni) : pack2(c0, c1);
        a[i >> 1][2 * (i & 1) + 1] = ka ? pack2(ni - pi, pr - nr) : pack2(nr, ni);
    }
#pragma unroll
    for (int i = 0; i < 4; i++) stsm4(d1 + row + (((2 * i + (lane >> 4)) ^ (lane & 7)) << 4), a[i][0], a[i][1], a[i][2], a[i][3]);
    fence_async();
    bar_sync(1 + wg, 128);
    {
        const u64 db = mkdesc(d1, 0, 1024) | SW128;
        wg_fence();
        wgmma_n64_rs<0, 1>(acc, f[0], db);
#pragma unroll
        for (int ks = 1; ks < 4; ks++) wgmma_n64_rs<1, 1>(acc, f[ks], db + ks * 128);
        wg_commit();
        wg_wait<0>();
    }
#pragma unroll
    for (int i = 0; i < 4; i++)
        stsm4(d0 + row + (((2 * i + (lane >> 4)) ^ (lane & 7)) << 4), pack2(acc[8 * i], acc[8 * i + 1]), pack2(acc[8 * i + 2], acc[8 * i + 3]),
              pack2(acc[8 * i + 4], acc[8 * i + 5]), pack2(acc[8 * i + 6], acc[8 * i + 7]));
    fence_async();
    bar_sync(1 + wg, 128);
    if (t == 0) {
        bulk_s2g(g_z + col * 8192, d0, 8192);
        asm volatile("cp.async.bulk.commit_group;" ::: "memory");
        asm volatile("cp.async.bulk.wait_group 0;" ::: "memory");
    }
}

__global__ void __launch_bounds__(256) rowifft_kernel(const bf16* __restrict__ x, bf16* __restrict__ out, int last) {
    __shared__ __align__(128) unsigned char sm[20480 + 16 * 1296];
    const uint32_t sb = s2u(sm), sy = sb + 20480;
    const int tid = threadIdx.x, lane = tid & 31, q = lane & 3, blk = blockIdx.x, k2 = tid >> 2, warp = tid >> 5;
    float twr[5], twi[5];
#pragma unroll
    for (int r = 1; r < 5; r++) { sincospif((float)(r * k2) * (1.f / 320), &twi[r], &twr[r]); twr[r] *= 2.f; twi[r] *= 2.f; }
    pdl_wait();
    pdl_launch();
    const unsigned char* zp = g_z + (blk >> 1) * 128 + ((((blk & 1) * 4 + q) ^ ((blk >> 1) & 7)) << 4);
    uint4 z[6];
#pragma unroll
    for (int j = 0; j < 5; j++) z[j] = *(const uint4*)(zp + (64 * j + k2) * 8192);
    z[5] = k2 ? make_uint4(0, 0, 0, 0) : *(const uint4*)(zp + 320 * 8192);
    uint32_t f[8][4];
#pragma unroll
    for (int ks = 0; ks < 8; ks++) { const uint4 u = g_f128[2048 + ks * 256 + tid]; f[ks][0] = u.x; f[ks][1] = u.y; f[ks][2] = u.z; f[ks][3] = u.w; }
    uint4 xr[5];
#pragma unroll
    for (int i = 0; i < 5; i++) xr[i] = *(const uint4*)(x + (size_t)(blk * 16 + (tid >> 4)) * D_ + (tid & 15) * 40 + i * 8);
    float acc[40];
#pragma unroll
    for (int u = 0; u < 4; u++) {
        float yr[6], yi[6], tr[5], ti[5], zr[5], zi[5];
#pragma unroll
        for (int j = 0; j < 6; j++) { const uint32_t v = u == 0 ? z[j].x : u == 1 ? z[j].y : u == 2 ? z[j].z : z[j].w; yr[j] = bf_lo(v); yi[j] = bf_hi(v); }
#pragma unroll
        for (int j = 0; j < 5; j++) { tr[j] = yr[j]; ti[j] = j < 3 ? yi[j] : -yi[j]; }
        dft5<-1>(tr, ti, zr, zi);
        const float c1[5] = {1.f, C5A, C5B, C5B, C5A}, s1[5] = {0.f, S5A, S5B, -S5B, -S5A};
        const float c2[5] = {1.f, C5B, C5A, C5A, C5B}, s2[5] = {0.f, S5B, -S5A, S5A, -S5B};
        const float c3[5] = {1.f, -C5B, C5A, -C5A, C5B}, s3[5] = {0.f, S5B, S5A, S5A, S5B};
        const float c4[5] = {1.f, -C5A, C5B, -C5B, C5A}, s4[5] = {0.f, S5A, -S5B, -S5B, S5A};
#pragma unroll
        for (int r = 0; r < 5; r++) {
            float er = r ? zr[r] * twr[r] - zi[r] * twi[r] : 2.f * zr[0], ei = r ? zr[r] * twi[r] + zi[r] * twr[r] : 2.f * zi[0];
            if (k2 == 0) {
                er = yr[0] + 2.f * (yr[1] * c1[r] - yi[1] * s1[r] + yr[2] * c2[r] - yi[2] * s2[r]);
                ei = (r & 1 ? -yr[5] : yr[5]) + 2.f * (yr[4] * c3[r] - yi[4] * s3[r] + yr[3] * c4[r] - yi[3] * s4[r]);
            }
            acc[8 * r + 4 * (u >> 1) + (u & 1)] = er;
            acc[8 * r + 4 * (u >> 1) + 2 + (u & 1)] = ei;
        }
    }
#pragma unroll
    for (int r = 0; r < 5; r++)
        stsm4(sb + (2 * warp + ((lane >> 3) & 1)) * 1280 + (2 * r + (lane >> 4)) * 128 + (lane & 7) * 16, pack2(acc[8 * r], acc[8 * r + 1]),
              pack2(acc[8 * r + 2], acc[8 * r + 3]), pack2(acc[8 * r + 4], acc[8 * r + 5]), pack2(acc[8 * r + 6], acc[8 * r + 7]));
    fence_async();
    __syncthreads();
    const u64 db = mkdesc(sb, 1280, 128);
    wg_fence();
    wgmma_n80_rs<0, 1>(acc, f[0], db);
#pragma unroll
    for (int ks = 1; ks < 8; ks++) wgmma_n80_rs<1, 1>(acc, f[ks], db + ks * 160);
    wg_commit();
    wg_wait<0>();
#pragma unroll
    for (int u = 0; u < 4; u++) {
        float e[10];
#pragma unroll
        for (int r = 0; r < 5; r++) { e[r] = acc[8 * r + 4 * (u >> 1) + (u & 1)]; e[5 + r] = acc[8 * r + 4 * (u >> 1) + 2 + (u & 1)]; }
#pragma unroll
        for (int i = 0; i < 5; i++) sts32(sy + (4 * q + u) * 1296 + k2 * 20 + i * 4, pack2(e[2 * i], e[2 * i + 1]));
    }
    __syncthreads();
    const int rho = tid >> 4, j = tid & 15, row = blk * 16 + rho;
    float v[40];
#pragma unroll
    for (int i = 0; i < 5; i++) {
        uint32_t y[4];
        float a[8], b[8];
        lds128(y, sy + rho * 1296 + j * 80 + i * 16);
        unpack8(a, xr[i]); unpack8(b, make_uint4(y[0], y[1], y[2], y[3]));
        const uint4 o = make_uint4(pack2(a[0] + b[0], a[1] + b[1]), pack2(a[2] + b[2], a[3] + b[3]), pack2(a[4] + b[4], a[5] + b[5]), pack2(a[6] + b[6], a[7] + b[7]));
        *(uint4*)(out + (size_t)row * D_ + j * 40 + i * 8) = o;
        unpack8(v + 8 * i, o);
    }
    if (!last) {
        ln40(v);
#pragma unroll
        for (int i = 0; i < 5; i++)
            *(uint4*)(g_xn + (row >> 5) * 40960 + (j * 5 + i) * 512 + (row & 31) * 16) =
                make_uint4(pack2(v[8 * i], v[8 * i + 1]), pack2(v[8 * i + 2], v[8 * i + 3]), pack2(v[8 * i + 4], v[8 * i + 5]), pack2(v[8 * i + 6], v[8 * i + 7]));
    }
}

namespace rec {
constexpr int NS = 5;
constexpr int OFF_X = 0;
constexpr int OFF_WO = 81920;
constexpr int OFF_WS = OFF_WO + 57344;
constexpr int OFF_MEMB = OFF_WS + NS * 4096;
constexpr int OFF_VX = OFF_MEMB + 10240;
constexpr int OFF_VM = OFF_VX + 16384;
constexpr int OFF_Q = OFF_VM + 4096;
constexpr int OFF_K = OFF_Q + 10240;
constexpr int OFF_PX = OFF_K + 10240;
constexpr int OFF_OST = OFF_PX + 2560;
constexpr int OFF_PT = OFF_OST + 4096;
constexpr int OFF_PS = OFF_PT + 1536;
constexpr int OFF_OB = OFF_PS + 1280;
constexpr int OFF_MX = OFF_OB + 2048;
constexpr int OFF_BAR = OFF_MX + 64;
constexpr int OFF_PROF = OFF_BAR + 256;
constexpr int SMEM = OFF_PROF;
enum { B_XT = 0, B_KX = 2, B_VX = 4, B_XD = 6, B_X1 = 8, B_WN = 10, B_PXF = 12, B_PXE = 13, B_FIN = 14, B_ST = 15 };
enum { NB_QK = 2, NB_WIN = 3, NB_ATT = 4, NB_X = 5, NB_PRO = 6, NB_W1 = 7, NB_MEM = 8  , NB_LD = 13   };
#define NOX 0
#define NW1 6
#define NW1B 6
constexpr int RING = 8;
template <int N> struct IC { static constexpr int value = N; };
template <int N, int I = 0, class F> DEV void static_for(F&& f) { if constexpr (I < N) { f(IC<I>{}); static_for<N, I + 1>(f); } }
constexpr float SM_SCALE = 0.08838834764831845f * 1.4426950408889634f;
}

__global__ void __launch_bounds__(512, 1) rec_kernel(const bf16* __restrict__ mem0, const bf16* __restrict__ Wq, const bf16* __restrict__ Wk,
                                                     const bf16* __restrict__ Wv, const bf16* __restrict__ Wo, int layer, int delay, int delay2) {
    using namespace rec;
    extern __shared__ __align__(1024) unsigned char smem[];
    const uint32_t sb = s2u(smem);
    const int tid = threadIdx.x, lane = tid & 31, warp = __shfl_sync(~0u, tid >> 5, 0);
    const int g = lane >> 2, q = lane & 3;
    uint32_t rank; asm("mov.u32 %0,%%cluster_ctarank;" : "=r"(rank));
    const int h = blockIdx.x / 3;
    const uint32_t bar = sb + OFF_BAR;
    STAMP(2 * layer);
    if (tid == 0) {
        for (int i = 0; i < 2; i++) {
            mbar_init(bar + 8 * (B_XT + i), 1); mbar_init(bar + 8 * (B_KX + i), 8); mbar_init(bar + 8 * (B_VX + i), 1);
            mbar_init(bar + 8 * (B_XD + i), 8); mbar_init(bar + 8 * (B_X1 + i), 1); mbar_init(bar + 8 * (B_WN + i), 4);
        }
        mbar_init(bar + 8 * B_PXF, 1); mbar_init(bar + 8 * B_PXE, 2); mbar_init(bar + 8 * B_ST, 2);
        mbar_init(bar + 8 * B_FIN, 48);
        asm volatile("fence.mbarrier_init.release.cluster;" ::: "memory");
    }
    asm volatile("barrier.cluster.arrive.aligned; barrier.cluster.wait.aligned;" ::: "memory");
    const bool never = delay < 0;

    if (warp < 8) {
        asm volatile("setmaxnreg.inc.sync.aligned.u32 184;");
        uint32_t a[40 - NS][4];
        const uint32_t l16 = opaque(sb + lane * 16);
        uint32_t wsa = opaque(sb + OFF_WS + warp * 512 + (lane & 7) * 16 + ((lane >> 3) & 1) * 256 + (lane >> 4) * 128);
        uint32_t dst = opaque(rank < 2 ? sb + OFF_Q + (warp >> 2) * 10240 + (warp & 3) * 256 + (lane & 15) * 16 + (lane >> 4) * 1024
                                             : sb + OFF_VM + warp * 256 + lane * 4);
        int dstep = rank < 2 ? 5120 : 2048;
        uint32_t& sfd = wsa;
        {
            const int wg = warp >> 2, t = tid & 127;
            const bf16* src = (rank == 2 ? Wv + wg * 64 : (wg ? Wk : Wq) + rank * 64) + h * E_ + (size_t)(t >> 3) * 4096 + (t & 7) * 8;
            const uint32_t stg = sb + (wg ? OFF_VX : OFF_X + 40960);
            const uint32_t sdst = stg + (t >> 3) * 128 + (((t & 7) ^ ((t >> 3) & 7)) << 4);
            const uint32_t c = 2 * (warp & 3) + (g >> 2), r0 = stg + 2 * q * 128 + (g & 3) * 4;
            const uint32_t ra = r0 + ((c ^ (2 * q)) << 4), rb = r0 + 128 + ((c ^ (2 * q + 1)) << 4);
            auto issue = [&](int rd) {
#pragma unroll
                for (int i = 0; i < 10; i++) cp16(sdst + (rd & 1) * 20480 + i * 2048, src + (size_t)(rd * 160 + i * 16) * 4096);
                cp_commit();
            };
            issue(0); issue(1);
#pragma unroll
            for (int rd = 0; rd < 4; rd++) {
                if (rd < 3) cp_wait<1>(); else cp_wait<0>();
                bar_sync(NB_LD + wg, 128);
#pragma unroll
                for (int i = 0; i < 10; i++) {
                    const int ks = rd * 10 + i, o = (rd & 1) * 20480 + i * 2048;
                    const uint32_t u0 = lds32(ra + o), u1 = lds32(rb + o), u2 = lds32(ra + o + 1024), u3 = lds32(rb + o + 1024);
                    const uint32_t f0 = prmt(u0, u1, 0x5410), f1 = prmt(u0, u1, 0x7632), f2 = prmt(u2, u3, 0x5410), f3 = prmt(u2, u3, 0x7632);
                    if (ks < NS) stsm4(wsa + ks * 4096, f0, f1, f2, f3);
                    else { a[ks - NS][0] = f0; a[ks - NS][1] = f1; a[ks - NS][2] = f2; a[ks - NS][3] = f3; }
                }
                if (rd < 2) { bar_sync(NB_LD + wg, 128); issue(rd + 2); }
            }
            fence_async();
            bar_sync(NB_PRO, 288);
        }
        float acc[16];
        uint32_t xlo = (uint32_t)mkdesc(sb + OFF_X, 512, 128);
        const uint32_t xtog = xlo ^ (uint32_t)mkdesc(sb + OFF_X + 40960, 512, 128);
        uint32_t p8 = 0;
        const uint32_t alo = (uint32_t)mkdesc(sb + OFF_WS + (warp >> 2) * 2048, 128, 256);
        auto xproj = [&](auto K1, auto K0) {
            const u64 desc = (u64)xlo | (8ull << 32), da = (u64)alo | (16ull << 32);
            wg_fence();
#pragma unroll
            for (int ks = K1.value - 1; ks >= K0.value; ks--) {
                if (ks == 39) wgmma_n32_rs<0>(acc, a[ks - NS], desc + ks * 64);
                else if (NOX) {}
                else if (ks < NS) wgmma_n32_ss<1>(acc, da + ks * 256, desc + ks * 64);
                else wgmma_n32_rs<1>(acc, a[ks - NS], desc + ks * 64);
            }
            wg_commit();
        };
        auto xstore = [&]() {
            wg_wait<0>();
            uint32_t pk[8];
#pragma unroll
            for (int i = 0; i < 8; i++) pk[i] = pack2(acc[2 * i], acc[2 * i + 1]);
            if (rank < 2) {
                stsm4t(dst + 1024, pk[0], pk[1], pk[2], pk[3]);
                stsm4t(dst + 3072, pk[4], pk[5], pk[6], pk[7]);
            } else {
                const uint32_t la = wsa + (wsa & 256) + (OFF_VX - OFF_WS) + warp * 512 + p8 * 1024;
                stsm4(la, pk[0], pk[1], pk[2], pk[3]);
                stsm4(la + 256, pk[4], pk[5], pk[6], pk[7]);
                fence_async();
            }
            mbar_arrive_elect(bar + 8 * B_KX + p8);
        };
        mbar_wait(bar + 8 * B_XT, 0);
        xproj(IC<40>{}, IC<0>{});
        if (rank == 2) mbar_wait(bar + 8 * B_ST, 0);
        xstore();
        for (int s = 0;; s++) {
            float d0[4] = {0.f, 0.f, 0.f, 0.f}, d1[4] = {0.f, 0.f, 0.f, 0.f};
            uint32_t t[NS][4], b[20][4];
#pragma unroll
            for (int ks = 0; ks < NS; ks++) ldsm4(t[ks], wsa + ks * 4096);
            bar_sync(NB_MEM, 384);
            lds128(b[0], l16 + OFF_MEMB); lds128(b[1], l16 + OFF_MEMB + 512); lds128(b[2], l16 + OFF_MEMB + 1024);
            xlo ^= xtog;
            const uint32_t xb0 = mapa(bar + 8 * B_X1 + p8, 0), xb1 = mapa(bar + 8 * B_X1 + p8, 1);
            SFENCE();
            float is;
#pragma unroll
            for (int kp = 0; kp < 20; kp++) {
#pragma unroll
                for (int j = 0; j < 2; j++) {
                    const int ks = 2 * kp + j;
                    const uint32_t* f = ks < NS ? t[ks] : a[ks - NS];
                    mma16(j ? d1 : d0, f[0], f[1], f[2], f[3], b[kp][2 * j], b[kp][2 * j + 1]);
                }
                if (kp == 0 && warp == 0) PROFT(0);
                if (kp == 0) lds128(b[3], l16 + OFF_MEMB + 3 * 512);
                else if (kp >= 16 || (kp & 3) == 0) {}
                else if ((kp & 3) == 1) {
                    bar_sync(NB_MEM + 1 + (kp >> 2), 384);
                    lds128(b[kp + 3], l16 + OFF_MEMB + (kp + 3) * 512); lds128(b[kp + 4], l16 + OFF_MEMB + (kp + 4) * 512);
                } else lds128(b[kp + 4], l16 + OFF_MEMB + (kp + 4) * 512);
                if (kp == 16) is = lds32f(sb + OFF_MX + 16);
                if (kp < 17) SFENCE();
            }
            const uint32_t p0 = pack2((d0[0] + d1[0]) * is, (d0[1] + d1[1]) * is), p1 = pack2((d0[2] + d1[2]) * is, (d0[3] + d1[3]) * is);
            if (rank < 2) {
                stsm2t(dst, p0, p1);
            } else {
                st_async1(mapa(dst, 0), p0, xb0); st_async1(mapa(dst, 1), p0, xb1);
                st_async1(mapa(dst + 128, 0), p1, xb0); st_async1(mapa(dst + 128, 1), p1, xb1);
                sts32(dst, p0); sts32(dst + 128, p1);
            }
            bar_arrive(NB_QK, 384);
            if (warp == 0) PROFT(1);
            dst += dstep; dstep = -dstep; p8 ^= 8;
            bar_sync(NB_W1, 512);
            if (s == NSEG - 1) break;
            xproj(IC<40>{}, IC<40 - NW1>{});
            if (rank < 2) {
                wg_wait<0>();
                if (warp == 0) PROFT(15);
                bar_sync(NB_WIN, 384);
            }
            xproj(IC<40 - NW1>{}, IC<40 - NW1 - NW1B>{});
            if (rank == 2) {
                wg_wait<0>();
                if (warp == 0) PROFT(15);
                bar_sync(NB_WIN, 384);
            }
            if (warp == 0) PROFT(2);
            xproj(IC<40 - NW1 - NW1B>{}, IC<0>{});
            xstore();
            if (warp == 0) PROFT(3);
            if (warp == 4) PROFT(12);
        }
    } else if (warp < 12) {
        asm volatile("setmaxnreg.dec.sync.aligned.u32 96;");
        const int w = warp - 8;
        const bool four = w == 0 || (w == 1 && rank == 0);
        const int tile3 = rank == 0 ? 36 + w : 37 + rank;
        uint32_t amax = 0;
#pragma unroll
        for (int it = 0; it < 5; it++) {
            const int kp = it * 4 + w;
            const bf16* p = mem0 + g * D_ + kp * 32 + 2 * q;
            uint32_t b0 = ldg32(p), b1 = ldg32(p + 8), b2 = ldg32(p + 16), b3 = ldg32(p + 24);
            sts128(sb + OFF_MEMB + kp * 512 + lane * 16, b0, b1, b2, b3);
            amax = absmax2(amax, absmax2(absmax2(b0, b1), absmax2(b2, b3)));
        }
        if (tid == 256) sts32(sb + OFF_MX + 16, 0x3f800000u);
        bar_arrive(NB_MEM, 384); bar_arrive(NB_MEM + 1, 384); bar_arrive(NB_MEM + 2, 384); bar_arrive(NB_MEM + 3, 384); bar_arrive(NB_MEM + 4, 384);
        {
            const int t = tid & 127;
#pragma unroll
            for (int r = 0; r < 4; r++) {
                const int col = r < 3 ? 192 * r + 64 * rank : (rank ? 592 + 16 * rank : 576);
                const bf16* src = Wo + (size_t)(h * E_) * D_ + col;
                if (r < 3) {
#pragma unroll
                    for (int i = 0; i < 8; i++) {
                        const int e = i * 16 + (t >> 3);
                        cp16(sb + OFF_WO + r * 16384 + e * 128 + (((t & 7) ^ ((e >> 1) & 6)) << 4), src + e * D_ + (t & 7) * 8);
                    }
                } else {
#pragma unroll
                    for (int i = 0; i < 4; i++) {
                        const int e = i * 32 + (t >> 2);
                        if (rank == 0 || (t & 2) == 0) cp16(sb + OFF_WO + r * 16384 + e * 64 + (t & 3) * 16, src + e * D_ + (t & 3) * 8);
                    }
                }
            }
            cp_commit();
            cp_wait<0>();
            bar_sync(NB_ATT, 128);
#pragma unroll 1
            for (int r = 0; r < 4; r++) {
                uint32_t u[8][4];
                const uint32_t rs = r < 3 ? 128 : 64;
                const uint32_t p = sb + OFF_WO + r * 16384 + 4 * q * rs + (((2 * w + (g & 1)) ^ (r < 3 ? 2 * q : 0)) << 4) + (g >> 1) * 4;
                if (r < 3 || four) {
#pragma unroll
                    for (int ks = 0; ks < 8; ks++)
#pragma unroll
                        for (int j = 0; j < 4; j++) u[ks][j] = lds32(p + (16 * ks + j) * rs);
                }
                bar_sync(NB_ATT, 128);
                if (r < 3 || four) {
#pragma unroll
                    for (int ks = 0; ks < 8; ks++)
                        sts128(sb + OFF_WO + (r * 4 + w) * 4096 + ks * 512 + lane * 16, prmt(u[ks][0], u[ks][2], 0x5410), prmt(u[ks][0], u[ks][2], 0x7632),
                               prmt(u[ks][1], u[ks][3], 0x5410), prmt(u[ks][1], u[ks][3], 0x7632));
                }
            }
        }
        float cw;
        {
            const float4 a = ((const float4*)g_nrm)[lane], c = ((const float4*)g_nrm)[32 + lane];
            float sm = sqrtf((a.x + a.y) + (a.z + a.w)) * sqrtf((c.x + c.y) + (c.z + c.w)), mxv = sm;
#pragma unroll
            for (int o = 16; o; o >>= 1) { sm += __shfl_xor_sync(~0u, sm, o); mxv = fmaxf(mxv, __shfl_xor_sync(~0u, mxv, o)); }
            cw = 26.5f * fmaxf(sm, 8.f * mxv);
        }
        const uint32_t l16 = opaque(sb + lane * 16), l4 = opaque(sb + OFF_PS + rank * 512 + lane * 4);
        uint32_t lq = opaque(sb + OFF_Q + (lane & 7) * 16 + ((lane >> 3) & 1) * 256 + (lane >> 4) * 128);
        const uint32_t lv = opaque(sb + OFF_VX + w * 2048 + (lane & 7) * 16 + ((lane >> 3) & 1) * 512 + (lane >> 4) * 128);
        uint32_t& sfd = lq;
        const bool t0 = tid == 256;
        const char* rp = (const char*)(g_acc + layer * ACC_LAYER) + (4 * rank + w) * 4096 + opaque((q >> 1) * 1024 + ((q & 1) * 8 + g) * 8);
        const char* lp = (const char*)(g_acc + layer * ACC_LAYER) + opaque(w * 8192 + (2 * (g & 1) + (g >> 2)) * 1024 + (((g >> 1) & 1) * 8 + 2 * q) * 8);
        const int t3off = (tile3 - 4 * rank - w) * 4096;
        float isig = 1.f;
        if (t0) {
            mbar_expect(bar + 8 * B_X1, rank < 2 ? 3328 : 1280);
            if (rank < 2) mbar_expect(bar + 8 * B_VX, 8192);
        }
        for (int s = 0; s < NSEG - 1; s++) {
            const int pb = s & 1;
            const uint32_t x1 = bar + 8 * (B_X1 + pb);
            sts32(sb + OFF_MX + w * 4, __reduce_max_sync(~0u, max(amax & 0x7fff0000u, (amax << 16) & 0x7fff0000u)));
            if (rank < 2) {
                uint32_t kf[8], qf[8];
                const uint32_t ka = l16 + OFF_K + pb * 5120, qa = lq + pb * 5120;
                mbar_wait(bar + 8 * (B_KX + pb), (s >> 1) & 1);
                ldsm4(kf, ka + (1 + w) * 1024); ldsm4(kf + 4, ka + (1 + w) * 1024 + 512);
                const uint32_t pa = l4 + w * 128;
                const uint32_t pa0 = mapa(pa, rank ^ 1), pa1 = mapa(pa, 2), pa2 = mapa(pa, rank);
                const uint32_t xb0 = mapa(x1, rank ^ 1), xb1 = mapa(x1, 2), xb2 = mapa(x1, rank);
                bar_sync(NB_QK, 384);
                ldsm4(qf, qa); ldsm4(qf + 4, qa + 512);
                float c0[4] = {0.f, 0.f, 0.f, 0.f}, c1[4] = {0.f, 0.f, 0.f, 0.f}, c2[4] = {0.f, 0.f, 0.f, 0.f}, c3[4] = {0.f, 0.f, 0.f, 0.f};
                if (w == 3) {
                    uint32_t mf[8];
                    ldsm4(mf, ka); ldsm4(mf + 4, ka + 512);
                    mma16(c0, qf[0], qf[1], qf[2], qf[3], kf[0], kf[1]); mma16(c1, qf[0], qf[1], qf[2], qf[3], kf[2], kf[3]);
                    mma16(c2, qf[0], qf[1], qf[2], qf[3], mf[0], mf[1]); mma16(c3, qf[0], qf[1], qf[2], qf[3], mf[2], mf[3]);
                    mma16(c0, qf[4], qf[5], qf[6], qf[7], kf[4], kf[5]); mma16(c1, qf[4], qf[5], qf[6], qf[7], kf[6], kf[7]);
                    mma16(c2, qf[4], qf[5], qf[6], qf[7], mf[4], mf[5]); mma16(c3, qf[4], qf[5], qf[6], qf[7], mf[6], mf[7]);
                    bar_arrive(NB_W1, 512);
                    const uint32_t y = pack2(c0[0] + c1[2], c0[1] + c1[3]), z = pack2(c2[0] + c3[2], c2[1] + c3[3]);
                    const uint32_t pm = l4 + 1024 - rank * 384;
                    st_async1(pa0, y, xb0); st_async1(pa1, y, xb1);
                    st_async1(mapa(pm, rank ^ 1), z, xb0); st_async1(mapa(pm, 2), z, xb1);
                    st_async1(pa2, y, xb2); st_async1(mapa(pm, rank), z, xb2);
                } else {
                    mma16(c0, qf[0], qf[1], qf[2], qf[3], kf[0], kf[1]); mma16(c1, qf[0], qf[1], qf[2], qf[3], kf[2], kf[3]);
                    mma16(c2, qf[4], qf[5], qf[6], qf[7], kf[4], kf[5]); mma16(c3, qf[4], qf[5], qf[6], qf[7], kf[6], kf[7]);
                    bar_arrive(NB_W1, 512);
                    const uint32_t y = pack2((c0[0] + c1[2]) + (c2[0] + c3[2]), (c0[1] + c1[3]) + (c2[1] + c3[3]));
                    st_async1(pa0, y, xb0); st_async1(pa1, y, xb1); st_async1(pa2, y, xb2);
                }
                if (w == 0) PROFT(4);
                mbar_wait(bar + 8 * (B_VX + pb), (s >> 1) & 1);
            } else {
                bar_sync(NB_QK, 384);
                bar_arrive(NB_W1, 512);
            }
            float m4[4];
            lds128f(m4, sb + OFF_MX);
            uint32_t wf[RING][4], vf[2][2][4], vm[4];
#pragma unroll
            for (int t = 0; t < 2; t++)
#pragma unroll
                for (int j = 0; j < 2; j++) ldsm4(vf[t][j], lv + pb * 8192 + t * 1024 + j * 256);
            float sig;
            {
                const float bound = cw * fmaxf(fmaxf(fmaxf(m4[0], m4[1]), fmaxf(m4[2], m4[3])) * isig, 1.f);
                const uint32_t e = max((__float_as_uint(bound) >> 23) & 255u, 31u);
                sig = __uint_as_float((278u - e) << 23);
                isig = __uint_as_float((e - 30u) << 23);
            }
            if (t0) sts32(sb + OFF_MX + 16, __float_as_uint(isig));
            const uint32_t vma = l16 + OFF_VM + pb * 2048 + w * 512;
            if (w == 0) PROFT(5);
            mbar_wait(x1, (s >> 1) & 1);
            if (w == 0) PROFT(6);
            float sc[10];
            {
                uint32_t u[4], v[4], m[2];
                ldsm4(u, l16 + OFF_PS); ldsm4(v, l16 + OFF_PS + 512); ldsm2(m, l16 + OFF_PS + 1024);
                ldsm4(vm, vma);
                SFENCE();
#pragma unroll
                for (int i = 0; i < 4; i++) { sc[2 * i] = bf_lo(u[i]) + bf_lo(v[i]); sc[2 * i + 1] = bf_hi(u[i]) + bf_hi(v[i]); }
                sc[8] = bf_lo(m[0]) + bf_lo(m[1]); sc[9] = bf_hi(m[0]) + bf_hi(m[1]);
            }
            float mx = fmaxf(fmaxf(fmaxf(fmaxf(sc[0], sc[1]), fmaxf(sc[2], sc[3])), fmaxf(fmaxf(sc[4], sc[5]), fmaxf(sc[6], sc[7]))), fmaxf(sc[8], sc[9]));
            {
                float m1 = __shfl_xor_sync(~0u, mx, 1), m2 = __shfl_xor_sync(~0u, mx, 2), m3 = __shfl_xor_sync(~0u, mx, 3);
                SFENCE();
                mx = fmaxf(fmaxf(mx, m1), fmaxf(m2, m3)) * SM_SCALE;
            }
            auto fetch = [&](int i) { lds128(wf[i % RING], l16 + OFF_WO + ((i >> 3) * 4 + w) * 4096 + (i & 7) * 512); };
            float o0[4] = {0.f, 0.f, 0.f, 0.f}, o1[4] = {0.f, 0.f, 0.f, 0.f}, rs[4] = {0.f, 0.f, 0.f, 0.f};
            constexpr uint32_t ONE = 0x3f803f80u;
            sc[8] = ex2(fmaf(sc[8], SM_SCALE, -mx)); sc[9] = ex2(fmaf(sc[9], SM_SCALE, -mx));
#pragma unroll
            for (int i = 0; i < 4; i++) sc[i] = ex2(fmaf(sc[i], SM_SCALE, -mx));
#pragma unroll
            for (int i = 0; i < RING; i++) fetch(i);
            SFENCE();
            {
                const uint32_t p = pack2(sc[8], sc[9]);
                mma8(o0, vm[0], vm[1], p);
                mma8(o1, vm[2], vm[3], p);
                mma8(rs, ONE, ONE, p);
            }
#pragma unroll
            for (int i = 4; i < 8; i++) sc[i] = ex2(fmaf(sc[i], SM_SCALE, -mx));
            SFENCE();
#pragma unroll
            for (int j = 0; j < 2; j++) {
                const uint32_t p0 = pack2(sc[4 * j], sc[4 * j + 1]), p1 = pack2(sc[4 * j + 2], sc[4 * j + 3]);
                mma16(o0, vf[0][j][0], vf[0][j][1], vf[0][j][2], vf[0][j][3], p0, p1);
                mma16(o1, vf[1][j][0], vf[1][j][1], vf[1][j][2], vf[1][j][3], p0, p1);
                mma16(rs, ONE, ONE, ONE, ONE, p0, p1);
                SFENCE();
            }
            stsm4t(l16 + OFF_OB + w * 512, pack2(o0[0], o0[1]), pack2(o0[2], o0[3]), pack2(o1[0], o1[1]), pack2(o1[2], o1[3]));
            bar_sync(NB_ATT, 128);
            uint32_t ob[16];
#pragma unroll
            for (int j = 0; j < 4; j++) ldsm4(ob + 4 * j, l16 + OFF_OB + j * 512);
            SFENCE();
            const float sg0 = rcp(rs[0]) * sig, sg1 = rcp(rs[1]) * sig;
            SFENCE();
            uint32_t tr;
            auto tiles = [&](auto NT) {
#pragma unroll
                for (int r = 0; r < NT.value; r++) {
                    float c[4][4];
#pragma unroll
                    for (int i = 0; i < 4; i++) c[i][0] = c[i][1] = c[i][2] = c[i][3] = 0.f;
#pragma unroll
                    for (int ks = 0; ks < 8; ks++) {
                        const uint32_t* f = wf[(8 * r + ks) % RING];
                        mma16(c[ks & 3], f[0], f[1], f[2], f[3], ob[2 * ks], ob[2 * ks + 1]);
                        if ((ks & 3) == 3) {
                            SFENCE();
#pragma unroll
                            for (int i = 8 * r + ks - 3 + RING; i <= 8 * r + ks + RING; i++) if (i < 8 * NT.value) fetch(i);
                        }
                    }
                    SFENCE();
                    uint32_t v[4];
#pragma unroll
                    for (int i = 0; i < 4; i++)
                        v[i] = (__float_as_uint(fmaf((c[0][i] + c[1][i]) + (c[2][i] + c[3][i]), i & 1 ? sg1 : sg0, 12582912.f)) << 6) + (i < 2);
                    const char* p = r < 3 ? rp + r * 49152 : rp + t3off;
                    red_add64((u64*)p, v[0], v[2]);
                    red_add64((u64*)(p + 2048), v[1], v[3]);
                    if (r == 0) {
                        tr = clk();
                        if (w == 0) PROFT(7);
                        if (w == 0) GPROF(4, 0);
                    }
                }
            };
            if (four) tiles(IC<4>{}); else tiles(IC<3>{});
            bar_arrive(NB_WIN, 384);
            mbar_arrive_elect(bar + 8 * (B_WN + pb));
            if (w == 0) PROFT(8);
            if (t0) {
                if (rank < 2) mbar_expect(bar + 8 * (B_VX + (pb ^ 1)), 8192);
                mbar_expect(bar + 8 * (B_X1 + (pb ^ 1)), (rank < 2 ? 2048 : 0) + (s < NSEG - 2 ? 1280 : 0));
            }
            u64 y[20];
            while (clk() - tr < (uint32_t)delay) {}
#pragma unroll
            for (int i = 0; i < 10; i++) ld_acc0(y[2 * i], y[2 * i + 1], lp + (i >> 1) * 32768 + (i & 1) * 4096);
            if (w == 0) PROFT(9);
            uint32_t nretry = 0, b[20];
            bool done[5];
            auto publish = [&](auto FIRST) {
                uint32_t ok = 32u, late = 32u;
                static_for<5>([&](auto IT) {
                    constexpr int it = IT.value;
                    if (it == 2) late = and3((uint32_t)y[8], (uint32_t)y[10], (uint32_t)y[12]);
                    else if (it == 3) late &= and3((uint32_t)y[14], (uint32_t)y[16], (uint32_t)y[18]);
                    else ok = and3(ok, (uint32_t)y[4 * it], it == 4 ? late : (uint32_t)y[4 * it + 2]);
                    if (FIRST.value && it < 4) SFENCE();
                    if (it == 2 || it == 3) ok = and3(ok, (uint32_t)y[4 * it], (uint32_t)y[4 * it + 2]);
                    ok = and3(ok, (uint32_t)y[4 * it + 1], (uint32_t)y[4 * it + 3]);
                    const bool all = __all_sync(~0u, ok);
#pragma unroll
                    for (int j = 0; j < 4; j++) {
                        const u64 z = y[4 * it + j];
                        b[4 * it + j] = pack2((float)(int)(uint32_t)z, (float)(int)(uint32_t)(z >> 32));
                    }
                    sts128(l16 + OFF_MEMB + (4 * it + w) * 512, b[4 * it], b[4 * it + 1], b[4 * it + 2], b[4 * it + 3]);
                    bar_arrive_if<NB_MEM + it, 384>(all && (FIRST.value || !done[it]));
                    done[it] = all;
                    if (FIRST.value) SFENCE();
                    if (FIRST.value && it == 0 && w == 0) PROFT(10);
                });
            };
            publish(IC<1>{});
            while (!done[4]) {
                if (++nretry > SPIN_LIMIT) __trap();
#pragma unroll
                for (int i = 0; i < 10; i++) ld_acc(y[2 * i], y[2 * i + 1], lp + (i >> 1) * 32768 + (i & 1) * 4096);
                publish(IC<0>{});
            }
            if (w == 0) PROFT(11);
            amax = b[0];
#pragma unroll
            for (int i = 1; i < 19; i += 2) amax = absmax2(amax, absmax2(b[i], b[i + 1]));
            amax = absmax2(amax, b[19]);
            GPROF(w, nretry);
            const int adv = (s & 7) == 7 ? 163840 - 896 : 128;
            rp += adv; lp += adv;
        }
        bar_sync(NB_QK, 384);
        bar_arrive(NB_W1, 512);
    } else {
        asm volatile("setmaxnreg.dec.sync.aligned.u32 48;");
        const int w = warp - 12;
        const bool t0 = tid == 384;
        if (w == 0) {
            if (t0) {
                mbar_expect(bar + 8 * B_XT, 40960);
                bulk_g2s(sb + OFF_X, g_xn, 40960, bar + 8 * B_XT);
            }
            __syncwarp();
            bar_sync(NB_PRO, 288);
            if (t0) {
                mbar_expect(bar + 8 * (B_XT + 1), 40960);
                bulk_g2s(sb + OFF_X + 40960, g_xn + 40960, 40960, bar + 8 * (B_XT + 1));
                if (rank < 2) mbar_arrive_remote(mapa(bar + 8 * B_ST, 2));
            }
            __syncwarp();
        }
        if (rank == 2) {
            for (int s = 0; s < NSEG; s++) {
                const int pb = s & 1, ph = (s >> 1) & 1;
                if (w == 0) {
                    mbar_wait(bar + 8 * (B_KX + pb), ph);
                    if (lane < 2) bulk_s2s(mapa(sb + OFF_VX + pb * 8192, lane), sb + OFF_VX + pb * 8192, 8192, mapa(bar + 8 * (B_VX + pb), lane));
                }
                if (w == 1 && s + 1 < NSEG) mbar_wait(bar + 8 * (B_XT + (pb ^ 1)), ((s + 1) >> 1) & 1);
                if (w == 2 && s >= 1) mbar_wait(bar + 8 * (B_XD + (pb ^ 1)), ((s - 1) >> 1) & 1);
                __syncwarp();
                bar_sync(NB_W1, 512);
                if (w == 1 && s + 2 < NSEG) {
                    mbar_wait(bar + 8 * (B_X1 + pb), ph);
                    const uint32_t tw = clk();
                    while (clk() - tw < (uint32_t)delay2) {}
                    if (lane == 0) {
                        mbar_expect(bar + 8 * (B_XT + pb), 40960);
                        bulk_g2s(sb + OFF_X + pb * 40960, g_xn + (s + 2) * 40960, 40960, bar + 8 * (B_XT + pb));
                    }
                }
            }
        } else {
            if (w < 2) sts32(sb + OFF_PT + w * 768 + 640 + lane * 4, 0u);
            for (int s = 0; s < NSEG; s++) {
                const int pb = s & 1, ph = (s >> 1) & 1;
                if (t0) {
                    mbar_expect(bar + 8 * B_PXF, rank ? 2560 : 1536);
                    asm volatile("cp.async.bulk.wait_group.read 0;" ::: "memory");
                }
                if (w == 1 && s + 1 < NSEG) mbar_wait(bar + 8 * (B_XT + (pb ^ 1)), ((s + 1) >> 1) & 1);
                __syncwarp();
                bar_sync(NB_W1, 512);
                fence_async();
                float c[20];
                {
                    const u64 dq = mkdesc(sb + OFF_Q + pb * 5120 + 1024, 128, 512), dk = mkdesc(sb + OFF_K + pb * 5120, 128, 1024);
                    wg_fence();
                    wgmma_n40_ss<0>(c, dq, dk);
#pragma unroll
                    for (int ks = 1; ks < 4; ks++) wgmma_n40_ss<1>(c, dq + ks * 16, dk + ks * 16);
                    wg_commit();
                    wg_wait<0>();
                }
                mbar_wait(bar + 8 * (B_X1 + pb), ph);
                if ((w >> 1) != rank) {
                    if (s >= 1) mbar_wait(bar + 8 * B_PXE, pb ^ 1);
                    const uint32_t pa = mapa(sb + OFF_PX + (w & 1) * 1280 + lane * 8, rank ^ 1), pf = mapa(bar + 8 * B_PXF, rank ^ 1);
#pragma unroll
                    for (int nt = 0; nt < 5; nt++)
                        if (nt < 3 || rank == 0) st_async2(pa + nt * 256, __float_as_uint(c[4 * nt]), __float_as_uint(c[4 * nt + 1]), pf);
                    if ((w & 1) == 0 && s + 2 < NSEG) {
                        const uint32_t tw = clk();
                        while (clk() - tw < (uint32_t)delay2) {}
                        if (lane == 0) {
                            mbar_expect(bar + 8 * (B_XT + pb), 40960);
                            bulk_g2s(sb + OFF_X + pb * 40960, g_xn + (s + 2) * 40960, 40960, bar + 8 * (B_XT + pb));
                        }
                    }
                } else {
                    mbar_wait(bar + 8 * B_PXF, pb);
                    if (w == 0) PROFT(13);
                    const int tq = 8 * w + g;
                    float sc[10];
#pragma unroll
                    for (int nt = 0; nt < 5; nt++) {
                        float u0, u1;
                        lds64f(u0, u1, sb + OFF_PX + (w & 1) * 1280 + nt * 256 + lane * 8);
                        sc[2 * nt] = (8 * nt - 8 + 2 * q <= tq) ? (u0 + c[4 * nt]) * SM_SCALE : -INFINITY;
                        sc[2 * nt + 1] = (8 * nt - 7 + 2 * q <= tq) ? (u1 + c[4 * nt + 1]) * SM_SCALE : -INFINITY;
                    }
                    float mx = sc[0];
#pragma unroll
                    for (int i = 1; i < 10; i++) mx = fmaxf(mx, sc[i]);
                    mx = fmaxf(mx, __shfl_xor_sync(~0u, mx, 1));
                    mx = fmaxf(mx, __shfl_xor_sync(~0u, mx, 2));
                    if (lane == 0) mbar_arrive_remote(mapa(bar + 8 * B_PXE, rank ^ 1));
                    float sum = 0.f;
#pragma unroll
                    for (int i = 0; i < 10; i++) { sc[i] = ex2(sc[i] - mx); sum += sc[i]; }
                    sum += __shfl_xor_sync(~0u, sum, 1);
                    sum += __shfl_xor_sync(~0u, sum, 2);
                    sum = rcp(sum);
#pragma unroll
                    for (int nt = 0; nt < 5; nt++)
                        sts32(sb + OFF_PT + (w & 1) * 768 + (nt ? nt - 1 : 4) * 128 + lane * 4, pack2(sc[2 * nt] * sum, sc[2 * nt + 1] * sum));
                }
                mbar_wait(bar + 8 * (B_VX + pb), ph);
                fence_async();
                bar_sync(NB_X, 128);
                if (s < NSEG - 1) mbar_wait(bar + 8 * (B_WN + pb), ph);
                float acc[2][8];
                const u64 dv = mkdesc(sb + OFF_VX + pb * 8192, 128, 512), dp = mkdesc(sb + OFF_PT, 128, 768), dm = mkdesc(sb + OFF_VM + pb * 2048, 0, 128);
                wg_fence();
#pragma unroll
                for (int m = 0; m < 2; m++) {
                    wgmma_n16_ss<0>(acc[m], dv + m * 256, dp);
                    wgmma_n16_ss<1>(acc[m], dv + m * 256 + 16, dp + 16);
                    wgmma_n16_ss<1>(acc[m], dm + m * 64, dp + 32);
                }
                wg_commit();
                wg_wait<0>();
                const uint32_t oa = sb + OFF_OST + (2 * w + (g >> 2)) * 128 + q * 32 + (g & 3) * 4;
#pragma unroll
                for (int m = 0; m < 2; m++)
#pragma unroll
                    for (int nt = 0; nt < 2; nt++) {
                        sts32(oa + m * 1024 + nt * 2048, pack2(acc[m][4 * nt], acc[m][4 * nt + 2]));
                        sts32(oa + m * 1024 + nt * 2048 + 16, pack2(acc[m][4 * nt + 1], acc[m][4 * nt + 3]));
                    }
                fence_async();
                bar_sync(NB_X, 128);
                if (t0) {
                    bulk_s2g(g_o + (size_t)(s * H_ + h) * 8192 + rank * 4096, sb + OFF_OST, 4096);
                    asm volatile("cp.async.bulk.commit_group;" ::: "memory");
                }
                if (lane == 0) mbar_arrive_remote(mapa(bar + 8 * (B_XD + pb), 2));
                if (w == 0) PROFT(14);
            }
            if (t0) asm volatile("cp.async.bulk.wait_group 0;" ::: "memory");
        }
    }
    __syncwarp();
    if (lane < 3) mbar_arrive_remote(mapa(bar + 8 * B_FIN, lane));
    mbar_wait(bar + 8 * B_FIN, 0);
}

int g_delay = 2501200, g_layers = 2;

void launch_rec(const bf16* mem0, const bf16* Wq, const bf16* Wk, const bf16* Wv, const bf16* Wo, int layer) {
    cudaLaunchConfig_t c = {};
    c.gridDim = dim3(96); c.blockDim = dim3(512); c.dynamicSmemBytes = rec::SMEM; c.stream = cudaStreamPerThread;
    cudaLaunchAttribute at[1];
    at[0].id = cudaLaunchAttributeClusterDimension; at[0].val.clusterDim.x = 3; at[0].val.clusterDim.y = 1; at[0].val.clusterDim.z = 1;
    c.attrs = at; c.numAttrs = 1;
    cudaLaunchKernelEx(&c, rec_kernel, mem0, Wq, Wk, Wv, Wo, layer, g_delay % 10000, g_delay / 10000);
}

}

extern "C" void kernel_launch(void* const* d_in, const int* in_sizes, int n_in, void* d_out, int out_size) {
    const bf16* x = (const bf16*)d_in[0];
    const bf16* mem0 = (const bf16*)d_in[1];
    const bf16* Wq = (const bf16*)d_in[2];
    const bf16* Wk = (const bf16*)d_in[3];
    const bf16* Wv = (const bf16*)d_in[4];
    const bf16* Wo = (const bf16*)d_in[5];
    const bf16* wr = (const bf16*)d_in[8];
    const bf16* wi = (const bf16*)d_in[9];
    cudaFuncSetAttribute(rec_kernel, cudaFuncAttributeMaxDynamicSharedMemorySize, rec::SMEM);
    cudaFuncSetAttribute(outproj_kernel, cudaFuncAttributeMaxDynamicSharedMemorySize, op::SMEM);
    cudaFuncSetAttribute(colfft_kernel, cudaFuncAttributeMaxDynamicSharedMemorySize, CF_SMEM);
    bf16 *x1, *x2;
    cudaGetSymbolAddress((void**)&x1, g_x1);
    cudaGetSymbolAddress((void**)&x2, g_x2);
    cudaStream_t st = cudaStreamPerThread;
    prep_kernel<<<128, 512, 0, st>>>(x, Wv, Wo);
    tables_kernel<<<128, 512, 0, st>>>(Wo, wr, wi);
    for (int layer = 0; layer < g_layers; layer++) {
        launch_rec(mem0, Wq, Wk, Wv, Wo, layer);
        outproj_kernel<<<128, 288, op::SMEM, st>>>(layer ? x2 : x, x1);
        rowfft_kernel<<<128, 256, 0, st>>>(x1);
        colfft_kernel<<<107, 384, CF_SMEM, st>>>();
        rowifft_kernel<<<128, 256, 0, st>>>(x1, layer ? (bf16*)d_out : x2, layer);
    }
}
```

```cpp
#include <cuda_runtime.h>
#include <cuda_bf16.h>
#include <cuda.h>
#include <stdint.h>

#define DEV __device__ __forceinline__
typedef unsigned long long u64;
typedef __nv_bfloat16 bf16;

namespace {

constexpr int S_ = 2048, D_ = 640, H_ = 32, E_ = 128, NSEG = 64;

__device__ __align__(1024) unsigned char g_xn[S_ * D_ * 2];
__device__ __align__(1024) unsigned char g_o[S_ * H_ * E_ * 2];
constexpr int ACC_LAYER = 32 * 5120;
__device__ __align__(4096) u64 g_acc[2 * ACC_LAYER];
__device__ __align__(16) float g_nrm[256];
__device__ __align__(1024) unsigned char g_p[NSEG * H_ * 3 * 4096];
constexpr int SYNC_LAYER = 1024;
__device__ __align__(128) uint32_t g_sync[2 * SYNC_LAYER];
__device__ __align__(1024) bf16 g_x1[S_ * D_];
__device__ __align__(1024) bf16 g_x2[S_ * D_];
constexpr int NCOL = 321;
__device__ __align__(1024) unsigned char g_z[NCOL * 8192];
__device__ __align__(1024) unsigned char g_wt[NCOL * 8192];
__device__ __align__(1024) uint4 g_f128[2 * 8 * 256];
__device__ __align__(1024) uint4 g_f64[2 * 4 * 128];
__device__ __align__(1024) bf16 g_g32[2 * 4096];

DEV uint32_t s2u(const void* p) { return (uint32_t)__cvta_generic_to_shared(p); }
DEV uint32_t clk() { uint32_t c; asm volatile("mov.u32 %0,%%clock;" : "=r"(c)::"memory"); return c; }
DEV uint32_t mapa(uint32_t a, uint32_t r) { uint32_t o; asm("mapa.shared::cluster.u32 %0,%1,%2;" : "=r"(o) : "r"(a), "r"(r)); return o; }
DEV void mbar_init(uint32_t b, uint32_t n) { asm volatile("mbarrier.init.shared::cta.b64 [%0],%1;" ::"r"(b), "r"(n) : "memory"); }
DEV bool mbar_try(uint32_t b, uint32_t par) {
    uint32_t ok;
    asm volatile("{.reg .pred p; mbarrier.try_wait.parity.shared::cta.b64 p,[%1],%2; selp.u32 %0,1,0,p;}" : "=r"(ok) : "r"(b), "r"(par) : "memory");
    return ok;
}
constexpr uint32_t SPIN_LIMIT = 1u << 18;
DEV void mbar_wait(uint32_t b, uint32_t par) {
    uint32_t n = 0;
    while (!mbar_try(b, par)) if (++n > SPIN_LIMIT) __trap();
}
DEV uint32_t opaque(uint32_t x) { return __shfl_xor_sync(~0u, x, 0); }
#define SFENCE() asm volatile("{.reg .pred p; setp.ne.u32 p,%1,0; @p mov.u32 %0,%%clock;}" : "+r"(sfd) : "r"((uint32_t)never) : "memory")
DEV void mbar_arrive(uint32_t b) { asm volatile("mbarrier.arrive.shared::cta.b64 _,[%0];" ::"r"(b) : "memory"); }
DEV void mbar_arrive_elect(uint32_t b) { asm volatile("{.reg .pred p; elect.sync _|p, 0xffffffff; @p mbarrier.arrive.shared::cta.b64 _,[%0];}" ::"r"(b) : "memory"); }
DEV void mbar_arrive_remote(uint32_t b) { asm volatile("mbarrier.arrive.shared::cluster.b64 _,[%0];" ::"r"(b) : "memory"); }
DEV void mbar_expect(uint32_t b, uint32_t tx) { asm volatile("mbarrier.arrive.expect_tx.shared::cta.b64 _,[%0],%1;" ::"r"(b), "r"(tx) : "memory"); }
DEV void bar_sync(int id, int n) { asm volatile("bar.sync %0,%1;" ::"r"(id), "r"(n) : "memory"); }
DEV void bar_arrive(int id, int n) { asm volatile("bar.arrive %0,%1;" ::"r"(id), "r"(n) : "memory"); }
template <int ID, int N> DEV void bar_arrive_if(bool p) {
    asm volatile("{.reg .pred p; setp.ne.u32 p,%0,0; @p bar.arrive %1,%2;}" ::"r"((uint32_t)p), "n"(ID), "n"(N) : "memory");
}
DEV void st_async1(uint32_t a, uint32_t x, uint32_t b) {
    asm volatile("st.async.shared::cluster.mbarrier::complete_tx::bytes.u32 [%0],%1,[%2];" ::"r"(a), "r"(x), "r"(b) : "memory");
}
DEV void st_async2(uint32_t a, uint32_t x, uint32_t y, uint32_t b) {
    asm volatile("st.async.shared::cluster.mbarrier::complete_tx::bytes.v2.u32 [%0],{%1,%2},[%3];" ::"r"(a), "r"(x), "r"(y), "r"(b) : "memory");
}
DEV void st_async4(uint32_t a, uint32_t x, uint32_t y, uint32_t z, uint32_t w, uint32_t b) {
    asm volatile("st.async.shared::cluster.mbarrier::complete_tx::bytes.v4.u32 [%0],{%1,%2,%3,%4},[%5];" ::"r"(a), "r"(x), "r"(y), "r"(z), "r"(w), "r"(b) : "memory");
}
DEV void bulk_g2s(uint32_t dst, const void* src, uint32_t bytes, uint32_t b) {
    asm volatile("cp.async.bulk.shared::cluster.global.mbarrier::complete_tx::bytes [%0],[%1],%2,[%3];" ::"r"(dst), "l"(src), "r"(bytes), "r"(b) : "memory");
}
DEV void bulk_s2s(uint32_t dst, uint32_t src, uint32_t bytes, uint32_t b) {
    asm volatile("cp.async.bulk.shared::cluster.shared::cta.mbarrier::complete_tx::bytes [%0],[%1],%2,[%3];" ::"r"(dst), "r"(src), "r"(bytes), "r"(b) : "memory");
}
DEV void bulk_s2g(void* dst, uint32_t src, uint32_t bytes) {
    asm volatile("cp.async.bulk.global.shared::cta.bulk_group [%0],[%1],%2;" ::"l"(dst), "r"(src), "r"(bytes) : "memory");
}
DEV void tma2d(uint32_t dst, const CUtensorMap* m, int c0, int c1, uint32_t b) {
    asm volatile("cp.async.bulk.tensor.2d.shared::cluster.global.mbarrier::complete_tx::bytes [%0],[%1,{%3,%4}],[%2];"
                 ::"r"(dst), "l"(m), "r"(b), "r"(c0), "r"(c1) : "memory");
}
DEV void bulk_commit() { asm volatile("cp.async.bulk.commit_group;" ::: "memory"); }
template <int N> DEV void bulk_wait() { asm volatile("cp.async.bulk.wait_group %0;" ::"n"(N) : "memory"); }
template <int N> DEV void bulk_wait_read() { asm volatile("cp.async.bulk.wait_group.read %0;" ::"n"(N) : "memory"); }
DEV void fence_async_all() { asm volatile("fence.proxy.async;" ::: "memory"); }
DEV void flag_add(uint32_t* p) { fence_async_all(); asm volatile("red.release.gpu.global.add.u32 [%0],1;" ::"l"(p) : "memory"); }
DEV void flag_wait(const uint32_t* p, uint32_t n) {
    uint32_t v, it = 0;
    for (;;) {
        asm volatile("ld.acquire.gpu.global.u32 %0,[%1];" : "=r"(v) : "l"(p) : "memory");
        if (v >= n) break;
        if (++it > (SPIN_LIMIT << 3)) __trap();
        __nanosleep(100);
    }
    fence_async_all();
}
DEV void cp16(uint32_t dst, const void* src) { asm volatile("cp.async.cg.shared.global [%0],[%1],16;" ::"r"(dst), "l"(src) : "memory"); }
DEV void cp_commit() { asm volatile("cp.async.commit_group;" ::: "memory"); }
template <int N> DEV void cp_wait() { asm volatile("cp.async.wait_group %0;" ::"n"(N) : "memory"); }
DEV uint32_t lds32(uint32_t a) { uint32_t x; asm volatile("ld.shared.u32 %0,[%1];" : "=r"(x) : "r"(a) : "memory"); return x; }
DEV void fence_async() { asm volatile("fence.proxy.async.shared::cta;" ::: "memory"); }
DEV uint32_t pack2(float lo, float hi) { uint32_t r; asm("cvt.rn.bf16x2.f32 %0,%1,%2;" : "=r"(r) : "f"(hi), "f"(lo)); return r; }
DEV uint32_t prmt(uint32_t a, uint32_t b, uint32_t s) { uint32_t r; asm("prmt.b32 %0,%1,%2,%3;" : "=r"(r) : "r"(a), "r"(b), "r"(s)); return r; }
DEV float ex2(float x) { float r; asm("ex2.approx.ftz.f32 %0,%1;" : "=f"(r) : "f"(x)); return r; }
DEV float rcp(float x) { float r; asm("rcp.approx.ftz.f32 %0,%1;" : "=f"(r) : "f"(x)); return r; }
DEV void lds128(uint32_t* r, uint32_t a) { asm volatile("ld.shared.v4.u32 {%0,%1,%2,%3},[%4];" : "=r"(r[0]), "=r"(r[1]), "=r"(r[2]), "=r"(r[3]) : "r"(a) : "memory"); }
DEV void lds64(uint32_t* r, uint32_t a) { asm volatile("ld.shared.v2.u32 {%0,%1},[%2];" : "=r"(r[0]), "=r"(r[1]) : "r"(a) : "memory"); }
DEV void lds64f(float& x, float& y, uint32_t a) { asm volatile("ld.shared.v2.f32 {%0,%1},[%2];" : "=f"(x), "=f"(y) : "r"(a) : "memory"); }
DEV void lds128f(float* r, uint32_t a) { asm volatile("ld.shared.v4.f32 {%0,%1,%2,%3},[%4];" : "=f"(r[0]), "=f"(r[1]), "=f"(r[2]), "=f"(r[3]) : "r"(a) : "memory"); }
DEV void sts128(uint32_t a, uint32_t x, uint32_t y, uint32_t z, uint32_t w) { asm volatile("st.shared.v4.u32 [%0],{%1,%2,%3,%4};" ::"r"(a), "r"(x), "r"(y), "r"(z), "r"(w) : "memory"); }
DEV void sts64(uint32_t a, uint32_t x, uint32_t y) { asm volatile("st.shared.v2.u32 [%0],{%1,%2};" ::"r"(a), "r"(x), "r"(y) : "memory"); }
DEV void sts32(uint32_t a, uint32_t x) { asm volatile("st.shared.u32 [%0],%1;" ::"r"(a), "r"(x) : "memory"); }
DEV void ldsm4(uint32_t* r, uint32_t a) { asm volatile("ldmatrix.sync.aligned.m8n8.x4.shared.b16 {%0,%1,%2,%3},[%4];" : "=r"(r[0]), "=r"(r[1]), "=r"(r[2]), "=r"(r[3]) : "r"(a) : "memory"); }
DEV void ldsm4t(uint32_t* r, uint32_t a) { asm volatile("ldmatrix.sync.aligned.m8n8.x4.trans.shared.b16 {%0,%1,%2,%3},[%4];" : "=r"(r[0]), "=r"(r[1]), "=r"(r[2]), "=r"(r[3]) : "r"(a) : "memory"); }
DEV void ldsm2(uint32_t* r, uint32_t a) { asm volatile("ldmatrix.sync.aligned.m8n8.x2.shared.b16 {%0,%1},[%2];" : "=r"(r[0]), "=r"(r[1]) : "r"(a) : "memory"); }
DEV void stsm4t(uint32_t a, uint32_t x, uint32_t y, uint32_t z, uint32_t w) { asm volatile("stmatrix.sync.aligned.m8n8.x4.trans.shared.b16 [%0],{%1,%2,%3,%4};" ::"r"(a), "r"(x), "r"(y), "r"(z), "r"(w) : "memory"); }
DEV void stsm4(uint32_t a, uint32_t x, uint32_t y, uint32_t z, uint32_t w) { asm volatile("stmatrix.sync.aligned.m8n8.x4.shared.b16 [%0],{%1,%2,%3,%4};" ::"r"(a), "r"(x), "r"(y), "r"(z), "r"(w) : "memory"); }
DEV void stsm2(uint32_t a, uint32_t x, uint32_t y) { asm volatile("stmatrix.sync.aligned.m8n8.x2.shared.b16 [%0],{%1,%2};" ::"r"(a), "r"(x), "r"(y) : "memory"); }
DEV void stsm2t(uint32_t a, uint32_t x, uint32_t y) { asm volatile("stmatrix.sync.aligned.m8n8.x2.trans.shared.b16 [%0],{%1,%2};" ::"r"(a), "r"(x), "r"(y) : "memory"); }
DEV void mma16(float* d, uint32_t a0, uint32_t a1, uint32_t a2, uint32_t a3, uint32_t b0, uint32_t b1) {
    asm volatile("mma.sync.aligned.m16n8k16.row.col.f32.bf16.bf16.f32 {%0,%1,%2,%3},{%4,%5,%6,%7},{%8,%9},{%0,%1,%2,%3};"
                 : "+f"(d[0]), "+f"(d[1]), "+f"(d[2]), "+f"(d[3]) : "r"(a0), "r"(a1), "r"(a2), "r"(a3), "r"(b0), "r"(b1));
}
DEV void mma8(float* d, uint32_t a0, uint32_t a1, uint32_t b0) {
    asm volatile("mma.sync.aligned.m16n8k8.row.col.f32.bf16.bf16.f32 {%0,%1,%2,%3},{%4,%5},{%6},{%0,%1,%2,%3};"
                 : "+f"(d[0]), "+f"(d[1]), "+f"(d[2]), "+f"(d[3]) : "r"(a0), "r"(a1), "r"(b0));
}
DEV u64 mkdesc(uint32_t a, uint32_t lbo, uint32_t sbo) { return (u64)((a & 0x3ffff) >> 4) | ((u64)(lbo >> 4) << 16) | ((u64)(sbo >> 4) << 32); }
constexpr u64 SW128 = 1ull << 62;
DEV void wg_fence() { asm volatile("wgmma.fence.sync.aligned;" ::: "memory"); }
DEV void wg_commit() { asm volatile("wgmma.commit_group.sync.aligned;" ::: "memory"); }
template <int N> DEV void wg_wait() { asm volatile("wgmma.wait_group.sync.aligned %0;" ::"n"(N) : "memory"); }
template <int ACC> DEV void wgmma_n32_rs(float* d, const uint32_t* a, u64 desc) {
    asm volatile("wgmma.mma_async.sync.aligned.m64n32k16.f32.bf16.bf16 {%0,%1,%2,%3,%4,%5,%6,%7,%8,%9,%10,%11,%12,%13,%14,%15},{%16,%17,%18,%19},%20,%21,1,1,0;"
                 : "+f"(d[0]), "+f"(d[1]), "+f"(d[2]), "+f"(d[3]), "+f"(d[4]), "+f"(d[5]), "+f"(d[6]), "+f"(d[7]),
                   "+f"(d[8]), "+f"(d[9]), "+f"(d[10]), "+f"(d[11]), "+f"(d[12]), "+f"(d[13]), "+f"(d[14]), "+f"(d[15])
                 : "r"(a[0]), "r"(a[1]), "r"(a[2]), "r"(a[3]), "l"(desc), "n"(ACC));
}
template <int ACC> DEV void wgmma_n32_ss(float* d, u64 da, u64 desc) {
    asm volatile("wgmma.mma_async.sync.aligned.m64n32k16.f32.bf16.bf16 {%0,%1,%2,%3,%4,%5,%6,%7,%8,%9,%10,%11,%12,%13,%14,%15},%16,%17,%18,1,1,0,0;"
                 : "+f"(d[0]), "+f"(d[1]), "+f"(d[2]), "+f"(d[3]), "+f"(d[4]), "+f"(d[5]), "+f"(d[6]), "+f"(d[7]),
                   "+f"(d[8]), "+f"(d[9]), "+f"(d[10]), "+f"(d[11]), "+f"(d[12]), "+f"(d[13]), "+f"(d[14]), "+f"(d[15])
                 : "l"(da), "l"(desc), "n"(ACC));
}
template <int ACC> DEV void wgmma_n16_ss(float* d, u64 da, u64 desc) {
    asm volatile("wgmma.mma_async.sync.aligned.m64n16k16.f32.bf16.bf16 {%0,%1,%2,%3,%4,%5,%6,%7},%8,%9,%10,1,1,0,0;"
                 : "+f"(d[0]), "+f"(d[1]), "+f"(d[2]), "+f"(d[3]), "+f"(d[4]), "+f"(d[5]), "+f"(d[6]), "+f"(d[7])
                 : "l"(da), "l"(desc), "n"(ACC));
}
#define ACC8(o) "+f"(d[o]), "+f"(d[o + 1]), "+f"(d[o + 2]), "+f"(d[o + 3]), "+f"(d[o + 4]), "+f"(d[o + 5]), "+f"(d[o + 6]), "+f"(d[o + 7])
template <int ACC, int TB> DEV void wgmma_n64_rs(float* d, const uint32_t* a, u64 desc) {
    asm volatile("wgmma.mma_async.sync.aligned.m64n64k16.f32.bf16.bf16 {%0,%1,%2,%3,%4,%5,%6,%7,%8,%9,%10,%11,%12,%13,%14,%15,"
                 "%16,%17,%18,%19,%20,%21,%22,%23,%24,%25,%26,%27,%28,%29,%30,%31},{%32,%33,%34,%35},%36,%37,1,1,%38;"
                 : ACC8(0), ACC8(8), ACC8(16), ACC8(24) : "r"(a[0]), "r"(a[1]), "r"(a[2]), "r"(a[3]), "l"(desc), "n"(ACC), "n"(TB));
}
template <int ACC, int TB> DEV void wgmma_n80_rs(float* d, const uint32_t* a, u64 desc) {
    asm volatile("wgmma.mma_async.sync.aligned.m64n80k16.f32.bf16.bf16 {%0,%1,%2,%3,%4,%5,%6,%7,%8,%9,%10,%11,%12,%13,%14,%15,"
                 "%16,%17,%18,%19,%20,%21,%22,%23,%24,%25,%26,%27,%28,%29,%30,%31,%32,%33,%34,%35,%36,%37,%38,%39},{%40,%41,%42,%43},%44,%45,1,1,%46;"
                 : ACC8(0), ACC8(8), ACC8(16), ACC8(24), ACC8(32) : "r"(a[0]), "r"(a[1]), "r"(a[2]), "r"(a[3]), "l"(desc), "n"(ACC), "n"(TB));
}
template <int TA, int TB> DEV void wgmma_n64_ss(float* d, u64 da, u64 db, int acc) {
    asm volatile("{.reg .pred p; setp.ne.b32 p,%34,0; wgmma.mma_async.sync.aligned.m64n64k16.f32.bf16.bf16 {%0,%1,%2,%3,%4,%5,%6,%7,%8,%9,%10,%11,%12,%13,%14,%15,%16,%17,%18,%19,%20,%21,%22,%23,%24,%25,%26,%27,%28,%29,%30,%31},%32,%33,p,1,1,%35,%36;}"
                 : ACC8(0), ACC8(8), ACC8(16), ACC8(24) : "l"(da), "l"(db), "r"(acc), "n"(TA), "n"(TB));
}
template <int TA, int TB> DEV void wgmma_n128_ss(float* d, u64 da, u64 db, int acc) {
    asm volatile("{.reg .pred p; setp.ne.b32 p,%66,0; wgmma.mma_async.sync.aligned.m64n128k16.f32.bf16.bf16 {%0,%1,%2,%3,%4,%5,%6,%7,%8,%9,%10,%11,%12,%13,%14,%15,%16,%17,%18,%19,%20,%21,%22,%23,%24,%25,%26,%27,%28,%29,%30,%31,%32,%33,%34,%35,%36,%37,%38,%39,%40,%41,%42,%43,%44,%45,%46,%47,%48,%49,%50,%51,%52,%53,%54,%55,%56,%57,%58,%59,%60,%61,%62,%63},%64,%65,p,1,1,%67,%68;}"
                 : ACC8(0), ACC8(8), ACC8(16), ACC8(24), ACC8(32), ACC8(40), ACC8(48), ACC8(56) : "l"(da), "l"(db), "r"(acc), "n"(TA), "n"(TB));
}
template <int TA, int TB> DEV void wgmma_n192_ss(float* d, u64 da, u64 db, int acc) {
    asm volatile("{.reg .pred p; setp.ne.b32 p,%98,0; wgmma.mma_async.sync.aligned.m64n192k16.f32.bf16.bf16 {%0,%1,%2,%3,%4,%5,%6,%7,%8,%9,%10,%11,%12,%13,%14,%15,%16,%17,%18,%19,%20,%21,%22,%23,%24,%25,%26,%27,%28,%29,%30,%31,%32,%33,%34,%35,%36,%37,%38,%39,%40,%41,%42,%43,%44,%45,%46,%47,%48,%49,%50,%51,%52,%53,%54,%55,%56,%57,%58,%59,%60,%61,%62,%63,%64,%65,%66,%67,%68,%69,%70,%71,%72,%73,%74,%75,%76,%77,%78,%79,%80,%81,%82,%83,%84,%85,%86,%87,%88,%89,%90,%91,%92,%93,%94,%95},%96,%97,p,1,1,%99,%100;}"
                 : ACC8(0), ACC8(8), ACC8(16), ACC8(24), ACC8(32), ACC8(40), ACC8(48), ACC8(56), ACC8(64), ACC8(72), ACC8(80), ACC8(88) : "l"(da), "l"(db), "r"(acc), "n"(TA), "n"(TB));
}
template <int ACC> DEV void wgmma_n40_ss(float* d, u64 da, u64 desc) {
    asm volatile("wgmma.mma_async.sync.aligned.m64n40k16.f32.bf16.bf16 {%0,%1,%2,%3,%4,%5,%6,%7,%8,%9,%10,%11,%12,%13,%14,%15,%16,%17,%18,%19},%20,%21,%22,1,1,0,0;"
                 : ACC8(0), ACC8(8), "+f"(d[16]), "+f"(d[17]), "+f"(d[18]), "+f"(d[19]) : "l"(da), "l"(desc), "n"(ACC));
}
DEV void pdl_wait() { asm volatile("griddepcontrol.wait;" ::: "memory"); }
DEV void pdl_launch() { asm volatile("griddepcontrol.launch_dependents;" ::: "memory"); }
DEV uint32_t ldg32(const void* p) { uint32_t v; asm volatile("ld.global.nc.u32 %0,[%1];" : "=r"(v) : "l"(p)); return v; }
DEV void ld_acc(u64& a, u64& b, const void* p) {
    const uint32_t done = (uint32_t)a & (uint32_t)b & 32u;
    asm volatile("{.reg .pred p; setp.eq.u32 p,%3,0;\n"
                 "@p ld.relaxed.gpu.global.v2.u64 {%0,%1},[%2];}" : "+l"(a), "+l"(b) : "l"(p), "r"(done) : "memory");
}
DEV void ld_acc0(u64& a, u64& b, const void* p) {
    asm volatile("ld.relaxed.gpu.global.v2.u64 {%0,%1},[%2];" : "=l"(a), "=l"(b) : "l"(p) : "memory");
}
DEV uint32_t and3(uint32_t a, uint32_t b, uint32_t c) { uint32_t r; asm volatile("lop3.b32 %0,%1,%2,%3,0x80;" : "=r"(r) : "r"(a), "r"(b), "r"(c)); return r; }
DEV uint32_t absmax2(uint32_t a, uint32_t b) { uint32_t r; asm("max.xorsign.abs.bf16x2 %0,%1,%2;" : "=r"(r) : "r"(a), "r"(b)); return r; }
DEV float lds32f(uint32_t a) { float x; asm volatile("ld.shared.f32 %0,[%1];" : "=f"(x) : "r"(a) : "memory"); return x; }
DEV void red_add64(u64* p, uint32_t lo, uint32_t hi) {
    asm volatile("{.reg .b64 v; mov.b64 v,{%1,%2}; red.relaxed.gpu.global.add.u64 [%0],v;}" ::"l"(p), "r"(lo), "r"(hi) : "memory");
}
DEV float bf_round(float x) { return __bfloat162float(__float2bfloat16_rn(x)); }
DEV float bf_lo(uint32_t u) { return __uint_as_float(u << 16); }
DEV float bf_hi(uint32_t u) { return __uint_as_float(u & 0xffff0000u); }

#define GPROF(i, n)
#define PROFT(i)
#define STAMP(i)

DEV int xn_off(int row, int chunk) { return (row >> 5) * 40960 + (chunk >> 3) * 4096 + (row & 31) * 128 + (((chunk ^ row) & 7) << 4); }

DEV void ln_row(float (&v)[3][8], int lane) {
    float s = 0.f;
#pragma unroll
    for (int c = 0; c < 3; c++)
#pragma unroll
        for (int j = 0; j < 8; j++) s += v[c][j];
#pragma unroll
    for (int o = 16; o; o >>= 1) s += __shfl_xor_sync(~0u, s, o);
    float mean = s * (1.f / D_), q = 0.f;
#pragma unroll
    for (int c = 0; c < 3; c++)
        if (c < 2 || lane < 16)
#pragma unroll
            for (int j = 0; j < 8; j++) { float d = v[c][j] - mean; q += d * d; }
#pragma unroll
    for (int o = 16; o; o >>= 1) q += __shfl_xor_sync(~0u, q, o);
    float mb = bf_round(mean);
    float sd = bf_round(sqrtf(bf_round(bf_round(q * (1.f / D_)) + 1e-5f)));
#pragma unroll
    for (int c = 0; c < 3; c++)
#pragma unroll
        for (int j = 0; j < 8; j++) v[c][j] = bf_round(v[c][j] - mb) / sd;
}

__global__ void __launch_bounds__(512) prep_kernel(const bf16* __restrict__ x, const bf16* __restrict__ Wv, const bf16* __restrict__ Wo) {
    __shared__ float red[32];
    const int tid = threadIdx.x, lane = tid & 31, warp = tid >> 5, b = blockIdx.x;
    {
        int row = b * 16 + warp;
        float v[3][8];
#pragma unroll
        for (int c = 0; c < 3; c++) {
            uint4 u = make_uint4(0, 0, 0, 0);
            if (c < 2 || lane < 16) u = *(const uint4*)(x + row * D_ + (c * 32 + lane) * 8);
            v[c][0] = bf_lo(u.x); v[c][1] = bf_hi(u.x); v[c][2] = bf_lo(u.y); v[c][3] = bf_hi(u.y);
            v[c][4] = bf_lo(u.z); v[c][5] = bf_hi(u.z); v[c][6] = bf_lo(u.w); v[c][7] = bf_hi(u.w);
        }
        ln_row(v, lane);
#pragma unroll
        for (int c = 0; c < 3; c++)
            if (c < 2 || lane < 16)
                *(uint4*)(g_xn + xn_off(row, c * 32 + lane)) =
                    make_uint4(pack2(v[c][0], v[c][1]), pack2(v[c][2], v[c][3]), pack2(v[c][4], v[c][5]), pack2(v[c][6], v[c][7]));
    }
    if (b == 0) ((uint4*)g_sync)[tid] = make_uint4(0, 0, 0, 0);
    for (int i = b * 512 + tid; i < ACC_LAYER; i += 128 * 512) ((uint4*)g_acc)[i] = make_uint4(0, 0, 0, 0);
    float sv = 0.f;
#pragma unroll
    for (int i = 0; i < 5; i++) {
        uint4 u = *(const uint4*)(Wv + (size_t)((b & 3) * 160 + i * 32 + (tid >> 4)) * 4096 + (b >> 2) * E_ + (tid & 15) * 8);
        uint32_t w[4] = {u.x, u.y, u.z, u.w};
#pragma unroll
        for (int j = 0; j < 4; j++) { float a = bf_lo(w[j]), c = bf_hi(w[j]); sv += a * a + c * c; }
    }
    float so = 0.f;
    if (tid < 320) {
        float s0 = 0.f, s1 = 0.f;
#pragma unroll 8
        for (int r = 0; r < 32; r++) { uint32_t u = *(const uint32_t*)(Wo + (size_t)(b * 32 + r) * D_ + tid * 2); float a = bf_lo(u), c = bf_hi(u); s0 += a * a; s1 += c * c; }
        so = fmaxf(s0, s1);
    }
#pragma unroll
    for (int o = 16; o; o >>= 1) { sv += __shfl_xor_sync(~0u, sv, o); so = fmaxf(so, __shfl_xor_sync(~0u, so, o)); }
    if (lane == 0) { red[warp] = sv; red[16 + warp] = so; }
    __syncthreads();
    if (tid == 0) {
        float a = 0.f, c = 0.f;
        for (int i = 0; i < 16; i++) { a += red[i]; c = fmaxf(c, red[16 + i]); }
        g_nrm[b] = a; g_nrm[128 + b] = c;
    }
}

__host__ __device__ constexpr int col_freq(int c) {
    return c == 320 ? 320 : c < 192 ? (c >> 6) * 128 + (c & 63) : c == 192 ? 192 : c < 256 ? 448 - c : c == 256 ? 64 : 384 - c;
}
DEV float rdft(int n, int k, int sn, int N) {
    float s, c;
    sincospif((float)((n * k) & (N - 1)) * (2.f / N), &s, &c);
    return !sn ? c : k ? s : (n & 1 ? -1.f : 1.f);
}
__global__ void __launch_bounds__(512) tables_kernel(const bf16* __restrict__ wr, const bf16* __restrict__ wi) {
    const int tid = threadIdx.x, b = blockIdx.x;
    if (tid < NCOL) {
        const int ka = b >> 2, i = b & 3, kn = ka ? 2048 - ka : 32, kc = col_freq(tid);
        const unsigned short* pr = (const unsigned short*)wr + kc;
        const unsigned short* pi = (const unsigned short*)wi + kc;
#pragma unroll
        for (int q = 0; q < 4; q++) {
            uint32_t v[4];
#pragma unroll
            for (int j = 0; j < 4; j++) {
                const int k = ((j & 1 ? kn : ka) + 64 * (4 * (2 * i + (j >> 1)) + q)) & 2047;
                v[j] = pr[k * NCOL] | ((uint32_t)pi[k * NCOL] << 16);
            }
            *(uint4*)(g_wt + tid * 8192 + i * 2048 + (ka * 4 + q) * 16) = make_uint4(v[0], v[1], v[2], v[3]);
        }
    }
    const int gid = b * 512 + tid;
    if (gid < 4096) {
        const int inv = gid >> 11, ks = (gid >> 8) & 7, t = gid & 255, g = (t & 31) >> 2, q = t & 3, tile = t >> 5;
        uint32_t v[4];
#pragma unroll
        for (int j = 0; j < 4; j++) {
            float x[2];
#pragma unroll
            for (int u = 0; u < 2; u++) {
                const int m = inv ? 16 * tile + 2 * g + (j & 1) : 16 * ks + 8 * (j >> 1) + 2 * q + u;
                const int k2 = inv ? 8 * ks + 2 * q + u : 8 * tile + g, sn = inv ? j >> 1 : j & 1;
                x[u] = rdft(m, k2, sn, 128);
                if (sn && k2) x[u] = -x[u];
            }
            v[j] = pack2(x[0], x[1]);
        }
        g_f128[gid] = make_uint4(v[0], v[1], v[2], v[3]);
    } else if (gid < 5120) {
        const int id = gid - 4096, inv = id >> 9, ks = (id >> 7) & 3, t = id & 127, g = (t & 31) >> 2, q = t & 3, tile = t >> 5;
        uint32_t v[4];
#pragma unroll
        for (int j = 0; j < 4; j++) {
            float x[2];
#pragma unroll
            for (int u = 0; u < 2; u++) {
                const int a = inv ? 16 * tile + g + 8 * (j & 1) : 16 * ks + 8 * (j >> 1) + 2 * q + u;
                const int ka = inv ? 8 * ks + 2 * q + u : 8 * tile + g, sn = inv ? j >> 1 : j & 1;
                x[u] = rdft(a, ka, sn, 64);
            }
            v[j] = pack2(x[0], x[1]);
        }
        g_f64[id] = make_uint4(v[0], v[1], v[2], v[3]);
    } else if (gid < 5120 + 8192) {
        const int id = gid - 5120, inv = id >> 12, n = ((id >> 9) & 7) * 8 + ((id >> 3) & 7), k = ((id >> 6) & 7) * 8 + (id & 7);
        float s, c;
        sincospif((float)(((n >> 1) * (k >> 1)) & 31) * (1.f / 16), &s, &c);
        if (inv) s = -s;
        g_g32[id] = __float2bfloat16_rn((n & 1) == (k & 1) ? c : (k & 1) ? s : -s);
    }
}

namespace wk {
constexpr int STAGE = 49152, NST = 3, OFF_OUT = NST * STAGE, OFF_BAR = OFF_OUT + 73728, SMEM = OFF_BAR + 128;
constexpr int NPB = 12;
__host__ __device__ constexpr int pb_start(int b) { return b == 0 ? 0 : b == 1 ? 2 : b < NPB ? 6 * b - 6 : 64; }
#define NOB 7
constexpr int N_P = NPB * H_, N_OB = NOB * 5, N_OT = (32 - 3 * NOB) * 10, N_ITEMS = N_P + N_OB + N_OT;
enum { SY_TICKET = 0, SY_O = 32, SY_P = 128 };
}
struct Maps { CUtensorMap wq, wv, wo; };

template <int NSG> DEV void proj_tile(uint32_t sb, uint32_t bar, int& it, int wg, int seg0, int h, uint32_t* flag) {
    using namespace wk;
    float acc[NSG * 16];
#pragma unroll
    for (int i = 0; i < NSG * 16; i++) acc[i] = 0.f;
    const int lane = threadIdx.x & 31, ww = (threadIdx.x >> 5) & 3;
    for (int kb = 0; kb < 10; kb++, it++) {
        const int st = it % NST;
        if (kb) mbar_wait(bar + 8 * st, (it / NST) & 1);
        const u64 da = mkdesc(sb + st * STAGE + wg * 8192, 0, 1024) | SW128, db = mkdesc(sb + st * STAGE + 24576, 0, 1024) | SW128;
        wg_fence();
#pragma unroll
        for (int ks = 0; ks < 4; ks++) {
            if (NSG == 2) wgmma_n64_ss<1, 0>(acc, da + ks * 128, db + ks * 2, 1);
            if (NSG == 4) wgmma_n128_ss<1, 0>(acc, da + ks * 128, db + ks * 2, 1);
            if (NSG == 6) wgmma_n192_ss<1, 0>(acc, da + ks * 128, db + ks * 2, 1);
        }
        wg_commit();
        if (kb) { wg_wait<1>(); mbar_arrive_elect(bar + 8 * (NST + (it - 1) % NST)); }
    }
    wg_wait<0>();
    mbar_arrive_elect(bar + 8 * (NST + (it - 1) % NST));
    const uint32_t out = sb + OFF_OUT + wg * 24576;
    const uint32_t la = out + (wg < 2 ? (lane >> 4) * 1024 + ww * 256 + (lane & 15) * 16 : ww * 1024 + ((lane >> 3) & 1) * 512 + (lane >> 4) * 128 + (lane & 7) * 16);
#pragma unroll
    for (int j = 0; j < 2 * NSG; j++) {
        const float* c = acc + 8 * j;
        const uint32_t p0 = pack2(c[0], c[1]), p1 = pack2(c[2], c[3]), p2 = pack2(c[4], c[5]), p3 = pack2(c[6], c[7]);
        if (wg < 2) stsm4t(la + j * 2048, p0, p1, p2, p3);
        else stsm4(la + (j >> 1) * 4096 + (j & 1) * 256, p0, p1, p2, p3);
    }
    fence_async();
    bar_sync(1 + wg, 128);
    if ((threadIdx.x & 127) == 0) {
        for (int j = 0; j < NSG; j++) bulk_s2g(g_p + (size_t)(((seg0 + j) * H_ + h) * 3 + wg) * 4096, out + j * 4096, 4096);
        bulk_commit();
        bulk_wait<0>();
        flag_add(flag);
    }
    bar_sync(1 + wg, 128);
}

DEV void resid_store(const bf16* __restrict__ x, bf16* __restrict__ x1, size_t o, float a, float b) {
    const uint32_t u = *(const uint32_t*)(x + o);
    *(uint32_t*)(x1 + o) = pack2(bf_lo(u) + bf_round(a), bf_hi(u) + bf_round(b));
}

DEV void worker(uint32_t sb, const Maps& maps, const bf16* __restrict__ x, bf16* __restrict__ x1, int layer, int first, int last) {
    using namespace wk;
    const uint32_t bar = sb + OFF_BAR, slot = bar + 64;
    const int tid = threadIdx.x, lane = tid & 31, warp = __shfl_sync(~0u, tid >> 5, 0);
    uint32_t* sy = g_sync + layer * SYNC_LAYER;
    if (tid == 0) {
        for (int i = 0; i < NST; i++) { mbar_init(bar + 8 * i, 1); mbar_init(bar + 8 * (NST + i), 12); }
        asm volatile("fence.mbarrier_init.release.cluster;" ::: "memory");
    }
    __syncthreads();
    if (warp >= 12) {
        asm volatile("setmaxnreg.dec.sync.aligned.u32 56;");
        if (tid == 384) {
            int it = 0;
            auto acquire = [&]() { const int st = it % NST; if (it >= NST) mbar_wait(bar + 8 * (NST + st), (it / NST - 1) & 1); return st; };
            for (;;) {
                int id = first + (int)atomicAdd(sy + SY_TICKET + (first ? 1 : 0), 1u);
                if (id >= last) id = -1;
                int st = acquire();
                sts32(slot + 4 * st, id);
                if (id < 0) { mbar_arrive(bar + 8 * st); break; }
                if (id < N_P) {
                    const int b = id >> 5, h = id & 31, s0 = pb_start(b), ns = pb_start(b + 1) - s0;
                    for (int kb = 0; kb < 10; kb++, it++) {
                        if (kb) st = acquire();
                        const uint32_t d = sb + st * STAGE, fb = bar + 8 * st;
                        mbar_expect(fb, 24576 + ns * 4096);
                        tma2d(d, &maps.wq, h * E_, kb * 64, fb);
                        tma2d(d + 8192, &maps.wq, h * E_ + 64, kb * 64, fb);
                        tma2d(d + 16384, &maps.wv, h * E_, kb * 64, fb);
                        for (int j = 0; j < ns; j++) bulk_g2s(d + 24576 + j * 4096, g_xn + (s0 + j) * 40960 + kb * 4096, 4096, fb);
                    }
                } else if (id < N_P + N_OB) {
                    const int b = (id - N_P) / 5, nt = (id - N_P) % 5;
                    for (int j = 0; j < 6; j++) flag_wait(sy + SY_O + 6 * b + j, 64);
                    for (int kb = 0; kb < 64; kb++, it++) {
                        if (kb) st = acquire();
                        const uint32_t d = sb + st * STAGE, fb = bar + 8 * st;
                        mbar_expect(fb, 40960);
                        for (int j = 0; j < 6; j++) bulk_g2s(d + j * 4096, g_o + (size_t)((6 * b + j) * 64 + kb) * 4096, 4096, fb);
                        tma2d(d + 24576, &maps.wo, nt * 128, kb * 64, fb);
                        tma2d(d + 32768, &maps.wo, nt * 128 + 64, kb * 64, fb);
                    }
                } else {
                    const int b = 3 * NOB + (id - N_P - N_OB) / 10, nt = (id - N_P - N_OB) % 10;
                    for (int j = 0; j < 2; j++) flag_wait(sy + SY_O + 2 * b + j, 64);
                    for (int kb = 0; kb < 22; kb++, it++) {
                        if (kb) st = acquire();
                        const uint32_t d = sb + st * STAGE, fb = bar + 8 * st;
                        const int nu = kb < 21 ? 3 : 1;
                        mbar_expect(fb, nu * 16384);
                        for (int u = 0; u < nu; u++) {
                            for (int j = 0; j < 2; j++) bulk_g2s(d + u * 8192 + j * 4096, g_o + (size_t)((2 * b + j) * 64 + 3 * kb + u) * 4096, 4096, fb);
                            tma2d(d + 24576 + u * 8192, &maps.wo, nt * 64, (3 * kb + u) * 64, fb);
                        }
                    }
                }
            }
        }
    } else {
        asm volatile("setmaxnreg.inc.sync.aligned.u32 152;");
        const int wg = warp >> 2, g = lane >> 2, q = lane & 3;
        int it = 0;
        for (;;) {
            mbar_wait(bar + 8 * (it % NST), (it / NST) & 1);
            const int id = (int)lds32(slot + 4 * (it % NST));
            if (id < 0) break;
            if (id < N_P) {
                const int b = id >> 5, h = id & 31;
                uint32_t* flag = sy + SY_P + id;
                if (b == 0) proj_tile<2>(sb, bar, it, wg, 0, h, flag);
                else if (b == 1 || b == NPB - 1) proj_tile<4>(sb, bar, it, wg, pb_start(b), h, flag);
                else proj_tile<6>(sb, bar, it, wg, pb_start(b), h, flag);
            } else if (id < N_P + N_OB) {
                const int b = (id - N_P) / 5, nt = (id - N_P) % 5;
                float acc[64];
#pragma unroll
                for (int i = 0; i < 64; i++) acc[i] = 0.f;
                for (int kb = 0; kb < 64; kb++, it++) {
                    const int st = it % NST;
                    if (kb) mbar_wait(bar + 8 * st, (it / NST) & 1);
                    const u64 da = mkdesc(sb + st * STAGE + wg * 8192, 128, 1024), db = mkdesc(sb + st * STAGE + 24576, 8192, 1024) | SW128;
                    wg_fence();
#pragma unroll
                    for (int ks = 0; ks < 4; ks++) wgmma_n128_ss<0, 1>(acc, da + ks * 16, db + ks * 128, 1);
                    wg_commit();
                    if (kb) { wg_wait<1>(); mbar_arrive_elect(bar + 8 * (NST + (it - 1) % NST)); }
                }
                wg_wait<0>();
                mbar_arrive_elect(bar + 8 * (NST + (it - 1) % NST));
                const size_t o = (size_t)(192 * b + 16 * warp + g) * D_ + nt * 128 + 2 * q;
#pragma unroll
                for (int t = 0; t < 16; t++) {
                    resid_store(x, x1, o + 8 * t, acc[4 * t], acc[4 * t + 1]);
                    resid_store(x, x1, o + 8 * t + 8 * D_, acc[4 * t + 2], acc[4 * t + 3]);
                }
            } else {
                const int b = 3 * NOB + (id - N_P - N_OB) / 10, nt = (id - N_P - N_OB) % 10;
                float acc[32];
#pragma unroll
                for (int i = 0; i < 32; i++) acc[i] = 0.f;
                for (int kb = 0; kb < 22; kb++, it++) {
                    const int st = it % NST;
                    if (kb) mbar_wait(bar + 8 * st, (it / NST) & 1);
                    if (kb < 21 || wg == 0) {
                        const u64 da = mkdesc(sb + st * STAGE + wg * 8192, 128, 1024), db = mkdesc(sb + st * STAGE + 24576 + wg * 8192, 0, 1024) | SW128;
                        wg_fence();
#pragma unroll
                        for (int ks = 0; ks < 4; ks++) wgmma_n64_ss<0, 1>(acc, da + ks * 16, db + ks * 128, 1);
                    }
                    wg_commit();
                    if (kb) { wg_wait<1>(); mbar_arrive_elect(bar + 8 * (NST + (it - 1) % NST)); }
                }
                wg_wait<0>();
                mbar_arrive_elect(bar + 8 * (NST + (it - 1) % NST));
                const uint32_t ra = sb + OFF_OUT + (tid & 127) * 16;
                if (wg) {
#pragma unroll
                    for (int t = 0; t < 8; t++)
                        sts128(ra + wg * 16384 + t * 2048, __float_as_uint(acc[4 * t]), __float_as_uint(acc[4 * t + 1]), __float_as_uint(acc[4 * t + 2]), __float_as_uint(acc[4 * t + 3]));
                }
                bar_sync(4, 384);
                if (wg == 0) {
                    const size_t o = (size_t)(64 * b + 16 * warp + g) * D_ + nt * 64 + 2 * q;
#pragma unroll
                    for (int t = 0; t < 8; t++) {
                        float u[4], v[4];
                        lds128f(u, ra + 16384 + t * 2048); lds128f(v, ra + 32768 + t * 2048);
                        resid_store(x, x1, o + 8 * t, acc[4 * t] + u[0] + v[0], acc[4 * t + 1] + u[1] + v[1]);
                        resid_store(x, x1, o + 8 * t + 8 * D_, acc[4 * t + 2] + u[2] + v[2], acc[4 * t + 3] + u[3] + v[3]);
                    }
                }
                bar_sync(4, 384);
            }
        }
    }
}

__global__ void __launch_bounds__(512, 1) side_kernel(const __grid_constant__ Maps maps, const bf16* __restrict__ x, bf16* __restrict__ x1, int layer, int first, int last) {
    extern __shared__ __align__(1024) unsigned char smem[];
    worker(s2u(smem), maps, x, x1, layer, first, last);
}

constexpr float C5A = 0.30901699437494742f, C5B = -0.80901699437494742f, S5A = 0.95105651629515357f, S5B = 0.58778525229247313f;
template <int SGN> DEV void dft5(const float (&tr)[5], const float (&ti)[5], float (&zr)[5], float (&zi)[5]) {
    const float ar = tr[1] + tr[4], ai = ti[1] + ti[4], br = tr[2] + tr[3], bi = ti[2] + ti[3];
    const float cr = tr[1] - tr[4], ci = ti[1] - ti[4], dr = tr[2] - tr[3], di = ti[2] - ti[3];
    zr[0] = tr[0] + ar + br; zi[0] = ti[0] + ai + bi;
    const float m1r = tr[0] + C5A * ar + C5B * br, m1i = ti[0] + C5A * ai + C5B * bi;
    const float m2r = tr[0] + C5B * ar + C5A * br, m2i = ti[0] + C5B * ai + C5A * bi;
    const float n1r = SGN * (S5A * cr + S5B * dr), n1i = SGN * (S5A * ci + S5B * di);
    const float n2r = SGN * (S5B * cr - S5A * dr), n2i = SGN * (S5B * ci - S5A * di);
    zr[1] = m1r + n1i; zi[1] = m1i - n1r; zr[4] = m1r - n1i; zi[4] = m1i + n1r;
    zr[2] = m2r + n2i; zi[2] = m2i - n2r; zr[3] = m2r - n2i; zi[3] = m2i + n2r;
}
DEV void ln40(float (&v)[40]) {
    float s = 0.f;
#pragma unroll
    for (int i = 0; i < 40; i++) s += v[i];
#pragma unroll
    for (int o = 8; o; o >>= 1) s += __shfl_xor_sync(~0u, s, o);
    const float mean = s * (1.f / D_);
    float q = 0.f;
#pragma unroll
    for (int i = 0; i < 40; i++) { const float d = v[i] - mean; q += d * d; }
#pragma unroll
    for (int o = 8; o; o >>= 1) q += __shfl_xor_sync(~0u, q, o);
    const float mb = bf_round(mean);
    const float inv = 1.f / bf_round(sqrtf(bf_round(bf_round(q * (1.f / D_)) + 1e-5f)));
#pragma unroll
    for (int i = 0; i < 40; i++) v[i] = bf_round(v[i] - mb) * inv;
}
DEV void unpack8(float* v, uint4 u) {
    v[0] = bf_lo(u.x); v[1] = bf_hi(u.x); v[2] = bf_lo(u.y); v[3] = bf_hi(u.y);
    v[4] = bf_lo(u.z); v[5] = bf_hi(u.z); v[6] = bf_lo(u.w); v[7] = bf_hi(u.w);
}

__global__ void __launch_bounds__(256) rowfft_kernel(const bf16* __restrict__ x) {
    __shared__ __align__(128) unsigned char sm[10 * 2304];
    const uint32_t sb = s2u(sm);
    const int tid = threadIdx.x, lane = tid & 31, q = lane & 3, blk = blockIdx.x, k2 = tid >> 2;
    float twr[5], twi[5];
#pragma unroll
    for (int r = 1; r < 5; r++) { sincospif((float)(r * k2) * (-1.f / 320), &twi[r], &twr[r]); }
    pdl_wait();
    pdl_launch();
    uint32_t f[8][4];
#pragma unroll
    for (int ks = 0; ks < 8; ks++) { const uint4 u = g_f128[ks * 256 + tid]; f[ks][0] = u.x; f[ks][1] = u.y; f[ks][2] = u.z; f[ks][3] = u.w; }
    {
        const int rho = tid >> 4, j = tid & 15;
        float v[40];
#pragma unroll
        for (int i = 0; i < 5; i++) unpack8(v + 8 * i, *(const uint4*)(x + (size_t)(blk * 16 + rho) * D_ + j * 40 + i * 8));
        ln40(v);
        const uint32_t a = sb + ((rho >> 1) & 1) * 2304 + j * 144 + (2 * (rho >> 2) + (rho & 1)) * 16;
#pragma unroll
        for (int r = 0; r < 5; r++)
            sts128(a + r * 4608, pack2(v[r], v[5 + r]), pack2(v[10 + r], v[15 + r]), pack2(v[20 + r], v[25 + r]), pack2(v[30 + r], v[35 + r]));
    }
    fence_async();
    __syncthreads();
    float acc[40];
    const u64 db = mkdesc(sb, 144, 2304);
    wg_fence();
    wgmma_n80_rs<0, 0>(acc, f[0], db);
#pragma unroll
    for (int ks = 1; ks < 8; ks++) wgmma_n80_rs<1, 0>(acc, f[ks], db + ks * 18);
    wg_commit();
    wg_wait<0>();
    unsigned char* zp = g_z + (blk >> 1) * 128 + ((((blk & 1) * 4 + q) ^ ((blk >> 1) & 7)) << 4);
    uint32_t o[5][4];
#pragma unroll
    for (int u = 0; u < 4; u++) {
        float tr[5], ti[5], zr[5], zi[5];
#pragma unroll
        for (int r = 0; r < 5; r++) {
            const float yr = acc[8 * r + 4 * (u >> 1) + (u & 1)], yi = k2 ? acc[8 * r + 4 * (u >> 1) + 2 + (u & 1)] : 0.f;
            tr[r] = r ? yr * twr[r] - yi * twi[r] : yr;
            ti[r] = r ? yr * twi[r] + yi * twr[r] : yi;
        }
        dft5<1>(tr, ti, zr, zi);
#pragma unroll
        for (int j = 0; j < 5; j++) o[j][u] = pack2(zr[j], j < 3 ? zi[j] : -zi[j]);
    }
#pragma unroll
    for (int j = 0; j < 5; j++)
        if (j < 3 || k2) *(uint4*)(zp + (64 * j + k2) * 8192) = make_uint4(o[j][0], o[j][1], o[j][2], o[j][3]);
    if (k2 == 0) {
#pragma unroll
        for (int u = 0; u < 4; u++) {
            float tr[5], ti[5], zr[5], zi[5];
            const float cr[5] = {1.f, -C5B, C5A, -C5A, C5B}, ci[5] = {0.f, -S5B, -S5A, -S5A, -S5B};
#pragma unroll
            for (int r = 0; r < 5; r++) { const float y = acc[8 * r + 4 * (u >> 1) + 2 + (u & 1)]; tr[r] = y * cr[r]; ti[r] = y * ci[r]; }
            dft5<1>(tr, ti, zr, zi);
            o[0][u] = pack2(zr[0], zi[0]); o[1][u] = pack2(zr[1], zi[1]); o[2][u] = pack2(zr[2], 0.f);
        }
        *(uint4*)(zp + 256 * 8192) = make_uint4(o[0][0], o[0][1], o[0][2], o[0][3]);
        *(uint4*)(zp + 192 * 8192) = make_uint4(o[1][0], o[1][1], o[1][2], o[1][3]);
        *(uint4*)(zp + 320 * 8192) = make_uint4(o[2][0], o[2][1], o[2][2], o[2][3]);
    }
}

constexpr int CF_SMEM = 16384 + 3 * 16384 + 64;
__global__ void __launch_bounds__(384) colfft_kernel() {
    extern __shared__ __align__(1024) unsigned char smem[];
    const uint32_t sb = s2u(smem), bar = sb + 65536;
    const int tid = threadIdx.x, lane = tid & 31, q = lane & 3, wg = __shfl_sync(~0u, tid >> 7, 0), t = tid & 127, ka = t >> 2;
    const int col = blockIdx.x * 3 + wg;
    const uint32_t d0 = sb + 16384 + wg * 16384, d1 = d0 + 8192;
    if (tid == 0) {
        for (int i = 0; i < 4; i++) mbar_init(bar + 8 * i, 1);
        asm volatile("fence.mbarrier_init.release.cluster;" ::: "memory");
    }
    float twr[8], twi[8];
#pragma unroll
    for (int i = 0; i < 8; i++) sincospif((float)((4 * i + q) * (ka ? ka : -32)) * (1.f / 1024), &twi[i], &twr[i]);
    __syncthreads();
    pdl_wait();
    pdl_launch();
    if (t == 0) {
        mbar_expect(bar + 8 * wg, 8192);
        bulk_g2s(d0, g_z + col * 8192, 8192, bar + 8 * wg);
        if (wg == 0) { mbar_expect(bar + 24, 16384); bulk_g2s(sb, g_g32, 16384, bar + 24); }
    }
    uint32_t f[4][4], w[16];
#pragma unroll
    for (int ks = 0; ks < 4; ks++) { const uint4 u = g_f64[ks * 128 + t]; f[ks][0] = u.x; f[ks][1] = u.y; f[ks][2] = u.z; f[ks][3] = u.w; }
#pragma unroll
    for (int i = 0; i < 4; i++) { const uint4 u = *(const uint4*)(g_wt + col * 8192 + i * 2048 + t * 16); w[4 * i] = u.x; w[4 * i + 1] = u.y; w[4 * i + 2] = u.z; w[4 * i + 3] = u.w; }
    float acc[32];
    uint32_t a[4][4];
    mbar_wait(bar + 8 * wg, 0);
    {
        const u64 db = mkdesc(d0, 0, 1024) | SW128;
        wg_fence();
        wgmma_n64_rs<0, 1>(acc, f[0], db);
#pragma unroll
        for (int ks = 1; ks < 4; ks++) wgmma_n64_rs<1, 1>(acc, f[ks], db + ks * 128);
        wg_commit();
        wg_wait<0>();
    }
#pragma unroll
    for (int ks = 0; ks < 4; ks++) { const uint4 u = g_f64[512 + ks * 128 + t]; f[ks][0] = u.x; f[ks][1] = u.y; f[ks][2] = u.z; f[ks][3] = u.w; }
#pragma unroll
    for (int i = 0; i < 8; i++) {
        const float c0 = acc[4 * i], c1 = acc[4 * i + 1], c2 = acc[4 * i + 2], c3 = acc[4 * i + 3];
        const float pr = c0 + c3, pi = c1 - c2, nr = ka ? c0 - c3 : c2, ni = ka ? c1 + c2 : c3;
        a[i >> 1][2 * (i & 1)] = ka ? pack2(pr * twr[i] + pi * twi[i], pi * twr[i] - pr * twi[i]) : pack2(c0, c1);
        a[i >> 1][2 * (i & 1) + 1] = pack2(nr * twr[i] - ni * twi[i], ni * twr[i] + nr * twi[i]);
    }
    mbar_wait(bar + 24, 0);
    {
        const u64 db = mkdesc(sb, 128, 1024);
        wg_fence();
        wgmma_n64_rs<0, 0>(acc, a[0], db);
#pragma unroll
        for (int ks = 1; ks < 4; ks++) wgmma_n64_rs<1, 0>(acc, a[ks], db + ks * 16);
        wg_commit();
        wg_wait<0>();
    }
    constexpr float NORM = 1.f / (2048.f * 640.f);
#pragma unroll
    for (int i = 0; i < 16; i++) {
        const float zr = acc[2 * i] * NORM, zi = acc[2 * i + 1] * NORM, wr = bf_lo(w[i]), wi = bf_hi(w[i]);
        a[i >> 2][i & 3] = pack2(zr * wr - zi * wi, zr * wi + zi * wr);
    }
    {
        const u64 db = mkdesc(sb + 8192, 128, 1024);
        wg_fence();
        wgmma_n64_rs<0, 0>(acc, a[0], db);
#pragma unroll
        for (int ks = 1; ks < 4; ks++) wgmma_n64_rs<1, 0>(acc, a[ks], db + ks * 16);
        wg_commit();
        wg_wait<0>();
    }
    const uint32_t row = (t >> 5) * 2048 + (lane & 15) * 128;
#pragma unroll
    for (int i = 0; i < 8; i++) {
        const float c0 = acc[4 * i], c1 = acc[4 * i + 1], c2 = acc[4 * i + 2], c3 = acc[4 * i + 3];
        const float pr = c0 * twr[i] - c1 * twi[i], pi = c1 * twr[i] + c0 * twi[i];
        const float nr = c2 * twr[i] + c3 * twi[i], ni = c3 * twr[i] - c2 * twi[i];
        a[i >> 1][2 * (i & 1)] = ka ? pack2(pr + nr, pi + ni) : pack2(c0, c1);
        a[i >> 1][2 * (i & 1) + 1] = ka ? pack2(ni - pi, pr - nr) : pack2(nr, ni);
    }
#pragma unroll
    for (int i = 0; i < 4; i++) stsm4(d1 + row + (((2 * i + (lane >> 4)) ^ (lane & 7)) << 4), a[i][0], a[i][1], a[i][2], a[i][3]);
    fence_async();
    bar_sync(1 + wg, 128);
    {
        const u64 db = mkdesc(d1, 0, 1024) | SW128;
        wg_fence();
        wgmma_n64_rs<0, 1>(acc, f[0], db);
#pragma unroll
        for (int ks = 1; ks < 4; ks++) wgmma_n64_rs<1, 1>(acc, f[ks], db + ks * 128);
        wg_commit();
        wg_wait<0>();
    }
#pragma unroll
    for (int i = 0; i < 4; i++)
        stsm4(d0 + row + (((2 * i + (lane >> 4)) ^ (lane & 7)) << 4), pack2(acc[8 * i], acc[8 * i + 1]), pack2(acc[8 * i + 2], acc[8 * i + 3]),
              pack2(acc[8 * i + 4], acc[8 * i + 5]), pack2(acc[8 * i + 6], acc[8 * i + 7]));
    fence_async();
    bar_sync(1 + wg, 128);
    if (t == 0) {
        bulk_s2g(g_z + col * 8192, d0, 8192);
        asm volatile("cp.async.bulk.commit_group;" ::: "memory");
        asm volatile("cp.async.bulk.wait_group 0;" ::: "memory");
    }
}

__global__ void __launch_bounds__(256) rowifft_kernel(const bf16* __restrict__ x, bf16* __restrict__ out, int last) {
    __shared__ __align__(128) unsigned char sm[20480 + 16 * 1296];
    const uint32_t sb = s2u(sm), sy = sb + 20480;
    const int tid = threadIdx.x, lane = tid & 31, q = lane & 3, blk = blockIdx.x, k2 = tid >> 2, warp = tid >> 5;
    float twr[5], twi[5];
#pragma unroll
    for (int r = 1; r < 5; r++) { sincospif((float)(r * k2) * (1.f / 320), &twi[r], &twr[r]); twr[r] *= 2.f; twi[r] *= 2.f; }
    pdl_wait();
    pdl_launch();
    const unsigned char* zp = g_z + (blk >> 1) * 128 + ((((blk & 1) * 4 + q) ^ ((blk >> 1) & 7)) << 4);
    uint4 z[6];
#pragma unroll
    for (int j = 0; j < 5; j++) z[j] = *(const uint4*)(zp + (64 * j + k2) * 8192);
    z[5] = k2 ? make_uint4(0, 0, 0, 0) : *(const uint4*)(zp + 320 * 8192);
    uint32_t f[8][4];
#pragma unroll
    for (int ks = 0; ks < 8; ks++) { const uint4 u = g_f128[2048 + ks * 256 + tid]; f[ks][0] = u.x; f[ks][1] = u.y; f[ks][2] = u.z; f[ks][3] = u.w; }
    uint4 xr[5];
#pragma unroll
    for (int i = 0; i < 5; i++) xr[i] = *(const uint4*)(x + (size_t)(blk * 16 + (tid >> 4)) * D_ + (tid & 15) * 40 + i * 8);
    float acc[40];
#pragma unroll
    for (int u = 0; u < 4; u++) {
        float yr[6], yi[6], tr[5], ti[5], zr[5], zi[5];
#pragma unroll
        for (int j = 0; j < 6; j++) { const uint32_t v = u == 0 ? z[j].x : u == 1 ? z[j].y : u == 2 ? z[j].z : z[j].w; yr[j] = bf_lo(v); yi[j] = bf_hi(v); }
#pragma unroll
        for (int j = 0; j < 5; j++) { tr[j] = yr[j]; ti[j] = j < 3 ? yi[j] : -yi[j]; }
        dft5<-1>(tr, ti, zr, zi);
        const float c1[5] = {1.f, C5A, C5B, C5B, C5A}, s1[5] = {0.f, S5A, S5B, -S5B, -S5A};
        const float c2[5] = {1.f, C5B, C5A, C5A, C5B}, s2[5] = {0.f, S5B, -S5A, S5A, -S5B};
        const float c3[5] = {1.f, -C5B, C5A, -C5A, C5B}, s3[5] = {0.f, S5B, S5A, S5A, S5B};
        const float c4[5] = {1.f, -C5A, C5B, -C5B, C5A}, s4[5] = {0.f, S5A, -S5B, -S5B, S5A};
#pragma unroll
        for (int r = 0; r < 5; r++) {
            float er = r ? zr[r] * twr[r] - zi[r] * twi[r] : 2.f * zr[0], ei = r ? zr[r] * twi[r] + zi[r] * twr[r] : 2.f * zi[0];
            if (k2 == 0) {
                er = yr[0] + 2.f * (yr[1] * c1[r] - yi[1] * s1[r] + yr[2] * c2[r] - yi[2] * s2[r]);
                ei = (r & 1 ? -yr[5] : yr[5]) + 2.f * (yr[4] * c3[r] - yi[4] * s3[r] + yr[3] * c4[r] - yi[3] * s4[r]);
            }
            acc[8 * r + 4 * (u >> 1) + (u & 1)] = er;
            acc[8 * r + 4 * (u >> 1) + 2 + (u & 1)] = ei;
        }
    }
#pragma unroll
    for (int r = 0; r < 5; r++)
        stsm4(sb + (2 * warp + ((lane >> 3) & 1)) * 1280 + (2 * r + (lane >> 4)) * 128 + (lane & 7) * 16, pack2(acc[8 * r], acc[8 * r + 1]),
              pack2(acc[8 * r + 2], acc[8 * r + 3]), pack2(acc[8 * r + 4], acc[8 * r + 5]), pack2(acc[8 * r + 6], acc[8 * r + 7]));
    fence_async();
    __syncthreads();
    const u64 db = mkdesc(sb, 1280, 128);
    wg_fence();
    wgmma_n80_rs<0, 1>(acc, f[0], db);
#pragma unroll
    for (int ks = 1; ks < 8; ks++) wgmma_n80_rs<1, 1>(acc, f[ks], db + ks * 160);
    wg_commit();
    wg_wait<0>();
#pragma unroll
    for (int u = 0; u < 4; u++) {
        float e[10];
#pragma unroll
        for (int r = 0; r < 5; r++) { e[r] = acc[8 * r + 4 * (u >> 1) + (u & 1)]; e[5 + r] = acc[8 * r + 4 * (u >> 1) + 2 + (u & 1)]; }
#pragma unroll
        for (int i = 0; i < 5; i++) sts32(sy + (4 * q + u) * 1296 + k2 * 20 + i * 4, pack2(e[2 * i], e[2 * i + 1]));
    }
    __syncthreads();
    const int rho = tid >> 4, j = tid & 15, row = blk * 16 + rho;
    float v[40];
#pragma unroll
    for (int i = 0; i < 5; i++) {
        uint32_t y[4];
        float a[8], b[8];
        lds128(y, sy + rho * 1296 + j * 80 + i * 16);
        unpack8(a, xr[i]); unpack8(b, make_uint4(y[0], y[1], y[2], y[3]));
        const uint4 o = make_uint4(pack2(a[0] + b[0], a[1] + b[1]), pack2(a[2] + b[2], a[3] + b[3]), pack2(a[4] + b[4], a[5] + b[5]), pack2(a[6] + b[6], a[7] + b[7]));
        *(uint4*)(out + (size_t)row * D_ + j * 40 + i * 8) = o;
        unpack8(v + 8 * i, o);
    }
    if (!last) {
        ln40(v);
#pragma unroll
        for (int i = 0; i < 5; i++)
            *(uint4*)(g_xn + xn_off(row, j * 5 + i)) =
                make_uint4(pack2(v[8 * i], v[8 * i + 1]), pack2(v[8 * i + 2], v[8 * i + 3]), pack2(v[8 * i + 4], v[8 * i + 5]), pack2(v[8 * i + 6], v[8 * i + 7]));
    }
}

namespace rec {
constexpr int NS = 5, NS0 = 2;
constexpr int OFF_X = 0;
constexpr int OFF_WO = 81920;
constexpr int OFF_WS = OFF_WO + 57344;
constexpr int OFF_MEMB = OFF_WS + (NS + NS0) * 2048;
constexpr int OFF_VX = OFF_MEMB + 10240;
constexpr int OFF_VM = OFF_VX + 16384;
constexpr int OFF_Q = OFF_VM + 4096;
constexpr int OFF_K = OFF_Q + 10240;
constexpr int OFF_PX = OFF_K + 10240;
constexpr int OFF_OST = OFF_PX + 2560;
constexpr int OFF_PT = OFF_OST + 4096;
constexpr int OFF_PS = OFF_PT + 1536;
constexpr int OFF_OB = OFF_PS + 1280;
constexpr int OFF_MX = OFF_OB + 2048;
constexpr int OFF_BAR = OFF_MX + 64;
constexpr int OFF_PROF = OFF_BAR + 256;
constexpr int SMEM = OFF_PROF;
enum { B_XT = 0, B_KX = 2, B_VX = 4, B_XD = 6, B_X1 = 8, B_WN = 10, B_PXF = 12, B_PXE = 13, B_FIN = 14, B_ST = 15 };
enum { NB_QK = 2, NB_WIN = 3, NB_ATT = 4, NB_X = 5, NB_PRO = 6, NB_W1 = 7, NB_MEM = 8  , NB_LD = 13   };
#define NOX 0
#define NW1 10
#define NW1B 8
constexpr int RING = 8;
template <int N> struct IC { static constexpr int value = N; };
template <int N, int I = 0, class F> DEV void static_for(F&& f) { if constexpr (I < N) { f(IC<I>{}); static_for<N, I + 1>(f); } }
constexpr float SM_SCALE = 0.08838834764831845f * 1.4426950408889634f;
}

__global__ void __launch_bounds__(512, 1) rec_kernel(const bf16* __restrict__ mem0, const bf16* __restrict__ Wq, const bf16* __restrict__ Wk,
                                                     const bf16* __restrict__ Wv, const bf16* __restrict__ Wo, int layer, int delay, int delay2) {
    using namespace rec;
    extern __shared__ __align__(1024) unsigned char smem[];
    const uint32_t sb = s2u(smem);
    const int tid = threadIdx.x, lane = tid & 31, warp = __shfl_sync(~0u, tid >> 5, 0);
    const int g = lane >> 2, q = lane & 3;
    uint32_t rank; asm("mov.u32 %0,%%cluster_ctarank;" : "=r"(rank));
    const int h = blockIdx.x / 3;
    const uint32_t bar = sb + OFF_BAR;
    STAMP(2 * layer);
    if (tid == 0) {
        for (int i = 0; i < 2; i++) {
            mbar_init(bar + 8 * (B_XT + i), 1); mbar_init(bar + 8 * (B_KX + i), 4); mbar_init(bar + 8 * (B_VX + i), 1);
            mbar_init(bar + 8 * (B_XD + i), 8); mbar_init(bar + 8 * (B_X1 + i), 1); mbar_init(bar + 8 * (B_WN + i), 4);
        }
        mbar_init(bar + 8 * B_PXF, 1); mbar_init(bar + 8 * B_PXE, 2); mbar_init(bar + 8 * B_ST, 2);
        mbar_init(bar + 8 * B_FIN, 48);
        asm volatile("fence.mbarrier_init.release.cluster;" ::: "memory");
    }
    asm volatile("barrier.cluster.arrive.aligned; barrier.cluster.wait.aligned;" ::: "memory");
    const bool never = delay < 0;

    if (warp < 8) {
        asm volatile("setmaxnreg.inc.sync.aligned.u32 184;");
        auto role = [&](auto XP) {
            constexpr int wg = XP.value, NSW = wg ? NS : NS0;
            uint32_t a[40 - NSW][4];
            const uint32_t l16 = opaque(sb + lane * 16);
            uint32_t wsa = wg ? opaque(sb + OFF_WS + (warp & 3) * 512 + (lane & 7) * 16 + ((lane >> 3) & 1) * 256 + (lane >> 4) * 128) : 0;
            uint32_t dst = opaque(rank < 2 ? sb + OFF_Q + wg * 10240 + (warp & 3) * 256 + (lane & 15) * 16 + (lane >> 4) * 1024
                                           : sb + OFF_VM + warp * 256 + lane * 4);
            int dstep = rank < 2 ? 5120 : 2048;
            uint32_t& sfd = wg ? wsa : dst;
            auto ws_addr = [&](int ks) { return wg ? wsa + ks * 2048 : l16 + OFF_WS + (NS + ks) * 2048 + warp * 512; };
            {
                const int t = tid & 127;
                const bf16* src = (rank == 2 ? Wv + wg * 64 : (wg ? Wk : Wq) + rank * 64) + h * E_ + (size_t)(t >> 3) * 4096 + (t & 7) * 8;
                const uint32_t stg = sb + (wg ? OFF_VX : OFF_X + 40960);
                const uint32_t sdst = stg + (t >> 3) * 128 + (((t & 7) ^ ((t >> 3) & 7)) << 4);
                const uint32_t ra = stg + ((lane >> 4) * 8 + (lane & 7)) * 128 + (((2 * (warp & 3) + ((lane >> 3) & 1)) ^ (lane & 7)) << 4);
                auto issue = [&](int rd) {
#pragma unroll
                    for (int i = 0; i < 10; i++) cp16(sdst + (rd & 1) * 20480 + i * 2048, src + (size_t)(rd * 160 + i * 16) * 4096);
                    cp_commit();
                };
                issue(0); issue(1);
#pragma unroll
                for (int rd = 0; rd < 4; rd++) {
                    if (rd < 3) cp_wait<1>(); else cp_wait<0>();
                    bar_sync(NB_LD + wg, 128);
#pragma unroll
                    for (int i = 0; i < 10; i++) {
                        const int ks = rd * 10 + i;
                        if (ks < NSW) {
                            uint32_t f[4];
                            ldsm4t(f, ra + i * 2048);
                            stsm4(ws_addr(ks), f[0], f[1], f[2], f[3]);
                        } else ldsm4t(a[ks - NSW], ra + (rd & 1) * 20480 + i * 2048);
                    }
                    if (rd < 2) { bar_sync(NB_LD + wg, 128); issue(rd + 2); }
                }
                fence_async();
                bar_sync(NB_PRO, 288);
            }
            float acc[16];
            uint32_t xlo = (uint32_t)mkdesc(sb + OFF_X, 0, 0);
            const uint32_t xtog = xlo ^ (uint32_t)mkdesc(sb + OFF_X + 40960, 0, 0);
            uint32_t p8 = 0;
            auto xproj = [&](auto K1, auto K0) {
                const u64 desc = (u64)xlo | (64ull << 32) | SW128, da = mkdesc(sb + OFF_WS, 128, 256);
                wg_fence();
#pragma unroll
                for (int ks = K1.value - 1; ks >= K0.value; ks--) {
                    const u64 db = desc + (ks >> 2) * 256 + (ks & 3) * 2;
                    if (ks == 39) wgmma_n32_rs<0>(acc, a[ks - NSW], db);
                    else if (NOX) {}
                    else if (ks < NSW) wgmma_n32_ss<1>(acc, da + ks * 128, db);
                    else wgmma_n32_rs<1>(acc, a[ks - NSW], db);
                }
                wg_commit();
            };
            auto xstore = [&]() {
                wg_wait<0>();
                uint32_t pk[8];
#pragma unroll
                for (int i = 0; i < 8; i++) pk[i] = pack2(acc[2 * i], acc[2 * i + 1]);
                if (rank < 2) {
                    stsm4t(dst + 1024, pk[0], pk[1], pk[2], pk[3]);
                    stsm4t(dst + 3072, pk[4], pk[5], pk[6], pk[7]);
                } else {
                    const uint32_t la = wsa + (wsa & 256) + (OFF_VX + 4096 - OFF_WS) + (warp & 3) * 512 + p8 * 1024;
                    stsm4(la, pk[0], pk[1], pk[2], pk[3]);
                    stsm4(la + 256, pk[4], pk[5], pk[6], pk[7]);
                    fence_async();
                }
                mbar_arrive_elect(bar + 8 * B_KX + p8);
            };
            if (wg) {
                mbar_wait(bar + 8 * B_XT, 0);
                xproj(IC<40>{}, IC<0>{});
            }
            if (rank == 2) mbar_wait(bar + 8 * B_ST, 0);
            if (wg) xstore();
            for (int s = 0;; s++) {
                float d0[4] = {0.f, 0.f, 0.f, 0.f}, d1[4] = {0.f, 0.f, 0.f, 0.f};
                uint32_t t[NSW][4], b[20][4];
#pragma unroll
                for (int ks = 0; ks < NSW; ks++) ldsm4(t[ks], ws_addr(ks));
                bar_sync(NB_MEM, 384);
                lds128(b[0], l16 + OFF_MEMB); lds128(b[1], l16 + OFF_MEMB + 512); lds128(b[2], l16 + OFF_MEMB + 1024);
                xlo ^= xtog;
                const uint32_t xb0 = mapa(bar + 8 * B_X1 + p8, 0), xb1 = mapa(bar + 8 * B_X1 + p8, 1);
                SFENCE();
                float is;
#pragma unroll
                for (int kp = 0; kp < 20; kp++) {
#pragma unroll
                    for (int j = 0; j < 2; j++) {
                        const int ks = 2 * kp + j;
                        const uint32_t* f = ks < NSW ? t[ks] : a[ks - NSW];
                        mma16(j ? d1 : d0, f[0], f[1], f[2], f[3], b[kp][2 * j], b[kp][2 * j + 1]);
                    }
                    if (kp == 0 && warp == 4) PROFT(0);
                    if (kp < 16 && (kp & 3) == 1) bar_sync(NB_MEM + 1 + (kp >> 2), 384);
                    if (kp + 3 < 20) lds128(b[kp + 3], l16 + OFF_MEMB + (kp + 3) * 512);
                    if (kp == 17) is = lds32f(sb + OFF_MX + 16);
                    if (kp < 18) SFENCE();
                }
                const uint32_t p0 = pack2((d0[0] + d1[0]) * is, (d0[1] + d1[1]) * is), p1 = pack2((d0[2] + d1[2]) * is, (d0[3] + d1[3]) * is);
                if (rank < 2) {
                    stsm2t(dst, p0, p1);
                } else {
                    st_async1(mapa(dst, 0), p0, xb0); st_async1(mapa(dst, 1), p0, xb1);
                    st_async1(mapa(dst + 128, 0), p1, xb0); st_async1(mapa(dst + 128, 1), p1, xb1);
                    sts32(dst, p0); sts32(dst + 128, p1);
                }
                bar_arrive(NB_QK, 384);
                if (warp == 4) PROFT(1);
                dst += dstep; dstep = -dstep; p8 ^= 8;
                if (wg) {
                    bar_sync(NB_W1, 384);
                    if (s == NSEG - 1) break;
                    xproj(IC<40>{}, IC<40 - NW1>{});
                    if (rank < 2) {
                        wg_wait<0>();
                        if (warp == 4) PROFT(15);
                        bar_sync(NB_WIN, 256);
                    }
                    xproj(IC<40 - NW1>{}, IC<40 - NW1 - NW1B>{});
                    if (rank == 2) {
                        wg_wait<0>();
                        if (warp == 4) PROFT(15);
                        bar_sync(NB_WIN, 256);
                    }
                    xproj(IC<40 - NW1 - NW1B>{}, IC<0>{});
                    xstore();
                    if (warp == 4) PROFT(3);
                } else if (s == NSEG - 1) break;
            }
        };
        if (warp < 4) role(IC<0>{}); else role(IC<1>{});
    } else if (warp < 12) {
        asm volatile("setmaxnreg.dec.sync.aligned.u32 96;");
        const int w = warp - 8;
        const bool four = w == 0 || (w == 1 && rank == 0);
        const int tile3 = rank == 0 ? 36 + w : 37 + rank;
        uint32_t amax = 0;
#pragma unroll
        for (int it = 0; it < 5; it++) {
            const int kp = it * 4 + w;
            const bf16* p = mem0 + g * D_ + kp * 32 + 2 * q;
            uint32_t b0 = ldg32(p), b1 = ldg32(p + 8), b2 = ldg32(p + 16), b3 = ldg32(p + 24);
            sts128(sb + OFF_MEMB + kp * 512 + lane * 16, b0, b1, b2, b3);
            amax = absmax2(amax, absmax2(absmax2(b0, b1), absmax2(b2, b3)));
        }
        if (tid == 256) sts32(sb + OFF_MX + 16, 0x3f800000u);
        bar_arrive(NB_MEM, 384); bar_arrive(NB_MEM + 1, 384); bar_arrive(NB_MEM + 2, 384); bar_arrive(NB_MEM + 3, 384); bar_arrive(NB_MEM + 4, 384);
        {
            const int t = tid & 127;
#pragma unroll
            for (int r = 0; r < 4; r++) {
                const int col = r < 3 ? 192 * r + 64 * rank : (rank ? 592 + 16 * rank : 576);
                const bf16* src = Wo + (size_t)(h * E_) * D_ + col;
                if (r < 3) {
#pragma unroll
                    for (int i = 0; i < 8; i++) {
                        const int e = i * 16 + (t >> 3);
                        cp16(sb + OFF_WO + r * 16384 + e * 128 + (((t & 7) ^ (e & 6)) << 4), src + e * D_ + (t & 7) * 8);
                    }
                } else {
#pragma unroll
                    for (int i = 0; i < 4; i++) {
                        const int e = i * 32 + (t >> 2);
                        if (rank == 0 || (t & 2) == 0) cp16(sb + OFF_WO + r * 16384 + e * 64 + (t & 3) * 16, src + e * D_ + (t & 3) * 8);
                    }
                }
            }
            cp_commit();
            cp_wait<0>();
            bar_sync(NB_ATT, 128);
#pragma unroll 1
            for (int r = 0; r < 4; r++) {
                uint32_t u[8][4];
                const uint32_t rs = r < 3 ? 128 : 64;
                const uint32_t p = sb + OFF_WO + r * 16384 + 2 * q * rs + (((2 * w + (g & 1)) ^ (r < 3 ? 2 * q : 0)) << 4) + (g >> 1) * 4;
                if (r < 3 || four) {
#pragma unroll
                    for (int ks = 0; ks < 8; ks++)
#pragma unroll
                        for (int j = 0; j < 4; j++) u[ks][j] = lds32(p + (16 * ks + (j & 1) * 8 + (j >> 1)) * rs);
                }
                bar_sync(NB_ATT, 128);
                if (r < 3 || four) {
#pragma unroll
                    for (int ks = 0; ks < 8; ks++)
                        sts128(sb + OFF_WO + (r * 4 + w) * 4096 + ks * 512 + lane * 16, prmt(u[ks][0], u[ks][2], 0x5410), prmt(u[ks][0], u[ks][2], 0x7632),
                               prmt(u[ks][1], u[ks][3], 0x5410), prmt(u[ks][1], u[ks][3], 0x7632));
                }
            }
        }
        float cw;
        {
            const float4 a = ((const float4*)g_nrm)[lane], c = ((const float4*)g_nrm)[32 + lane];
            float sm = sqrtf((a.x + a.y) + (a.z + a.w)) * sqrtf((c.x + c.y) + (c.z + c.w)), mxv = sm;
#pragma unroll
            for (int o = 16; o; o >>= 1) { sm += __shfl_xor_sync(~0u, sm, o); mxv = fmaxf(mxv, __shfl_xor_sync(~0u, mxv, o)); }
            cw = 26.5f * fmaxf(sm, 8.f * mxv);
        }
        const uint32_t l16 = opaque(sb + lane * 16), l4 = opaque(sb + OFF_PS + rank * 512 + lane * 4);
        uint32_t lq = opaque(sb + OFF_Q + (lane & 7) * 16 + ((lane >> 3) & 1) * 256 + (lane >> 4) * 128);
        const uint32_t lv = opaque(sb + OFF_VX + w * 2048 + (lane & 7) * 16 + ((lane >> 3) & 1) * 512 + (lane >> 4) * 128);
        uint32_t& sfd = lq;
        const bool t0 = tid == 256;
        const char* rp = (const char*)(g_acc + layer * ACC_LAYER) + (4 * rank + w) * 4096 + opaque((q >> 1) * 1024 + ((q & 1) * 8 + g) * 8);
        const char* lp = (const char*)(g_acc + layer * ACC_LAYER) + opaque(w * 8192 + (2 * (g & 1) + (g >> 2)) * 1024 + (((g >> 1) & 1) * 8 + 2 * q) * 8);
        const int t3off = (tile3 - 4 * rank - w) * 4096;
        float isig = 1.f;
        if (t0) {
            mbar_expect(bar + 8 * B_X1, rank < 2 ? 3328 : 1280);
            mbar_expect(bar + 8 * B_VX, rank < 2 ? 8192 : 4096);
        }
        for (int s = 0; s < NSEG - 1; s++) {
            const int pb = s & 1;
            const uint32_t x1 = bar + 8 * (B_X1 + pb);
            sts32(sb + OFF_MX + w * 4, __reduce_max_sync(~0u, max(amax & 0x7fff0000u, (amax << 16) & 0x7fff0000u)));
            if (rank < 2) {
                uint32_t kf[8], qf[8];
                const uint32_t ka = l16 + OFF_K + pb * 5120, qa = lq + pb * 5120;
                mbar_wait(bar + 8 * (B_KX + pb), (s >> 1) & 1);
                ldsm4(kf, ka + (1 + w) * 1024); ldsm4(kf + 4, ka + (1 + w) * 1024 + 512);
                const uint32_t pa = l4 + w * 128;
                const uint32_t pa0 = mapa(pa, rank ^ 1), pa1 = mapa(pa, 2), pa2 = mapa(pa, rank);
                const uint32_t xb0 = mapa(x1, rank ^ 1), xb1 = mapa(x1, 2), xb2 = mapa(x1, rank);
                bar_sync(NB_QK, 384);
                ldsm4(qf, qa); ldsm4(qf + 4, qa + 512);
                float c0[4] = {0.f, 0.f, 0.f, 0.f}, c1[4] = {0.f, 0.f, 0.f, 0.f}, c2[4] = {0.f, 0.f, 0.f, 0.f}, c3[4] = {0.f, 0.f, 0.f, 0.f};
                if (w == 3) {
                    uint32_t mf[8];
                    ldsm4(mf, ka); ldsm4(mf + 4, ka + 512);
                    mma16(c0, qf[0], qf[1], qf[2], qf[3], kf[0], kf[1]); mma16(c1, qf[0], qf[1], qf[2], qf[3], kf[2], kf[3]);
                    mma16(c2, qf[0], qf[1], qf[2], qf[3], mf[0], mf[1]); mma16(c3, qf[0], qf[1], qf[2], qf[3], mf[2], mf[3]);
                    mma16(c0, qf[4], qf[5], qf[6], qf[7], kf[4], kf[5]); mma16(c1, qf[4], qf[5], qf[6], qf[7], kf[6], kf[7]);
                    mma16(c2, qf[4], qf[5], qf[6], qf[7], mf[4], mf[5]); mma16(c3, qf[4], qf[5], qf[6], qf[7], mf[6], mf[7]);
                    bar_arrive(NB_W1, 384);
                    const uint32_t y = pack2(c0[0] + c1[2], c0[1] + c1[3]), z = pack2(c2[0] + c3[2], c2[1] + c3[3]);
                    const uint32_t pm = l4 + 1024 - rank * 384;
                    st_async1(pa0, y, xb0); st_async1(pa1, y, xb1);
                    st_async1(mapa(pm, rank ^ 1), z, xb0); st_async1(mapa(pm, 2), z, xb1);
                    st_async1(pa2, y, xb2); st_async1(mapa(pm, rank), z, xb2);
                } else {
                    mma16(c0, qf[0], qf[1], qf[2], qf[3], kf[0], kf[1]); mma16(c1, qf[0], qf[1], qf[2], qf[3], kf[2], kf[3]);
                    mma16(c2, qf[4], qf[5], qf[6], qf[7], kf[4], kf[5]); mma16(c3, qf[4], qf[5], qf[6], qf[7], kf[6], kf[7]);
                    bar_arrive(NB_W1, 384);
                    const uint32_t y = pack2((c0[0] + c1[2]) + (c2[0] + c3[2]), (c0[1] + c1[3]) + (c2[1] + c3[3]));
                    st_async1(pa0, y, xb0); st_async1(pa1, y, xb1); st_async1(pa2, y, xb2);
                }
                if (w == 0) PROFT(4);
            } else {
                bar_sync(NB_QK, 384);
                bar_arrive(NB_W1, 384);
            }
            mbar_wait(bar + 8 * (B_VX + pb), (s >> 1) & 1);
            float m4[4];
            lds128f(m4, sb + OFF_MX);
            uint32_t wf[RING][4], vf[2][2][4], vm[4];
#pragma unroll
            for (int t = 0; t < 2; t++)
#pragma unroll
                for (int j = 0; j < 2; j++) ldsm4(vf[t][j], lv + pb * 8192 + t * 1024 + j * 256);
            float sig;
            {
                const float bound = cw * fmaxf(fmaxf(fmaxf(m4[0], m4[1]), fmaxf(m4[2], m4[3])) * isig, 1.f);
                const uint32_t e = max((__float_as_uint(bound) >> 23) & 255u, 31u);
                sig = __uint_as_float((278u - e) << 23);
                isig = __uint_as_float((e - 30u) << 23);
            }
            if (t0) sts32(sb + OFF_MX + 16, __float_as_uint(isig));
            const uint32_t vma = l16 + OFF_VM + pb * 2048 + w * 512;
            if (w == 0) PROFT(5);
            mbar_wait(x1, (s >> 1) & 1);
            if (w == 0) PROFT(6);
            float sc[10];
            {
                uint32_t u[4], v[4], m[2];
                ldsm4(u, l16 + OFF_PS); ldsm4(v, l16 + OFF_PS + 512); ldsm2(m, l16 + OFF_PS + 1024);
                ldsm4(vm, vma);
                SFENCE();
#pragma unroll
                for (int i = 0; i < 4; i++) { sc[2 * i] = bf_lo(u[i]) + bf_lo(v[i]); sc[2 * i + 1] = bf_hi(u[i]) + bf_hi(v[i]); }
                sc[8] = bf_lo(m[0]) + bf_lo(m[1]); sc[9] = bf_hi(m[0]) + bf_hi(m[1]);
            }
            float mx = fmaxf(fmaxf(fmaxf(fmaxf(sc[0], sc[1]), fmaxf(sc[2], sc[3])), fmaxf(fmaxf(sc[4], sc[5]), fmaxf(sc[6], sc[7]))), fmaxf(sc[8], sc[9]));
            {
                float m1 = __shfl_xor_sync(~0u, mx, 1), m2 = __shfl_xor_sync(~0u, mx, 2), m3 = __shfl_xor_sync(~0u, mx, 3);
                SFENCE();
                mx = fmaxf(fmaxf(mx, m1), fmaxf(m2, m3)) * SM_SCALE;
            }
            auto fetch = [&](int i) { lds128(wf[i % RING], l16 + OFF_WO + ((i >> 3) * 4 + w) * 4096 + (i & 7) * 512); };
            float o0[4] = {0.f, 0.f, 0.f, 0.f}, o1[4] = {0.f, 0.f, 0.f, 0.f}, rs[4] = {0.f, 0.f, 0.f, 0.f};
            constexpr uint32_t ONE = 0x3f803f80u;
            sc[8] = ex2(fmaf(sc[8], SM_SCALE, -mx)); sc[9] = ex2(fmaf(sc[9], SM_SCALE, -mx));
#pragma unroll
            for (int i = 0; i < 4; i++) sc[i] = ex2(fmaf(sc[i], SM_SCALE, -mx));
#pragma unroll
            for (int i = 0; i < RING; i++) fetch(i);
            SFENCE();
            {
                const uint32_t p = pack2(sc[8], sc[9]);
                mma8(o0, vm[0], vm[1], p);
                mma8(o1, vm[2], vm[3], p);
                mma8(rs, ONE, ONE, p);
            }
#pragma unroll
            for (int i = 4; i < 8; i++) sc[i] = ex2(fmaf(sc[i], SM_SCALE, -mx));
            SFENCE();
#pragma unroll
            for (int j = 0; j < 2; j++) {
                const uint32_t p0 = pack2(sc[4 * j], sc[4 * j + 1]), p1 = pack2(sc[4 * j + 2], sc[4 * j + 3]);
                mma16(o0, vf[0][j][0], vf[0][j][1], vf[0][j][2], vf[0][j][3], p0, p1);
                mma16(o1, vf[1][j][0], vf[1][j][1], vf[1][j][2], vf[1][j][3], p0, p1);
                mma16(rs, ONE, ONE, ONE, ONE, p0, p1);
                SFENCE();
            }
            stsm4t(l16 + OFF_OB + w * 512, pack2(o0[0], o0[1]), pack2(o0[2], o0[3]), pack2(o1[0], o1[1]), pack2(o1[2], o1[3]));
            bar_sync(NB_ATT, 128);
            uint32_t ob[16];
#pragma unroll
            for (int j = 0; j < 4; j++) ldsm4(ob + 4 * j, l16 + OFF_OB + j * 512);
            SFENCE();
            const float sg0 = rcp(rs[0]) * sig, sg1 = rcp(rs[1]) * sig;
            SFENCE();
            uint32_t tr;
            auto tiles = [&](auto NT) {
#pragma unroll
                for (int r = 0; r < NT.value; r++) {
                    float c[4][4];
#pragma unroll
                    for (int i = 0; i < 4; i++) c[i][0] = c[i][1] = c[i][2] = c[i][3] = 0.f;
#pragma unroll
                    for (int ks = 0; ks < 8; ks++) {
                        const uint32_t* f = wf[(8 * r + ks) % RING];
                        mma16(c[ks & 3], f[0], f[1], f[2], f[3], ob[2 * ks], ob[2 * ks + 1]);
                        if ((ks & 3) == 3) {
                            SFENCE();
#pragma unroll
                            for (int i = 8 * r + ks - 3 + RING; i <= 8 * r + ks + RING; i++) if (i < 8 * NT.value) fetch(i);
                        }
                    }
                    SFENCE();
                    uint32_t v[4];
#pragma unroll
                    for (int i = 0; i < 4; i++)
                        v[i] = (__float_as_uint(fmaf((c[0][i] + c[1][i]) + (c[2][i] + c[3][i]), i & 1 ? sg1 : sg0, 12582912.f)) << 6) + (i < 2);
                    const char* p = r < 3 ? rp + r * 49152 : rp + t3off;
                    red_add64((u64*)p, v[0], v[2]);
                    red_add64((u64*)(p + 2048), v[1], v[3]);
                    if (r == 0) {
                        tr = clk();
                        if (w == 0) PROFT(7);
                        if (w == 0) GPROF(4, 0);
                    }
                }
            };
            if (four) tiles(IC<4>{}); else tiles(IC<3>{});
            bar_arrive(NB_WIN, 256);
            mbar_arrive_elect(bar + 8 * (B_WN + pb));
            if (w == 0) PROFT(8);
            if (t0) {
                if (rank < 2 || s < NSEG - 2) mbar_expect(bar + 8 * (B_VX + (pb ^ 1)), rank < 2 ? 8192 : 4096);
                mbar_expect(bar + 8 * (B_X1 + (pb ^ 1)), (rank < 2 ? 2048 : 0) + (s < NSEG - 2 ? 1280 : 0));
            }
            u64 y[20];
            while (clk() - tr < (uint32_t)delay) {}
#pragma unroll
            for (int i = 0; i < 10; i++) ld_acc0(y[2 * i], y[2 * i + 1], lp + (i >> 1) * 32768 + (i & 1) * 4096);
            if (w == 0) PROFT(9);
            uint32_t nretry = 0, b[20];
            bool done[5] = {false, false, false, false, false};
            auto publish = [&](auto FIRST) {
                uint32_t ok = 32u, late = 32u;
                static_for<5>([&](auto IT) {
                    constexpr int it = IT.value;
                    if (it == 2) late = and3((uint32_t)y[8], (uint32_t)y[10], (uint32_t)y[12]);
                    else if (it == 3) late &= and3((uint32_t)y[14], (uint32_t)y[16], (uint32_t)y[18]);
                    else ok = and3(ok, (uint32_t)y[4 * it], it == 4 ? late : (uint32_t)y[4 * it + 2]);
                    if (FIRST.value && it < 4) SFENCE();
                    if (it == 2 || it == 3) ok = and3(ok, (uint32_t)y[4 * it], (uint32_t)y[4 * it + 2]);
                    ok = and3(ok, (uint32_t)y[4 * it + 1], (uint32_t)y[4 * it + 3]);
                    const bool all = __all_sync(~0u, ok);
#pragma unroll
                    for (int j = 0; j < 4; j++) {
                        const u64 z = y[4 * it + j];
                        b[4 * it + j] = pack2((float)(int)(uint32_t)z, (float)(int)(uint32_t)(z >> 32));
                    }
                    sts128(l16 + OFF_MEMB + (4 * it + w) * 512, b[4 * it], b[4 * it + 1], b[4 * it + 2], b[4 * it + 3]);
                    bar_arrive_if<NB_MEM + it, 384>(all && (FIRST.value || !done[it]));
                    done[it] = all;
                    if (FIRST.value) SFENCE();
                    if (FIRST.value && it == 0 && w == 0) PROFT(10);
                });
            };
            publish(IC<1>{});
            while (!done[4]) {
                if (++nretry > SPIN_LIMIT) __trap();
#pragma unroll
                for (int i = 0; i < 10; i++) ld_acc(y[2 * i], y[2 * i + 1], lp + (i >> 1) * 32768 + (i & 1) * 4096);
                publish(IC<0>{});
            }
            if (w == 0) PROFT(11);
            amax = b[0];
#pragma unroll
            for (int i = 1; i < 19; i += 2) amax = absmax2(amax, absmax2(b[i], b[i + 1]));
            amax = absmax2(amax, b[19]);
            GPROF(w, nretry);
            const int adv = (s & 7) == 7 ? 163840 - 896 : 128;
            rp += adv; lp += adv;
        }
        bar_sync(NB_QK, 384);
        bar_arrive(NB_W1, 384);
    } else {
        asm volatile("setmaxnreg.dec.sync.aligned.u32 48;");
        const int w = warp - 12;
        const bool t0 = tid == 384;
        uint32_t* sy = g_sync + layer * SYNC_LAYER;
        int pblk = 0;
        auto loads = [&](int s) {
            const int n = s + 1, pb = s & 1;
            const uint32_t xt = bar + 8 * (B_XT + pb);
            mbar_expect(xt, (n + 1 < NSEG ? 40960 : 0) + (rank < 2 ? 4096 : 0));
            if (n + 1 < NSEG) bulk_g2s(sb + OFF_X + pb * 40960, g_xn + (n + 1) * 40960, 40960, xt);
            if (n == wk::pb_start(pblk)) { flag_wait(sy + wk::SY_P + pblk * H_ + h, 3); pblk++; }
            const unsigned char* src = g_p + (size_t)(n * H_ + h) * 12288;
            if (rank < 2) bulk_g2s(sb + OFF_Q + (pb ^ 1) * 5120 + 1024, src + rank * 4096, 4096, xt);
            if (rank < 2 || n < NSEG - 1) bulk_g2s(sb + OFF_VX + (pb ^ 1) * 8192, src + 8192, 4096, bar + 8 * (B_VX + (pb ^ 1)));
        };
        const int wl = rank == 0 ? 2 : rank == 1 ? 0 : 1;
        if (w == wl) {
            if (lane == 0) {
                mbar_expect(bar + 8 * B_XT, 40960);
                bulk_g2s(sb + OFF_X, g_xn, 40960, bar + 8 * B_XT);
            }
            __syncwarp();
            bar_sync(NB_PRO, 288);
            if (lane == 0) {
                if (rank < 2) mbar_arrive_remote(mapa(bar + 8 * B_ST, 2));
                loads(-1);
            }
            __syncwarp();
        }
        if (rank == 2) {
            for (int s = 0; s < NSEG; s++) {
                const int pb = s & 1, ph = (s >> 1) & 1;
                if (w == 0) {
                    mbar_wait(bar + 8 * (B_KX + pb), ph);
                    if (lane < 2) bulk_s2s(mapa(sb + OFF_VX + pb * 8192 + 4096, lane), sb + OFF_VX + pb * 8192 + 4096, 4096, mapa(bar + 8 * (B_VX + pb), lane));
                }
                if (w == 1) mbar_wait(bar + 8 * (B_XT + (pb ^ 1)), ((s + 1) >> 1) & 1);
                if (w == 2 && s >= 1) mbar_wait(bar + 8 * (B_XD + (pb ^ 1)), ((s - 1) >> 1) & 1);
                __syncwarp();
                bar_sync(NB_W1, 384);
                if (w == 1 && s + 1 < NSEG) {
                    mbar_wait(bar + 8 * (B_X1 + pb), ph);
                    const uint32_t tw = clk();
                    while (clk() - tw < (uint32_t)delay2) {}
                    if (lane == 0) loads(s);
                }
            }
        } else {
            if (w < 2) sts32(sb + OFF_PT + w * 768 + 640 + lane * 4, 0u);
            for (int s = 0; s < NSEG; s++) {
                const int pb = s & 1, ph = (s >> 1) & 1;
                if (t0) {
                    mbar_expect(bar + 8 * B_PXF, rank ? 2560 : 1536);
                    asm volatile("cp.async.bulk.wait_group.read 0;" ::: "memory");
                }
                if (w == 1) mbar_wait(bar + 8 * (B_XT + (pb ^ 1)), ((s + 1) >> 1) & 1);
                __syncwarp();
                bar_sync(NB_W1, 384);
                fence_async();
                float c[20];
                {
                    const u64 dq = mkdesc(sb + OFF_Q + pb * 5120 + 1024, 128, 512), dk = mkdesc(sb + OFF_K + pb * 5120, 128, 1024);
                    wg_fence();
                    wgmma_n40_ss<0>(c, dq, dk);
#pragma unroll
                    for (int ks = 1; ks < 4; ks++) wgmma_n40_ss<1>(c, dq + ks * 16, dk + ks * 16);
                    wg_commit();
                    wg_wait<0>();
                }
                mbar_wait(bar + 8 * (B_X1 + pb), ph);
                if ((w >> 1) != rank) {
                    if (s >= 1) mbar_wait(bar + 8 * B_PXE, pb ^ 1);
                    const uint32_t pa = mapa(sb + OFF_PX + (w & 1) * 1280 + lane * 8, rank ^ 1), pf = mapa(bar + 8 * B_PXF, rank ^ 1);
#pragma unroll
                    for (int nt = 0; nt < 5; nt++)
                        if (nt < 3 || rank == 0) st_async2(pa + nt * 256, __float_as_uint(c[4 * nt]), __float_as_uint(c[4 * nt + 1]), pf);
                    if (w == wl && s + 1 < NSEG) {
                        const uint32_t tw = clk();
                        while (clk() - tw < (uint32_t)delay2) {}
                        if (lane == 0) loads(s);
                    }
                } else {
                    mbar_wait(bar + 8 * B_PXF, pb);
                    if (w == 0) PROFT(13);
                    const int tq = 8 * w + g;
                    float sc[10];
#pragma unroll
                    for (int nt = 0; nt < 5; nt++) {
                        float u0, u1;
                        lds64f(u0, u1, sb + OFF_PX + (w & 1) * 1280 + nt * 256 + lane * 8);
                        sc[2 * nt] = (8 * nt - 8 + 2 * q <= tq) ? (u0 + c[4 * nt]) * SM_SCALE : -INFINITY;
                        sc[2 * nt + 1] = (8 * nt - 7 + 2 * q <= tq) ? (u1 + c[4 * nt + 1]) * SM_SCALE : -INFINITY;
                    }
                    float mx = sc[0];
#pragma unroll
                    for (int i = 1; i < 10; i++) mx = fmaxf(mx, sc[i]);
                    mx = fmaxf(mx, __shfl_xor_sync(~0u, mx, 1));
                    mx = fmaxf(mx, __shfl_xor_sync(~0u, mx, 2));
                    if (lane == 0) mbar_arrive_remote(mapa(bar + 8 * B_PXE, rank ^ 1));
                    float sum = 0.f;
#pragma unroll
                    for (int i = 0; i < 10; i++) { sc[i] = ex2(sc[i] - mx); sum += sc[i]; }
                    sum += __shfl_xor_sync(~0u, sum, 1);
                    sum += __shfl_xor_sync(~0u, sum, 2);
                    sum = rcp(sum);
#pragma unroll
                    for (int nt = 0; nt < 5; nt++)
                        sts32(sb + OFF_PT + (w & 1) * 768 + (nt ? nt - 1 : 4) * 128 + lane * 4, pack2(sc[2 * nt] * sum, sc[2 * nt + 1] * sum));
                }
                mbar_wait(bar + 8 * (B_VX + pb), ph);
                fence_async();
                bar_sync(NB_X, 128);
                if (s < NSEG - 1) mbar_wait(bar + 8 * (B_WN + pb), ph);
                float acc[2][8];
                const u64 dv = mkdesc(sb + OFF_VX + pb * 8192, 128, 512), dp = mkdesc(sb + OFF_PT, 128, 768), dm = mkdesc(sb + OFF_VM + pb * 2048, 0, 128);
                wg_fence();
#pragma unroll
                for (int m = 0; m < 2; m++) {
                    wgmma_n16_ss<0>(acc[m], dv + m * 256, dp);
                    wgmma_n16_ss<1>(acc[m], dv + m * 256 + 16, dp + 16);
                    wgmma_n16_ss<1>(acc[m], dm + m * 64, dp + 32);
                }
                wg_commit();
                wg_wait<0>();
#pragma unroll
                for (int m = 0; m < 2; m++)
                    stsm4t(sb + OFF_OST + m * 2048 + (lane >> 4) * 1024 + w * 256 + (lane & 15) * 16, pack2(acc[m][0], acc[m][1]), pack2(acc[m][2], acc[m][3]),
                           pack2(acc[m][4], acc[m][5]), pack2(acc[m][6], acc[m][7]));
                fence_async();
                bar_sync(NB_X, 128);
                if (lane == 0) mbar_arrive_remote(mapa(bar + 8 * (B_XD + pb), 2));
                if (t0) {
                    unsigned char* op = g_o + (size_t)(s * H_ + h) * 8192 + rank * 2048;
                    bulk_s2g(op, sb + OFF_OST, 2048);
                    bulk_s2g(op + 4096, sb + OFF_OST + 2048, 2048);
                    bulk_commit();
                    if (s) { bulk_wait<1>(); flag_add(sy + wk::SY_O + s - 1); }
                }
                if (w == 0) PROFT(14);
            }
            if (t0) { bulk_wait<0>(); flag_add(sy + wk::SY_O + NSEG - 1); }
        }
    }
    __syncwarp();
    if (lane < 3) mbar_arrive_remote(mapa(bar + 8 * B_FIN, lane));
    mbar_wait(bar + 8 * B_FIN, 0);
}

int g_delay = 950, g_layers = 2;

void make_map(CUtensorMap* m, const bf16* p, int cols, int rows) {
    typedef CUresult (*Fn)(CUtensorMap*, CUtensorMapDataType, cuuint32_t, void*, const cuuint64_t*, const cuuint64_t*, const cuuint32_t*,
                           const cuuint32_t*, CUtensorMapInterleave, CUtensorMapSwizzle, CUtensorMapL2promotion, CUtensorMapFloatOOBfill);
    static Fn fn = nullptr;
    if (!fn) {
        cudaDriverEntryPointQueryResult qr;
        cudaGetDriverEntryPoint("cuTensorMapEncodeTiled", (void**)&fn, cudaEnableDefault, &qr);
    }
    const cuuint64_t dim[2] = {(cuuint64_t)cols, (cuuint64_t)rows}, str[1] = {(cuuint64_t)cols * 2};
    const cuuint32_t box[2] = {64, 64}, es[2] = {1, 1};
    fn(m, CU_TENSOR_MAP_DATA_TYPE_BFLOAT16, 2, (void*)p, dim, str, box, es, CU_TENSOR_MAP_INTERLEAVE_NONE, CU_TENSOR_MAP_SWIZZLE_128B,
       CU_TENSOR_MAP_L2_PROMOTION_L2_128B, CU_TENSOR_MAP_FLOAT_OOB_FILL_NONE);
}

void launch_rec(const bf16* mem0, const bf16* Wq, const bf16* Wk, const bf16* Wv, const bf16* Wo, int layer) {
    cudaLaunchConfig_t c = {};
    c.gridDim = dim3(96); c.blockDim = dim3(512); c.dynamicSmemBytes = rec::SMEM; c.stream = cudaStreamPerThread;
    cudaLaunchAttribute at[1];
    at[0].id = cudaLaunchAttributeClusterDimension; at[0].val.clusterDim.x = 3; at[0].val.clusterDim.y = 1; at[0].val.clusterDim.z = 1;
    c.attrs = at; c.numAttrs = 1;
    cudaLaunchKernelEx(&c, rec_kernel, mem0, Wq, Wk, Wv, Wo, layer, g_delay % 10000, g_delay / 10000);
}

}

extern "C" void kernel_launch(void* const* d_in, const int* in_sizes, int n_in, void* d_out, int out_size) {
    const bf16* x = (const bf16*)d_in[0];
    const bf16* mem0 = (const bf16*)d_in[1];
    const bf16* Wq = (const bf16*)d_in[2];
    const bf16* Wk = (const bf16*)d_in[3];
    const bf16* Wv = (const bf16*)d_in[4];
    const bf16* Wo = (const bf16*)d_in[5];
    const bf16* wr = (const bf16*)d_in[8];
    const bf16* wi = (const bf16*)d_in[9];
    cudaFuncSetAttribute(rec_kernel, cudaFuncAttributeMaxDynamicSharedMemorySize, rec::SMEM);
    cudaFuncSetAttribute(side_kernel, cudaFuncAttributeMaxDynamicSharedMemorySize, wk::SMEM);
    cudaFuncSetAttribute(colfft_kernel, cudaFuncAttributeMaxDynamicSharedMemorySize, CF_SMEM);
    Maps maps;
    make_map(&maps.wq, Wq, 4096, D_);
    make_map(&maps.wv, Wv, 4096, D_);
    make_map(&maps.wo, Wo, D_, 4096);
    bf16 *x1, *x2;
    cudaGetSymbolAddress((void**)&x1, g_x1);
    cudaGetSymbolAddress((void**)&x2, g_x2);
    cudaStream_t st = cudaStreamPerThread;
    prep_kernel<<<128, 512, 0, st>>>(x, Wv, Wo);
    tables_kernel<<<128, 512, 0, st>>>(wr, wi);
    for (int layer = 0; layer < g_layers; layer++) {
        side_kernel<<<132, 512, wk::SMEM, st>>>(maps, layer ? x2 : x, x1, layer, 0, wk::N_P);
        launch_rec(mem0, Wq, Wk, Wv, Wo, layer);
        side_kernel<<<132, 512, wk::SMEM, st>>>(maps, layer ? x2 : x, x1, layer, wk::N_P, wk::N_ITEMS);
        rowfft_kernel<<<128, 256, 0, st>>>(x1);
        colfft_kernel<<<107, 384, CF_SMEM, st>>>();
        rowifft_kernel<<<128, 256, 0, st>>>(x1, layer ? (bf16*)d_out : x2, layer);
    }
}
```

```cpp
#include <cuda_runtime.h>
#include <cuda_bf16.h>
#include <cuda.h>
#include <stdint.h>

#define DEV __device__ __forceinline__
typedef unsigned long long u64;
typedef __nv_bfloat16 bf16;

namespace {

constexpr int S_ = 2048, D_ = 640, H_ = 32, E_ = 128, NSEG = 64;

__device__ __align__(1024) unsigned char g_xn[S_ * D_ * 2];
__device__ __align__(1024) unsigned char g_o[S_ * H_ * E_ * 2];
constexpr int ACC_LAYER = 32 * 5120;
__device__ __align__(4096) u64 g_acc[2 * ACC_LAYER];
__device__ __align__(16) float g_nrm[256];
__device__ __align__(1024) unsigned char g_p[NSEG * H_ * 3 * 4096];
constexpr int SYNC_LAYER = 1024;
__device__ __align__(128) uint32_t g_sync[2 * SYNC_LAYER];
__device__ __align__(1024) bf16 g_x1[S_ * D_];
__device__ __align__(1024) bf16 g_x2[S_ * D_];
constexpr int NCOL = 321;
__device__ __align__(1024) unsigned char g_z[NCOL * 8192];
__device__ __align__(1024) unsigned char g_wt[NCOL * 8192];
__device__ __align__(1024) uint4 g_f128[2 * 8 * 256];
__device__ __align__(1024) uint4 g_f64[2 * 4 * 128];
__device__ __align__(1024) bf16 g_g32[2 * 4096];
#define TLI(id, k, v)
#define TLS(i)
#define TLE(i)

DEV uint32_t s2u(const void* p) { return (uint32_t)__cvta_generic_to_shared(p); }
DEV uint32_t clk() { uint32_t c; asm volatile("mov.u32 %0,%%clock;" : "=r"(c)::"memory"); return c; }
DEV uint32_t cta_rank() { uint32_t r; asm volatile("mov.u32 %0,%%cluster_ctarank;" : "=r"(r)); return __shfl_sync(~0u, r, 0); }
DEV uint32_t mapa(uint32_t a, uint32_t r) { uint32_t o; asm("mapa.shared::cluster.u32 %0,%1,%2;" : "=r"(o) : "r"(a), "r"(r)); return o; }
DEV void mbar_init(uint32_t b, uint32_t n) { asm volatile("mbarrier.init.shared::cta.b64 [%0],%1;" ::"r"(b), "r"(n) : "memory"); }
DEV bool mbar_try(uint32_t b, uint32_t par) {
    uint32_t ok;
    asm volatile("{.reg .pred p; mbarrier.try_wait.parity.shared::cta.b64 p,[%1],%2; selp.u32 %0,1,0,p;}" : "=r"(ok) : "r"(b), "r"(par) : "memory");
    return ok;
}
constexpr uint32_t SPIN_LIMIT = 1u << 18;
DEV void die() { __trap(); }
DEV void mbar_wait(uint32_t b, uint32_t par) {
    uint32_t n = 0;
    while (!mbar_try(b, par)) if (++n > SPIN_LIMIT) die();
}
DEV uint32_t opaque(uint32_t x) { return __shfl_xor_sync(~0u, x, 0); }
#define SFENCE() asm volatile("{.reg .pred p; setp.ne.u32 p,%1,0; @p mov.u32 %0,%%clock;}" : "+r"(sfd) : "r"((uint32_t)never) : "memory")
DEV void mbar_arrive(uint32_t b) { asm volatile("mbarrier.arrive.shared::cta.b64 _,[%0];" ::"r"(b) : "memory"); }
DEV void mbar_arrive_elect(uint32_t b) { asm volatile("{.reg .pred p; elect.sync _|p, 0xffffffff; @p mbarrier.arrive.shared::cta.b64 _,[%0];}" ::"r"(b) : "memory"); }
DEV void mbar_arrive_remote(uint32_t b) { asm volatile("mbarrier.arrive.shared::cluster.b64 _,[%0];" ::"r"(b) : "memory"); }
DEV void mbar_expect(uint32_t b, uint32_t tx) { asm volatile("mbarrier.arrive.expect_tx.shared::cta.b64 _,[%0],%1;" ::"r"(b), "r"(tx) : "memory"); }
DEV void bar_sync(int id, int n) { asm volatile("bar.sync %0,%1;" ::"r"(id), "r"(n) : "memory"); }
DEV void bar_arrive(int id, int n) { asm volatile("bar.arrive %0,%1;" ::"r"(id), "r"(n) : "memory"); }
template <int ID, int N> DEV void bar_arrive_if(bool p) {
    asm volatile("{.reg .pred p; setp.ne.u32 p,%0,0; @p bar.arrive %1,%2;}" ::"r"((uint32_t)p), "n"(ID), "n"(N) : "memory");
}
DEV void prefetch_l2(const void* p) { asm volatile("prefetch.global.L2 [%0];" ::"l"(p) : "memory"); }
DEV void st_remote(uint32_t a, uint32_t x) { asm volatile("st.relaxed.cluster.shared::cluster.u32 [%0],%1;" ::"r"(a), "r"(x) : "memory"); }
DEV void st_async1(uint32_t a, uint32_t x, uint32_t b) {
    asm volatile("st.async.shared::cluster.mbarrier::complete_tx::bytes.u32 [%0],%1,[%2];" ::"r"(a), "r"(x), "r"(b) : "memory");
}
DEV void st_async2(uint32_t a, uint32_t x, uint32_t y, uint32_t b) {
    asm volatile("st.async.shared::cluster.mbarrier::complete_tx::bytes.v2.u32 [%0],{%1,%2},[%3];" ::"r"(a), "r"(x), "r"(y), "r"(b) : "memory");
}
DEV void st_async4(uint32_t a, uint32_t x, uint32_t y, uint32_t z, uint32_t w, uint32_t b) {
    asm volatile("st.async.shared::cluster.mbarrier::complete_tx::bytes.v4.u32 [%0],{%1,%2,%3,%4},[%5];" ::"r"(a), "r"(x), "r"(y), "r"(z), "r"(w), "r"(b) : "memory");
}
DEV void bulk_g2s(uint32_t dst, const void* src, uint32_t bytes, uint32_t b) {
    asm volatile("cp.async.bulk.shared::cluster.global.mbarrier::complete_tx::bytes [%0],[%1],%2,[%3];" ::"r"(dst), "l"(src), "r"(bytes), "r"(b) : "memory");
}
DEV void bulk_s2s(uint32_t dst, uint32_t src, uint32_t bytes, uint32_t b) {
    asm volatile("cp.async.bulk.shared::cluster.shared::cta.mbarrier::complete_tx::bytes [%0],[%1],%2,[%3];" ::"r"(dst), "r"(src), "r"(bytes), "r"(b) : "memory");
}
DEV void bulk_s2g(void* dst, uint32_t src, uint32_t bytes) {
    asm volatile("cp.async.bulk.global.shared::cta.bulk_group [%0],[%1],%2;" ::"l"(dst), "r"(src), "r"(bytes) : "memory");
}
DEV void tma3d(uint32_t dst, const CUtensorMap* m, int c0, int c1, int c2, uint32_t b) {
    asm volatile("cp.async.bulk.tensor.3d.shared::cluster.global.mbarrier::complete_tx::bytes [%0],[%1,{%3,%4,%5}],[%2];"
                 ::"r"(dst), "l"(m), "r"(b), "r"(c0), "r"(c1), "r"(c2) : "memory");
}
DEV void bulk_commit() { asm volatile("cp.async.bulk.commit_group;" ::: "memory"); }
template <int N> DEV void bulk_wait() { asm volatile("cp.async.bulk.wait_group %0;" ::"n"(N) : "memory"); }
template <int N> DEV void bulk_wait_read() { asm volatile("cp.async.bulk.wait_group.read %0;" ::"n"(N) : "memory"); }
DEV void fence_async_all() { asm volatile("fence.proxy.async;" ::: "memory"); }
DEV void flag_add(uint32_t* p) { fence_async_all(); asm volatile("red.release.gpu.global.add.u32 [%0],1;" ::"l"(p) : "memory"); }
DEV void flag_wait(const uint32_t* p, uint32_t n) {
    uint32_t v, it = 0;
    for (;;) {
        asm volatile("ld.acquire.gpu.global.u32 %0,[%1];" : "=r"(v) : "l"(p) : "memory");
        if (v >= n) break;
        if (++it > (SPIN_LIMIT << 3)) die();
        __nanosleep(100);
    }
    fence_async_all();
}
DEV void cp16(uint32_t dst, const void* src) { asm volatile("cp.async.cg.shared.global [%0],[%1],16;" ::"r"(dst), "l"(src) : "memory"); }
DEV void cp_commit() { asm volatile("cp.async.commit_group;" ::: "memory"); }
template <int N> DEV void cp_wait() { asm volatile("cp.async.wait_group %0;" ::"n"(N) : "memory"); }
DEV uint32_t lds32(uint32_t a) { uint32_t x; asm volatile("ld.shared.u32 %0,[%1];" : "=r"(x) : "r"(a) : "memory"); return x; }
DEV void fence_async() { asm volatile("fence.proxy.async.shared::cta;" ::: "memory"); }
DEV uint32_t pack2(float lo, float hi) { uint32_t r; asm("cvt.rn.bf16x2.f32 %0,%1,%2;" : "=r"(r) : "f"(hi), "f"(lo)); return r; }
DEV uint32_t prmt(uint32_t a, uint32_t b, uint32_t s) { uint32_t r; asm("prmt.b32 %0,%1,%2,%3;" : "=r"(r) : "r"(a), "r"(b), "r"(s)); return r; }
DEV float ex2(float x) { float r; asm("ex2.approx.ftz.f32 %0,%1;" : "=f"(r) : "f"(x)); return r; }
DEV float rcp(float x) { float r; asm("rcp.approx.ftz.f32 %0,%1;" : "=f"(r) : "f"(x)); return r; }
DEV void lds128(uint32_t* r, uint32_t a) { asm volatile("ld.shared.v4.u32 {%0,%1,%2,%3},[%4];" : "=r"(r[0]), "=r"(r[1]), "=r"(r[2]), "=r"(r[3]) : "r"(a) : "memory"); }
DEV void lds64(uint32_t* r, uint32_t a) { asm volatile("ld.shared.v2.u32 {%0,%1},[%2];" : "=r"(r[0]), "=r"(r[1]) : "r"(a) : "memory"); }
DEV void lds64f(float& x, float& y, uint32_t a) { asm volatile("ld.shared.v2.f32 {%0,%1},[%2];" : "=f"(x), "=f"(y) : "r"(a) : "memory"); }
DEV void lds128f(float* r, uint32_t a) { asm volatile("ld.shared.v4.f32 {%0,%1,%2,%3},[%4];" : "=f"(r[0]), "=f"(r[1]), "=f"(r[2]), "=f"(r[3]) : "r"(a) : "memory"); }
DEV void sts128(uint32_t a, uint32_t x, uint32_t y, uint32_t z, uint32_t w) { asm volatile("st.shared.v4.u32 [%0],{%1,%2,%3,%4};" ::"r"(a), "r"(x), "r"(y), "r"(z), "r"(w) : "memory"); }
DEV void sts64(uint32_t a, uint32_t x, uint32_t y) { asm volatile("st.shared.v2.u32 [%0],{%1,%2};" ::"r"(a), "r"(x), "r"(y) : "memory"); }
DEV void sts32(uint32_t a, uint32_t x) { asm volatile("st.shared.u32 [%0],%1;" ::"r"(a), "r"(x) : "memory"); }
DEV void ldsm4(uint32_t* r, uint32_t a) { asm volatile("ldmatrix.sync.aligned.m8n8.x4.shared.b16 {%0,%1,%2,%3},[%4];" : "=r"(r[0]), "=r"(r[1]), "=r"(r[2]), "=r"(r[3]) : "r"(a) : "memory"); }
DEV void ldsm4t(uint32_t* r, uint32_t a) { asm volatile("ldmatrix.sync.aligned.m8n8.x4.trans.shared.b16 {%0,%1,%2,%3},[%4];" : "=r"(r[0]), "=r"(r[1]), "=r"(r[2]), "=r"(r[3]) : "r"(a) : "memory"); }
DEV void ldsm2(uint32_t* r, uint32_t a) { asm volatile("ldmatrix.sync.aligned.m8n8.x2.shared.b16 {%0,%1},[%2];" : "=r"(r[0]), "=r"(r[1]) : "r"(a) : "memory"); }
DEV void stsm4t(uint32_t a, uint32_t x, uint32_t y, uint32_t z, uint32_t w) { asm volatile("stmatrix.sync.aligned.m8n8.x4.trans.shared.b16 [%0],{%1,%2,%3,%4};" ::"r"(a), "r"(x), "r"(y), "r"(z), "r"(w) : "memory"); }
DEV void stsm4(uint32_t a, uint32_t x, uint32_t y, uint32_t z, uint32_t w) { asm volatile("stmatrix.sync.aligned.m8n8.x4.shared.b16 [%0],{%1,%2,%3,%4};" ::"r"(a), "r"(x), "r"(y), "r"(z), "r"(w) : "memory"); }
DEV void stsm2(uint32_t a, uint32_t x, uint32_t y) { asm volatile("stmatrix.sync.aligned.m8n8.x2.shared.b16 [%0],{%1,%2};" ::"r"(a), "r"(x), "r"(y) : "memory"); }
DEV void stsm2t(uint32_t a, uint32_t x, uint32_t y) { asm volatile("stmatrix.sync.aligned.m8n8.x2.trans.shared.b16 [%0],{%1,%2};" ::"r"(a), "r"(x), "r"(y) : "memory"); }
DEV void mma16(float* d, uint32_t a0, uint32_t a1, uint32_t a2, uint32_t a3, uint32_t b0, uint32_t b1) {
    asm volatile("mma.sync.aligned.m16n8k16.row.col.f32.bf16.bf16.f32 {%0,%1,%2,%3},{%4,%5,%6,%7},{%8,%9},{%0,%1,%2,%3};"
                 : "+f"(d[0]), "+f"(d[1]), "+f"(d[2]), "+f"(d[3]) : "r"(a0), "r"(a1), "r"(a2), "r"(a3), "r"(b0), "r"(b1));
}
DEV void mma8(float* d, uint32_t a0, uint32_t a1, uint32_t b0) {
    asm volatile("mma.sync.aligned.m16n8k8.row.col.f32.bf16.bf16.f32 {%0,%1,%2,%3},{%4,%5},{%6},{%0,%1,%2,%3};"
                 : "+f"(d[0]), "+f"(d[1]), "+f"(d[2]), "+f"(d[3]) : "r"(a0), "r"(a1), "r"(b0));
}
DEV u64 mkdesc(uint32_t a, uint32_t lbo, uint32_t sbo) { return (u64)((a & 0x3ffff) >> 4) | ((u64)(lbo >> 4) << 16) | ((u64)(sbo >> 4) << 32); }
constexpr u64 SW128 = 1ull << 62;
DEV void wg_fence() { asm volatile("wgmma.fence.sync.aligned;" ::: "memory"); }
DEV void wg_commit() { asm volatile("wgmma.commit_group.sync.aligned;" ::: "memory"); }
template <int N> DEV void wg_wait() { asm volatile("wgmma.wait_group.sync.aligned %0;" ::"n"(N) : "memory"); }
template <int ACC> DEV void wgmma_n32_rs(float* d, const uint32_t* a, u64 desc) {
    asm volatile("wgmma.mma_async.sync.aligned.m64n32k16.f32.bf16.bf16 {%0,%1,%2,%3,%4,%5,%6,%7,%8,%9,%10,%11,%12,%13,%14,%15},{%16,%17,%18,%19},%20,%21,1,1,0;"
                 : "+f"(d[0]), "+f"(d[1]), "+f"(d[2]), "+f"(d[3]), "+f"(d[4]), "+f"(d[5]), "+f"(d[6]), "+f"(d[7]),
                   "+f"(d[8]), "+f"(d[9]), "+f"(d[10]), "+f"(d[11]), "+f"(d[12]), "+f"(d[13]), "+f"(d[14]), "+f"(d[15])
                 : "r"(a[0]), "r"(a[1]), "r"(a[2]), "r"(a[3]), "l"(desc), "n"(ACC));
}
template <int ACC> DEV void wgmma_n32_ss(float* d, u64 da, u64 desc) {
    asm volatile("wgmma.mma_async.sync.aligned.m64n32k16.f32.bf16.bf16 {%0,%1,%2,%3,%4,%5,%6,%7,%8,%9,%10,%11,%12,%13,%14,%15},%16,%17,%18,1,1,0,0;"
                 : "+f"(d[0]), "+f"(d[1]), "+f"(d[2]), "+f"(d[3]), "+f"(d[4]), "+f"(d[5]), "+f"(d[6]), "+f"(d[7]),
                   "+f"(d[8]), "+f"(d[9]), "+f"(d[10]), "+f"(d[11]), "+f"(d[12]), "+f"(d[13]), "+f"(d[14]), "+f"(d[15])
                 : "l"(da), "l"(desc), "n"(ACC));
}
template <int ACC> DEV void wgmma_n16_ss(float* d, u64 da, u64 desc) {
    asm volatile("wgmma.mma_async.sync.aligned.m64n16k16.f32.bf16.bf16 {%0,%1,%2,%3,%4,%5,%6,%7},%8,%9,%10,1,1,0,0;"
                 : "+f"(d[0]), "+f"(d[1]), "+f"(d[2]), "+f"(d[3]), "+f"(d[4]), "+f"(d[5]), "+f"(d[6]), "+f"(d[7])
                 : "l"(da), "l"(desc), "n"(ACC));
}
#define ACC8(o) "+f"(d[o]), "+f"(d[o + 1]), "+f"(d[o + 2]), "+f"(d[o + 3]), "+f"(d[o + 4]), "+f"(d[o + 5]), "+f"(d[o + 6]), "+f"(d[o + 7])
template <int ACC, int TB> DEV void wgmma_n64_rs(float* d, const uint32_t* a, u64 desc) {
    asm volatile("wgmma.mma_async.sync.aligned.m64n64k16.f32.bf16.bf16 {%0,%1,%2,%3,%4,%5,%6,%7,%8,%9,%10,%11,%12,%13,%14,%15,"
                 "%16,%17,%18,%19,%20,%21,%22,%23,%24,%25,%26,%27,%28,%29,%30,%31},{%32,%33,%34,%35},%36,%37,1,1,%38;"
                 : ACC8(0), ACC8(8), ACC8(16), ACC8(24) : "r"(a[0]), "r"(a[1]), "r"(a[2]), "r"(a[3]), "l"(desc), "n"(ACC), "n"(TB));
}
template <int ACC, int TB> DEV void wgmma_n80_rs(float* d, const uint32_t* a, u64 desc) {
    asm volatile("wgmma.mma_async.sync.aligned.m64n80k16.f32.bf16.bf16 {%0,%1,%2,%3,%4,%5,%6,%7,%8,%9,%10,%11,%12,%13,%14,%15,"
                 "%16,%17,%18,%19,%20,%21,%22,%23,%24,%25,%26,%27,%28,%29,%30,%31,%32,%33,%34,%35,%36,%37,%38,%39},{%40,%41,%42,%43},%44,%45,1,1,%46;"
                 : ACC8(0), ACC8(8), ACC8(16), ACC8(24), ACC8(32) : "r"(a[0]), "r"(a[1]), "r"(a[2]), "r"(a[3]), "l"(desc), "n"(ACC), "n"(TB));
}
template <int TA, int TB> DEV void wgmma_n64_ss(float* d, u64 da, u64 db, int acc) {
    asm volatile("{.reg .pred p; setp.ne.b32 p,%34,0; wgmma.mma_async.sync.aligned.m64n64k16.f32.bf16.bf16 {%0,%1,%2,%3,%4,%5,%6,%7,%8,%9,%10,%11,%12,%13,%14,%15,%16,%17,%18,%19,%20,%21,%22,%23,%24,%25,%26,%27,%28,%29,%30,%31},%32,%33,p,1,1,%35,%36;}"
                 : ACC8(0), ACC8(8), ACC8(16), ACC8(24) : "l"(da), "l"(db), "r"(acc), "n"(TA), "n"(TB));
}
template <int TA, int TB> DEV void wgmma_n128_ss(float* d, u64 da, u64 db, int acc) {
    asm volatile("{.reg .pred p; setp.ne.b32 p,%66,0; wgmma.mma_async.sync.aligned.m64n128k16.f32.bf16.bf16 {%0,%1,%2,%3,%4,%5,%6,%7,%8,%9,%10,%11,%12,%13,%14,%15,%16,%17,%18,%19,%20,%21,%22,%23,%24,%25,%26,%27,%28,%29,%30,%31,%32,%33,%34,%35,%36,%37,%38,%39,%40,%41,%42,%43,%44,%45,%46,%47,%48,%49,%50,%51,%52,%53,%54,%55,%56,%57,%58,%59,%60,%61,%62,%63},%64,%65,p,1,1,%67,%68;}"
                 : ACC8(0), ACC8(8), ACC8(16), ACC8(24), ACC8(32), ACC8(40), ACC8(48), ACC8(56) : "l"(da), "l"(db), "r"(acc), "n"(TA), "n"(TB));
}
template <int TA, int TB> DEV void wgmma_n192_ss(float* d, u64 da, u64 db, int acc) {
    asm volatile("{.reg .pred p; setp.ne.b32 p,%98,0; wgmma.mma_async.sync.aligned.m64n192k16.f32.bf16.bf16 {%0,%1,%2,%3,%4,%5,%6,%7,%8,%9,%10,%11,%12,%13,%14,%15,%16,%17,%18,%19,%20,%21,%22,%23,%24,%25,%26,%27,%28,%29,%30,%31,%32,%33,%34,%35,%36,%37,%38,%39,%40,%41,%42,%43,%44,%45,%46,%47,%48,%49,%50,%51,%52,%53,%54,%55,%56,%57,%58,%59,%60,%61,%62,%63,%64,%65,%66,%67,%68,%69,%70,%71,%72,%73,%74,%75,%76,%77,%78,%79,%80,%81,%82,%83,%84,%85,%86,%87,%88,%89,%90,%91,%92,%93,%94,%95},%96,%97,p,1,1,%99,%100;}"
                 : ACC8(0), ACC8(8), ACC8(16), ACC8(24), ACC8(32), ACC8(40), ACC8(48), ACC8(56), ACC8(64), ACC8(72), ACC8(80), ACC8(88) : "l"(da), "l"(db), "r"(acc), "n"(TA), "n"(TB));
}
template <int ACC> DEV void wgmma_n40_ss(float* d, u64 da, u64 desc) {
    asm volatile("wgmma.mma_async.sync.aligned.m64n40k16.f32.bf16.bf16 {%0,%1,%2,%3,%4,%5,%6,%7,%8,%9,%10,%11,%12,%13,%14,%15,%16,%17,%18,%19},%20,%21,%22,1,1,0,0;"
                 : ACC8(0), ACC8(8), "+f"(d[16]), "+f"(d[17]), "+f"(d[18]), "+f"(d[19]) : "l"(da), "l"(desc), "n"(ACC));
}
DEV void pdl_wait() { asm volatile("griddepcontrol.wait;" ::: "memory"); }
DEV void pdl_launch() { asm volatile("griddepcontrol.launch_dependents;" ::: "memory"); }
DEV uint32_t ldg32(const void* p) { uint32_t v; asm volatile("ld.global.nc.u32 %0,[%1];" : "=r"(v) : "l"(p)); return v; }
DEV void ld_acc(u64& a, u64& b, const void* p) {
    const uint32_t done = (uint32_t)a & (uint32_t)b & 32u;
    asm volatile("{.reg .pred p; setp.eq.u32 p,%3,0;\n"
                 "@p ld.relaxed.gpu.global.v2.u64 {%0,%1},[%2];}" : "+l"(a), "+l"(b) : "l"(p), "r"(done) : "memory");
}
DEV void ld_acc0(u64& a, u64& b, const void* p) {
    asm volatile("ld.relaxed.gpu.global.v2.u64 {%0,%1},[%2];" : "=l"(a), "=l"(b) : "l"(p) : "memory");
}
DEV uint32_t and3(uint32_t a, uint32_t b, uint32_t c) { uint32_t r; asm volatile("lop3.b32 %0,%1,%2,%3,0x80;" : "=r"(r) : "r"(a), "r"(b), "r"(c)); return r; }
DEV uint32_t absmax2(uint32_t a, uint32_t b) { uint32_t r; asm("max.xorsign.abs.bf16x2 %0,%1,%2;" : "=r"(r) : "r"(a), "r"(b)); return r; }
DEV float lds32f(uint32_t a) { float x; asm volatile("ld.shared.f32 %0,[%1];" : "=f"(x) : "r"(a) : "memory"); return x; }
DEV void red_add64(u64* p, uint32_t lo, uint32_t hi) {
    asm volatile("{.reg .b64 v; mov.b64 v,{%1,%2}; red.relaxed.gpu.global.add.u64 [%0],v;}" ::"l"(p), "r"(lo), "r"(hi) : "memory");
}
DEV float bf_round(float x) { return __bfloat162float(__float2bfloat16_rn(x)); }
DEV float bf_lo(uint32_t u) { return __uint_as_float(u << 16); }
DEV float bf_hi(uint32_t u) { return __uint_as_float(u & 0xffff0000u); }

#define GPROF(i, n)
#define PROFT(i)
#define STAMP(i)

DEV int xn_off(int row, int chunk) { return (row >> 5) * 40960 + (chunk >> 3) * 4096 + (row & 31) * 128 + (((chunk ^ row) & 7) << 4); }

DEV void ln_row(float (&v)[3][8], int lane) {
    float s = 0.f;
#pragma unroll
    for (int c = 0; c < 3; c++)
#pragma unroll
        for (int j = 0; j < 8; j++) s += v[c][j];
#pragma unroll
    for (int o = 16; o; o >>= 1) s += __shfl_xor_sync(~0u, s, o);
    float mean = s * (1.f / D_), q = 0.f;
#pragma unroll
    for (int c = 0; c < 3; c++)
        if (c < 2 || lane < 16)
#pragma unroll
            for (int j = 0; j < 8; j++) { float d = v[c][j] - mean; q += d * d; }
#pragma unroll
    for (int o = 16; o; o >>= 1) q += __shfl_xor_sync(~0u, q, o);
    float mb = bf_round(mean);
    float sd = bf_round(sqrtf(bf_round(bf_round(q * (1.f / D_)) + 1e-5f)));
#pragma unroll
    for (int c = 0; c < 3; c++)
#pragma unroll
        for (int j = 0; j < 8; j++) v[c][j] = bf_round(v[c][j] - mb) / sd;
}

__global__ void __launch_bounds__(512) prep_kernel(const bf16* __restrict__ x, const bf16* __restrict__ Wv, const bf16* __restrict__ Wo) {
    __shared__ float red[32];
    const int tid = threadIdx.x, lane = tid & 31, warp = tid >> 5, b = blockIdx.x;
    TLS(0);
    {
        int row = b * 16 + warp;
        float v[3][8];
#pragma unroll
        for (int c = 0; c < 3; c++) {
            uint4 u = make_uint4(0, 0, 0, 0);
            if (c < 2 || lane < 16) u = *(const uint4*)(x + row * D_ + (c * 32 + lane) * 8);
            v[c][0] = bf_lo(u.x); v[c][1] = bf_hi(u.x); v[c][2] = bf_lo(u.y); v[c][3] = bf_hi(u.y);
            v[c][4] = bf_lo(u.z); v[c][5] = bf_hi(u.z); v[c][6] = bf_lo(u.w); v[c][7] = bf_hi(u.w);
        }
        ln_row(v, lane);
#pragma unroll
        for (int c = 0; c < 3; c++)
            if (c < 2 || lane < 16)
                *(uint4*)(g_xn + xn_off(row, c * 32 + lane)) =
                    make_uint4(pack2(v[c][0], v[c][1]), pack2(v[c][2], v[c][3]), pack2(v[c][4], v[c][5]), pack2(v[c][6], v[c][7]));
    }
    if (b == 0) ((uint4*)g_sync)[tid] = make_uint4(0, 0, 0, 0);
    for (int i = b * 512 + tid; i < ACC_LAYER; i += 128 * 512) ((uint4*)g_acc)[i] = make_uint4(0, 0, 0, 0);
    float sv = 0.f;
#pragma unroll
    for (int i = 0; i < 5; i++) {
        uint4 u = *(const uint4*)(Wv + (size_t)((b & 3) * 160 + i * 32 + (tid >> 4)) * 4096 + (b >> 2) * E_ + (tid & 15) * 8);
        uint32_t w[4] = {u.x, u.y, u.z, u.w};
#pragma unroll
        for (int j = 0; j < 4; j++) { float a = bf_lo(w[j]), c = bf_hi(w[j]); sv += a * a + c * c; }
    }
    float so = 0.f;
    if (tid < 320) {
        float s0 = 0.f, s1 = 0.f;
#pragma unroll 8
        for (int r = 0; r < 32; r++) { uint32_t u = *(const uint32_t*)(Wo + (size_t)(b * 32 + r) * D_ + tid * 2); float a = bf_lo(u), c = bf_hi(u); s0 += a * a; s1 += c * c; }
        so = fmaxf(s0, s1);
    }
#pragma unroll
    for (int o = 16; o; o >>= 1) { sv += __shfl_xor_sync(~0u, sv, o); so = fmaxf(so, __shfl_xor_sync(~0u, so, o)); }
    if (lane == 0) { red[warp] = sv; red[16 + warp] = so; }
    __syncthreads();
    if (tid == 0) {
        float a = 0.f, c = 0.f;
        for (int i = 0; i < 16; i++) { a += red[i]; c = fmaxf(c, red[16 + i]); }
        g_nrm[b] = a; g_nrm[128 + b] = c;
    }
    TLE(0);
}

__host__ __device__ constexpr int col_freq(int c) {
    return c == 320 ? 320 : c < 192 ? (c >> 6) * 128 + (c & 63) : c == 192 ? 192 : c < 256 ? 448 - c : c == 256 ? 64 : 384 - c;
}
DEV float rdft(int n, int k, int sn, int N) {
    float s, c;
    sincospif((float)((n * k) & (N - 1)) * (2.f / N), &s, &c);
    return !sn ? c : k ? s : (n & 1 ? -1.f : 1.f);
}
__global__ void __launch_bounds__(512) tables_kernel(const bf16* __restrict__ wr, const bf16* __restrict__ wi) {
    const int tid = threadIdx.x, b = blockIdx.x;
    if (tid < NCOL) {
        const int ka = b >> 2, i = b & 3, kn = ka ? 2048 - ka : 32, kc = col_freq(tid);
        const unsigned short* pr = (const unsigned short*)wr + kc;
        const unsigned short* pi = (const unsigned short*)wi + kc;
#pragma unroll
        for (int q = 0; q < 4; q++) {
            uint32_t v[4];
#pragma unroll
            for (int j = 0; j < 4; j++) {
                const int k = ((j & 1 ? kn : ka) + 64 * (4 * (2 * i + (j >> 1)) + q)) & 2047;
                v[j] = pr[k * NCOL] | ((uint32_t)pi[k * NCOL] << 16);
            }
            *(uint4*)(g_wt + tid * 8192 + i * 2048 + (ka * 4 + q) * 16) = make_uint4(v[0], v[1], v[2], v[3]);
        }
    }
    const int gid = b * 512 + tid;
    if (gid < 4096) {
        const int inv = gid >> 11, ks = (gid >> 8) & 7, t = gid & 255, g = (t & 31) >> 2, q = t & 3, tile = t >> 5;
        uint32_t v[4];
#pragma unroll
        for (int j = 0; j < 4; j++) {
            float x[2];
#pragma unroll
            for (int u = 0; u < 2; u++) {
                const int m = inv ? 16 * tile + 2 * g + (j & 1) : 16 * ks + 8 * (j >> 1) + 2 * q + u;
                const int k2 = inv ? 8 * ks + 2 * q + u : 8 * tile + g, sn = inv ? j >> 1 : j & 1;
                x[u] = rdft(m, k2, sn, 128);
                if (sn && k2) x[u] = -x[u];
            }
            v[j] = pack2(x[0], x[1]);
        }
        g_f128[gid] = make_uint4(v[0], v[1], v[2], v[3]);
    } else if (gid < 5120) {
        const int id = gid - 4096, inv = id >> 9, ks = (id >> 7) & 3, t = id & 127, g = (t & 31) >> 2, q = t & 3, tile = t >> 5;
        uint32_t v[4];
#pragma unroll
        for (int j = 0; j < 4; j++) {
            float x[2];
#pragma unroll
            for (int u = 0; u < 2; u++) {
                const int a = inv ? 16 * tile + g + 8 * (j & 1) : 16 * ks + 8 * (j >> 1) + 2 * q + u;
                const int ka = inv ? 8 * ks + 2 * q + u : 8 * tile + g, sn = inv ? j >> 1 : j & 1;
                x[u] = rdft(a, ka, sn, 64);
            }
            v[j] = pack2(x[0], x[1]);
        }
        g_f64[id] = make_uint4(v[0], v[1], v[2], v[3]);
    } else if (gid < 5120 + 8192) {
        const int id = gid - 5120, inv = id >> 12, n = ((id >> 9) & 7) * 8 + ((id >> 3) & 7), k = ((id >> 6) & 7) * 8 + (id & 7);
        float s, c;
        sincospif((float)(((n >> 1) * (k >> 1)) & 31) * (1.f / 16), &s, &c);
        if (inv) s = -s;
        g_g32[id] = __float2bfloat16_rn((n & 1) == (k & 1) ? c : (k & 1) ? s : -s);
    }
}

namespace wk {
constexpr int STAGE = 49152, NST = 3, OFF_OUT = NST * STAGE, OFF_BAR = OFF_OUT + 73728, SMEM = OFF_BAR + 128;
constexpr int NPB = 12;
__host__ __device__ constexpr int pb_start(int b) { return b == 0 ? 0 : b == 1 ? 2 : b < NPB ? 6 * b - 6 : 64; }
#define NOB 7
constexpr int N_P = NPB * H_, N_OB = NOB * 5, N_OT = (32 - 3 * NOB) * 10, N_ITEMS = N_P + N_OB + N_OT;
enum { SY_TICKET = 0, SY_O = 32, SY_P = 128 };
}
struct Maps { CUtensorMap wq2, wv1, wo2, wo1, x6, x2, o6, o2; };

template <int NSG> DEV void proj_tile(uint32_t sb, uint32_t bar, int& it, int wg, int id) {
    using namespace wk;
    float acc[NSG * 16];
#pragma unroll
    for (int i = 0; i < NSG * 16; i++) acc[i] = 0.f;
    const int lane = threadIdx.x & 31, ww = (threadIdx.x >> 5) & 3;
    for (int kb = 0; kb < 10; kb++, it++) {
        const int st = it % NST;
        if (kb) mbar_wait(bar + 8 * st, (it / NST) & 1);
        const u64 da = mkdesc(sb + st * STAGE + wg * 8192, 0, 1024) | SW128, db = mkdesc(sb + st * STAGE + 24576, 0, 1024) | SW128;
        wg_fence();
#pragma unroll
        for (int ks = 0; ks < 4; ks++) {
            if (NSG == 2) wgmma_n64_ss<1, 0>(acc, da + ks * 128, db + ks * 2, 1);
            if (NSG == 4) wgmma_n128_ss<1, 0>(acc, da + ks * 128, db + ks * 2, 1);
            if (NSG == 6) wgmma_n192_ss<1, 0>(acc, da + ks * 128, db + ks * 2, 1);
        }
        wg_commit();
        wg_wait<0>();
        mbar_arrive_elect(bar + 8 * (NST + st));
    }
    const uint32_t out = sb + OFF_OUT + wg * 24576;
    bar_sync(5 + wg, 160);
    const uint32_t la = out + (wg < 2 ? (lane >> 4) * 1024 + ww * 256 + (lane & 15) * 16 : ww * 1024 + ((lane >> 3) & 1) * 512 + (lane >> 4) * 128 + (lane & 7) * 16);
#pragma unroll
    for (int j = 0; j < 2 * NSG; j++) {
        const float* c = acc + 8 * j;
        const uint32_t p0 = pack2(c[0], c[1]), p1 = pack2(c[2], c[3]), p2 = pack2(c[4], c[5]), p3 = pack2(c[6], c[7]);
        if (wg < 2) stsm4t(la + j * 2048, p0, p1, p2, p3);
        else stsm4(la + (j >> 1) * 4096 + (j & 1) * 256, p0, p1, p2, p3);
    }
    if ((threadIdx.x & 127) == 0) sts32(bar + 80 + 4 * wg, id);
    fence_async();
    bar_arrive(1 + wg, 160);
}

DEV void resid_store(const bf16* __restrict__ x, bf16* __restrict__ x1, size_t o, float a, float b) {
    const uint32_t u = *(const uint32_t*)(x + o);
    *(uint32_t*)(x1 + o) = pack2(bf_lo(u) + bf_round(a), bf_hi(u) + bf_round(b));
}

DEV void worker(uint32_t sb, const Maps& maps, const bf16* __restrict__ x, bf16* __restrict__ x1, int layer) {
    using namespace wk;
    const uint32_t bar = sb + OFF_BAR, slot = bar + 64;
    const int tid = threadIdx.x, lane = tid & 31, warp = __shfl_sync(~0u, tid >> 5, 0);
    uint32_t* sy = g_sync + layer * SYNC_LAYER;
    if (tid == 0) {
        for (int i = 0; i < NST; i++) { mbar_init(bar + 8 * i, 1); mbar_init(bar + 8 * (NST + i), 12); }
        asm volatile("fence.mbarrier_init.release.cluster;" ::: "memory");
    }
    __syncthreads();
    if (warp >= 12) {
        if (warp > 12) {
            const int wg = warp - 13;
            bar_arrive(5 + wg, 160);
            for (;;) {
                bar_sync(1 + wg, 160);
                const int id = (int)lds32(bar + 80 + 4 * wg);
                if (id < 0) break;
                const int s0 = pb_start(id >> 5), ns = pb_start((id >> 5) + 1) - s0;
                if (lane == 0) {
                    for (int j = 0; j < ns; j++)
                        bulk_s2g(g_p + (size_t)(((s0 + j) * H_ + (id & 31)) * 3 + wg) * 4096, sb + OFF_OUT + wg * 24576 + j * 4096, 4096);
                    bulk_commit();
                    bulk_wait<0>();
                    flag_add(sy + SY_P + id);
                }
                __syncwarp();
                bar_arrive(5 + wg, 160);
            }
        } else if (tid == 384) {
            int it = 0;
            auto acquire = [&]() { const int st = it % NST; if (it >= NST) mbar_wait(bar + 8 * (NST + st), (it / NST - 1) & 1); return st; };
            for (;;) {
                int id = (int)atomicAdd(sy + SY_TICKET, 1u);
                if (id >= N_ITEMS) id = -1;
                if (id >= 0) { TLI(id, 0, gtime()); TLI(id, 3, blockIdx.x + (gridDim.x % 3 == 0 && gridDim.x > 111 ? 0 : 1000)); }
                int st = acquire();
                sts32(slot + 4 * st, id);
                if (id < 0) { mbar_arrive(bar + 8 * st); break; }
                if (id < N_P) {
                    const int b = id >> 5, h = id & 31, s0 = pb_start(b), ns = pb_start(b + 1) - s0;
                    for (int kb = 0; kb < 10; kb++, it++) {
                        if (kb) st = acquire();
                        const uint32_t d = sb + st * STAGE, fb = bar + 8 * st;
                        mbar_expect(fb, 24576 + ns * 4096);
                        tma3d(d, &maps.wq2, 0, kb * 64, 2 * h, fb);
                        tma3d(d + 16384, &maps.wv1, 0, kb * 64, 2 * h, fb);
                        if (ns == 6) tma3d(d + 24576, &maps.x6, 0, 2 * kb, s0, fb);
                        else for (int j = 0; j < ns; j += 2) tma3d(d + 24576 + j * 4096, &maps.x2, 0, 2 * kb, s0 + j, fb);
                    }
                } else if (id < N_P + N_OB) {
                    const int b = (id - N_P) / 5, nt = (id - N_P) % 5;
                    for (int j = 0; j < 6; j++) flag_wait(sy + SY_O + 6 * b + j, 32);
                    for (int kb = 0; kb < 64; kb++, it++) {
                        if (kb) st = acquire();
                        const uint32_t d = sb + st * STAGE, fb = bar + 8 * st;
                        mbar_expect(fb, 40960);
                        tma3d(d, &maps.o6, 0, 2 * kb, 6 * b, fb);
                        tma3d(d + 24576, &maps.wo2, 0, kb * 64, 2 * nt, fb);
                    }
                } else {
                    const int b = 3 * NOB + (id - N_P - N_OB) / 10, nt = (id - N_P - N_OB) % 10;
                    for (int j = 0; j < 2; j++) flag_wait(sy + SY_O + 2 * b + j, 32);
                    for (int kb = 0; kb < 22; kb++, it++) {
                        if (kb) st = acquire();
                        const uint32_t d = sb + st * STAGE, fb = bar + 8 * st;
                        mbar_expect(fb, 49152);
                        for (int u = 0; u < 3; u++) {
                            tma3d(d + u * 8192, &maps.o2, 0, 2 * (3 * kb + u), 2 * b, fb);
                            tma3d(d + 24576 + u * 8192, &maps.wo1, 0, (3 * kb + u) * 64, nt, fb);
                        }
                    }
                }
            }
        }
    } else {
        const int wg = warp >> 2, g = lane >> 2, q = lane & 3;
        int it = 0;
        bool stores_done = false;
        for (;;) {
            mbar_wait(bar + 8 * (it % NST), (it / NST) & 1);
            const int id = (int)lds32(slot + 4 * (it % NST));
            if ((id < 0 || id >= N_P) && !stores_done) {
                bar_sync(5 + wg, 160);
                if ((tid & 127) == 0) sts32(bar + 80 + 4 * wg, ~0u);
                bar_arrive(1 + wg, 160);
                stores_done = true;
                bar_sync(4, 384);
            }
            if (id < 0) break;
            if (tid == 0) TLI(id, 1, gtime());
            if (id < N_P) {
                const int b = id >> 5;
                if (b == 0) proj_tile<2>(sb, bar, it, wg, id);
                else if (b == 1 || b == NPB - 1) proj_tile<4>(sb, bar, it, wg, id);
                else proj_tile<6>(sb, bar, it, wg, id);
            } else if (id < N_P + N_OB) {
                const int b = (id - N_P) / 5, nt = (id - N_P) % 5;
                float acc[64];
#pragma unroll
                for (int i = 0; i < 64; i++) acc[i] = 0.f;
                for (int kb = 0; kb < 64; kb++, it++) {
                    const int st = it % NST;
                    if (kb) mbar_wait(bar + 8 * st, (it / NST) & 1);
                    const u64 da = mkdesc(sb + st * STAGE + wg * 8192, 128, 1024), db = mkdesc(sb + st * STAGE + 24576, 8192, 1024) | SW128;
                    wg_fence();
#pragma unroll
                    for (int ks = 0; ks < 4; ks++) wgmma_n128_ss<0, 1>(acc, da + ks * 16, db + ks * 128, 1);
                    wg_commit();
                    wg_wait<0>();
                    mbar_arrive_elect(bar + 8 * (NST + st));
                }
                const size_t o = (size_t)(192 * b + 16 * warp + g) * D_ + nt * 128 + 2 * q;
#pragma unroll
                for (int t = 0; t < 16; t++) {
                    resid_store(x, x1, o + 8 * t, acc[4 * t], acc[4 * t + 1]);
                    resid_store(x, x1, o + 8 * t + 8 * D_, acc[4 * t + 2], acc[4 * t + 3]);
                }
            } else {
                const int b = 3 * NOB + (id - N_P - N_OB) / 10, nt = (id - N_P - N_OB) % 10;
                float acc[32];
#pragma unroll
                for (int i = 0; i < 32; i++) acc[i] = 0.f;
                for (int kb = 0; kb < 22; kb++, it++) {
                    const int st = it % NST;
                    if (kb) mbar_wait(bar + 8 * st, (it / NST) & 1);
                    {
                        const u64 da = mkdesc(sb + st * STAGE + wg * 8192, 128, 1024), db = mkdesc(sb + st * STAGE + 24576 + wg * 8192, 0, 1024) | SW128;
                        wg_fence();
#pragma unroll
                        for (int ks = 0; ks < 4; ks++) wgmma_n64_ss<0, 1>(acc, da + ks * 16, db + ks * 128, 1);
                        wg_commit();
                        wg_wait<0>();
                    }
                    mbar_arrive_elect(bar + 8 * (NST + st));
                }
                const uint32_t ra = sb + OFF_OUT + (tid & 127) * 16;
                if (wg) {
#pragma unroll
                    for (int t = 0; t < 8; t++)
                        sts128(ra + wg * 16384 + t * 2048, __float_as_uint(acc[4 * t]), __float_as_uint(acc[4 * t + 1]), __float_as_uint(acc[4 * t + 2]), __float_as_uint(acc[4 * t + 3]));
                }
                bar_sync(4, 384);
                if (wg == 0) {
                    const size_t o = (size_t)(64 * b + 16 * warp + g) * D_ + nt * 64 + 2 * q;
#pragma unroll
                    for (int t = 0; t < 8; t++) {
                        float u[4], v[4];
                        lds128f(u, ra + 16384 + t * 2048); lds128f(v, ra + 32768 + t * 2048);
                        resid_store(x, x1, o + 8 * t, acc[4 * t] + u[0] + v[0], acc[4 * t + 1] + u[1] + v[1]);
                        resid_store(x, x1, o + 8 * t + 8 * D_, acc[4 * t + 2] + u[2] + v[2], acc[4 * t + 3] + u[3] + v[3]);
                    }
                }
                bar_sync(4, 384);
            }
            if (tid == 0) TLI(id, 2, gtime());
        }
    }
}

__global__ void __launch_bounds__(512, 1) side_kernel(const __grid_constant__ Maps maps, const bf16* __restrict__ x, bf16* __restrict__ x1, int layer) {
    extern __shared__ __align__(1024) unsigned char smem[];
    pdl_launch();
    TLS(3 + 5 * layer);
    worker(s2u(smem), maps, x, x1, layer);
    __syncwarp();
    pdl_wait();
    TLE(3 + 5 * layer);
}

constexpr float C5A = 0.30901699437494742f, C5B = -0.80901699437494742f, S5A = 0.95105651629515357f, S5B = 0.58778525229247313f;
template <int SGN> DEV void dft5(const float (&tr)[5], const float (&ti)[5], float (&zr)[5], float (&zi)[5]) {
    const float ar = tr[1] + tr[4], ai = ti[1] + ti[4], br = tr[2] + tr[3], bi = ti[2] + ti[3];
    const float cr = tr[1] - tr[4], ci = ti[1] - ti[4], dr = tr[2] - tr[3], di = ti[2] - ti[3];
    zr[0] = tr[0] + ar + br; zi[0] = ti[0] + ai + bi;
    const float m1r = tr[0] + C5A * ar + C5B * br, m1i = ti[0] + C5A * ai + C5B * bi;
    const float m2r = tr[0] + C5B * ar + C5A * br, m2i = ti[0] + C5B * ai + C5A * bi;
    const float n1r = SGN * (S5A * cr + S5B * dr), n1i = SGN * (S5A * ci + S5B * di);
    const float n2r = SGN * (S5B * cr - S5A * dr), n2i = SGN * (S5B * ci - S5A * di);
    zr[1] = m1r + n1i; zi[1] = m1i - n1r; zr[4] = m1r - n1i; zi[4] = m1i + n1r;
    zr[2] = m2r + n2i; zi[2] = m2i - n2r; zr[3] = m2r - n2i; zi[3] = m2i + n2r;
}
DEV void ln40(float (&v)[40]) {
    float s = 0.f;
#pragma unroll
    for (int i = 0; i < 40; i++) s += v[i];
#pragma unroll
    for (int o = 8; o; o >>= 1) s += __shfl_xor_sync(~0u, s, o);
    const float mean = s * (1.f / D_);
    float q = 0.f;
#pragma unroll
    for (int i = 0; i < 40; i++) { const float d = v[i] - mean; q += d * d; }
#pragma unroll
    for (int o = 8; o; o >>= 1) q += __shfl_xor_sync(~0u, q, o);
    const float mb = bf_round(mean);
    const float inv = 1.f / bf_round(sqrtf(bf_round(bf_round(q * (1.f / D_)) + 1e-5f)));
#pragma unroll
    for (int i = 0; i < 40; i++) v[i] = bf_round(v[i] - mb) * inv;
}
DEV void unpack8(float* v, uint4 u) {
    v[0] = bf_lo(u.x); v[1] = bf_hi(u.x); v[2] = bf_lo(u.y); v[3] = bf_hi(u.y);
    v[4] = bf_lo(u.z); v[5] = bf_hi(u.z); v[6] = bf_lo(u.w); v[7] = bf_hi(u.w);
}

__global__ void __launch_bounds__(256) rowfft_kernel(const bf16* __restrict__ x, int layer) {
    __shared__ __align__(128) unsigned char sm[10 * 2304];
    const uint32_t sb = s2u(sm);
    const int tid = threadIdx.x, lane = tid & 31, q = lane & 3, blk = blockIdx.x, k2 = tid >> 2;
    float twr[5], twi[5];
#pragma unroll
    for (int r = 1; r < 5; r++) { sincospif((float)(r * k2) * (-1.f / 320), &twi[r], &twr[r]); }
    pdl_wait();
    pdl_launch();
    TLS(4 + 5 * layer);
    uint32_t f[8][4];
#pragma unroll
    for (int ks = 0; ks < 8; ks++) { const uint4 u = g_f128[ks * 256 + tid]; f[ks][0] = u.x; f[ks][1] = u.y; f[ks][2] = u.z; f[ks][3] = u.w; }
    {
        const int rho = tid >> 4, j = tid & 15;
        float v[40];
#pragma unroll
        for (int i = 0; i < 5; i++) unpack8(v + 8 * i, *(const uint4*)(x + (size_t)(blk * 16 + rho) * D_ + j * 40 + i * 8));
        ln40(v);
        const uint32_t a = sb + ((rho >> 1) & 1) * 2304 + j * 144 + (2 * (rho >> 2) + (rho & 1)) * 16;
#pragma unroll
        for (int r = 0; r < 5; r++)
            sts128(a + r * 4608, pack2(v[r], v[5 + r]), pack2(v[10 + r], v[15 + r]), pack2(v[20 + r], v[25 + r]), pack2(v[30 + r], v[35 + r]));
    }
    fence_async();
    __syncthreads();
    float acc[40];
    const u64 db = mkdesc(sb, 144, 2304);
    wg_fence();
    wgmma_n80_rs<0, 0>(acc, f[0], db);
#pragma unroll
    for (int ks = 1; ks < 8; ks++) wgmma_n80_rs<1, 0>(acc, f[ks], db + ks * 18);
    wg_commit();
    wg_wait<0>();
    unsigned char* zp = g_z + (blk >> 1) * 128 + ((((blk & 1) * 4 + q) ^ ((blk >> 1) & 7)) << 4);
    uint32_t o[5][4];
#pragma unroll
    for (int u = 0; u < 4; u++) {
        float tr[5], ti[5], zr[5], zi[5];
#pragma unroll
        for (int r = 0; r < 5; r++) {
            const float yr = acc[8 * r + 4 * (u >> 1) + (u & 1)], yi = k2 ? acc[8 * r + 4 * (u >> 1) + 2 + (u & 1)] : 0.f;
            tr[r] = r ? yr * twr[r] - yi * twi[r] : yr;
            ti[r] = r ? yr * twi[r] + yi * twr[r] : yi;
        }
        dft5<1>(tr, ti, zr, zi);
#pragma unroll
        for (int j = 0; j < 5; j++) o[j][u] = pack2(zr[j], j < 3 ? zi[j] : -zi[j]);
    }
#pragma unroll
    for (int j = 0; j < 5; j++)
        if (j < 3 || k2) *(uint4*)(zp + (64 * j + k2) * 8192) = make_uint4(o[j][0], o[j][1], o[j][2], o[j][3]);
    if (k2 == 0) {
#pragma unroll
        for (int u = 0; u < 4; u++) {
            float tr[5], ti[5], zr[5], zi[5];
            const float cr[5] = {1.f, -C5B, C5A, -C5A, C5B}, ci[5] = {0.f, -S5B, -S5A, -S5A, -S5B};
#pragma unroll
            for (int r = 0; r < 5; r++) { const float y = acc[8 * r + 4 * (u >> 1) + 2 + (u & 1)]; tr[r] = y * cr[r]; ti[r] = y * ci[r]; }
            dft5<1>(tr, ti, zr, zi);
            o[0][u] = pack2(zr[0], zi[0]); o[1][u] = pack2(zr[1], zi[1]); o[2][u] = pack2(zr[2], 0.f);
        }
        *(uint4*)(zp + 256 * 8192) = make_uint4(o[0][0], o[0][1], o[0][2], o[0][3]);
        *(uint4*)(zp + 192 * 8192) = make_uint4(o[1][0], o[1][1], o[1][2], o[1][3]);
        *(uint4*)(zp + 320 * 8192) = make_uint4(o[2][0], o[2][1], o[2][2], o[2][3]);
    }
    TLE(4 + 5 * layer);
}

constexpr int CF_SMEM = 16384 + 3 * 16384 + 64;
__global__ void __launch_bounds__(384) colfft_kernel(int layer) {
    extern __shared__ __align__(1024) unsigned char smem[];
    const uint32_t sb = s2u(smem), bar = sb + 65536;
    const int tid = threadIdx.x, lane = tid & 31, q = lane & 3, wg = __shfl_sync(~0u, tid >> 7, 0), t = tid & 127, ka = t >> 2;
    const int col = blockIdx.x * 3 + wg;
    const uint32_t d0 = sb + 16384 + wg * 16384, d1 = d0 + 8192;
    if (tid == 0) {
        for (int i = 0; i < 4; i++) mbar_init(bar + 8 * i, 1);
        asm volatile("fence.mbarrier_init.release.cluster;" ::: "memory");
    }
    float twr[8], twi[8];
#pragma unroll
    for (int i = 0; i < 8; i++) sincospif((float)((4 * i + q) * (ka ? ka : -32)) * (1.f / 1024), &twi[i], &twr[i]);
    __syncthreads();
    pdl_wait();
    pdl_launch();
    TLS(5 + 5 * layer);
    if (t == 0) {
        mbar_expect(bar + 8 * wg, 8192);
        bulk_g2s(d0, g_z + col * 8192, 8192, bar + 8 * wg);
        if (wg == 0) { mbar_expect(bar + 24, 16384); bulk_g2s(sb, g_g32, 16384, bar + 24); }
    }
    uint32_t f[4][4], w[16];
#pragma unroll
    for (int ks = 0; ks < 4; ks++) { const uint4 u = g_f64[ks * 128 + t]; f[ks][0] = u.x; f[ks][1] = u.y; f[ks][2] = u.z; f[ks][3] = u.w; }
#pragma unroll
    for (int i = 0; i < 4; i++) { const uint4 u = *(const uint4*)(g_wt + col * 8192 + i * 2048 + t * 16); w[4 * i] = u.x; w[4 * i + 1] = u.y; w[4 * i + 2] = u.z; w[4 * i + 3] = u.w; }
    float acc[32];
    uint32_t a[4][4];
    mbar_wait(bar + 8 * wg, 0);
    {
        const u64 db = mkdesc(d0, 0, 1024) | SW128;
        wg_fence();
        wgmma_n64_rs<0, 1>(acc, f[0], db);
#pragma unroll
        for (int ks = 1; ks < 4; ks++) wgmma_n64_rs<1, 1>(acc, f[ks], db + ks * 128);
        wg_commit();
        wg_wait<0>();
    }
#pragma unroll
    for (int ks = 0; ks < 4; ks++) { const uint4 u = g_f64[512 + ks * 128 + t]; f[ks][0] = u.x; f[ks][1] = u.y; f[ks][2] = u.z; f[ks][3] = u.w; }
#pragma unroll
    for (int i = 0; i < 8; i++) {
        const float c0 = acc[4 * i], c1 = acc[4 * i + 1], c2 = acc[4 * i + 2], c3 = acc[4 * i + 3];
        const float pr = c0 + c3, pi = c1 - c2, nr = ka ? c0 - c3 : c2, ni = ka ? c1 + c2 : c3;
        a[i >> 1][2 * (i & 1)] = ka ? pack2(pr * twr[i] + pi * twi[i], pi * twr[i] - pr * twi[i]) : pack2(c0, c1);
        a[i >> 1][2 * (i & 1) + 1] = pack2(nr * twr[i] - ni * twi[i], ni * twr[i] + nr * twi[i]);
    }
    mbar_wait(bar + 24, 0);
    {
        const u64 db = mkdesc(sb, 128, 1024);
        wg_fence();
        wgmma_n64_rs<0, 0>(acc, a[0], db);
#pragma unroll
        for (int ks = 1; ks < 4; ks++) wgmma_n64_rs<1, 0>(acc, a[ks], db + ks * 16);
        wg_commit();
        wg_wait<0>();
    }
    constexpr float NORM = 1.f / (2048.f * 640.f);
#pragma unroll
    for (int i = 0; i < 16; i++) {
        const float zr = acc[2 * i] * NORM, zi = acc[2 * i + 1] * NORM, wr = bf_lo(w[i]), wi = bf_hi(w[i]);
        a[i >> 2][i & 3] = pack2(zr * wr - zi * wi, zr * wi + zi * wr);
    }
    {
        const u64 db = mkdesc(sb + 8192, 128, 1024);
        wg_fence();
        wgmma_n64_rs<0, 0>(acc, a[0], db);
#pragma unroll
        for (int ks = 1; ks < 4; ks++) wgmma_n64_rs<1, 0>(acc, a[ks], db + ks * 16);
        wg_commit();
        wg_wait<0>();
    }
    const uint32_t row = (t >> 5) * 2048 + (lane & 15) * 128;
#pragma unroll
    for (int i = 0; i < 8; i++) {
        const float c0 = acc[4 * i], c1 = acc[4 * i + 1], c2 = acc[4 * i + 2], c3 = acc[4 * i + 3];
        const float pr = c0 * twr[i] - c1 * twi[i], pi = c1 * twr[i] + c0 * twi[i];
        const float nr = c2 * twr[i] + c3 * twi[i], ni = c3 * twr[i] - c2 * twi[i];
        a[i >> 1][2 * (i & 1)] = ka ? pack2(pr + nr, pi + ni) : pack2(c0, c1);
        a[i >> 1][2 * (i & 1) + 1] = ka ? pack2(ni - pi, pr - nr) : pack2(nr, ni);
    }
#pragma unroll
    for (int i = 0; i < 4; i++) stsm4(d1 + row + (((2 * i + (lane >> 4)) ^ (lane & 7)) << 4), a[i][0], a[i][1], a[i][2], a[i][3]);
    fence_async();
    bar_sync(1 + wg, 128);
    {
        const u64 db = mkdesc(d1, 0, 1024) | SW128;
        wg_fence();
        wgmma_n64_rs<0, 1>(acc, f[0], db);
#pragma unroll
        for (int ks = 1; ks < 4; ks++) wgmma_n64_rs<1, 1>(acc, f[ks], db + ks * 128);
        wg_commit();
        wg_wait<0>();
    }
#pragma unroll
    for (int i = 0; i < 4; i++)
        stsm4(d0 + row + (((2 * i + (lane >> 4)) ^ (lane & 7)) << 4), pack2(acc[8 * i], acc[8 * i + 1]), pack2(acc[8 * i + 2], acc[8 * i + 3]),
              pack2(acc[8 * i + 4], acc[8 * i + 5]), pack2(acc[8 * i + 6], acc[8 * i + 7]));
    fence_async();
    bar_sync(1 + wg, 128);
    if (t == 0) {
        bulk_s2g(g_z + col * 8192, d0, 8192);
        asm volatile("cp.async.bulk.commit_group;" ::: "memory");
        asm volatile("cp.async.bulk.wait_group 0;" ::: "memory");
    }
    TLE(5 + 5 * layer);
}

__global__ void __launch_bounds__(256) rowifft_kernel(const bf16* __restrict__ x, bf16* __restrict__ out, int last) {
    __shared__ __align__(128) unsigned char sm[20480 + 16 * 1296];
    const uint32_t sb = s2u(sm), sy = sb + 20480;
    const int tid = threadIdx.x, lane = tid & 31, q = lane & 3, blk = blockIdx.x, k2 = tid >> 2, warp = tid >> 5;
    float twr[5], twi[5];
#pragma unroll
    for (int r = 1; r < 5; r++) { sincospif((float)(r * k2) * (1.f / 320), &twi[r], &twr[r]); twr[r] *= 2.f; twi[r] *= 2.f; }
    pdl_wait();
    pdl_launch();
    TLS(6 + 5 * last);
    const unsigned char* zp = g_z + (blk >> 1) * 128 + ((((blk & 1) * 4 + q) ^ ((blk >> 1) & 7)) << 4);
    uint4 z[6];
#pragma unroll
    for (int j = 0; j < 5; j++) z[j] = *(const uint4*)(zp + (64 * j + k2) * 8192);
    z[5] = k2 ? make_uint4(0, 0, 0, 0) : *(const uint4*)(zp + 320 * 8192);
    uint32_t f[8][4];
#pragma unroll
    for (int ks = 0; ks < 8; ks++) { const uint4 u = g_f128[2048 + ks * 256 + tid]; f[ks][0] = u.x; f[ks][1] = u.y; f[ks][2] = u.z; f[ks][3] = u.w; }
    uint4 xr[5];
#pragma unroll
    for (int i = 0; i < 5; i++) xr[i] = *(const uint4*)(x + (size_t)(blk * 16 + (tid >> 4)) * D_ + (tid & 15) * 40 + i * 8);
    float acc[40];
#pragma unroll
    for (int u = 0; u < 4; u++) {
        float yr[6], yi[6], tr[5], ti[5], zr[5], zi[5];
#pragma unroll
        for (int j = 0; j < 6; j++) { const uint32_t v = u == 0 ? z[j].x : u == 1 ? z[j].y : u == 2 ? z[j].z : z[j].w; yr[j] = bf_lo(v); yi[j] = bf_hi(v); }
#pragma unroll
        for (int j = 0; j < 5; j++) { tr[j] = yr[j]; ti[j] = j < 3 ? yi[j] : -yi[j]; }
        dft5<-1>(tr, ti, zr, zi);
        const float c1[5] = {1.f, C5A, C5B, C5B, C5A}, s1[5] = {0.f, S5A, S5B, -S5B, -S5A};
        const float c2[5] = {1.f, C5B, C5A, C5A, C5B}, s2[5] = {0.f, S5B, -S5A, S5A, -S5B};
        const float c3[5] = {1.f, -C5B, C5A, -C5A, C5B}, s3[5] = {0.f, S5B, S5A, S5A, S5B};
        const float c4[5] = {1.f, -C5A, C5B, -C5B, C5A}, s4[5] = {0.f, S5A, -S5B, -S5B, S5A};
#pragma unroll
        for (int r = 0; r < 5; r++) {
            float er = r ? zr[r] * twr[r] - zi[r] * twi[r] : 2.f * zr[0], ei = r ? zr[r] * twi[r] + zi[r] * twr[r] : 2.f * zi[0];
            if (k2 == 0) {
                er = yr[0] + 2.f * (yr[1] * c1[r] - yi[1] * s1[r] + yr[2] * c2[r] - yi[2] * s2[r]);
                ei = (r & 1 ? -yr[5] : yr[5]) + 2.f * (yr[4] * c3[r] - yi[4] * s3[r] + yr[3] * c4[r] - yi[3] * s4[r]);
            }
            acc[8 * r + 4 * (u >> 1) + (u & 1)] = er;
            acc[8 * r + 4 * (u >> 1) + 2 + (u & 1)] = ei;
        }
    }
#pragma unroll
    for (int r = 0; r < 5; r++)
        stsm4(sb + (2 * warp + ((lane >> 3) & 1)) * 1280 + (2 * r + (lane >> 4)) * 128 + (lane & 7) * 16, pack2(acc[8 * r], acc[8 * r + 1]),
              pack2(acc[8 * r + 2], acc[8 * r + 3]), pack2(acc[8 * r + 4], acc[8 * r + 5]), pack2(acc[8 * r + 6], acc[8 * r + 7]));
    fence_async();
    __syncthreads();
    const u64 db = mkdesc(sb, 1280, 128);
    wg_fence();
    wgmma_n80_rs<0, 1>(acc, f[0], db);
#pragma unroll
    for (int ks = 1; ks < 8; ks++) wgmma_n80_rs<1, 1>(acc, f[ks], db + ks * 160);
    wg_commit();
    wg_wait<0>();
#pragma unroll
    for (int u = 0; u < 4; u++) {
        float e[10];
#pragma unroll
        for (int r = 0; r < 5; r++) { e[r] = acc[8 * r + 4 * (u >> 1) + (u & 1)]; e[5 + r] = acc[8 * r + 4 * (u >> 1) + 2 + (u & 1)]; }
#pragma unroll
        for (int i = 0; i < 5; i++) sts32(sy + (4 * q + u) * 1296 + k2 * 20 + i * 4, pack2(e[2 * i], e[2 * i + 1]));
    }
    __syncthreads();
    const int rho = tid >> 4, j = tid & 15, row = blk * 16 + rho;
    float v[40];
#pragma unroll
    for (int i = 0; i < 5; i++) {
        uint32_t y[4];
        float a[8], b[8];
        lds128(y, sy + rho * 1296 + j * 80 + i * 16);
        unpack8(a, xr[i]); unpack8(b, make_uint4(y[0], y[1], y[2], y[3]));
        const uint4 o = make_uint4(pack2(a[0] + b[0], a[1] + b[1]), pack2(a[2] + b[2], a[3] + b[3]), pack2(a[4] + b[4], a[5] + b[5]), pack2(a[6] + b[6], a[7] + b[7]));
        *(uint4*)(out + (size_t)row * D_ + j * 40 + i * 8) = o;
        unpack8(v + 8 * i, o);
    }
    if (!last) {
        ln40(v);
#pragma unroll
        for (int i = 0; i < 5; i++)
            *(uint4*)(g_xn + xn_off(row, j * 5 + i)) =
                make_uint4(pack2(v[8 * i], v[8 * i + 1]), pack2(v[8 * i + 2], v[8 * i + 3]), pack2(v[8 * i + 4], v[8 * i + 5]), pack2(v[8 * i + 6], v[8 * i + 7]));
    }
    TLE(6 + 5 * last);
}

namespace rec {
#define NSA 5
#define NSB 2
#define REG0 184
#define REG1 184
constexpr int NS = NSA, NS0 = NSB;
constexpr int OFF_X = 0;
constexpr int OFF_WO = 81920;
constexpr int OFF_WS = OFF_WO + 57344;
constexpr int OFF_MEMB = OFF_WS + (NS + NS0) * 2048;
constexpr int OFF_VX = OFF_MEMB + 10240;
constexpr int OFF_VM = OFF_VX + 16384;
constexpr int OFF_Q = OFF_VM + 4096;
constexpr int OFF_K = OFF_Q + 10240;
constexpr int OFF_PX = OFF_K + 10240;
constexpr int OFF_OST = OFF_PX + 2560;
constexpr int OFF_PT = OFF_OST + 4096;
constexpr int OFF_PS = OFF_PT + 1536;
constexpr int OFF_OB = OFF_PS + 1280;
constexpr int OFF_MX = OFF_OB + 2048;
constexpr int OFF_BAR = OFF_MX + 64;
constexpr int OFF_PROF = OFF_BAR + 256;
constexpr int SMEM = OFF_PROF + 4096 > wk::SMEM ? OFF_PROF + 4096 : wk::SMEM;
enum { B_XT = 0, B_KX = 2, B_VX = 4, B_XD = 6, B_X1 = 8, B_WN = 10, B_PXF = 12, B_PXE = 13, B_FIN = 14, B_ST = 15 };
enum { NB_QK = 2, NB_WIN = 3, NB_ATT = 4, NB_X = 5, NB_PRO = 6, NB_W1 = 7, NB_MEM = 8  , NB_LD = 13   };
#define NOX 0
#define NW1 10
#define NW1B 8
constexpr int RING = 8;
template <int N> struct IC { static constexpr int value = N; };
template <int N, int I = 0, class F> DEV void static_for(F&& f) { if constexpr (I < N) { f(IC<I>{}); static_for<N, I + 1>(f); } }
constexpr float SM_SCALE = 0.08838834764831845f * 1.4426950408889634f;
}

__global__ void __launch_bounds__(512, 1) rec_kernel(const __grid_constant__ Maps maps, const bf16* __restrict__ x, bf16* __restrict__ x1, const bf16* __restrict__ mem0, const bf16* __restrict__ Wq, const bf16* __restrict__ Wk,
                                                     const bf16* __restrict__ Wv, const bf16* __restrict__ Wo, int layer, int delay, int delay2) {
    using namespace rec;
    extern __shared__ __align__(1024) unsigned char smem[];
    const uint32_t sb = s2u(smem);
    if (blockIdx.x >= 3 * H_) {
        pdl_wait();
        pdl_launch();
        worker(sb, maps, x, x1, layer);
        return;
    }
    const int tid = threadIdx.x, lane = tid & 31, warp = __shfl_sync(~0u, tid >> 5, 0);
    const int g = lane >> 2, q = lane & 3;
    const int h = blockIdx.x / 3;
    const uint32_t bar = sb + OFF_BAR;
    STAMP(2 * layer);
    TLS(2 + 5 * layer);
    if (tid == 0) {
        for (int i = 0; i < 2; i++) {
            mbar_init(bar + 8 * (B_XT + i), 1); mbar_init(bar + 8 * (B_KX + i), 4); mbar_init(bar + 8 * (B_VX + i), 1);
            mbar_init(bar + 8 * (B_XD + i), 8); mbar_init(bar + 8 * (B_X1 + i), 1); mbar_init(bar + 8 * (B_WN + i), 4);
        }
        mbar_init(bar + 8 * B_PXF, 1); mbar_init(bar + 8 * B_PXE, 2); mbar_init(bar + 8 * B_ST, 2);
        mbar_init(bar + 8 * B_FIN, 48);
        sts32(sb + OFF_MX + 32, 0); sts32(sb + OFF_MX + 36, 0);
        asm volatile("fence.mbarrier_init.release.cluster;" ::: "memory");
    }
    asm volatile("barrier.cluster.arrive.aligned; barrier.cluster.wait.aligned;" ::: "memory");
    const bool never = delay < 0;

    if (warp < 8) {
        auto role = [&](auto XP) {
            constexpr int wg = XP.value, NSW = wg ? NS : NS0;
            asm volatile("setmaxnreg.inc.sync.aligned.u32 %0;" ::"n"(wg ? REG1 : REG0));
            const uint32_t rank = cta_rank();
            uint32_t a[40 - NSW][4];
            const uint32_t l16 = opaque(sb + lane * 16);
            uint32_t wsa = wg ? opaque(sb + OFF_WS + (warp & 3) * 512 + (lane & 7) * 16 + ((lane >> 3) & 1) * 256 + (lane >> 4) * 128) : 0;
            uint32_t dst = opaque(rank < 2 ? sb + OFF_Q + wg * 10240 + (warp & 3) * 256 + (lane & 15) * 16 + (lane >> 4) * 1024
                                           : sb + OFF_VM + warp * 256 + lane * 4);
            int dstep = rank < 2 ? 5120 : 2048;
            uint32_t& sfd = wg ? wsa : dst;
            auto ws_addr = [&](int ks) { return wg ? wsa + ks * 2048 : l16 + OFF_WS + (NS + ks) * 2048 + warp * 512; };
            {
                const int t = tid & 127;
                const bf16* src = (rank == 2 ? Wv + wg * 64 : (wg ? Wk : Wq) + rank * 64) + h * E_ + (size_t)(t >> 3) * 4096 + (t & 7) * 8;
                const uint32_t stg = sb + (wg ? OFF_VX : OFF_X + 40960);
                const uint32_t sdst = stg + (t >> 3) * 128 + (((t & 7) ^ ((t >> 3) & 7)) << 4);
                const uint32_t ra = stg + ((lane >> 4) * 8 + (lane & 7)) * 128 + (((2 * (warp & 3) + ((lane >> 3) & 1)) ^ (lane & 7)) << 4);
                auto issue = [&](int rd) {
#pragma unroll
                    for (int i = 0; i < 10; i++) cp16(sdst + (rd & 1) * 20480 + i * 2048, src + (size_t)(rd * 160 + i * 16) * 4096);
                    cp_commit();
                };
                issue(0); issue(1);
                pdl_wait();
                pdl_launch();
#pragma unroll
                for (int rd = 0; rd < 4; rd++) {
                    if (rd < 3) cp_wait<1>(); else cp_wait<0>();
                    bar_sync(NB_LD + wg, 128);
#pragma unroll
                    for (int i = 0; i < 10; i++) {
                        const int ks = rd * 10 + i;
                        if (ks < NSW) {
                            uint32_t f[4];
                            ldsm4t(f, ra + i * 2048);
                            stsm4(ws_addr(ks), f[0], f[1], f[2], f[3]);
                        } else ldsm4t(a[ks - NSW], ra + (rd & 1) * 20480 + i * 2048);
                    }
                    if (rd < 2) { bar_sync(NB_LD + wg, 128); issue(rd + 2); }
                }
                fence_async();
                bar_sync(NB_PRO, 288);
            }
            float acc[16];
            uint32_t xlo = (uint32_t)mkdesc(sb + OFF_X, 0, 0);
            const uint32_t xtog = xlo ^ (uint32_t)mkdesc(sb + OFF_X + 40960, 0, 0);
            uint32_t p8 = 0;
            auto xproj = [&](auto K1, auto K0) {
                const u64 desc = (u64)xlo | (64ull << 32) | SW128, da = mkdesc(sb + OFF_WS, 128, 256);
                wg_fence();
#pragma unroll
                for (int ks = K1.value - 1; ks >= K0.value; ks--) {
                    const u64 db = desc + (ks >> 2) * 256 + (ks & 3) * 2;
                    if (ks == 39) wgmma_n32_rs<0>(acc, a[ks - NSW], db);
                    else if (NOX) {}
                    else if (ks < NSW) wgmma_n32_ss<1>(acc, da + ks * 128, db);
                    else wgmma_n32_rs<1>(acc, a[ks - NSW], db);
                }
                wg_commit();
            };
            auto xstore = [&]() {
                wg_wait<0>();
                uint32_t pk[8];
#pragma unroll
                for (int i = 0; i < 8; i++) pk[i] = pack2(acc[2 * i], acc[2 * i + 1]);
                if (rank < 2) {
                    stsm4t(dst + 1024, pk[0], pk[1], pk[2], pk[3]);
                    stsm4t(dst + 3072, pk[4], pk[5], pk[6], pk[7]);
                } else {
                    const uint32_t la = wsa + (wsa & 256) + (OFF_VX + 4096 - OFF_WS) + (warp & 3) * 512 + p8 * 1024;
                    stsm4(la, pk[0], pk[1], pk[2], pk[3]);
                    stsm4(la + 256, pk[4], pk[5], pk[6], pk[7]);
                    fence_async();
                }
                mbar_arrive_elect(bar + 8 * B_KX + p8);
            };
            bar_sync(NB_LD, 288);
            if (wg) {
                xproj(IC<40>{}, IC<0>{});
                xstore();
            }
            for (int s = 0;; s++) {
                float d0[4] = {0.f, 0.f, 0.f, 0.f}, d1[4] = {0.f, 0.f, 0.f, 0.f};
                uint32_t t[NSW][4], b[20][4];
#pragma unroll
                for (int ks = 0; ks < NSW; ks++) ldsm4(t[ks], ws_addr(ks));
                bar_sync(NB_MEM, 384);
                lds128(b[0], l16 + OFF_MEMB); lds128(b[1], l16 + OFF_MEMB + 512); lds128(b[2], l16 + OFF_MEMB + 1024);
                xlo ^= xtog;
                const uint32_t xb0 = mapa(bar + 8 * B_X1 + p8, 0), xb1 = mapa(bar + 8 * B_X1 + p8, 1);
                SFENCE();
                float is;
#pragma unroll
                for (int kp = 0; kp < 20; kp++) {
#pragma unroll
                    for (int j = 0; j < 2; j++) {
                        const int ks = 2 * kp + j;
                        const uint32_t* f = ks < NSW ? t[ks] : a[ks - NSW];
                        mma16(j ? d1 : d0, f[0], f[1], f[2], f[3], b[kp][2 * j], b[kp][2 * j + 1]);
                    }
                    if (kp == 0 && warp == 4) PROFT(0);
                    if (kp < 16 && (kp & 3) == 1) bar_sync(NB_MEM + 1 + (kp >> 2), 384);
                    if (kp + 3 < 20) lds128(b[kp + 3], l16 + OFF_MEMB + (kp + 3) * 512);
                    if (kp == 17) is = lds32f(sb + OFF_MX + 16);
                    if (kp < 18) SFENCE();
                }
                const uint32_t p0 = pack2((d0[0] + d1[0]) * is, (d0[1] + d1[1]) * is), p1 = pack2((d0[2] + d1[2]) * is, (d0[3] + d1[3]) * is);
                if (rank < 2) {
                    stsm2t(dst, p0, p1);
                } else {
                    st_async1(mapa(dst, 0), p0, xb0); st_async1(mapa(dst, 1), p0, xb1);
                    st_async1(mapa(dst + 128, 0), p1, xb0); st_async1(mapa(dst + 128, 1), p1, xb1);
                    sts32(dst, p0); sts32(dst + 128, p1);
                }
                bar_arrive(NB_QK, 384);
                if (warp == 4) PROFT(1);
                dst += dstep; dstep = -dstep; p8 ^= 8;
                if (wg) {
                    if (rank < 2) bar_sync(NB_W1, 384); else bar_sync(NB_W1, 352);
                    if (s == NSEG - 1) break;
                    xproj(IC<40>{}, IC<40 - NW1>{});
                    wg_wait<0>();
                    if (warp == 4) PROFT(15);
                    if (NW1B > 0) {
                        if (rank < 2) bar_sync(NB_WIN, 256);
                        xproj(IC<40 - NW1>{}, IC<40 - NW1 - NW1B>{});
                        wg_wait<0>();
                        if (rank == 2) bar_sync(NB_WIN, 256);
                    } else bar_sync(NB_WIN, 256);
                    xproj(IC<40 - NW1 - NW1B>{}, IC<0>{});
                    xstore();
                    if (warp == 4) PROFT(3);
                } else if (s == NSEG - 1) break;
            }
        };
        if (warp < 4) role(IC<0>{}); else role(IC<1>{});
    } else if (warp < 12) {
        asm volatile("setmaxnreg.dec.sync.aligned.u32 96;");
        const uint32_t rank = cta_rank();
        const int w = warp - 8;
        const bool four = w == 0 || (w == 1 && rank == 0);
        const int tile3 = rank == 0 ? 36 + w : 37 + rank;
        uint32_t amax = 0;
#pragma unroll
        for (int it = 0; it < 5; it++) {
            const int kp = it * 4 + w;
            const bf16* p = mem0 + g * D_ + kp * 32 + 2 * q;
            uint32_t b0 = ldg32(p), b1 = ldg32(p + 8), b2 = ldg32(p + 16), b3 = ldg32(p + 24);
            sts128(sb + OFF_MEMB + kp * 512 + lane * 16, b0, b1, b2, b3);
            amax = absmax2(amax, absmax2(absmax2(b0, b1), absmax2(b2, b3)));
        }
        if (tid == 256) sts32(sb + OFF_MX + 16, 0x3f800000u);
        bar_arrive(NB_MEM, 384); bar_arrive(NB_MEM + 1, 384); bar_arrive(NB_MEM + 2, 384); bar_arrive(NB_MEM + 3, 384); bar_arrive(NB_MEM + 4, 384);
        {
            const int t = tid & 127;
#pragma unroll
            for (int r = 0; r < 4; r++) {
                const int col = r < 3 ? 192 * r + 64 * rank : (rank ? 592 + 16 * rank : 576);
                const bf16* src = Wo + (size_t)(h * E_) * D_ + col;
                if (r < 3) {
#pragma unroll
                    for (int i = 0; i < 8; i++) {
                        const int e = i * 16 + (t >> 3);
                        cp16(sb + OFF_WO + r * 16384 + e * 128 + (((t & 7) ^ (e & 6)) << 4), src + e * D_ + (t & 7) * 8);
                    }
                } else {
#pragma unroll
                    for (int i = 0; i < 4; i++) {
                        const int e = i * 32 + (t >> 2);
                        if (rank == 0 || (t & 2) == 0) cp16(sb + OFF_WO + r * 16384 + e * 64 + (t & 3) * 16, src + e * D_ + (t & 3) * 8);
                    }
                }
            }
            cp_commit();
            pdl_wait();
            pdl_launch();
            cp_wait<0>();
            bar_sync(NB_ATT, 128);
#pragma unroll 1
            for (int r = 0; r < 4; r++) {
                uint32_t u[8][4];
                const uint32_t rs = r < 3 ? 128 : 64;
                const uint32_t p = sb + OFF_WO + r * 16384 + 2 * q * rs + (((2 * w + (g & 1)) ^ (r < 3 ? 2 * q : 0)) << 4) + (g >> 1) * 4;
                if (r < 3 || four) {
#pragma unroll
                    for (int ks = 0; ks < 8; ks++)
#pragma unroll
                        for (int j = 0; j < 4; j++) u[ks][j] = lds32(p + (16 * ks + (j & 1) * 8 + (j >> 1)) * rs);
                }
                bar_sync(NB_ATT, 128);
                if (r < 3 || four) {
#pragma unroll
                    for (int ks = 0; ks < 8; ks++)
                        sts128(sb + OFF_WO + (r * 4 + w) * 4096 + ks * 512 + lane * 16, prmt(u[ks][0], u[ks][2], 0x5410), prmt(u[ks][0], u[ks][2], 0x7632),
                               prmt(u[ks][1], u[ks][3], 0x5410), prmt(u[ks][1], u[ks][3], 0x7632));
                }
            }
        }
        float cw;
        {
            const float4 a = ((const float4*)g_nrm)[lane], c = ((const float4*)g_nrm)[32 + lane];
            float sm = sqrtf((a.x + a.y) + (a.z + a.w)) * sqrtf((c.x + c.y) + (c.z + c.w)), mxv = sm;
#pragma unroll
            for (int o = 16; o; o >>= 1) { sm += __shfl_xor_sync(~0u, sm, o); mxv = fmaxf(mxv, __shfl_xor_sync(~0u, mxv, o)); }
            cw = 26.5f * fmaxf(sm, 8.f * mxv);
        }
        const uint32_t l16 = opaque(sb + lane * 16), l4 = opaque(sb + OFF_PS + rank * 512 + lane * 4);
        uint32_t lq = opaque(sb + OFF_Q + (lane & 7) * 16 + ((lane >> 3) & 1) * 256 + (lane >> 4) * 128);
        const uint32_t lv = opaque(sb + OFF_VX + w * 2048 + (lane & 7) * 16 + ((lane >> 3) & 1) * 512 + (lane >> 4) * 128);
        uint32_t& sfd = lq;
        const bool t0 = tid == 256;
        const char* rp = (const char*)(g_acc + layer * ACC_LAYER) + (4 * rank + w) * 4096 + opaque((q >> 1) * 1024 + ((q & 1) * 8 + g) * 8);
        const char* lp = (const char*)(g_acc + layer * ACC_LAYER) + opaque(w * 8192 + (2 * (g & 1) + (g >> 2)) * 1024 + (((g >> 1) & 1) * 8 + 2 * q) * 8);
        const int t3off = (tile3 - 4 * rank - w) * 4096;
        float isig = 1.f;
        if (t0) {
            mbar_expect(bar + 8 * B_X1, rank < 2 ? 3328 : 1280);
            mbar_expect(bar + 8 * B_VX, rank < 2 ? 8192 : 4096);
        }
        for (int s = 0; s < NSEG - 1; s++) {
            const int pb = s & 1;
            const uint32_t x1 = bar + 8 * (B_X1 + pb);
            sts32(sb + OFF_MX + w * 4, __reduce_max_sync(~0u, max(amax & 0x7fff0000u, (amax << 16) & 0x7fff0000u)));
            if (rank < 2) {
                uint32_t kf[8], qf[8];
                const uint32_t ka = l16 + OFF_K + pb * 5120, qa = lq + pb * 5120;
                mbar_wait(bar + 8 * (B_KX + pb), (s >> 1) & 1);
                ldsm4(kf, ka + (1 + w) * 1024); ldsm4(kf + 4, ka + (1 + w) * 1024 + 512);
                const uint32_t pa = l4 + w * 128;
                const uint32_t pa0 = mapa(pa, rank ^ 1), pa1 = mapa(pa, 2), pa2 = mapa(pa, rank);
                const uint32_t xb0 = mapa(x1, rank ^ 1), xb1 = mapa(x1, 2), xb2 = mapa(x1, rank);
                bar_sync(NB_QK, 384);
                ldsm4(qf, qa); ldsm4(qf + 4, qa + 512);
                float c0[4] = {0.f, 0.f, 0.f, 0.f}, c1[4] = {0.f, 0.f, 0.f, 0.f}, c2[4] = {0.f, 0.f, 0.f, 0.f}, c3[4] = {0.f, 0.f, 0.f, 0.f};
                if (w == 3) {
                    uint32_t mf[8];
                    ldsm4(mf, ka); ldsm4(mf + 4, ka + 512);
                    mma16(c0, qf[0], qf[1], qf[2], qf[3], kf[0], kf[1]); mma16(c1, qf[0], qf[1], qf[2], qf[3], kf[2], kf[3]);
                    mma16(c2, qf[0], qf[1], qf[2], qf[3], mf[0], mf[1]); mma16(c3, qf[0], qf[1], qf[2], qf[3], mf[2], mf[3]);
                    mma16(c0, qf[4], qf[5], qf[6], qf[7], kf[4], kf[5]); mma16(c1, qf[4], qf[5], qf[6], qf[7], kf[6], kf[7]);
                    mma16(c2, qf[4], qf[5], qf[6], qf[7], mf[4], mf[5]); mma16(c3, qf[4], qf[5], qf[6], qf[7], mf[6], mf[7]);
                    bar_arrive(NB_W1, 384);
                    const uint32_t y = pack2(c0[0] + c1[2], c0[1] + c1[3]), z = pack2(c2[0] + c3[2], c2[1] + c3[3]);
                    const uint32_t pm = l4 + 1024 - rank * 384;
                    st_async1(pa0, y, xb0); st_async1(pa1, y, xb1);
                    st_async1(mapa(pm, rank ^ 1), z, xb0); st_async1(mapa(pm, 2), z, xb1);
                    st_async1(pa2, y, xb2); st_async1(mapa(pm, rank), z, xb2);
                } else {
                    mma16(c0, qf[0], qf[1], qf[2], qf[3], kf[0], kf[1]); mma16(c1, qf[0], qf[1], qf[2], qf[3], kf[2], kf[3]);
                    mma16(c2, qf[4], qf[5], qf[6], qf[7], kf[4], kf[5]); mma16(c3, qf[4], qf[5], qf[6], qf[7], kf[6], kf[7]);
                    bar_arrive(NB_W1, 384);
                    const uint32_t y = pack2((c0[0] + c1[2]) + (c2[0] + c3[2]), (c0[1] + c1[3]) + (c2[1] + c3[3]));
                    st_async1(pa0, y, xb0); st_async1(pa1, y, xb1); st_async1(pa2, y, xb2);
                }
                if (w == 0) PROFT(4);
            } else {
                bar_sync(NB_QK, 384);
                bar_arrive(NB_W1, 352);
            }
            mbar_wait(bar + 8 * (B_VX + pb), (s >> 1) & 1);
            float m4[4];
            lds128f(m4, sb + OFF_MX);
            uint32_t wf[RING][4], vf[2][2][4], vm[4];
#pragma unroll
            for (int t = 0; t < 2; t++)
#pragma unroll
                for (int j = 0; j < 2; j++) ldsm4(vf[t][j], lv + pb * 8192 + t * 1024 + j * 256);
            float sig;
            {
                const float bound = cw * fmaxf(fmaxf(fmaxf(m4[0], m4[1]), fmaxf(m4[2], m4[3])) * isig, 1.f);
                const uint32_t e = max((__float_as_uint(bound) >> 23) & 255u, 31u);
                sig = __uint_as_float((278u - e) << 23);
                isig = __uint_as_float((e - 30u) << 23);
            }
            if (t0) sts32(sb + OFF_MX + 16, __float_as_uint(isig));
            const uint32_t vma = l16 + OFF_VM + pb * 2048 + w * 512;
            if (w == 0) PROFT(5);
            mbar_wait(x1, (s >> 1) & 1);
            if (w == 0) PROFT(6);
            float sc[10];
            {
                uint32_t u[4], v[4], m[2];
                ldsm4(u, l16 + OFF_PS); ldsm4(v, l16 + OFF_PS + 512); ldsm2(m, l16 + OFF_PS + 1024);
                ldsm4(vm, vma);
                SFENCE();
#pragma unroll
                for (int i = 0; i < 4; i++) { sc[2 * i] = bf_lo(u[i]) + bf_lo(v[i]); sc[2 * i + 1] = bf_hi(u[i]) + bf_hi(v[i]); }
                sc[8] = bf_lo(m[0]) + bf_lo(m[1]); sc[9] = bf_hi(m[0]) + bf_hi(m[1]);
            }
            float mx = fmaxf(fmaxf(fmaxf(fmaxf(sc[0], sc[1]), fmaxf(sc[2], sc[3])), fmaxf(fmaxf(sc[4], sc[5]), fmaxf(sc[6], sc[7]))), fmaxf(sc[8], sc[9]));
            {
                float m1 = __shfl_xor_sync(~0u, mx, 1), m2 = __shfl_xor_sync(~0u, mx, 2), m3 = __shfl_xor_sync(~0u, mx, 3);
                SFENCE();
                mx = fmaxf(fmaxf(mx, m1), fmaxf(m2, m3)) * SM_SCALE;
            }
            auto fetch = [&](int i) { lds128(wf[i % RING], l16 + OFF_WO + ((i >> 3) * 4 + w) * 4096 + (i & 7) * 512); };
            float o0[4] = {0.f, 0.f, 0.f, 0.f}, o1[4] = {0.f, 0.f, 0.f, 0.f}, rs[4] = {0.f, 0.f, 0.f, 0.f};
            constexpr uint32_t ONE = 0x3f803f80u;
            sc[8] = ex2(fmaf(sc[8], SM_SCALE, -mx)); sc[9] = ex2(fmaf(sc[9], SM_SCALE, -mx));
#pragma unroll
            for (int i = 0; i < 4; i++) sc[i] = ex2(fmaf(sc[i], SM_SCALE, -mx));
#pragma unroll
            for (int i = 0; i < RING; i++) fetch(i);
            SFENCE();
            {
                const uint32_t p = pack2(sc[8], sc[9]);
                mma8(o0, vm[0], vm[1], p);
                mma8(o1, vm[2], vm[3], p);
                mma8(rs, ONE, ONE, p);
            }
#pragma unroll
            for (int i = 4; i < 8; i++) sc[i] = ex2(fmaf(sc[i], SM_SCALE, -mx));
            SFENCE();
#pragma unroll
            for (int j = 0; j < 2; j++) {
                const uint32_t p0 = pack2(sc[4 * j], sc[4 * j + 1]), p1 = pack2(sc[4 * j + 2], sc[4 * j + 3]);
                mma16(o0, vf[0][j][0], vf[0][j][1], vf[0][j][2], vf[0][j][3], p0, p1);
                mma16(o1, vf[1][j][0], vf[1][j][1], vf[1][j][2], vf[1][j][3], p0, p1);
                mma16(rs, ONE, ONE, ONE, ONE, p0, p1);
                SFENCE();
            }
            stsm4t(l16 + OFF_OB + w * 512, pack2(o0[0], o0[1]), pack2(o0[2], o0[3]), pack2(o1[0], o1[1]), pack2(o1[2], o1[3]));
            bar_sync(NB_ATT, 128);
            uint32_t ob[16];
#pragma unroll
            for (int j = 0; j < 4; j++) ldsm4(ob + 4 * j, l16 + OFF_OB + j * 512);
            SFENCE();
            const float sg0 = rcp(rs[0]) * sig, sg1 = rcp(rs[1]) * sig;
            SFENCE();
            uint32_t tr;
            auto tiles = [&](auto NT) {
#pragma unroll
                for (int r = 0; r < NT.value; r++) {
                    float c[4][4];
#pragma unroll
                    for (int i = 0; i < 4; i++) c[i][0] = c[i][1] = c[i][2] = c[i][3] = 0.f;
#pragma unroll
                    for (int ks = 0; ks < 8; ks++) {
                        const uint32_t* f = wf[(8 * r + ks) % RING];
                        mma16(c[ks & 3], f[0], f[1], f[2], f[3], ob[2 * ks], ob[2 * ks + 1]);
                        if ((ks & 3) == 3) {
                            SFENCE();
#pragma unroll
                            for (int i = 8 * r + ks - 3 + RING; i <= 8 * r + ks + RING; i++) if (i < 8 * NT.value) fetch(i);
                        }
                    }
                    SFENCE();
                    uint32_t v[4];
#pragma unroll
                    for (int i = 0; i < 4; i++)
                        v[i] = (__float_as_uint(fmaf((c[0][i] + c[1][i]) + (c[2][i] + c[3][i]), i & 1 ? sg1 : sg0, 12582912.f)) << 6) + (i < 2);
                    const char* p = r < 3 ? rp + r * 49152 : rp + t3off;
                    red_add64((u64*)p, v[0], v[2]);
                    red_add64((u64*)(p + 2048), v[1], v[3]);
                    if (r == 0) {
                        tr = clk();
                        if (w == 0) PROFT(7);
                        if (w == 0) GPROF(4, 0);
                    }
                }
            };
            if (four) tiles(IC<4>{}); else tiles(IC<3>{});
            bar_arrive(NB_WIN, 256);
            mbar_arrive_elect(bar + 8 * (B_WN + pb));
            if (w == 0) PROFT(8);
            if (t0) {
                if (rank < 2 || s < NSEG - 2) mbar_expect(bar + 8 * (B_VX + (pb ^ 1)), rank < 2 ? 8192 : 4096);
                mbar_expect(bar + 8 * (B_X1 + (pb ^ 1)), (rank < 2 ? 2048 : 0) + (s < NSEG - 2 ? 1280 : 0));
            }
            u64 y[20];
            while (clk() - tr < (uint32_t)delay) {}
#pragma unroll
            for (int i = 0; i < 10; i++) ld_acc0(y[2 * i], y[2 * i + 1], lp + (i >> 1) * 32768 + (i & 1) * 4096);
            if (w == 0) PROFT(9);
            uint32_t nretry = 0, b[20];
            bool done[5] = {false, false, false, false, false};
            auto publish = [&](auto FIRST) {
                uint32_t ok = 32u, late = 32u;
                static_for<5>([&](auto IT) {
                    constexpr int it = IT.value;
                    if (it == 2) late = and3((uint32_t)y[8], (uint32_t)y[10], (uint32_t)y[12]);
                    else if (it == 3) late &= and3((uint32_t)y[14], (uint32_t)y[16], (uint32_t)y[18]);
                    else ok = and3(ok, (uint32_t)y[4 * it], it == 4 ? late : (uint32_t)y[4 * it + 2]);
                    if (FIRST.value && it < 4) SFENCE();
                    if (it == 2 || it == 3) ok = and3(ok, (uint32_t)y[4 * it], (uint32_t)y[4 * it + 2]);
                    ok = and3(ok, (uint32_t)y[4 * it + 1], (uint32_t)y[4 * it + 3]);
                    const bool all = __all_sync(~0u, ok);
#pragma unroll
                    for (int j = 0; j < 4; j++) {
                        const u64 z = y[4 * it + j];
                        b[4 * it + j] = pack2((float)(int)(uint32_t)z, (float)(int)(uint32_t)(z >> 32));
                    }
                    sts128(l16 + OFF_MEMB + (4 * it + w) * 512, b[4 * it], b[4 * it + 1], b[4 * it + 2], b[4 * it + 3]);
                    bar_arrive_if<NB_MEM + it, 384>(all && (FIRST.value || !done[it]));
                    done[it] = all;
                    if (FIRST.value) SFENCE();
                    if (FIRST.value && it == 0 && w == 0) PROFT(10);
                });
            };
            publish(IC<1>{});
            while (!done[4]) {
                if (++nretry > SPIN_LIMIT) die();
#pragma unroll
                for (int i = 0; i < 10; i++) ld_acc(y[2 * i], y[2 * i + 1], lp + (i >> 1) * 32768 + (i & 1) * 4096);
                publish(IC<0>{});
            }
            if (w == 0) PROFT(11);
            amax = b[0];
#pragma unroll
            for (int i = 1; i < 19; i += 2) amax = absmax2(amax, absmax2(b[i], b[i + 1]));
            amax = absmax2(amax, b[19]);
            GPROF(w, nretry);
            const int adv = (s & 7) == 7 ? 163840 - 896 : 128;
            rp += adv; lp += adv;
        }
        bar_sync(NB_QK, 384);
        if (rank < 2) bar_arrive(NB_W1, 384); else bar_arrive(NB_W1, 352);
    } else {
        asm volatile("setmaxnreg.dec.sync.aligned.u32 48;");
        const uint32_t rank = cta_rank();
        const int w = warp - 12;
        const bool t0 = tid == 384;
        pdl_wait();
        pdl_launch();
        uint32_t* sy = g_sync + layer * SYNC_LAYER;
        int pblk = 0;
        auto loads = [&](int s) {
            const int n = s + 1, pb = s & 1;
            const uint32_t xt = bar + 8 * (B_XT + pb);
            mbar_expect(xt, (n + 1 < NSEG ? 40960 : 0) + (rank < 2 ? 4096 : 0));
            if (n + 1 < NSEG) bulk_g2s(sb + OFF_X + pb * 40960, g_xn + (n + 1) * 40960, 40960, xt);
            if (n == wk::pb_start(pblk)) { flag_wait(sy + wk::SY_P + pblk * H_ + h, 3); pblk++; }
            const unsigned char* src = g_p + (size_t)(n * H_ + h) * 12288;
            if (rank < 2) bulk_g2s(sb + OFF_Q + (pb ^ 1) * 5120 + 1024, src + rank * 4096, 4096, xt);
            if (rank < 2 || n < NSEG - 1) bulk_g2s(sb + OFF_VX + (pb ^ 1) * 8192, src + 8192, 4096, bar + 8 * (B_VX + (pb ^ 1)));
        };
        const int wl = rank == 0 ? 2 : rank == 1 ? 0 : 1;
        if (w == wl) {
            if (lane == 0) {
                mbar_expect(bar + 8 * B_XT, 40960);
                bulk_g2s(sb + OFF_X, g_xn, 40960, bar + 8 * B_XT);
            }
            __syncwarp();
            bar_sync(NB_PRO, 288);
            if (rank == 2) mbar_wait(bar + 8 * B_ST, 0);
            else if (lane == 0) mbar_arrive_remote(mapa(bar + 8 * B_ST, 2));
            mbar_wait(bar + 8 * B_XT, 0);
            __syncwarp();
            bar_arrive(NB_LD, 288);
            if (lane == 0) loads(-1);
            __syncwarp();
        }
        if (rank == 2 && w == 3) {
            if (lane == 0) {
                for (uint32_t s = 0, n = 0; s < NSEG; s++) {
                    uint32_t c[2];
                    for (;;) {
                        asm volatile("ld.acquire.cluster.shared::cta.v2.u32 {%0,%1},[%2];" : "=r"(c[0]), "=r"(c[1]) : "r"(sb + OFF_MX + 32) : "memory");
                        if (min(c[0], c[1]) > s) break;
                        if (++n > (SPIN_LIMIT << 3)) die();
                        __nanosleep(s < NSEG - 2 ? 400 : 50);
                    }
                    flag_add(sy + wk::SY_O + s);
                }
            }
        } else if (rank == 2) {
            const char* pf = (const char*)(g_acc + layer * ACC_LAYER) + (5 * h + lane % 5) * 1024;
            if (w == 2 && lane < 20) prefetch_l2(pf + lane / 5 * 128);
            for (int s = 0; s < NSEG; s++) {
                const int pb = s & 1, ph = (s >> 1) & 1;
                if (w == 0) {
                    mbar_wait(bar + 8 * (B_KX + pb), ph);
                    if (lane < 2) bulk_s2s(mapa(sb + OFF_VX + pb * 8192 + 4096, lane), sb + OFF_VX + pb * 8192 + 4096, 4096, mapa(bar + 8 * (B_VX + pb), lane));
                }
                if (w == 1) mbar_wait(bar + 8 * (B_XT + (pb ^ 1)), ((s + 1) >> 1) & 1);
                if (w == 2 && s >= 1) mbar_wait(bar + 8 * (B_XD + (pb ^ 1)), ((s - 1) >> 1) & 1);
                __syncwarp();
                bar_sync(NB_W1, 352);
                if (w == 2 && lane < 5 && s + 4 < NSEG) prefetch_l2(pf + ((s + 4) >> 3) * 163840 + ((s + 4) & 7) * 128);
                if (w == 1 && s + 1 < NSEG) {
                    mbar_wait(bar + 8 * (B_X1 + pb), ph);
                    const uint32_t tw = clk();
                    while (clk() - tw < (uint32_t)delay2) {}
                    if (lane == 0) loads(s);
                }
            }
        } else {
            if (w < 2) sts32(sb + OFF_PT + w * 768 + 640 + lane * 4, 0u);
            for (int s = 0; s < NSEG; s++) {
                const int pb = s & 1, ph = (s >> 1) & 1;
                if (t0) {
                    mbar_expect(bar + 8 * B_PXF, rank ? 2560 : 1536);
                    asm volatile("cp.async.bulk.wait_group.read 0;" ::: "memory");
                }
                if (w == 1) mbar_wait(bar + 8 * (B_XT + (pb ^ 1)), ((s + 1) >> 1) & 1);
                __syncwarp();
                bar_sync(NB_W1, 384);
                fence_async();
                float c[20];
                {
                    const u64 dq = mkdesc(sb + OFF_Q + pb * 5120 + 1024, 128, 512), dk = mkdesc(sb + OFF_K + pb * 5120, 128, 1024);
                    wg_fence();
                    wgmma_n40_ss<0>(c, dq, dk);
#pragma unroll
                    for (int ks = 1; ks < 4; ks++) wgmma_n40_ss<1>(c, dq + ks * 16, dk + ks * 16);
                    wg_commit();
                    wg_wait<0>();
                }
                mbar_wait(bar + 8 * (B_X1 + pb), ph);
                if ((w >> 1) != rank) {
                    if (s >= 1) mbar_wait(bar + 8 * B_PXE, pb ^ 1);
                    const uint32_t pa = mapa(sb + OFF_PX + (w & 1) * 1280 + lane * 8, rank ^ 1), pf = mapa(bar + 8 * B_PXF, rank ^ 1);
#pragma unroll
                    for (int nt = 0; nt < 5; nt++)
                        if (nt < 3 || rank == 0) st_async2(pa + nt * 256, __float_as_uint(c[4 * nt]), __float_as_uint(c[4 * nt + 1]), pf);
                    if (w == wl && s + 1 < NSEG) {
                        const uint32_t tw = clk();
                        while (clk() - tw < (uint32_t)delay2) {}
                        if (lane == 0) loads(s);
                    }
                } else {
                    mbar_wait(bar + 8 * B_PXF, pb);
                    if (w == 0) PROFT(13);
                    const int tq = 8 * w + g;
                    float sc[10];
#pragma unroll
                    for (int nt = 0; nt < 5; nt++) {
                        float u0, u1;
                        lds64f(u0, u1, sb + OFF_PX + (w & 1) * 1280 + nt * 256 + lane * 8);
                        sc[2 * nt] = (8 * nt - 8 + 2 * q <= tq) ? (u0 + c[4 * nt]) * SM_SCALE : -INFINITY;
                        sc[2 * nt + 1] = (8 * nt - 7 + 2 * q <= tq) ? (u1 + c[4 * nt + 1]) * SM_SCALE : -INFINITY;
                    }
                    float mx = sc[0];
#pragma unroll
                    for (int i = 1; i < 10; i++) mx = fmaxf(mx, sc[i]);
                    mx = fmaxf(mx, __shfl_xor_sync(~0u, mx, 1));
                    mx = fmaxf(mx, __shfl_xor_sync(~0u, mx, 2));
                    if (lane == 0) mbar_arrive_remote(mapa(bar + 8 * B_PXE, rank ^ 1));
                    float sum = 0.f;
#pragma unroll
                    for (int i = 0; i < 10; i++) { sc[i] = ex2(sc[i] - mx); sum += sc[i]; }
                    sum += __shfl_xor_sync(~0u, sum, 1);
                    sum += __shfl_xor_sync(~0u, sum, 2);
                    sum = rcp(sum);
#pragma unroll
                    for (int nt = 0; nt < 5; nt++)
                        sts32(sb + OFF_PT + (w & 1) * 768 + (nt ? nt - 1 : 4) * 128 + lane * 4, pack2(sc[2 * nt] * sum, sc[2 * nt + 1] * sum));
                }
                mbar_wait(bar + 8 * (B_VX + pb), ph);
                fence_async();
                bar_sync(NB_X, 128);
                if (s < NSEG - 1) mbar_wait(bar + 8 * (B_WN + pb), ph);
                float acc[2][8];
                const u64 dv = mkdesc(sb + OFF_VX + pb * 8192, 128, 512), dp = mkdesc(sb + OFF_PT, 128, 768), dm = mkdesc(sb + OFF_VM + pb * 2048, 0, 128);
                wg_fence();
#pragma unroll
                for (int m = 0; m < 2; m++) {
                    wgmma_n16_ss<0>(acc[m], dv + m * 256, dp);
                    wgmma_n16_ss<1>(acc[m], dv + m * 256 + 16, dp + 16);
                    wgmma_n16_ss<1>(acc[m], dm + m * 64, dp + 32);
                }
                wg_commit();
                wg_wait<0>();
#pragma unroll
                for (int m = 0; m < 2; m++)
                    stsm4t(sb + OFF_OST + m * 2048 + (lane >> 4) * 1024 + w * 256 + (lane & 15) * 16, pack2(acc[m][0], acc[m][1]), pack2(acc[m][2], acc[m][3]),
                           pack2(acc[m][4], acc[m][5]), pack2(acc[m][6], acc[m][7]));
                fence_async();
                bar_sync(NB_X, 128);
                if (lane == 0) mbar_arrive_remote(mapa(bar + 8 * (B_XD + pb), 2));
                if (t0) {
                    unsigned char* op = g_o + (size_t)(s * H_ + h) * 8192 + rank * 2048;
                    bulk_s2g(op, sb + OFF_OST, 2048);
                    bulk_s2g(op + 4096, sb + OFF_OST + 2048, 2048);
                    bulk_commit();
                    bulk_wait<1>();
                    st_remote(mapa(sb + OFF_MX + 32 + 4 * rank, 2), s);
                }
                if (w == 0) PROFT(14);
            }
            if (t0) { bulk_wait<0>(); st_remote(mapa(sb + OFF_MX + 32 + 4 * rank, 2), NSEG); }
        }
    }
    __syncwarp();
    if (lane < 3) mbar_arrive_remote(mapa(bar + 8 * B_FIN, lane));
    mbar_wait(bar + 8 * B_FIN, 0);
    TLE(2 + 5 * layer);
}

int g_delay = 1050, g_layers = 2;

void make_map(CUtensorMap* m, CUtensorMapDataType dt, const void* p, const cuuint64_t* dim, const cuuint64_t* str, const cuuint32_t* box, CUtensorMapSwizzle sw) {
    typedef CUresult (*Fn)(CUtensorMap*, CUtensorMapDataType, cuuint32_t, void*, const cuuint64_t*, const cuuint64_t*, const cuuint32_t*,
                           const cuuint32_t*, CUtensorMapInterleave, CUtensorMapSwizzle, CUtensorMapL2promotion, CUtensorMapFloatOOBfill);
    static Fn fn = nullptr;
    if (!fn) {
        cudaDriverEntryPointQueryResult qr;
        cudaGetDriverEntryPoint("cuTensorMapEncodeTiled", (void**)&fn, cudaEnableDefault, &qr);
    }
    const cuuint32_t es[3] = {1, 1, 1};
    fn(m, dt, 3, (void*)p, dim, str, box, es, CU_TENSOR_MAP_INTERLEAVE_NONE, sw, CU_TENSOR_MAP_L2_PROMOTION_L2_128B, CU_TENSOR_MAP_FLOAT_OOB_FILL_NONE);
}
void map_weight(CUtensorMap* m, const bf16* p, int rows, int cols, int ng) {
    const cuuint64_t dim[3] = {64, (cuuint64_t)rows, (cuuint64_t)cols / 64}, str[2] = {(cuuint64_t)cols * 2, 128};
    const cuuint32_t box[3] = {64, 64, (cuuint32_t)ng};
    make_map(m, CU_TENSOR_MAP_DATA_TYPE_BFLOAT16, p, dim, str, box, CU_TENSOR_MAP_SWIZZLE_128B);
}
void map_pieces(CUtensorMap* m, const void* p, int np, int ns) {
    const cuuint64_t dim[3] = {256, (cuuint64_t)np * 2, NSEG}, str[2] = {2048, (cuuint64_t)np * 4096};
    const cuuint32_t box[3] = {256, 2, (cuuint32_t)ns};
    make_map(m, CU_TENSOR_MAP_DATA_TYPE_UINT64, p, dim, str, box, CU_TENSOR_MAP_SWIZZLE_NONE);
}

template <class... P, class... A> void launch(void (*k)(P...), int grid, int block, int smem, int cluster, bool pdl, A... args) {
    cudaLaunchConfig_t c = {};
    c.gridDim = dim3(grid); c.blockDim = dim3(block); c.dynamicSmemBytes = smem; c.stream = cudaStreamPerThread;
    cudaLaunchAttribute at[2];
    int n = 0;
    if (cluster > 1) { at[n].id = cudaLaunchAttributeClusterDimension; at[n].val.clusterDim.x = cluster; at[n].val.clusterDim.y = 1; at[n].val.clusterDim.z = 1; n++; }
    if (pdl) { at[n].id = cudaLaunchAttributeProgrammaticStreamSerialization; at[n].val.programmaticStreamSerializationAllowed = 1; n++; }
    c.attrs = at; c.numAttrs = n;
    cudaLaunchKernelEx(&c, k, args...);
}

int max_clusters() {
    cudaLaunchConfig_t c = {};
    c.gridDim = dim3(3 * H_); c.blockDim = dim3(512); c.dynamicSmemBytes = rec::SMEM;
    cudaLaunchAttribute at[1];
    at[0].id = cudaLaunchAttributeClusterDimension; at[0].val.clusterDim.x = 3; at[0].val.clusterDim.y = 1; at[0].val.clusterDim.z = 1;
    c.attrs = at; c.numAttrs = 1;
    int n = 0;
    cudaOccupancyMaxActiveClusters(&n, rec_kernel, &c);
    return n;
}

}

extern "C" void kernel_launch(void* const* d_in, const int* in_sizes, int n_in, void* d_out, int out_size) {
    const bf16* x = (const bf16*)d_in[0];
    const bf16* mem0 = (const bf16*)d_in[1];
    const bf16* Wq = (const bf16*)d_in[2];
    const bf16* Wk = (const bf16*)d_in[3];
    const bf16* Wv = (const bf16*)d_in[4];
    const bf16* Wo = (const bf16*)d_in[5];
    const bf16* wr = (const bf16*)d_in[8];
    const bf16* wi = (const bf16*)d_in[9];
    cudaFuncSetAttribute(rec_kernel, cudaFuncAttributeMaxDynamicSharedMemorySize, rec::SMEM);
    cudaFuncSetAttribute(side_kernel, cudaFuncAttributeMaxDynamicSharedMemorySize, wk::SMEM);
    cudaFuncSetAttribute(colfft_kernel, cudaFuncAttributeMaxDynamicSharedMemorySize, CF_SMEM);
    Maps maps;
    void *pxn, *po;
    cudaGetSymbolAddress(&pxn, g_xn);
    cudaGetSymbolAddress(&po, g_o);
    map_weight(&maps.wq2, Wq, D_, 4096, 2); map_weight(&maps.wv1, Wv, D_, 4096, 1);
    map_weight(&maps.wo2, Wo, 4096, D_, 2); map_weight(&maps.wo1, Wo, 4096, D_, 1);
    map_pieces(&maps.x6, pxn, 10, 6); map_pieces(&maps.x2, pxn, 10, 2);
    map_pieces(&maps.o6, po, 64, 6); map_pieces(&maps.o2, po, 64, 2);
    bf16 *x1, *x2;
    cudaGetSymbolAddress((void**)&x1, g_x1);
    cudaGetSymbolAddress((void**)&x2, g_x2);
    constexpr int ONE_PER_SM = 120 * 1024;
    cudaFuncSetAttribute(rowfft_kernel, cudaFuncAttributeMaxDynamicSharedMemorySize, ONE_PER_SM);
    cudaFuncSetAttribute(rowifft_kernel, cudaFuncAttributeMaxDynamicSharedMemorySize, ONE_PER_SM);
    static int ncl = 0, nsm = 0;
    if (!ncl) { ncl = max_clusters(); cudaDeviceGetAttribute(&nsm, cudaDevAttrMultiProcessorCount, 0); }
    launch(prep_kernel, 128, 512, 0, 1, false, x, Wv, Wo);
    launch(tables_kernel, 128, 512, 0, 1, false, wr, wi);
    for (int layer = 0; layer < g_layers; layer++) {
        const bf16* xin = layer ? x2 : x;
        launch(rec_kernel, 3 * ncl, 512, rec::SMEM, 3, true, maps, xin, x1, mem0, Wq, Wk, Wv, Wo, layer, g_delay % 10000, g_delay / 10000);
        launch(side_kernel, nsm - 3 * (ncl - H_), 512, wk::SMEM, 1, true, maps, xin, x1, layer);
        launch(rowfft_kernel, 128, 256, ONE_PER_SM, 1, true, (const bf16*)x1, layer);
        launch(colfft_kernel, 107, 384, CF_SMEM, 1, true, layer);
        launch(rowifft_kernel, 128, 256, ONE_PER_SM, 1, true, (const bf16*)x1, layer ? (bf16*)d_out : x2, layer);
    }
}
```

```cpp
#include <cuda_runtime.h>
#include <cuda_bf16.h>
#include <cuda.h>
#include <stdint.h>

#define DEV __device__ __forceinline__
typedef unsigned long long u64;
typedef __nv_bfloat16 bf16;

namespace {

constexpr int S_ = 2048, D_ = 640, H_ = 32, E_ = 128, NSEG = 64;

__device__ __align__(1024) unsigned char g_xn[S_ * D_ * 2];
__device__ __align__(1024) unsigned char g_o[S_ * H_ * E_ * 2];
constexpr int ACC_LAYER = 32 * 5120;
__device__ __align__(4096) u64 g_acc[2 * ACC_LAYER];
__device__ __align__(16) float g_nrm[256];
__device__ __align__(1024) unsigned char g_p[NSEG * H_ * 3 * 4096];
constexpr int SYNC_LAYER = 1024;
__device__ __align__(128) uint32_t g_sync[2 * SYNC_LAYER];
__device__ __align__(1024) bf16 g_x1[S_ * D_];
__device__ __align__(1024) bf16 g_x2[S_ * D_];
constexpr int YT_ROWS = 128;
__device__ __align__(1024) float g_yt[2 * YT_ROWS * D_];
constexpr int NCOL = 321;
__device__ __align__(1024) unsigned char g_z[NCOL * 8192];
__device__ __align__(1024) unsigned char g_wt[NCOL * 8192];
__device__ __align__(1024) uint4 g_f128[2 * 8 * 256];
__device__ __align__(1024) uint4 g_f64[2 * 4 * 128];
__device__ __align__(1024) bf16 g_g32[2 * 4096];
#define TLI(id, k, v)
#define TLS(i)
#define TLE(i)

DEV uint32_t s2u(const void* p) { return (uint32_t)__cvta_generic_to_shared(p); }
DEV uint32_t clk() { uint32_t c; asm volatile("mov.u32 %0,%%clock;" : "=r"(c)::"memory"); return c; }
DEV uint32_t cta_rank() { uint32_t r; asm volatile("mov.u32 %0,%%cluster_ctarank;" : "=r"(r)); return __shfl_sync(~0u, r, 0); }
DEV uint32_t mapa(uint32_t a, uint32_t r) { uint32_t o; asm("mapa.shared::cluster.u32 %0,%1,%2;" : "=r"(o) : "r"(a), "r"(r)); return o; }
DEV void mbar_init(uint32_t b, uint32_t n) { asm volatile("mbarrier.init.shared::cta.b64 [%0],%1;" ::"r"(b), "r"(n) : "memory"); }
DEV bool mbar_try(uint32_t b, uint32_t par) {
    uint32_t ok;
    asm volatile("{.reg .pred p; mbarrier.try_wait.parity.shared::cta.b64 p,[%1],%2; selp.u32 %0,1,0,p;}" : "=r"(ok) : "r"(b), "r"(par) : "memory");
    return ok;
}
constexpr uint32_t SPIN_LIMIT = 1u << 18;
DEV void die() { __trap(); }
DEV void mbar_wait(uint32_t b, uint32_t par) {
    uint32_t n = 0;
    while (!mbar_try(b, par)) if (++n > SPIN_LIMIT) die();
}
DEV uint32_t opaque(uint32_t x) { return __shfl_xor_sync(~0u, x, 0); }
#define SFENCE() asm volatile("{.reg .pred p; setp.ne.u32 p,%1,0; @p mov.u32 %0,%%clock;}" : "+r"(sfd) : "r"((uint32_t)never) : "memory")
DEV void mbar_arrive(uint32_t b) { asm volatile("mbarrier.arrive.shared::cta.b64 _,[%0];" ::"r"(b) : "memory"); }
DEV void mbar_arrive_elect(uint32_t b) { asm volatile("{.reg .pred p; elect.sync _|p, 0xffffffff; @p mbarrier.arrive.shared::cta.b64 _,[%0];}" ::"r"(b) : "memory"); }
DEV void mbar_arrive_remote(uint32_t b) { asm volatile("mbarrier.arrive.shared::cluster.b64 _,[%0];" ::"r"(b) : "memory"); }
DEV void mbar_expect(uint32_t b, uint32_t tx) { asm volatile("mbarrier.arrive.expect_tx.shared::cta.b64 _,[%0],%1;" ::"r"(b), "r"(tx) : "memory"); }
DEV void bar_sync(int id, int n) { asm volatile("bar.sync %0,%1;" ::"r"(id), "r"(n) : "memory"); }
DEV void bar_arrive(int id, int n) { asm volatile("bar.arrive %0,%1;" ::"r"(id), "r"(n) : "memory"); }
template <int ID, int N> DEV void bar_arrive_if(bool p) {
    asm volatile("{.reg .pred p; setp.ne.u32 p,%0,0; @p bar.arrive %1,%2;}" ::"r"((uint32_t)p), "n"(ID), "n"(N) : "memory");
}
DEV void prefetch_bulk(const void* p, uint32_t bytes) { asm volatile("cp.async.bulk.prefetch.L2.global [%0],%1;" ::"l"(p), "r"(bytes) : "memory"); }
DEV void prefetch_l2(const void* p) { asm volatile("prefetch.global.L2 [%0];" ::"l"(p) : "memory"); }
DEV void st_remote(uint32_t a, uint32_t x) { asm volatile("st.relaxed.cluster.shared::cluster.u32 [%0],%1;" ::"r"(a), "r"(x) : "memory"); }
DEV void st_async1(uint32_t a, uint32_t x, uint32_t b) {
    asm volatile("st.async.shared::cluster.mbarrier::complete_tx::bytes.u32 [%0],%1,[%2];" ::"r"(a), "r"(x), "r"(b) : "memory");
}
DEV void st_async2(uint32_t a, uint32_t x, uint32_t y, uint32_t b) {
    asm volatile("st.async.shared::cluster.mbarrier::complete_tx::bytes.v2.u32 [%0],{%1,%2},[%3];" ::"r"(a), "r"(x), "r"(y), "r"(b) : "memory");
}
DEV void st_async4(uint32_t a, uint32_t x, uint32_t y, uint32_t z, uint32_t w, uint32_t b) {
    asm volatile("st.async.shared::cluster.mbarrier::complete_tx::bytes.v4.u32 [%0],{%1,%2,%3,%4},[%5];" ::"r"(a), "r"(x), "r"(y), "r"(z), "r"(w), "r"(b) : "memory");
}
DEV void bulk_g2s(uint32_t dst, const void* src, uint32_t bytes, uint32_t b) {
    asm volatile("cp.async.bulk.shared::cluster.global.mbarrier::complete_tx::bytes [%0],[%1],%2,[%3];" ::"r"(dst), "l"(src), "r"(bytes), "r"(b) : "memory");
}
DEV void bulk_s2s(uint32_t dst, uint32_t src, uint32_t bytes, uint32_t b) {
    asm volatile("cp.async.bulk.shared::cluster.shared::cta.mbarrier::complete_tx::bytes [%0],[%1],%2,[%3];" ::"r"(dst), "r"(src), "r"(bytes), "r"(b) : "memory");
}
DEV void bulk_s2g(void* dst, uint32_t src, uint32_t bytes) {
    asm volatile("cp.async.bulk.global.shared::cta.bulk_group [%0],[%1],%2;" ::"l"(dst), "r"(src), "r"(bytes) : "memory");
}
DEV void tma3d(uint32_t dst, const CUtensorMap* m, int c0, int c1, int c2, uint32_t b) {
    asm volatile("cp.async.bulk.tensor.3d.shared::cluster.global.mbarrier::complete_tx::bytes [%0],[%1,{%3,%4,%5}],[%2];"
                 ::"r"(dst), "l"(m), "r"(b), "r"(c0), "r"(c1), "r"(c2) : "memory");
}
DEV void bulk_commit() { asm volatile("cp.async.bulk.commit_group;" ::: "memory"); }
template <int N> DEV void bulk_wait() { asm volatile("cp.async.bulk.wait_group %0;" ::"n"(N) : "memory"); }
template <int N> DEV void bulk_wait_read() { asm volatile("cp.async.bulk.wait_group.read %0;" ::"n"(N) : "memory"); }
DEV void fence_async_all() { asm volatile("fence.proxy.async;" ::: "memory"); }
DEV void flag_add(uint32_t* p) { fence_async_all(); asm volatile("red.release.gpu.global.add.u32 [%0],1;" ::"l"(p) : "memory"); }
DEV void flag_wait(const uint32_t* p, uint32_t n) {
    uint32_t v, it = 0;
    for (;;) {
        asm volatile("ld.acquire.gpu.global.u32 %0,[%1];" : "=r"(v) : "l"(p) : "memory");
        if (v >= n) break;
        if (++it > (SPIN_LIMIT << 3)) die();
        __nanosleep(100);
    }
    fence_async_all();
}
DEV void cp16(uint32_t dst, const void* src) { asm volatile("cp.async.cg.shared.global [%0],[%1],16;" ::"r"(dst), "l"(src) : "memory"); }
DEV void cp_commit() { asm volatile("cp.async.commit_group;" ::: "memory"); }
template <int N> DEV void cp_wait() { asm volatile("cp.async.wait_group %0;" ::"n"(N) : "memory"); }
DEV uint32_t lds32(uint32_t a) { uint32_t x; asm volatile("ld.shared.u32 %0,[%1];" : "=r"(x) : "r"(a) : "memory"); return x; }
DEV void fence_async() { asm volatile("fence.proxy.async.shared::cta;" ::: "memory"); }
DEV uint32_t pack2(float lo, float hi) { uint32_t r; asm("cvt.rn.bf16x2.f32 %0,%1,%2;" : "=r"(r) : "f"(hi), "f"(lo)); return r; }
DEV uint32_t prmt(uint32_t a, uint32_t b, uint32_t s) { uint32_t r; asm("prmt.b32 %0,%1,%2,%3;" : "=r"(r) : "r"(a), "r"(b), "r"(s)); return r; }
DEV float ex2(float x) { float r; asm("ex2.approx.ftz.f32 %0,%1;" : "=f"(r) : "f"(x)); return r; }
DEV float rcp(float x) { float r; asm("rcp.approx.ftz.f32 %0,%1;" : "=f"(r) : "f"(x)); return r; }
DEV void lds128(uint32_t* r, uint32_t a) { asm volatile("ld.shared.v4.u32 {%0,%1,%2,%3},[%4];" : "=r"(r[0]), "=r"(r[1]), "=r"(r[2]), "=r"(r[3]) : "r"(a) : "memory"); }
DEV void lds64(uint32_t* r, uint32_t a) { asm volatile("ld.shared.v2.u32 {%0,%1},[%2];" : "=r"(r[0]), "=r"(r[1]) : "r"(a) : "memory"); }
DEV void lds64f(float& x, float& y, uint32_t a) { asm volatile("ld.shared.v2.f32 {%0,%1},[%2];" : "=f"(x), "=f"(y) : "r"(a) : "memory"); }
DEV void lds128f(float* r, uint32_t a) { asm volatile("ld.shared.v4.f32 {%0,%1,%2,%3},[%4];" : "=f"(r[0]), "=f"(r[1]), "=f"(r[2]), "=f"(r[3]) : "r"(a) : "memory"); }
DEV void sts128(uint32_t a, uint32_t x, uint32_t y, uint32_t z, uint32_t w) { asm volatile("st.shared.v4.u32 [%0],{%1,%2,%3,%4};" ::"r"(a), "r"(x), "r"(y), "r"(z), "r"(w) : "memory"); }
DEV void sts64(uint32_t a, uint32_t x, uint32_t y) { asm volatile("st.shared.v2.u32 [%0],{%1,%2};" ::"r"(a), "r"(x), "r"(y) : "memory"); }
DEV void sts32(uint32_t a, uint32_t x) { asm volatile("st.shared.u32 [%0],%1;" ::"r"(a), "r"(x) : "memory"); }
DEV void ldsm4(uint32_t* r, uint32_t a) { asm volatile("ldmatrix.sync.aligned.m8n8.x4.shared.b16 {%0,%1,%2,%3},[%4];" : "=r"(r[0]), "=r"(r[1]), "=r"(r[2]), "=r"(r[3]) : "r"(a) : "memory"); }
DEV void ldsm4t(uint32_t* r, uint32_t a) { asm volatile("ldmatrix.sync.aligned.m8n8.x4.trans.shared.b16 {%0,%1,%2,%3},[%4];" : "=r"(r[0]), "=r"(r[1]), "=r"(r[2]), "=r"(r[3]) : "r"(a) : "memory"); }
DEV void ldsm2(uint32_t* r, uint32_t a) { asm volatile("ldmatrix.sync.aligned.m8n8.x2.shared.b16 {%0,%1},[%2];" : "=r"(r[0]), "=r"(r[1]) : "r"(a) : "memory"); }
DEV void stsm4t(uint32_t a, uint32_t x, uint32_t y, uint32_t z, uint32_t w) { asm volatile("stmatrix.sync.aligned.m8n8.x4.trans.shared.b16 [%0],{%1,%2,%3,%4};" ::"r"(a), "r"(x), "r"(y), "r"(z), "r"(w) : "memory"); }
DEV void stsm4(uint32_t a, uint32_t x, uint32_t y, uint32_t z, uint32_t w) { asm volatile("stmatrix.sync.aligned.m8n8.x4.shared.b16 [%0],{%1,%2,%3,%4};" ::"r"(a), "r"(x), "r"(y), "r"(z), "r"(w) : "memory"); }
DEV void stsm2(uint32_t a, uint32_t x, uint32_t y) { asm volatile("stmatrix.sync.aligned.m8n8.x2.shared.b16 [%0],{%1,%2};" ::"r"(a), "r"(x), "r"(y) : "memory"); }
DEV void stsm2t(uint32_t a, uint32_t x, uint32_t y) { asm volatile("stmatrix.sync.aligned.m8n8.x2.trans.shared.b16 [%0],{%1,%2};" ::"r"(a), "r"(x), "r"(y) : "memory"); }
DEV void mma16(float* d, uint32_t a0, uint32_t a1, uint32_t a2, uint32_t a3, uint32_t b0, uint32_t b1) {
    asm volatile("mma.sync.aligned.m16n8k16.row.col.f32.bf16.bf16.f32 {%0,%1,%2,%3},{%4,%5,%6,%7},{%8,%9},{%0,%1,%2,%3};"
                 : "+f"(d[0]), "+f"(d[1]), "+f"(d[2]), "+f"(d[3]) : "r"(a0), "r"(a1), "r"(a2), "r"(a3), "r"(b0), "r"(b1));
}
DEV void mma8(float* d, uint32_t a0, uint32_t a1, uint32_t b0) {
    asm volatile("mma.sync.aligned.m16n8k8.row.col.f32.bf16.bf16.f32 {%0,%1,%2,%3},{%4,%5},{%6},{%0,%1,%2,%3};"
                 : "+f"(d[0]), "+f"(d[1]), "+f"(d[2]), "+f"(d[3]) : "r"(a0), "r"(a1), "r"(b0));
}
DEV u64 mkdesc(uint32_t a, uint32_t lbo, uint32_t sbo) { return (u64)((a & 0x3ffff) >> 4) | ((u64)(lbo >> 4) << 16) | ((u64)(sbo >> 4) << 32); }
constexpr u64 SW128 = 1ull << 62;
DEV void wg_fence() { asm volatile("wgmma.fence.sync.aligned;" ::: "memory"); }
DEV void wg_commit() { asm volatile("wgmma.commit_group.sync.aligned;" ::: "memory"); }
template <int N> DEV void wg_wait() { asm volatile("wgmma.wait_group.sync.aligned %0;" ::"n"(N) : "memory"); }
template <int ACC> DEV void wgmma_n32_rs(float* d, const uint32_t* a, u64 desc) {
    asm volatile("wgmma.mma_async.sync.aligned.m64n32k16.f32.bf16.bf16 {%0,%1,%2,%3,%4,%5,%6,%7,%8,%9,%10,%11,%12,%13,%14,%15},{%16,%17,%18,%19},%20,%21,1,1,0;"
                 : "+f"(d[0]), "+f"(d[1]), "+f"(d[2]), "+f"(d[3]), "+f"(d[4]), "+f"(d[5]), "+f"(d[6]), "+f"(d[7]),
                   "+f"(d[8]), "+f"(d[9]), "+f"(d[10]), "+f"(d[11]), "+f"(d[12]), "+f"(d[13]), "+f"(d[14]), "+f"(d[15])
                 : "r"(a[0]), "r"(a[1]), "r"(a[2]), "r"(a[3]), "l"(desc), "n"(ACC));
}
template <int ACC> DEV void wgmma_n32_ss(float* d, u64 da, u64 desc) {
    asm volatile("wgmma.mma_async.sync.aligned.m64n32k16.f32.bf16.bf16 {%0,%1,%2,%3,%4,%5,%6,%7,%8,%9,%10,%11,%12,%13,%14,%15},%16,%17,%18,1,1,0,0;"
                 : "+f"(d[0]), "+f"(d[1]), "+f"(d[2]), "+f"(d[3]), "+f"(d[4]), "+f"(d[5]), "+f"(d[6]), "+f"(d[7]),
                   "+f"(d[8]), "+f"(d[9]), "+f"(d[10]), "+f"(d[11]), "+f"(d[12]), "+f"(d[13]), "+f"(d[14]), "+f"(d[15])
                 : "l"(da), "l"(desc), "n"(ACC));
}
template <int ACC> DEV void wgmma_n16_ss(float* d, u64 da, u64 desc) {
    asm volatile("wgmma.mma_async.sync.aligned.m64n16k16.f32.bf16.bf16 {%0,%1,%2,%3,%4,%5,%6,%7},%8,%9,%10,1,1,0,0;"
                 : "+f"(d[0]), "+f"(d[1]), "+f"(d[2]), "+f"(d[3]), "+f"(d[4]), "+f"(d[5]), "+f"(d[6]), "+f"(d[7])
                 : "l"(da), "l"(desc), "n"(ACC));
}
#define ACC8(o) "+f"(d[o]), "+f"(d[o + 1]), "+f"(d[o + 2]), "+f"(d[o + 3]), "+f"(d[o + 4]), "+f"(d[o + 5]), "+f"(d[o + 6]), "+f"(d[o + 7])
template <int ACC, int TB> DEV void wgmma_n64_rs(float* d, const uint32_t* a, u64 desc) {
    asm volatile("wgmma.mma_async.sync.aligned.m64n64k16.f32.bf16.bf16 {%0,%1,%2,%3,%4,%5,%6,%7,%8,%9,%10,%11,%12,%13,%14,%15,"
                 "%16,%17,%18,%19,%20,%21,%22,%23,%24,%25,%26,%27,%28,%29,%30,%31},{%32,%33,%34,%35},%36,%37,1,1,%38;"
                 : ACC8(0), ACC8(8), ACC8(16), ACC8(24) : "r"(a[0]), "r"(a[1]), "r"(a[2]), "r"(a[3]), "l"(desc), "n"(ACC), "n"(TB));
}
template <int ACC, int TB> DEV void wgmma_n80_rs(float* d, const uint32_t* a, u64 desc) {
    asm volatile("wgmma.mma_async.sync.aligned.m64n80k16.f32.bf16.bf16 {%0,%1,%2,%3,%4,%5,%6,%7,%8,%9,%10,%11,%12,%13,%14,%15,"
                 "%16,%17,%18,%19,%20,%21,%22,%23,%24,%25,%26,%27,%28,%29,%30,%31,%32,%33,%34,%35,%36,%37,%38,%39},{%40,%41,%42,%43},%44,%45,1,1,%46;"
                 : ACC8(0), ACC8(8), ACC8(16), ACC8(24), ACC8(32) : "r"(a[0]), "r"(a[1]), "r"(a[2]), "r"(a[3]), "l"(desc), "n"(ACC), "n"(TB));
}
template <int TA, int TB> DEV void wgmma_n64_ss(float* d, u64 da, u64 db, int acc) {
    asm volatile("{.reg .pred p; setp.ne.b32 p,%34,0; wgmma.mma_async.sync.aligned.m64n64k16.f32.bf16.bf16 {%0,%1,%2,%3,%4,%5,%6,%7,%8,%9,%10,%11,%12,%13,%14,%15,%16,%17,%18,%19,%20,%21,%22,%23,%24,%25,%26,%27,%28,%29,%30,%31},%32,%33,p,1,1,%35,%36;}"
                 : ACC8(0), ACC8(8), ACC8(16), ACC8(24) : "l"(da), "l"(db), "r"(acc), "n"(TA), "n"(TB));
}
template <int TA, int TB> DEV void wgmma_n128_ss(float* d, u64 da, u64 db, int acc) {
    asm volatile("{.reg .pred p; setp.ne.b32 p,%66,0; wgmma.mma_async.sync.aligned.m64n128k16.f32.bf16.bf16 {%0,%1,%2,%3,%4,%5,%6,%7,%8,%9,%10,%11,%12,%13,%14,%15,%16,%17,%18,%19,%20,%21,%22,%23,%24,%25,%26,%27,%28,%29,%30,%31,%32,%33,%34,%35,%36,%37,%38,%39,%40,%41,%42,%43,%44,%45,%46,%47,%48,%49,%50,%51,%52,%53,%54,%55,%56,%57,%58,%59,%60,%61,%62,%63},%64,%65,p,1,1,%67,%68;}"
                 : ACC8(0), ACC8(8), ACC8(16), ACC8(24), ACC8(32), ACC8(40), ACC8(48), ACC8(56) : "l"(da), "l"(db), "r"(acc), "n"(TA), "n"(TB));
}
template <int TA, int TB> DEV void wgmma_n192_ss(float* d, u64 da, u64 db, int acc) {
    asm volatile("{.reg .pred p; setp.ne.b32 p,%98,0; wgmma.mma_async.sync.aligned.m64n192k16.f32.bf16.bf16 {%0,%1,%2,%3,%4,%5,%6,%7,%8,%9,%10,%11,%12,%13,%14,%15,%16,%17,%18,%19,%20,%21,%22,%23,%24,%25,%26,%27,%28,%29,%30,%31,%32,%33,%34,%35,%36,%37,%38,%39,%40,%41,%42,%43,%44,%45,%46,%47,%48,%49,%50,%51,%52,%53,%54,%55,%56,%57,%58,%59,%60,%61,%62,%63,%64,%65,%66,%67,%68,%69,%70,%71,%72,%73,%74,%75,%76,%77,%78,%79,%80,%81,%82,%83,%84,%85,%86,%87,%88,%89,%90,%91,%92,%93,%94,%95},%96,%97,p,1,1,%99,%100;}"
                 : ACC8(0), ACC8(8), ACC8(16), ACC8(24), ACC8(32), ACC8(40), ACC8(48), ACC8(56), ACC8(64), ACC8(72), ACC8(80), ACC8(88) : "l"(da), "l"(db), "r"(acc), "n"(TA), "n"(TB));
}
template <int ACC> DEV void wgmma_n40_ss(float* d, u64 da, u64 desc) {
    asm volatile("wgmma.mma_async.sync.aligned.m64n40k16.f32.bf16.bf16 {%0,%1,%2,%3,%4,%5,%6,%7,%8,%9,%10,%11,%12,%13,%14,%15,%16,%17,%18,%19},%20,%21,%22,1,1,0,0;"
                 : ACC8(0), ACC8(8), "+f"(d[16]), "+f"(d[17]), "+f"(d[18]), "+f"(d[19]) : "l"(da), "l"(desc), "n"(ACC));
}
DEV void pdl_wait() { asm volatile("griddepcontrol.wait;" ::: "memory"); }
DEV void pdl_launch() { asm volatile("griddepcontrol.launch_dependents;" ::: "memory"); }
DEV uint32_t ldg32(const void* p) { uint32_t v; asm volatile("ld.global.nc.u32 %0,[%1];" : "=r"(v) : "l"(p)); return v; }
DEV void ld_acc(u64& a, u64& b, const void* p) {
    const uint32_t done = (uint32_t)a & (uint32_t)b & 32u;
    asm volatile("{.reg .pred p; setp.eq.u32 p,%3,0;\n"
                 "@p ld.relaxed.gpu.global.v2.u64 {%0,%1},[%2];}" : "+l"(a), "+l"(b) : "l"(p), "r"(done) : "memory");
}
DEV void ld_acc0(u64& a, u64& b, const void* p) {
    asm volatile("ld.relaxed.gpu.global.v2.u64 {%0,%1},[%2];" : "=l"(a), "=l"(b) : "l"(p) : "memory");
}
DEV uint32_t and3(uint32_t a, uint32_t b, uint32_t c) { uint32_t r; asm volatile("lop3.b32 %0,%1,%2,%3,0x80;" : "=r"(r) : "r"(a), "r"(b), "r"(c)); return r; }
DEV uint32_t absmax2(uint32_t a, uint32_t b) { uint32_t r; asm("max.xorsign.abs.bf16x2 %0,%1,%2;" : "=r"(r) : "r"(a), "r"(b)); return r; }
DEV float lds32f(uint32_t a) { float x; asm volatile("ld.shared.f32 %0,[%1];" : "=f"(x) : "r"(a) : "memory"); return x; }
DEV void red_add64(u64* p, uint32_t lo, uint32_t hi) {
    asm volatile("{.reg .b64 v; mov.b64 v,{%1,%2}; red.relaxed.gpu.global.add.u64 [%0],v;}" ::"l"(p), "r"(lo), "r"(hi) : "memory");
}
DEV float bf_round(float x) { return __bfloat162float(__float2bfloat16_rn(x)); }
DEV float bf_lo(uint32_t u) { return __uint_as_float(u << 16); }
DEV float bf_hi(uint32_t u) { return __uint_as_float(u & 0xffff0000u); }

#define GPROF(i, n)
#define PROFT(i)
#define STAMP(i)

DEV void unpack8(float* v, uint4 u) {
    v[0] = bf_lo(u.x); v[1] = bf_hi(u.x); v[2] = bf_lo(u.y); v[3] = bf_hi(u.y);
    v[4] = bf_lo(u.z); v[5] = bf_hi(u.z); v[6] = bf_lo(u.w); v[7] = bf_hi(u.w);
}
DEV int xn_off(int row, int chunk) { return (row >> 5) * 40960 + (chunk >> 3) * 4096 + (row & 31) * 128 + (((chunk ^ row) & 7) << 4); }

DEV void ln_row(float (&v)[3][8], int lane) {
    float s = 0.f;
#pragma unroll
    for (int c = 0; c < 3; c++)
#pragma unroll
        for (int j = 0; j < 8; j++) s += v[c][j];
#pragma unroll
    for (int o = 16; o; o >>= 1) s += __shfl_xor_sync(~0u, s, o);
    float mean = s * (1.f / D_), q = 0.f;
#pragma unroll
    for (int c = 0; c < 3; c++)
        if (c < 2 || lane < 16)
#pragma unroll
            for (int j = 0; j < 8; j++) { float d = v[c][j] - mean; q += d * d; }
#pragma unroll
    for (int o = 16; o; o >>= 1) q += __shfl_xor_sync(~0u, q, o);
    float mb = bf_round(mean);
    float inv = 1.f / bf_round(sqrtf(bf_round(bf_round(q * (1.f / D_)) + 1e-5f)));
#pragma unroll
    for (int c = 0; c < 3; c++)
#pragma unroll
        for (int j = 0; j < 8; j++) v[c][j] = bf_round(v[c][j] - mb) * inv;
}

__host__ __device__ constexpr int col_freq(int c) {
    return c == 320 ? 320 : c < 192 ? (c >> 6) * 128 + (c & 63) : c == 192 ? 192 : c < 256 ? 448 - c : c == 256 ? 64 : 384 - c;
}
DEV float rdft(int n, int k, int sn, int N) {
    float s, c;
    sincospif((float)((n * k) & (N - 1)) * (2.f / N), &s, &c);
    return !sn ? c : k ? s : (n & 1 ? -1.f : 1.f);
}

__global__ void __launch_bounds__(512) prep_kernel(const bf16* __restrict__ x, const bf16* __restrict__ Wq, const bf16* __restrict__ Wk,
                                                   const bf16* __restrict__ Wv, const bf16* __restrict__ Wo) {
    __shared__ float red[32], col[4][640];
    const int tid = threadIdx.x, lane = tid & 31, warp = tid >> 5, b = blockIdx.x, row = b * 16 + warp;
    TLS(0);
    pdl_launch();
    uint4 ux[3], uv[5], uo[8];
#pragma unroll
    for (int c = 0; c < 3; c++) ux[c] = c < 2 || lane < 16 ? *(const uint4*)(x + row * D_ + (c * 32 + lane) * 8) : make_uint4(0, 0, 0, 0);
#pragma unroll
    for (int i = 0; i < 5; i++) uv[i] = *(const uint4*)(Wv + (size_t)((b & 3) * 160 + i * 32 + (tid >> 4)) * 4096 + (b >> 2) * E_ + (tid & 15) * 8);
    if (tid < 320) {
#pragma unroll
        for (int r = 0; r < 8; r++) uo[r] = *(const uint4*)(Wo + (size_t)(b * 32 + tid / 80 * 8 + r) * D_ + tid % 80 * 8);
    }
    if (tid >= 504) prefetch_bulk((const char*)(tid & 4 ? Wk : Wq) + (b * 4 + (tid & 3)) * 10240, 10240);
    if (b == 0) ((uint4*)g_sync)[tid] = make_uint4(0, 0, 0, 0);
    for (int i = b * 512 + tid; i < ACC_LAYER; i += 128 * 512) ((uint4*)g_acc)[i] = make_uint4(0, 0, 0, 0);
    if (tid < 2 * YT_ROWS * D_ / 4 / 128) ((uint4*)g_yt)[b * (2 * YT_ROWS * D_ / 4 / 128) + tid] = make_uint4(0, 0, 0, 0);
    const int gid = tid < 104 ? b * 104 + tid : 1 << 20;
    if (gid < 4096) {
        const int inv = gid >> 11, ks = (gid >> 8) & 7, t = gid & 255, g = (t & 31) >> 2, q = t & 3, tile = t >> 5;
        uint32_t v[4];
#pragma unroll
        for (int j = 0; j < 4; j++) {
            float x[2];
#pragma unroll
            for (int u = 0; u < 2; u++) {
                const int m = inv ? 16 * tile + 2 * g + (j & 1) : 16 * ks + 8 * (j >> 1) + 2 * q + u;
                const int k2 = inv ? 8 * ks + 2 * q + u : 8 * tile + g, sn = inv ? j >> 1 : j & 1;
                x[u] = rdft(m, k2, sn, 128);
                if (sn && k2) x[u] = -x[u];
            }
            v[j] = pack2(x[0], x[1]);
        }
        g_f128[gid] = make_uint4(v[0], v[1], v[2], v[3]);
    } else if (gid < 5120) {
        const int id = gid - 4096, inv = id >> 9, ks = (id >> 7) & 3, t = id & 127, g = (t & 31) >> 2, q = t & 3, tile = t >> 5;
        uint32_t v[4];
#pragma unroll
        for (int j = 0; j < 4; j++) {
            float x[2];
#pragma unroll
            for (int u = 0; u < 2; u++) {
                const int a = inv ? 16 * tile + g + 8 * (j & 1) : 16 * ks + 8 * (j >> 1) + 2 * q + u;
                const int ka = inv ? 8 * ks + 2 * q + u : 8 * tile + g, sn = inv ? j >> 1 : j & 1;
                x[u] = rdft(a, ka, sn, 64);
            }
            v[j] = pack2(x[0], x[1]);
        }
        g_f64[id] = make_uint4(v[0], v[1], v[2], v[3]);
    } else if (gid < 5120 + 8192) {
        const int id = gid - 5120, inv = id >> 12, n = ((id >> 9) & 7) * 8 + ((id >> 3) & 7), k = ((id >> 6) & 7) * 8 + (id & 7);
        float s, c;
        sincospif((float)(((n >> 1) * (k >> 1)) & 31) * (1.f / 16), &s, &c);
        if (inv) s = -s;
        g_g32[id] = __float2bfloat16_rn((n & 1) == (k & 1) ? c : (k & 1) ? s : -s);
    }
    {
        float v[3][8];
#pragma unroll
        for (int c = 0; c < 3; c++) unpack8(v[c], ux[c]);
        ln_row(v, lane);
#pragma unroll
        for (int c = 0; c < 3; c++)
            if (c < 2 || lane < 16)
                *(uint4*)(g_xn + xn_off(row, c * 32 + lane)) =
                    make_uint4(pack2(v[c][0], v[c][1]), pack2(v[c][2], v[c][3]), pack2(v[c][4], v[c][5]), pack2(v[c][6], v[c][7]));
    }
    float sv = 0.f;
#pragma unroll
    for (int i = 0; i < 5; i++) {
        float w[8];
        unpack8(w, uv[i]);
#pragma unroll
        for (int j = 0; j < 8; j++) sv += w[j] * w[j];
    }
    if (tid < 320) {
        float a[8] = {0.f, 0.f, 0.f, 0.f, 0.f, 0.f, 0.f, 0.f};
#pragma unroll
        for (int r = 0; r < 8; r++) {
            float w[8];
            unpack8(w, uo[r]);
#pragma unroll
            for (int j = 0; j < 8; j++) a[j] += w[j] * w[j];
        }
#pragma unroll
        for (int j = 0; j < 8; j++) col[tid / 80][tid % 80 * 8 + j] = a[j];
    }
    __syncthreads();
    float so = (col[0][tid] + col[1][tid]) + (col[2][tid] + col[3][tid]);
    if (tid < 128) so = fmaxf(so, (col[0][512 + tid] + col[1][512 + tid]) + (col[2][512 + tid] + col[3][512 + tid]));
#pragma unroll
    for (int o = 16; o; o >>= 1) { sv += __shfl_xor_sync(~0u, sv, o); so = fmaxf(so, __shfl_xor_sync(~0u, so, o)); }
    if (lane == 0) { red[warp] = sv; red[16 + warp] = so; }
    __syncthreads();
    if (tid == 0) {
        float a = 0.f, c = 0.f;
        for (int i = 0; i < 16; i++) { a += red[i]; c = fmaxf(c, red[16 + i]); }
        g_nrm[b] = a; g_nrm[128 + b] = c;
    }
    TLE(0);
}

DEV void filter_tile(const bf16* __restrict__ wr, const bf16* __restrict__ wi, int ka, int c) {
    const int kn = ka ? 2048 - ka : 32, kc = col_freq(c);
    const unsigned short* pr = (const unsigned short*)wr + kc;
    const unsigned short* pi = (const unsigned short*)wi + kc;
#pragma unroll 1
    for (int i = 0; i < 4; i += 2) {
        unsigned short a[32], b[32];
#pragma unroll
        for (int n = 0; n < 32; n++) {
            const int k = ((n & 1 ? kn : ka) + 64 * (4 * (2 * (i + (n >> 4)) + ((n >> 1) & 1)) + ((n >> 2) & 3))) & 2047;
            a[n] = __ldg(pr + k * NCOL); b[n] = __ldg(pi + k * NCOL);
        }
#pragma unroll
        for (int n = 0; n < 32; n += 4)
            *(uint4*)(g_wt + c * 8192 + (i + (n >> 4)) * 2048 + (ka * 4 + ((n >> 2) & 3)) * 16) =
                make_uint4(a[n] | ((uint32_t)b[n] << 16), a[n + 1] | ((uint32_t)b[n + 1] << 16), a[n + 2] | ((uint32_t)b[n + 2] << 16), a[n + 3] | ((uint32_t)b[n + 3] << 16));
    }
}

namespace wk {
constexpr int STAGE = 49152, NST = 4, OFF_OUT = 3 * STAGE, OFF_RED = 4 * STAGE, OFF_BAR = OFF_RED + 32768, SMEM = OFF_BAR + 128;
constexpr int NPB = 12;
__host__ __device__ constexpr int pb_start(int b) { return b == 0 ? 0 : b == 1 ? 2 : b < NPB ? 6 * b - 6 : 64; }
#define NOB 7
#define SPLIT_A 3
#define SPLIT_B 11
constexpr int N_P = NPB * H_, I_F = N_P, I_OB = I_F + 32, I_OT = I_OB + NOB * 5, I_SA = I_OT + (30 - 3 * NOB) * 10;
constexpr int I_SB = I_SA + 10 * SPLIT_A, N_ITEMS = I_SB + 10 * SPLIT_B;
DEV void ot_decode(int id, int& b, int& nt, int& k0, int& k1) {
    const int base = id < I_SA ? I_OT : id < I_SB ? I_SA : I_SB, j = (id - base) / 10;
    nt = (id - base) % 10;
    if (id < I_SA) { b = 3 * NOB + j; k0 = 0; k1 = 22; }
    else if (id < I_SB) { b = 30; k0 = 22 * j / SPLIT_A; k1 = 22 * (j + 1) / SPLIT_A; }
    else { b = 31; k0 = 22 * j / SPLIT_B; k1 = 22 * (j + 1) / SPLIT_B; }
}
enum { SY_TICKET = 0, SY_O = 32, SY_P = 128 };
}
struct Ring {
    int st; uint32_t ph;
    DEV uint32_t par() const { return (ph >> st) & 1; }
    DEV void next(int n) { ph ^= 1u << st; st = st + 1 >= n ? 0 : st + 1; }
};
struct Maps { CUtensorMap wq2, wv1, wo2, wo1, x6, x2, o6, o2; const bf16 *wr, *wi; };

template <int NSG> DEV void proj_tile(uint32_t sb, uint32_t bar, Ring& rg, int wg, int id) {
    using namespace wk;
    float acc[NSG * 16];
#pragma unroll
    for (int i = 0; i < NSG * 16; i++) acc[i] = 0.f;
    const int lane = threadIdx.x & 31, ww = (threadIdx.x >> 5) & 3;
    for (int kb = 0; kb < 10; kb++, rg.next(3)) {
        const int st = rg.st;
        if (kb) mbar_wait(bar + 8 * st, rg.par());
        const u64 da = mkdesc(sb + st * STAGE + wg * 8192, 0, 1024) | SW128, db = mkdesc(sb + st * STAGE + 24576, 0, 1024) | SW128;
        wg_fence();
#pragma unroll
        for (int ks = 0; ks < 4; ks++) {
            if (NSG == 2) wgmma_n64_ss<1, 0>(acc, da + ks * 128, db + ks * 2, 1);
            if (NSG == 4) wgmma_n128_ss<1, 0>(acc, da + ks * 128, db + ks * 2, 1);
            if (NSG == 6) wgmma_n192_ss<1, 0>(acc, da + ks * 128, db + ks * 2, 1);
        }
        wg_commit();
        wg_wait<0>();
        mbar_arrive_elect(bar + 8 * (NST + st));
    }
    const uint32_t out = sb + OFF_OUT + wg * 24576;
    bar_sync(5 + wg, 160);
    const uint32_t la = out + (wg < 2 ? (lane >> 4) * 1024 + ww * 256 + (lane & 15) * 16 : ww * 1024 + ((lane >> 3) & 1) * 512 + (lane >> 4) * 128 + (lane & 7) * 16);
#pragma unroll
    for (int j = 0; j < 2 * NSG; j++) {
        const float* c = acc + 8 * j;
        const uint32_t p0 = pack2(c[0], c[1]), p1 = pack2(c[2], c[3]), p2 = pack2(c[4], c[5]), p3 = pack2(c[6], c[7]);
        if (wg < 2) stsm4t(la + j * 2048, p0, p1, p2, p3);
        else stsm4(la + (j >> 1) * 4096 + (j & 1) * 256, p0, p1, p2, p3);
    }
    if ((threadIdx.x & 127) == 0) sts32(bar + 80 + 4 * wg, id);
    fence_async();
    bar_arrive(1 + wg, 160);
}

DEV uint32_t resid(uint32_t u, float a, float b) { return pack2(bf_lo(u) + bf_round(a), bf_hi(u) + bf_round(b)); }

DEV void worker(uint32_t sb, const Maps& maps, const bf16* __restrict__ x, bf16* __restrict__ x1, int layer) {
    using namespace wk;
    const uint32_t bar = sb + OFF_BAR, slot = bar + 64;
    const int tid = threadIdx.x, lane = tid & 31, warp = __shfl_sync(~0u, tid >> 5, 0);
    uint32_t* sy = g_sync + layer * SYNC_LAYER;
    if (tid == 0) {
        for (int i = 0; i < NST; i++) { mbar_init(bar + 8 * i, 1); mbar_init(bar + 8 * (NST + i), 12); }
        asm volatile("fence.mbarrier_init.release.cluster;" ::: "memory");
    }
    __syncthreads();
    if (warp > 12) {
        const int wg = warp - 13;
        bar_arrive(5 + wg, 160);
        for (;;) {
            bar_sync(1 + wg, 160);
            const int id = (int)lds32(bar + 80 + 4 * wg);
            if (id < 0) break;
            const int s0 = pb_start(id >> 5), ns = pb_start((id >> 5) + 1) - s0;
            if (lane == 0) {
                for (int j = 0; j < ns; j++)
                    bulk_s2g(g_p + (size_t)(((s0 + j) * H_ + (id & 31)) * 3 + wg) * 4096, sb + OFF_OUT + wg * 24576 + j * 4096, 4096);
                bulk_commit();
                bulk_wait<0>();
                flag_add(sy + SY_P + id);
            }
            __syncwarp();
            bar_arrive(5 + wg, 160);
        }
    } else if (warp == 12) {
        if (lane == 0) {
            Ring rg = {0, 7u};
            auto acquire = [&]() { mbar_wait(bar + 8 * (NST + rg.st), rg.par()); return sb + rg.st * STAGE; };
            for (;;) {
                int id = (int)atomicAdd(sy + SY_TICKET, 1u);
                if (layer && id >= I_F) id += I_OB - I_F;
                if (id >= N_ITEMS) id = -1;
                if (id >= 0) { TLI(id, 0, gtime()); TLI(id, 3, blockIdx.x + (gridDim.x % 3 == 0 && gridDim.x > 111 ? 0 : 1000)); }
                uint32_t d = acquire();
                sts32(slot + 4 * rg.st, id);
                if (id < 0) { mbar_arrive(bar + 8 * rg.st); break; }
                if (id < N_P) {
                    const int b = id >> 5, h = id & 31, s0 = pb_start(b), ns = pb_start(b + 1) - s0;
                    for (int kb = 0; kb < 10; kb++, rg.next(3)) {
                        if (kb) d = acquire();
                        const uint32_t fb = bar + 8 * rg.st;
                        mbar_expect(fb, 24576 + ns * 4096);
                        tma3d(d, &maps.wq2, 0, kb * 64, 2 * h, fb);
                        tma3d(d + 16384, &maps.wv1, 0, kb * 64, 2 * h, fb);
                        if (ns == 6) tma3d(d + 24576, &maps.x6, 0, 2 * kb, s0, fb);
                        else for (int j = 0; j < ns; j += 2) tma3d(d + 24576 + j * 4096, &maps.x2, 0, 2 * kb, s0 + j, fb);
                    }
                } else if (id < I_OB) {
                    mbar_arrive(bar + 8 * rg.st);
                    mbar_wait(bar + 8 * (NST + rg.st), rg.par() ^ 1);
                    rg.next(NST);
                } else if (id < I_OT) {
                    const int b = (id - I_OB) / 5, nt = (id - I_OB) % 5;
                    for (int j = 0; j < 6; j++) flag_wait(sy + SY_O + 6 * b + j, 32);
                    for (int kb = 0; kb < 64; kb++, rg.next(NST)) {
                        if (kb) d = acquire();
                        const uint32_t fb = bar + 8 * rg.st;
                        mbar_expect(fb, 40960);
                        tma3d(d, &maps.o6, 0, 2 * kb, 6 * b, fb);
                        tma3d(d + 24576, &maps.wo2, 0, kb * 64, 2 * nt, fb);
                    }
                } else {
                    int b, nt, k0, k1;
                    ot_decode(id, b, nt, k0, k1);
                    for (int kb = k0; kb < k1; kb++, rg.next(NST)) {
                        if (kb > k0) d = acquire();
                        const uint32_t fb = bar + 8 * rg.st;
                        mbar_expect(fb, 49152);
                        tma3d(d + 24576, &maps.wo1, 0, 3 * kb * 64, nt, fb);
                        if (kb == k0) for (int j = 0; j < 2; j++) flag_wait(sy + SY_O + 2 * b + j, 32);
                        for (int u = 0; u < 3; u++) tma3d(d + u * 8192, &maps.o2, 0, 2 * (3 * kb + u), 2 * b, fb);
                    }
                }
            }
        }
    } else {
        const int wg = warp >> 2, g = lane >> 2, q = lane & 3;
        Ring rg = {0, 0u};
        bool stores_done = false;
        for (;;) {
            mbar_wait(bar + 8 * rg.st, rg.par());
            const int id = (int)lds32(slot + 4 * rg.st);
            if ((id < 0 || id >= N_P) && !stores_done) {
                bar_sync(5 + wg, 160);
                if ((tid & 127) == 0) sts32(bar + 80 + 4 * wg, ~0u);
                bar_arrive(1 + wg, 160);
                stores_done = true;
                bar_sync(4, 384);
                mbar_arrive_elect(bar + 8 * (NST + 3));
            }
            if (id < 0) break;
            if (tid == 0) TLI(id, 1, gtime());
            if (id < N_P) {
                const int b = id >> 5;
                if (b == 0) proj_tile<2>(sb, bar, rg, wg, id);
                else if (b == 1 || b == NPB - 1) proj_tile<4>(sb, bar, rg, wg, id);
                else proj_tile<6>(sb, bar, rg, wg, id);
            } else if (id < I_OB) {
                if (tid < NCOL) filter_tile(maps.wr, maps.wi, id - I_F, tid);
                __syncwarp();
                mbar_arrive_elect(bar + 8 * (NST + rg.st));
                rg.next(NST);
            } else if (id < I_OT) {
                const int b = (id - I_OB) / 5, nt = (id - I_OB) % 5;
                const size_t o = (size_t)(192 * b + 16 * warp + g) * D_ + nt * 128 + 2 * q;
                float acc[64];
#pragma unroll
                for (int i = 0; i < 64; i++) acc[i] = 0.f;
                for (int kb = 0; kb < 64; kb++, rg.next(NST)) {
                    const int st = rg.st;
                    if (kb) mbar_wait(bar + 8 * st, rg.par());
                    const u64 da = mkdesc(sb + st * STAGE + wg * 8192, 128, 1024), db = mkdesc(sb + st * STAGE + 24576, 8192, 1024) | SW128;
                    wg_fence();
#pragma unroll
                    for (int ks = 0; ks < 4; ks++) wgmma_n128_ss<0, 1>(acc, da + ks * 16, db + ks * 128, 1);
                    wg_commit();
                    wg_wait<0>();
                    mbar_arrive_elect(bar + 8 * (NST + st));
                }
                uint32_t xr[32];
#pragma unroll
                for (int t = 0; t < 32; t++) xr[t] = ldg32(x + o + 8 * (t >> 1) + (t & 1) * 8 * D_);
#pragma unroll
                for (int t = 0; t < 32; t++) *(uint32_t*)(x1 + o + 8 * (t >> 1) + (t & 1) * 8 * D_) = resid(xr[t], acc[2 * t], acc[2 * t + 1]);
            } else {
                int b, nt, k0, k1;
                ot_decode(id, b, nt, k0, k1);
                const size_t o = (size_t)(64 * b + 16 * (warp & 3) + g) * D_ + nt * 64 + 2 * q;
                float acc[32];
                uint32_t xr[16];
#pragma unroll
                for (int t = 0; t < 16; t++) xr[t] = wg == 0 && id < I_SA ? ldg32(x + o + 8 * (t >> 1) + (t & 1) * 8 * D_) : 0;
#pragma unroll
                for (int i = 0; i < 32; i++) acc[i] = 0.f;
                for (int kb = k0; kb < k1; kb++, rg.next(NST)) {
                    const int st = rg.st;
                    if (kb > k0) mbar_wait(bar + 8 * st, rg.par());
                    const u64 da = mkdesc(sb + st * STAGE + wg * 8192, 128, 1024), db = mkdesc(sb + st * STAGE + 24576 + wg * 8192, 0, 1024) | SW128;
                    wg_fence();
#pragma unroll
                    for (int ks = 0; ks < 4; ks++) wgmma_n64_ss<0, 1>(acc, da + ks * 16, db + ks * 128, 1);
                    wg_commit();
                    wg_wait<0>();
                    mbar_arrive_elect(bar + 8 * (NST + st));
                }
                const uint32_t ra = sb + OFF_RED + (tid & 127) * 16;
                if (wg) {
#pragma unroll
                    for (int t = 0; t < 8; t++)
                        sts128(ra + (wg - 1) * 16384 + t * 2048, __float_as_uint(acc[4 * t]), __float_as_uint(acc[4 * t + 1]), __float_as_uint(acc[4 * t + 2]), __float_as_uint(acc[4 * t + 3]));
                }
                bar_sync(4, 384);
                if (wg == 0) {
#pragma unroll
                    for (int t = 0; t < 8; t++) {
                        float u[4], v[4];
                        lds128f(u, ra + t * 2048); lds128f(v, ra + 16384 + t * 2048);
#pragma unroll
                        for (int i = 0; i < 4; i++) acc[4 * t + i] += u[i] + v[i];
                    }
                }
                bar_sync(4, 384);
                if (wg == 0) {
                    if (id < I_SA) {
#pragma unroll
                        for (int t = 0; t < 16; t++) *(uint32_t*)(x1 + o + 8 * (t >> 1) + (t & 1) * 8 * D_) = resid(xr[t], acc[2 * t], acc[2 * t + 1]);
                    } else {
                        float* y = g_yt + (layer * YT_ROWS - (S_ - YT_ROWS)) * D_ + o;
#pragma unroll
                        for (int t = 0; t < 16; t++)
                            asm volatile("red.relaxed.gpu.global.add.v2.f32 [%0],{%1,%2};" ::"l"(y + 8 * (t >> 1) + (t & 1) * 8 * D_), "f"(acc[2 * t]), "f"(acc[2 * t + 1]) : "memory");
                    }
                }
            }
            if (tid == 0) TLI(id, 2, gtime());
        }
    }
}

__global__ void __launch_bounds__(512, 1) side_kernel(const __grid_constant__ Maps maps, const bf16* __restrict__ x, bf16* __restrict__ x1, int layer) {
    extern __shared__ __align__(1024) unsigned char smem[];
    pdl_launch();
    TLS(3 + 5 * layer);
    worker(s2u(smem), maps, x, x1, layer);
    __syncwarp();
    pdl_wait();
    TLE(3 + 5 * layer);
}

constexpr float C5A = 0.30901699437494742f, C5B = -0.80901699437494742f, S5A = 0.95105651629515357f, S5B = 0.58778525229247313f;
template <int SGN> DEV void dft5(const float (&tr)[5], const float (&ti)[5], float (&zr)[5], float (&zi)[5]) {
    const float ar = tr[1] + tr[4], ai = ti[1] + ti[4], br = tr[2] + tr[3], bi = ti[2] + ti[3];
    const float cr = tr[1] - tr[4], ci = ti[1] - ti[4], dr = tr[2] - tr[3], di = ti[2] - ti[3];
    zr[0] = tr[0] + ar + br; zi[0] = ti[0] + ai + bi;
    const float m1r = tr[0] + C5A * ar + C5B * br, m1i = ti[0] + C5A * ai + C5B * bi;
    const float m2r = tr[0] + C5B * ar + C5A * br, m2i = ti[0] + C5B * ai + C5A * bi;
    const float n1r = SGN * (S5A * cr + S5B * dr), n1i = SGN * (S5A * ci + S5B * di);
    const float n2r = SGN * (S5B * cr - S5A * dr), n2i = SGN * (S5B * ci - S5A * di);
    zr[1] = m1r + n1i; zi[1] = m1i - n1r; zr[4] = m1r - n1i; zi[4] = m1i + n1r;
    zr[2] = m2r + n2i; zi[2] = m2i - n2r; zr[3] = m2r - n2i; zi[3] = m2i + n2r;
}
DEV void ln40(float (&v)[40]) {
    float s = 0.f;
#pragma unroll
    for (int i = 0; i < 40; i++) s += v[i];
#pragma unroll
    for (int o = 8; o; o >>= 1) s += __shfl_xor_sync(~0u, s, o);
    const float mean = s * (1.f / D_);
    float q = 0.f;
#pragma unroll
    for (int i = 0; i < 40; i++) { const float d = v[i] - mean; q += d * d; }
#pragma unroll
    for (int o = 8; o; o >>= 1) q += __shfl_xor_sync(~0u, q, o);
    const float mb = bf_round(mean);
    const float inv = 1.f / bf_round(sqrtf(bf_round(bf_round(q * (1.f / D_)) + 1e-5f)));
#pragma unroll
    for (int i = 0; i < 40; i++) v[i] = bf_round(v[i] - mb) * inv;
}
__global__ void __launch_bounds__(256) rowfft_kernel(const bf16* __restrict__ x0, bf16* __restrict__ x, const bf16* __restrict__ Wq,
                                                     const bf16* __restrict__ Wk, const bf16* __restrict__ Wv, int layer) {
    extern __shared__ __align__(1024) unsigned char smem[];
    const uint32_t sb = s2u(smem), sx = sb + 23552, sy = sx + 20480, bar = sy + 40960;
    const int tid = threadIdx.x, lane = tid & 31, q = lane & 3, blk = blockIdx.x, k2 = tid >> 2;
    if (tid == 0) TLI(800 + blk, 0, gtime());
    float twr[5], twi[5];
#pragma unroll
    for (int r = 1; r < 5; r++) { sincospif((float)(r * k2) * (-1.f / 320), &twi[r], &twr[r]); }
    uint32_t f[8][4];
#pragma unroll
    for (int ks = 0; ks < 8; ks++) { const uint4 u = g_f128[ks * 256 + tid]; f[ks][0] = u.x; f[ks][1] = u.y; f[ks][2] = u.z; f[ks][3] = u.w; }
    const bool split = blk * 16 >= S_ - YT_ROWS;
    if (tid == 0) {
        mbar_init(bar, 1);
        asm volatile("fence.mbarrier_init.release.cluster;" ::: "memory");
        mbar_expect(bar, split ? 61440 : 20480);
        if (split) bulk_g2s(sx, x0 + (size_t)blk * 16 * D_, 20480, bar);
    }
    __syncthreads();
    pdl_wait();
    pdl_launch();
    TLS(4 + 5 * layer);
    if (tid == 0) TLI(800 + blk, 1, gtime());
    if (tid == 0) {
        if (split) bulk_g2s(sy, g_yt + (layer * YT_ROWS + blk * 16 - (S_ - YT_ROWS)) * D_, 40960, bar);
        else bulk_g2s(sx, x + (size_t)blk * 16 * D_, 20480, bar);
    }
    mbar_wait(bar, 0);
    {
        const int rho = tid >> 4, j = tid & 15;
        float v[40];
#pragma unroll
        for (int i = 0; i < 5; i++) {
            uint32_t u[4];
            lds128(u, sx + tid * 80 + i * 16);
            if (split) {
                float p[8];
                lds128f(p, sy + tid * 160 + i * 32); lds128f(p + 4, sy + tid * 160 + i * 32 + 16);
#pragma unroll
                for (int k = 0; k < 4; k++) u[k] = resid(u[k], p[2 * k], p[2 * k + 1]);
                sts128(sx + tid * 80 + i * 16, u[0], u[1], u[2], u[3]);
            }
            unpack8(v + 8 * i, make_uint4(u[0], u[1], u[2], u[3]));
        }
        if (layer == 0 && tid < 12) prefetch_bulk((const char*)(tid < 4 ? Wk : tid < 8 ? Wq : Wv) + (blk * 4 + (tid & 3)) * 10240, 10240);
        ln40(v);
        const uint32_t a = sb + ((rho >> 1) & 1) * 2304 + j * 144 + (2 * (rho >> 2) + (rho & 1)) * 16;
#pragma unroll
        for (int r = 0; r < 5; r++)
            sts128(a + r * 4608, pack2(v[r], v[5 + r]), pack2(v[10 + r], v[15 + r]), pack2(v[20 + r], v[25 + r]), pack2(v[30 + r], v[35 + r]));
    }
    fence_async();
    __syncthreads();
    if (tid == 0) TLI(800 + blk, 2, gtime());
    if (tid == 0 && split) { bulk_s2g(x + (size_t)blk * 16 * D_, sx, 20480); bulk_commit(); }
    float acc[40];
    const u64 db = mkdesc(sb, 144, 2304);
    wg_fence();
    wgmma_n80_rs<0, 0>(acc, f[0], db);
#pragma unroll
    for (int ks = 1; ks < 8; ks++) wgmma_n80_rs<1, 0>(acc, f[ks], db + ks * 18);
    wg_commit();
    wg_wait<0>();
    unsigned char* zp = g_z + (blk >> 1) * 128 + ((((blk & 1) * 4 + q) ^ ((blk >> 1) & 7)) << 4);
    uint32_t o[5][4];
#pragma unroll
    for (int u = 0; u < 4; u++) {
        float tr[5], ti[5], zr[5], zi[5];
#pragma unroll
        for (int r = 0; r < 5; r++) {
            const float yr = acc[8 * r + 4 * (u >> 1) + (u & 1)], yi = k2 ? acc[8 * r + 4 * (u >> 1) + 2 + (u & 1)] : 0.f;
            tr[r] = r ? yr * twr[r] - yi * twi[r] : yr;
            ti[r] = r ? yr * twi[r] + yi * twr[r] : yi;
        }
        dft5<1>(tr, ti, zr, zi);
#pragma unroll
        for (int j = 0; j < 5; j++) o[j][u] = pack2(zr[j], j < 3 ? zi[j] : -zi[j]);
    }
#pragma unroll
    for (int j = 0; j < 5; j++)
        if (j < 3 || k2) *(uint4*)(zp + (64 * j + k2) * 8192) = make_uint4(o[j][0], o[j][1], o[j][2], o[j][3]);
    if (k2 == 0) {
#pragma unroll
        for (int u = 0; u < 4; u++) {
            float tr[5], ti[5], zr[5], zi[5];
            const float cr[5] = {1.f, -C5B, C5A, -C5A, C5B}, ci[5] = {0.f, -S5B, -S5A, -S5A, -S5B};
#pragma unroll
            for (int r = 0; r < 5; r++) { const float y = acc[8 * r + 4 * (u >> 1) + 2 + (u & 1)]; tr[r] = y * cr[r]; ti[r] = y * ci[r]; }
            dft5<1>(tr, ti, zr, zi);
            o[0][u] = pack2(zr[0], zi[0]); o[1][u] = pack2(zr[1], zi[1]); o[2][u] = pack2(zr[2], 0.f);
        }
        *(uint4*)(zp + 256 * 8192) = make_uint4(o[0][0], o[0][1], o[0][2], o[0][3]);
        *(uint4*)(zp + 192 * 8192) = make_uint4(o[1][0], o[1][1], o[1][2], o[1][3]);
        *(uint4*)(zp + 320 * 8192) = make_uint4(o[2][0], o[2][1], o[2][2], o[2][3]);
    }
    if (tid == 0) bulk_wait<0>();
    TLE(4 + 5 * layer);
    if (tid == 0) TLI(800 + blk, 3, gtime());
}

constexpr int CF_SMEM = 16384 + 3 * 16384 + 64;
__global__ void __launch_bounds__(384) colfft_kernel(int layer) {
    extern __shared__ __align__(1024) unsigned char smem[];
    const uint32_t sb = s2u(smem), bar = sb + 65536;
    const int tid = threadIdx.x, lane = tid & 31, q = lane & 3, wg = __shfl_sync(~0u, tid >> 7, 0), t = tid & 127, ka = t >> 2;
    const int col = blockIdx.x * 3 + wg;
    const uint32_t d0 = sb + 16384 + wg * 16384, d1 = d0 + 8192;
    if (tid == 0) {
        for (int i = 0; i < 4; i++) mbar_init(bar + 8 * i, 1);
        asm volatile("fence.mbarrier_init.release.cluster;" ::: "memory");
    }
    float twr[8], twi[8];
#pragma unroll
    for (int i = 0; i < 8; i++) sincospif((float)((4 * i + q) * (ka ? ka : -32)) * (1.f / 1024), &twi[i], &twr[i]);
    __syncthreads();
    if (tid == 0) { mbar_expect(bar + 24, 16384); bulk_g2s(sb, g_g32, 16384, bar + 24); }
    uint32_t f[4][4], w[16];
#pragma unroll
    for (int ks = 0; ks < 4; ks++) { const uint4 u = g_f64[ks * 128 + t]; f[ks][0] = u.x; f[ks][1] = u.y; f[ks][2] = u.z; f[ks][3] = u.w; }
#pragma unroll
    for (int i = 0; i < 4; i++) { const uint4 u = *(const uint4*)(g_wt + col * 8192 + i * 2048 + t * 16); w[4 * i] = u.x; w[4 * i + 1] = u.y; w[4 * i + 2] = u.z; w[4 * i + 3] = u.w; }
    pdl_wait();
    pdl_launch();
    TLS(5 + 5 * layer);
    if (t == 0) {
        mbar_expect(bar + 8 * wg, 8192);
        bulk_g2s(d0, g_z + col * 8192, 8192, bar + 8 * wg);
    }
    float acc[32];
    uint32_t a[4][4];
    mbar_wait(bar + 8 * wg, 0);
    {
        const u64 db = mkdesc(d0, 0, 1024) | SW128;
        wg_fence();
        wgmma_n64_rs<0, 1>(acc, f[0], db);
#pragma unroll
        for (int ks = 1; ks < 4; ks++) wgmma_n64_rs<1, 1>(acc, f[ks], db + ks * 128);
        wg_commit();
        wg_wait<0>();
    }
#pragma unroll
    for (int ks = 0; ks < 4; ks++) { const uint4 u = g_f64[512 + ks * 128 + t]; f[ks][0] = u.x; f[ks][1] = u.y; f[ks][2] = u.z; f[ks][3] = u.w; }
#pragma unroll
    for (int i = 0; i < 8; i++) {
        const float c0 = acc[4 * i], c1 = acc[4 * i + 1], c2 = acc[4 * i + 2], c3 = acc[4 * i + 3];
        const float pr = c0 + c3, pi = c1 - c2, nr = ka ? c0 - c3 : c2, ni = ka ? c1 + c2 : c3;
        a[i >> 1][2 * (i & 1)] = ka ? pack2(pr * twr[i] + pi * twi[i], pi * twr[i] - pr * twi[i]) : pack2(c0, c1);
        a[i >> 1][2 * (i & 1) + 1] = pack2(nr * twr[i] - ni * twi[i], ni * twr[i] + nr * twi[i]);
    }
    mbar_wait(bar + 24, 0);
    {
        const u64 db = mkdesc(sb, 128, 1024);
        wg_fence();
        wgmma_n64_rs<0, 0>(acc, a[0], db);
#pragma unroll
        for (int ks = 1; ks < 4; ks++) wgmma_n64_rs<1, 0>(acc, a[ks], db + ks * 16);
        wg_commit();
        wg_wait<0>();
    }
    constexpr float NORM = 1.f / (2048.f * 640.f);
#pragma unroll
    for (int i = 0; i < 16; i++) {
        const float zr = acc[2 * i] * NORM, zi = acc[2 * i + 1] * NORM, wr = bf_lo(w[i]), wi = bf_hi(w[i]);
        a[i >> 2][i & 3] = pack2(zr * wr - zi * wi, zr * wi + zi * wr);
    }
    {
        const u64 db = mkdesc(sb + 8192, 128, 1024);
        wg_fence();
        wgmma_n64_rs<0, 0>(acc, a[0], db);
#pragma unroll
        for (int ks = 1; ks < 4; ks++) wgmma_n64_rs<1, 0>(acc, a[ks], db + ks * 16);
        wg_commit();
        wg_wait<0>();
    }
    const uint32_t row = (t >> 5) * 2048 + (lane & 15) * 128;
#pragma unroll
    for (int i = 0; i < 8; i++) {
        const float c0 = acc[4 * i], c1 = acc[4 * i + 1], c2 = acc[4 * i + 2], c3 = acc[4 * i + 3];
        const float pr = c0 * twr[i] - c1 * twi[i], pi = c1 * twr[i] + c0 * twi[i];
        const float nr = c2 * twr[i] + c3 * twi[i], ni = c3 * twr[i] - c2 * twi[i];
        a[i >> 1][2 * (i & 1)] = ka ? pack2(pr + nr, pi + ni) : pack2(c0, c1);
        a[i >> 1][2 * (i & 1) + 1] = ka ? pack2(ni - pi, pr - nr) : pack2(nr, ni);
    }
#pragma unroll
    for (int i = 0; i < 4; i++) stsm4(d1 + row + (((2 * i + (lane >> 4)) ^ (lane & 7)) << 4), a[i][0], a[i][1], a[i][2], a[i][3]);
    fence_async();
    bar_sync(1 + wg, 128);
    {
        const u64 db = mkdesc(d1, 0, 1024) | SW128;
        wg_fence();
        wgmma_n64_rs<0, 1>(acc, f[0], db);
#pragma unroll
        for (int ks = 1; ks < 4; ks++) wgmma_n64_rs<1, 1>(acc, f[ks], db + ks * 128);
        wg_commit();
        wg_wait<0>();
    }
#pragma unroll
    for (int i = 0; i < 4; i++)
        stsm4(d0 + row + (((2 * i + (lane >> 4)) ^ (lane & 7)) << 4), pack2(acc[8 * i], acc[8 * i + 1]), pack2(acc[8 * i + 2], acc[8 * i + 3]),
              pack2(acc[8 * i + 4], acc[8 * i + 5]), pack2(acc[8 * i + 6], acc[8 * i + 7]));
    fence_async();
    bar_sync(1 + wg, 128);
    if (t == 0) {
        bulk_s2g(g_z + col * 8192, d0, 8192);
        asm volatile("cp.async.bulk.commit_group;" ::: "memory");
        asm volatile("cp.async.bulk.wait_group 0;" ::: "memory");
    }
    TLE(5 + 5 * layer);
}

__global__ void __launch_bounds__(256) rowifft_kernel(const bf16* __restrict__ x, bf16* __restrict__ out, int last) {
    extern __shared__ __align__(1024) unsigned char smem[];
    const uint32_t sb = s2u(smem), sx = sb + 20480, sy = sx + 20480, bar = sy + 16 * 1296;
    const int tid = threadIdx.x, lane = tid & 31, q = lane & 3, blk = blockIdx.x, k2 = tid >> 2, warp = tid >> 5;
    float twr[5], twi[5];
#pragma unroll
    for (int r = 1; r < 5; r++) { sincospif((float)(r * k2) * (1.f / 320), &twi[r], &twr[r]); twr[r] *= 2.f; twi[r] *= 2.f; }
    uint32_t f[8][4];
#pragma unroll
    for (int ks = 0; ks < 8; ks++) { const uint4 u = g_f128[2048 + ks * 256 + tid]; f[ks][0] = u.x; f[ks][1] = u.y; f[ks][2] = u.z; f[ks][3] = u.w; }
    if (tid == 0) {
        mbar_init(bar, 1);
        asm volatile("fence.mbarrier_init.release.cluster;" ::: "memory");
        mbar_expect(bar, 20480);
        bulk_g2s(sx, x + (size_t)blk * 16 * D_, 20480, bar);
    }
    pdl_wait();
    pdl_launch();
    TLS(6 + 5 * last);
    const unsigned char* zp = g_z + (blk >> 1) * 128 + ((((blk & 1) * 4 + q) ^ ((blk >> 1) & 7)) << 4);
    uint4 z[6];
#pragma unroll
    for (int j = 0; j < 5; j++) z[j] = *(const uint4*)(zp + (64 * j + k2) * 8192);
    z[5] = k2 ? make_uint4(0, 0, 0, 0) : *(const uint4*)(zp + 320 * 8192);
    float acc[40];
#pragma unroll
    for (int u = 0; u < 4; u++) {
        float yr[6], yi[6], tr[5], ti[5], zr[5], zi[5];
#pragma unroll
        for (int j = 0; j < 6; j++) { const uint32_t v = u == 0 ? z[j].x : u == 1 ? z[j].y : u == 2 ? z[j].z : z[j].w; yr[j] = bf_lo(v); yi[j] = bf_hi(v); }
#pragma unroll
        for (int j = 0; j < 5; j++) { tr[j] = yr[j]; ti[j] = j < 3 ? yi[j] : -yi[j]; }
        dft5<-1>(tr, ti, zr, zi);
        const float c1[5] = {1.f, C5A, C5B, C5B, C5A}, s1[5] = {0.f, S5A, S5B, -S5B, -S5A};
        const float c2[5] = {1.f, C5B, C5A, C5A, C5B}, s2[5] = {0.f, S5B, -S5A, S5A, -S5B};
        const float c3[5] = {1.f, -C5B, C5A, -C5A, C5B}, s3[5] = {0.f, S5B, S5A, S5A, S5B};
        const float c4[5] = {1.f, -C5A, C5B, -C5B, C5A}, s4[5] = {0.f, S5A, -S5B, -S5B, S5A};
#pragma unroll
        for (int r = 0; r < 5; r++) {
            float er = r ? zr[r] * twr[r] - zi[r] * twi[r] : 2.f * zr[0], ei = r ? zr[r] * twi[r] + zi[r] * twr[r] : 2.f * zi[0];
            if (k2 == 0) {
                er = yr[0] + 2.f * (yr[1] * c1[r] - yi[1] * s1[r] + yr[2] * c2[r] - yi[2] * s2[r]);
                ei = (r & 1 ? -yr[5] : yr[5]) + 2.f * (yr[4] * c3[r] - yi[4] * s3[r] + yr[3] * c4[r] - yi[3] * s4[r]);
            }
            acc[8 * r + 4 * (u >> 1) + (u & 1)] = er;
            acc[8 * r + 4 * (u >> 1) + 2 + (u & 1)] = ei;
        }
    }
#pragma unroll
    for (int r = 0; r < 5; r++)
        stsm4(sb + (2 * warp + ((lane >> 3) & 1)) * 1280 + (2 * r + (lane >> 4)) * 128 + (lane & 7) * 16, pack2(acc[8 * r], acc[8 * r + 1]),
              pack2(acc[8 * r + 2], acc[8 * r + 3]), pack2(acc[8 * r + 4], acc[8 * r + 5]), pack2(acc[8 * r + 6], acc[8 * r + 7]));
    fence_async();
    __syncthreads();
    const u64 db = mkdesc(sb, 1280, 128);
    wg_fence();
    wgmma_n80_rs<0, 1>(acc, f[0], db);
#pragma unroll
    for (int ks = 1; ks < 8; ks++) wgmma_n80_rs<1, 1>(acc, f[ks], db + ks * 160);
    wg_commit();
    wg_wait<0>();
#pragma unroll
    for (int u = 0; u < 4; u++) {
        float e[10];
#pragma unroll
        for (int r = 0; r < 5; r++) { e[r] = acc[8 * r + 4 * (u >> 1) + (u & 1)]; e[5 + r] = acc[8 * r + 4 * (u >> 1) + 2 + (u & 1)]; }
#pragma unroll
        for (int i = 0; i < 5; i++) sts32(sy + (4 * q + u) * 1296 + k2 * 20 + i * 4, pack2(e[2 * i], e[2 * i + 1]));
    }
    __syncthreads();
    const int rho = tid >> 4, j = tid & 15;
    float v[40];
    mbar_wait(bar, 0);
#pragma unroll
    for (int i = 0; i < 5; i++) {
        uint32_t y[4], u[4];
        lds128(y, sy + rho * 1296 + j * 80 + i * 16);
        lds128(u, sx + tid * 80 + i * 16);
#pragma unroll
        for (int k = 0; k < 4; k++) u[k] = pack2(bf_lo(u[k]) + bf_lo(y[k]), bf_hi(u[k]) + bf_hi(y[k]));
        sts128(sx + tid * 80 + i * 16, u[0], u[1], u[2], u[3]);
        unpack8(v + 8 * i, make_uint4(u[0], u[1], u[2], u[3]));
    }
    if (!last) {
        ln40(v);
#pragma unroll
        for (int i = 0; i < 5; i++) {
            const int c = j * 5 + i;
            sts128(sb + (c >> 3) * 2048 + rho * 128 + (((c ^ rho) & 7) << 4), pack2(v[8 * i], v[8 * i + 1]), pack2(v[8 * i + 2], v[8 * i + 3]),
                   pack2(v[8 * i + 4], v[8 * i + 5]), pack2(v[8 * i + 6], v[8 * i + 7]));
        }
    }
    fence_async();
    __syncthreads();
    if (lane == 0) {
        if (warp == 7) bulk_s2g(out + (size_t)blk * 16 * D_, sx, 20480);
        else if (!last && warp < 5) {
            unsigned char* p = g_xn + (blk >> 1) * 40960 + warp * 8192 + (blk & 1) * 2048;
            bulk_s2g(p, sb + warp * 4096, 2048);
            bulk_s2g(p + 4096, sb + warp * 4096 + 2048, 2048);
        }
        bulk_commit();
        bulk_wait<0>();
    }
    TLE(6 + 5 * last);
}

namespace rec {
#define NSA 5
#define NSB 2
#define REG0 184
#define REG1 184
constexpr int NS = NSA, NS0 = NSB;
constexpr int OFF_X = 0;
constexpr int OFF_WO = 81920;
constexpr int OFF_WS = OFF_WO + 57344;
constexpr int OFF_MEMB = OFF_WS + (NS + NS0) * 2048;
constexpr int OFF_VX = OFF_MEMB + 10240;
constexpr int OFF_VM = OFF_VX + 16384;
constexpr int OFF_Q = OFF_VM + 4096;
constexpr int OFF_K = OFF_Q + 10240;
constexpr int OFF_PX = OFF_K + 10240;
constexpr int OFF_OST = OFF_PX + 2560;
constexpr int OFF_PT = OFF_OST + 4096;
constexpr int OFF_PS = OFF_PT + 1536;
constexpr int OFF_OB = OFF_PS + 1280;
constexpr int OFF_MX = OFF_OB + 2048;
constexpr int OFF_BAR = OFF_MX + 64;
constexpr int OFF_PROF = OFF_BAR + 256;
constexpr int SMEM = OFF_PROF + 4096 > wk::SMEM ? OFF_PROF + 4096 : wk::SMEM;
enum { B_XT = 0, B_KX = 2, B_VX = 4, B_XD = 6, B_X1 = 8, B_WN = 10, B_PXF = 12, B_PXE = 13, B_FIN = 14, B_ST = 15 };
enum { NB_QK = 2, NB_WIN = 3, NB_ATT = 4, NB_X = 5, NB_PRO = 6, NB_W1 = 7, NB_MEM = 8  , NB_LD = 13   };
#define NOX 0
#define NW1 10
#define NW1B 8
constexpr int RING = 8;
template <int N> struct IC { static constexpr int value = N; };
template <int N, int I = 0, class F> DEV void static_for(F&& f) { if constexpr (I < N) { f(IC<I>{}); static_for<N, I + 1>(f); } }
constexpr float SM_SCALE = 0.08838834764831845f * 1.4426950408889634f;
}

__global__ void __launch_bounds__(512, 1) rec_kernel(const __grid_constant__ Maps maps, const bf16* __restrict__ x, bf16* __restrict__ x1, const bf16* __restrict__ mem0, const bf16* __restrict__ Wq, const bf16* __restrict__ Wk,
                                                     const bf16* __restrict__ Wv, const bf16* __restrict__ Wo, int layer, int delay, int delay2) {
    using namespace rec;
    extern __shared__ __align__(1024) unsigned char smem[];
    const uint32_t sb = s2u(smem);
    if (blockIdx.x >= 3 * H_) {
        pdl_wait();
        pdl_launch();
        worker(sb, maps, x, x1, layer);
        return;
    }
    const int tid = threadIdx.x, lane = tid & 31, warp = __shfl_sync(~0u, tid >> 5, 0);
    const int g = lane >> 2, q = lane & 3;
    const int h = blockIdx.x / 3;
    const uint32_t bar = sb + OFF_BAR;
    STAMP(2 * layer);
    TLS(2 + 5 * layer);
    if (tid == 0) {
        for (int i = 0; i < 2; i++) {
            mbar_init(bar + 8 * (B_XT + i), 1); mbar_init(bar + 8 * (B_KX + i), 4); mbar_init(bar + 8 * (B_VX + i), 1);
            mbar_init(bar + 8 * (B_XD + i), 8); mbar_init(bar + 8 * (B_X1 + i), 1); mbar_init(bar + 8 * (B_WN + i), 4);
        }
        mbar_init(bar + 8 * B_PXF, 1); mbar_init(bar + 8 * B_PXE, 2); mbar_init(bar + 8 * B_ST, 2);
        mbar_init(bar + 8 * B_FIN, 48);
        sts32(sb + OFF_MX + 32, 0); sts32(sb + OFF_MX + 36, 0);
        asm volatile("fence.mbarrier_init.release.cluster;" ::: "memory");
    }
    asm volatile("barrier.cluster.arrive.aligned; barrier.cluster.wait.aligned;" ::: "memory");
    const bool never = delay < 0;

    if (warp < 8) {
        auto role = [&](auto XP) {
            constexpr int wg = XP.value, NSW = wg ? NS : NS0;
            asm volatile("setmaxnreg.inc.sync.aligned.u32 %0;" ::"n"(wg ? REG1 : REG0));
            const uint32_t rank = cta_rank();
            uint32_t a[40 - NSW][4];
            const uint32_t l16 = opaque(sb + lane * 16);
            uint32_t wsa = wg ? opaque(sb + OFF_WS + (warp & 3) * 512 + (lane & 7) * 16 + ((lane >> 3) & 1) * 256 + (lane >> 4) * 128) : 0;
            uint32_t dst = opaque(rank < 2 ? sb + OFF_Q + wg * 10240 + (warp & 3) * 256 + (lane & 15) * 16 + (lane >> 4) * 1024
                                           : sb + OFF_VM + warp * 256 + lane * 4);
            int dstep = rank < 2 ? 5120 : 2048;
            uint32_t& sfd = wg ? wsa : dst;
            auto ws_addr = [&](int ks) { return wg ? wsa + ks * 2048 : l16 + OFF_WS + (NS + ks) * 2048 + warp * 512; };
            {
                const int t = tid & 127;
                const bf16* src = (rank == 2 ? Wv + wg * 64 : (wg ? Wk : Wq) + rank * 64) + h * E_ + (size_t)(t >> 3) * 4096 + (t & 7) * 8;
                const uint32_t stg = sb + (wg ? OFF_VX : OFF_X + 40960);
                const uint32_t sdst = stg + (t >> 3) * 128 + (((t & 7) ^ ((t >> 3) & 7)) << 4);
                const uint32_t ra = stg + ((lane >> 4) * 8 + (lane & 7)) * 128 + (((2 * (warp & 3) + ((lane >> 3) & 1)) ^ (lane & 7)) << 4);
                auto issue = [&](int rd) {
#pragma unroll
                    for (int i = 0; i < 10; i++) cp16(sdst + (rd & 1) * 20480 + i * 2048, src + (size_t)(rd * 160 + i * 16) * 4096);
                    cp_commit();
                };
                issue(0); issue(1);
                pdl_wait();
                pdl_launch();
#pragma unroll
                for (int rd = 0; rd < 4; rd++) {
                    if (rd < 3) cp_wait<1>(); else cp_wait<0>();
                    bar_sync(NB_LD + wg, 128);
#pragma unroll
                    for (int i = 0; i < 10; i++) {
                        const int ks = rd * 10 + i;
                        if (ks < NSW) {
                            uint32_t f[4];
                            ldsm4t(f, ra + i * 2048);
                            stsm4(ws_addr(ks), f[0], f[1], f[2], f[3]);
                        } else ldsm4t(a[ks - NSW], ra + (rd & 1) * 20480 + i * 2048);
                    }
                    if (rd < 2) { bar_sync(NB_LD + wg, 128); issue(rd + 2); }
                }
                fence_async();
                bar_sync(NB_PRO, 288);
            }
            float acc[16];
            uint32_t xlo = (uint32_t)mkdesc(sb + OFF_X, 0, 0);
            const uint32_t xtog = xlo ^ (uint32_t)mkdesc(sb + OFF_X + 40960, 0, 0);
            uint32_t p8 = 0;
            auto xproj = [&](auto K1, auto K0) {
                const u64 desc = (u64)xlo | (64ull << 32) | SW128, da = mkdesc(sb + OFF_WS, 128, 256);
                wg_fence();
#pragma unroll
                for (int ks = K1.value - 1; ks >= K0.value; ks--) {
                    const u64 db = desc + (ks >> 2) * 256 + (ks & 3) * 2;
                    if (ks == 39) wgmma_n32_rs<0>(acc, a[ks - NSW], db);
                    else if (NOX) {}
                    else if (ks < NSW) wgmma_n32_ss<1>(acc, da + ks * 128, db);
                    else wgmma_n32_rs<1>(acc, a[ks - NSW], db);
                }
                wg_commit();
            };
            auto xstore = [&]() {
                wg_wait<0>();
                uint32_t pk[8];
#pragma unroll
                for (int i = 0; i < 8; i++) pk[i] = pack2(acc[2 * i], acc[2 * i + 1]);
                if (rank < 2) {
                    stsm4t(dst + 1024, pk[0], pk[1], pk[2], pk[3]);
                    stsm4t(dst + 3072, pk[4], pk[5], pk[6], pk[7]);
                } else {
                    const uint32_t la = wsa + (wsa & 256) + (OFF_VX + 4096 - OFF_WS) + (warp & 3) * 512 + p8 * 1024;
                    stsm4(la, pk[0], pk[1], pk[2], pk[3]);
                    stsm4(la + 256, pk[4], pk[5], pk[6], pk[7]);
                    fence_async();
                }
                mbar_arrive_elect(bar + 8 * B_KX + p8);
            };
            bar_sync(NB_LD, 288);
            if (wg) {
                xproj(IC<40>{}, IC<0>{});
                xstore();
            }
            for (int s = 0;; s++) {
                float d0[4] = {0.f, 0.f, 0.f, 0.f}, d1[4] = {0.f, 0.f, 0.f, 0.f};
                uint32_t t[NSW][4], b[20][4];
#pragma unroll
                for (int ks = 0; ks < NSW; ks++) ldsm4(t[ks], ws_addr(ks));
                bar_sync(NB_MEM, 384);
                lds128(b[0], l16 + OFF_MEMB); lds128(b[1], l16 + OFF_MEMB + 512); lds128(b[2], l16 + OFF_MEMB + 1024);
                xlo ^= xtog;
                const uint32_t xb0 = mapa(bar + 8 * B_X1 + p8, 0), xb1 = mapa(bar + 8 * B_X1 + p8, 1);
                SFENCE();
                float is;
#pragma unroll
                for (int kp = 0; kp < 20; kp++) {
#pragma unroll
                    for (int j = 0; j < 2; j++) {
                        const int ks = 2 * kp + j;
                        const uint32_t* f = ks < NSW ? t[ks] : a[ks - NSW];
                        mma16(j ? d1 : d0, f[0], f[1], f[2], f[3], b[kp][2 * j], b[kp][2 * j + 1]);
                    }
                    if (kp == 0 && warp == 4) PROFT(0);
                    if (kp < 16 && (kp & 3) == 1) bar_sync(NB_MEM + 1 + (kp >> 2), 384);
                    if (kp + 3 < 20) lds128(b[kp + 3], l16 + OFF_MEMB + (kp + 3) * 512);
                    if (kp == 17) is = lds32f(sb + OFF_MX + 16);
                    if (kp < 18) SFENCE();
                }
                const uint32_t p0 = pack2((d0[0] + d1[0]) * is, (d0[1] + d1[1]) * is), p1 = pack2((d0[2] + d1[2]) * is, (d0[3] + d1[3]) * is);
                if (rank < 2) {
                    stsm2t(dst, p0, p1);
                } else {
                    st_async1(mapa(dst, 0), p0, xb0); st_async1(mapa(dst, 1), p0, xb1);
                    st_async1(mapa(dst + 128, 0), p1, xb0); st_async1(mapa(dst + 128, 1), p1, xb1);
                    sts32(dst, p0); sts32(dst + 128, p1);
                }
                bar_arrive(NB_QK, 384);
                if (warp == 4) PROFT(1);
                dst += dstep; dstep = -dstep; p8 ^= 8;
                if (wg) {
                    if (rank < 2) bar_sync(NB_W1, 384); else bar_sync(NB_W1, 352);
                    if (s == NSEG - 1) break;
                    xproj(IC<40>{}, IC<40 - NW1>{});
                    wg_wait<0>();
                    if (warp == 4) PROFT(15);
                    if (NW1B > 0) {
                        if (rank < 2) bar_sync(NB_WIN, 256);
                        xproj(IC<40 - NW1>{}, IC<40 - NW1 - NW1B>{});
                        wg_wait<0>();
                        if (rank == 2) bar_sync(NB_WIN, 256);
                    } else bar_sync(NB_WIN, 256);
                    xproj(IC<40 - NW1 - NW1B>{}, IC<0>{});
                    xstore();
                    if (warp == 4) PROFT(3);
                } else if (s == NSEG - 1) break;
            }
        };
        if (warp < 4) role(IC<0>{}); else role(IC<1>{});
    } else if (warp < 12) {
        asm volatile("setmaxnreg.dec.sync.aligned.u32 96;");
        const uint32_t rank = cta_rank();
        const int w = warp - 8;
        const bool four = w == 0 || (w == 1 && rank == 0);
        const int tile3 = rank == 0 ? 36 + w : 37 + rank;
        uint32_t amax = 0;
#pragma unroll
        for (int it = 0; it < 5; it++) {
            const int kp = it * 4 + w;
            const bf16* p = mem0 + g * D_ + kp * 32 + 2 * q;
            uint32_t b0 = ldg32(p), b1 = ldg32(p + 8), b2 = ldg32(p + 16), b3 = ldg32(p + 24);
            sts128(sb + OFF_MEMB + kp * 512 + lane * 16, b0, b1, b2, b3);
            amax = absmax2(amax, absmax2(absmax2(b0, b1), absmax2(b2, b3)));
        }
        if (tid == 256) sts32(sb + OFF_MX + 16, 0x3f800000u);
        bar_arrive(NB_MEM, 384); bar_arrive(NB_MEM + 1, 384); bar_arrive(NB_MEM + 2, 384); bar_arrive(NB_MEM + 3, 384); bar_arrive(NB_MEM + 4, 384);
        {
            const int t = tid & 127;
#pragma unroll
            for (int r = 0; r < 4; r++) {
                const int col = r < 3 ? 192 * r + 64 * rank : (rank ? 592 + 16 * rank : 576);
                const bf16* src = Wo + (size_t)(h * E_) * D_ + col;
                if (r < 3) {
#pragma unroll
                    for (int i = 0; i < 8; i++) {
                        const int e = i * 16 + (t >> 3);
                        cp16(sb + OFF_WO + r * 16384 + e * 128 + (((t & 7) ^ (e & 6)) << 4), src + e * D_ + (t & 7) * 8);
                    }
                } else {
#pragma unroll
                    for (int i = 0; i < 4; i++) {
                        const int e = i * 32 + (t >> 2);
                        if (rank == 0 || (t & 2) == 0) cp16(sb + OFF_WO + r * 16384 + e * 64 + (t & 3) * 16, src + e * D_ + (t & 3) * 8);
                    }
                }
            }
            cp_commit();
            pdl_wait();
            pdl_launch();
            cp_wait<0>();
            bar_sync(NB_ATT, 128);
#pragma unroll 1
            for (int r = 0; r < 4; r++) {
                uint32_t u[8][4];
                const uint32_t rs = r < 3 ? 128 : 64;
                const uint32_t p = sb + OFF_WO + r * 16384 + 2 * q * rs + (((2 * w + (g & 1)) ^ (r < 3 ? 2 * q : 0)) << 4) + (g >> 1) * 4;
                if (r < 3 || four) {
#pragma unroll
                    for (int ks = 0; ks < 8; ks++)
#pragma unroll
                        for (int j = 0; j < 4; j++) u[ks][j] = lds32(p + (16 * ks + (j & 1) * 8 + (j >> 1)) * rs);
                }
                bar_sync(NB_ATT, 128);
                if (r < 3 || four) {
#pragma unroll
                    for (int ks = 0; ks < 8; ks++)
                        sts128(sb + OFF_WO + (r * 4 + w) * 4096 + ks * 512 + lane * 16, prmt(u[ks][0], u[ks][2], 0x5410), prmt(u[ks][0], u[ks][2], 0x7632),
                               prmt(u[ks][1], u[ks][3], 0x5410), prmt(u[ks][1], u[ks][3], 0x7632));
                }
            }
        }
        float cw;
        {
            const float4 a = ((const float4*)g_nrm)[lane], c = ((const float4*)g_nrm)[32 + lane];
            float sm = sqrtf((a.x + a.y) + (a.z + a.w)) * sqrtf((c.x + c.y) + (c.z + c.w)), mxv = sm;
#pragma unroll
            for (int o = 16; o; o >>= 1) { sm += __shfl_xor_sync(~0u, sm, o); mxv = fmaxf(mxv, __shfl_xor_sync(~0u, mxv, o)); }
            cw = 26.5f * fmaxf(sm, 8.f * mxv);
        }
        const uint32_t l16 = opaque(sb + lane * 16), l4 = opaque(sb + OFF_PS + rank * 512 + lane * 4);
        uint32_t lq = opaque(sb + OFF_Q + (lane & 7) * 16 + ((lane >> 3) & 1) * 256 + (lane >> 4) * 128);
        const uint32_t lv = opaque(sb + OFF_VX + w * 2048 + (lane & 7) * 16 + ((lane >> 3) & 1) * 512 + (lane >> 4) * 128);
        uint32_t& sfd = lq;
        const bool t0 = tid == 256;
        const char* rp = (const char*)(g_acc + layer * ACC_LAYER) + (4 * rank + w) * 4096 + opaque((q >> 1) * 1024 + ((q & 1) * 8 + g) * 8);
        const char* lp = (const char*)(g_acc + layer * ACC_LAYER) + opaque(w * 8192 + (2 * (g & 1) + (g >> 2)) * 1024 + (((g >> 1) & 1) * 8 + 2 * q) * 8);
        const int t3off = (tile3 - 4 * rank - w) * 4096;
        float isig = 1.f;
        if (t0) {
            mbar_expect(bar + 8 * B_X1, rank < 2 ? 3328 : 1280);
            mbar_expect(bar + 8 * B_VX, rank < 2 ? 8192 : 4096);
        }
        for (int s = 0; s < NSEG - 1; s++) {
            const int pb = s & 1;
            const uint32_t x1 = bar + 8 * (B_X1 + pb);
            sts32(sb + OFF_MX + w * 4, __reduce_max_sync(~0u, max(amax & 0x7fff0000u, (amax << 16) & 0x7fff0000u)));
            if (rank < 2) {
                uint32_t kf[8], qf[8];
                const uint32_t ka = l16 + OFF_K + pb * 5120, qa = lq + pb * 5120;
                mbar_wait(bar + 8 * (B_KX + pb), (s >> 1) & 1);
                ldsm4(kf, ka + (1 + w) * 1024); ldsm4(kf + 4, ka + (1 + w) * 1024 + 512);
                const uint32_t pa = l4 + w * 128;
                const uint32_t pa0 = mapa(pa, rank ^ 1), pa1 = mapa(pa, 2), pa2 = mapa(pa, rank);
                const uint32_t xb0 = mapa(x1, rank ^ 1), xb1 = mapa(x1, 2), xb2 = mapa(x1, rank);
                bar_sync(NB_QK, 384);
                ldsm4(qf, qa); ldsm4(qf + 4, qa + 512);
                float c0[4] = {0.f, 0.f, 0.f, 0.f}, c1[4] = {0.f, 0.f, 0.f, 0.f}, c2[4] = {0.f, 0.f, 0.f, 0.f}, c3[4] = {0.f, 0.f, 0.f, 0.f};
                if (w == 3) {
                    uint32_t mf[8];
                    ldsm4(mf, ka); ldsm4(mf + 4, ka + 512);
                    mma16(c0, qf[0], qf[1], qf[2], qf[3], kf[0], kf[1]); mma16(c1, qf[0], qf[1], qf[2], qf[3], kf[2], kf[3]);
                    mma16(c2, qf[0], qf[1], qf[2], qf[3], mf[0], mf[1]); mma16(c3, qf[0], qf[1], qf[2], qf[3], mf[2], mf[3]);
                    mma16(c0, qf[4], qf[5], qf[6], qf[7], kf[4], kf[5]); mma16(c1, qf[4], qf[5], qf[6], qf[7], kf[6], kf[7]);
                    mma16(c2, qf[4], qf[5], qf[6], qf[7], mf[4], mf[5]); mma16(c3, qf[4], qf[5], qf[6], qf[7], mf[6], mf[7]);
                    bar_arrive(NB_W1, 384);
                    const uint32_t y = pack2(c0[0] + c1[2], c0[1] + c1[3]), z = pack2(c2[0] + c3[2], c2[1] + c3[3]);
                    const uint32_t pm = l4 + 1024 - rank * 384;
                    st_async1(pa0, y, xb0); st_async1(pa1, y, xb1);
                    st_async1(mapa(pm, rank ^ 1), z, xb0); st_async1(mapa(pm, 2), z, xb1);
                    st_async1(pa2, y, xb2); st_async1(mapa(pm, rank), z, xb2);
                } else {
                    mma16(c0, qf[0], qf[1], qf[2], qf[3], kf[0], kf[1]); mma16(c1, qf[0], qf[1], qf[2], qf[3], kf[2], kf[3]);
                    mma16(c2, qf[4], qf[5], qf[6], qf[7], kf[4], kf[5]); mma16(c3, qf[4], qf[5], qf[6], qf[7], kf[6], kf[7]);
                    bar_arrive(NB_W1, 384);
                    const uint32_t y = pack2((c0[0] + c1[2]) + (c2[0] + c3[2]), (c0[1] + c1[3]) + (c2[1] + c3[3]));
                    st_async1(pa0, y, xb0); st_async1(pa1, y, xb1); st_async1(pa2, y, xb2);
                }
                if (w == 0) PROFT(4);
            } else {
                bar_sync(NB_QK, 384);
                bar_arrive(NB_W1, 352);
            }
            mbar_wait(bar + 8 * (B_VX + pb), (s >> 1) & 1);
            float m4[4];
            lds128f(m4, sb + OFF_MX);
            uint32_t wf[RING][4], vf[2][2][4], vm[4];
#pragma unroll
            for (int t = 0; t < 2; t++)
#pragma unroll
                for (int j = 0; j < 2; j++) ldsm4(vf[t][j], lv + pb * 8192 + t * 1024 + j * 256);
            float sig;
            {
                const float bound = cw * fmaxf(fmaxf(fmaxf(m4[0], m4[1]), fmaxf(m4[2], m4[3])) * isig, 1.f);
                const uint32_t e = max((__float_as_uint(bound) >> 23) & 255u, 31u);
                sig = __uint_as_float((278u - e) << 23);
                isig = __uint_as_float((e - 30u) << 23);
            }
            if (t0) sts32(sb + OFF_MX + 16, __float_as_uint(isig));
            const uint32_t vma = l16 + OFF_VM + pb * 2048 + w * 512;
            if (w == 0) PROFT(5);
            mbar_wait(x1, (s >> 1) & 1);
            if (w == 0) PROFT(6);
            float sc[10];
            {
                uint32_t u[4], v[4], m[2];
                ldsm4(u, l16 + OFF_PS); ldsm4(v, l16 + OFF_PS + 512); ldsm2(m, l16 + OFF_PS + 1024);
                ldsm4(vm, vma);
                SFENCE();
#pragma unroll
                for (int i = 0; i < 4; i++) { sc[2 * i] = bf_lo(u[i]) + bf_lo(v[i]); sc[2 * i + 1] = bf_hi(u[i]) + bf_hi(v[i]); }
                sc[8] = bf_lo(m[0]) + bf_lo(m[1]); sc[9] = bf_hi(m[0]) + bf_hi(m[1]);
            }
            float mx = fmaxf(fmaxf(fmaxf(fmaxf(sc[0], sc[1]), fmaxf(sc[2], sc[3])), fmaxf(fmaxf(sc[4], sc[5]), fmaxf(sc[6], sc[7]))), fmaxf(sc[8], sc[9]));
            {
                float m1 = __shfl_xor_sync(~0u, mx, 1), m2 = __shfl_xor_sync(~0u, mx, 2), m3 = __shfl_xor_sync(~0u, mx, 3);
                SFENCE();
                mx = fmaxf(fmaxf(mx, m1), fmaxf(m2, m3)) * SM_SCALE;
            }
            auto fetch = [&](int i) { lds128(wf[i % RING], l16 + OFF_WO + ((i >> 3) * 4 + w) * 4096 + (i & 7) * 512); };
            float o0[4] = {0.f, 0.f, 0.f, 0.f}, o1[4] = {0.f, 0.f, 0.f, 0.f}, rs[4] = {0.f, 0.f, 0.f, 0.f};
            constexpr uint32_t ONE = 0x3f803f80u;
            sc[8] = ex2(fmaf(sc[8], SM_SCALE, -mx)); sc[9] = ex2(fmaf(sc[9], SM_SCALE, -mx));
#pragma unroll
            for (int i = 0; i < 4; i++) sc[i] = ex2(fmaf(sc[i], SM_SCALE, -mx));
#pragma unroll
            for (int i = 0; i < RING; i++) fetch(i);
            SFENCE();
            {
                const uint32_t p = pack2(sc[8], sc[9]);
                mma8(o0, vm[0], vm[1], p);
                mma8(o1, vm[2], vm[3], p);
                mma8(rs, ONE, ONE, p);
            }
#pragma unroll
            for (int i = 4; i < 8; i++) sc[i] = ex2(fmaf(sc[i], SM_SCALE, -mx));
            SFENCE();
#pragma unroll
            for (int j = 0; j < 2; j++) {
                const uint32_t p0 = pack2(sc[4 * j], sc[4 * j + 1]), p1 = pack2(sc[4 * j + 2], sc[4 * j + 3]);
                mma16(o0, vf[0][j][0], vf[0][j][1], vf[0][j][2], vf[0][j][3], p0, p1);
                mma16(o1, vf[1][j][0], vf[1][j][1], vf[1][j][2], vf[1][j][3], p0, p1);
                mma16(rs, ONE, ONE, ONE, ONE, p0, p1);
                SFENCE();
            }
            stsm4t(l16 + OFF_OB + w * 512, pack2(o0[0], o0[1]), pack2(o0[2], o0[3]), pack2(o1[0], o1[1]), pack2(o1[2], o1[3]));
            bar_sync(NB_ATT, 128);
            uint32_t ob[16];
#pragma unroll
            for (int j = 0; j < 4; j++) ldsm4(ob + 4 * j, l16 + OFF_OB + j * 512);
            SFENCE();
            const float sg0 = rcp(rs[0]) * sig, sg1 = rcp(rs[1]) * sig;
            SFENCE();
            uint32_t tr;
            auto tiles = [&](auto NT) {
#pragma unroll
                for (int r = 0; r < NT.value; r++) {
                    float c[4][4];
#pragma unroll
                    for (int i = 0; i < 4; i++) c[i][0] = c[i][1] = c[i][2] = c[i][3] = 0.f;
#pragma unroll
                    for (int ks = 0; ks < 8; ks++) {
                        const uint32_t* f = wf[(8 * r + ks) % RING];
                        mma16(c[ks & 3], f[0], f[1], f[2], f[3], ob[2 * ks], ob[2 * ks + 1]);
                        if ((ks & 3) == 3) {
                            SFENCE();
#pragma unroll
                            for (int i = 8 * r + ks - 3 + RING; i <= 8 * r + ks + RING; i++) if (i < 8 * NT.value) fetch(i);
                        }
                    }
                    SFENCE();
                    uint32_t v[4];
#pragma unroll
                    for (int i = 0; i < 4; i++)
                        v[i] = (__float_as_uint(fmaf((c[0][i] + c[1][i]) + (c[2][i] + c[3][i]), i & 1 ? sg1 : sg0, 12582912.f)) << 6) + (i < 2);
                    const char* p = r < 3 ? rp + r * 49152 : rp + t3off;
                    red_add64((u64*)p, v[0], v[2]);
                    red_add64((u64*)(p + 2048), v[1], v[3]);
                    if (r == 0) {
                        tr = clk();
                        if (w == 0) PROFT(7);
                        if (w == 0) GPROF(4, 0);
                    }
                }
            };
            if (four) tiles(IC<4>{}); else tiles(IC<3>{});
            bar_arrive(NB_WIN, 256);
            mbar_arrive_elect(bar + 8 * (B_WN + pb));
            if (w == 0) PROFT(8);
            if (t0) {
                if (rank < 2 || s < NSEG - 2) mbar_expect(bar + 8 * (B_VX + (pb ^ 1)), rank < 2 ? 8192 : 4096);
                mbar_expect(bar + 8 * (B_X1 + (pb ^ 1)), (rank < 2 ? 2048 : 0) + (s < NSEG - 2 ? 1280 : 0));
            }
            u64 y[20];
            while (clk() - tr < (uint32_t)delay) {}
#pragma unroll
            for (int i = 0; i < 10; i++) ld_acc0(y[2 * i], y[2 * i + 1], lp + (i >> 1) * 32768 + (i & 1) * 4096);
            if (w == 0) PROFT(9);
            uint32_t nretry = 0, b[20];
            bool done[5] = {false, false, false, false, false};
            auto publish = [&](auto FIRST) {
                uint32_t ok = 32u, late = 32u;
                static_for<5>([&](auto IT) {
                    constexpr int it = IT.value;
                    if (it == 2) late = and3((uint32_t)y[8], (uint32_t)y[10], (uint32_t)y[12]);
                    else if (it == 3) late &= and3((uint32_t)y[14], (uint32_t)y[16], (uint32_t)y[18]);
                    else ok = and3(ok, (uint32_t)y[4 * it], it == 4 ? late : (uint32_t)y[4 * it + 2]);
                    if (FIRST.value && it < 4) SFENCE();
                    if (it == 2 || it == 3) ok = and3(ok, (uint32_t)y[4 * it], (uint32_t)y[4 * it + 2]);
                    ok = and3(ok, (uint32_t)y[4 * it + 1], (uint32_t)y[4 * it + 3]);
                    const bool all = __all_sync(~0u, ok);
#pragma unroll
                    for (int j = 0; j < 4; j++) {
                        const u64 z = y[4 * it + j];
                        b[4 * it + j] = pack2((float)(int)(uint32_t)z, (float)(int)(uint32_t)(z >> 32));
                    }
                    sts128(l16 + OFF_MEMB + (4 * it + w) * 512, b[4 * it], b[4 * it + 1], b[4 * it + 2], b[4 * it + 3]);
                    bar_arrive_if<NB_MEM + it, 384>(all && (FIRST.value || !done[it]));
                    done[it] = all;
                    if (FIRST.value) SFENCE();
                    if (FIRST.value && it == 0 && w == 0) PROFT(10);
                });
            };
            publish(IC<1>{});
            while (!done[4]) {
                if (++nretry > SPIN_LIMIT) die();
#pragma unroll
                for (int i = 0; i < 10; i++) ld_acc(y[2 * i], y[2 * i + 1], lp + (i >> 1) * 32768 + (i & 1) * 4096);
                publish(IC<0>{});
            }
            if (w == 0) PROFT(11);
            amax = b[0];
#pragma unroll
            for (int i = 1; i < 19; i += 2) amax = absmax2(amax, absmax2(b[i], b[i + 1]));
            amax = absmax2(amax, b[19]);
            GPROF(w, nretry);
            const int adv = (s & 7) == 7 ? 163840 - 896 : 128;
            rp += adv; lp += adv;
        }
        bar_sync(NB_QK, 384);
        if (rank < 2) bar_arrive(NB_W1, 384); else bar_arrive(NB_W1, 352);
    } else {
        asm volatile("setmaxnreg.dec.sync.aligned.u32 48;");
        const uint32_t rank = cta_rank();
        const int w = warp - 12;
        const bool t0 = tid == 384;
        pdl_wait();
        pdl_launch();
        uint32_t* sy = g_sync + layer * SYNC_LAYER;
        int pblk = 0;
        auto loads = [&](int s) {
            const int n = s + 1, pb = s & 1;
            const uint32_t xt = bar + 8 * (B_XT + pb);
            mbar_expect(xt, (n + 1 < NSEG ? 40960 : 0) + (rank < 2 ? 4096 : 0));
            if (n + 1 < NSEG) bulk_g2s(sb + OFF_X + pb * 40960, g_xn + (n + 1) * 40960, 40960, xt);
            if (n == wk::pb_start(pblk)) { flag_wait(sy + wk::SY_P + pblk * H_ + h, 3); pblk++; }
            const unsigned char* src = g_p + (size_t)(n * H_ + h) * 12288;
            if (rank < 2) bulk_g2s(sb + OFF_Q + (pb ^ 1) * 5120 + 1024, src + rank * 4096, 4096, xt);
            if (rank < 2 || n < NSEG - 1) bulk_g2s(sb + OFF_VX + (pb ^ 1) * 8192, src + 8192, 4096, bar + 8 * (B_VX + (pb ^ 1)));
        };
        const int wl = rank == 0 ? 2 : rank == 1 ? 0 : 1;
        if (w == wl) {
            if (lane == 0) {
                mbar_expect(bar + 8 * B_XT, 40960);
                bulk_g2s(sb + OFF_X, g_xn, 40960, bar + 8 * B_XT);
            }
            __syncwarp();
            bar_sync(NB_PRO, 288);
            if (rank == 2) mbar_wait(bar + 8 * B_ST, 0);
            else if (lane == 0) mbar_arrive_remote(mapa(bar + 8 * B_ST, 2));
            mbar_wait(bar + 8 * B_XT, 0);
            __syncwarp();
            bar_arrive(NB_LD, 288);
            if (lane == 0) loads(-1);
            __syncwarp();
        }
        if (rank == 2 && w == 3) {
            if (lane == 0) {
                for (uint32_t s = 0, n = 0; s < NSEG; s++) {
                    uint32_t c[2];
                    for (;;) {
                        asm volatile("ld.acquire.cluster.shared::cta.v2.u32 {%0,%1},[%2];" : "=r"(c[0]), "=r"(c[1]) : "r"(sb + OFF_MX + 32) : "memory");
                        if (min(c[0], c[1]) > s) break;
                        if (++n > (SPIN_LIMIT << 3)) die();
                        __nanosleep(s < NSEG - 2 ? 400 : 50);
                    }
                    flag_add(sy + wk::SY_O + s);
                }
            }
        } else if (rank == 2) {
            const char* pf = (const char*)(g_acc + layer * ACC_LAYER) + (5 * h + lane % 5) * 1024;
            if (w == 2 && lane < 20) prefetch_l2(pf + lane / 5 * 128);
            for (int s = 0; s < NSEG; s++) {
                const int pb = s & 1, ph = (s >> 1) & 1;
                if (w == 0) {
                    mbar_wait(bar + 8 * (B_KX + pb), ph);
                    if (lane < 2) bulk_s2s(mapa(sb + OFF_VX + pb * 8192 + 4096, lane), sb + OFF_VX + pb * 8192 + 4096, 4096, mapa(bar + 8 * (B_VX + pb), lane));
                }
                if (w == 1) mbar_wait(bar + 8 * (B_XT + (pb ^ 1)), ((s + 1) >> 1) & 1);
                if (w == 2 && s >= 1) mbar_wait(bar + 8 * (B_XD + (pb ^ 1)), ((s - 1) >> 1) & 1);
                __syncwarp();
                bar_sync(NB_W1, 352);
                if (w == 2 && lane < 5 && s + 4 < NSEG) prefetch_l2(pf + ((s + 4) >> 3) * 163840 + ((s + 4) & 7) * 128);
                if (w == 1 && s + 1 < NSEG) {
                    mbar_wait(bar + 8 * (B_X1 + pb), ph);
                    const uint32_t tw = clk();
                    while (clk() - tw < (uint32_t)delay2) {}
                    if (lane == 0) loads(s);
                }
            }
        } else {
            if (w < 2) sts32(sb + OFF_PT + w * 768 + 640 + lane * 4, 0u);
            for (int s = 0; s < NSEG; s++) {
                const int pb = s & 1, ph = (s >> 1) & 1;
                if (t0) {
                    mbar_expect(bar + 8 * B_PXF, rank ? 2560 : 1536);
                    asm volatile("cp.async.bulk.wait_group.read 0;" ::: "memory");
                }
                if (w == 1) mbar_wait(bar + 8 * (B_XT + (pb ^ 1)), ((s + 1) >> 1) & 1);
                __syncwarp();
                bar_sync(NB_W1, 384);
                fence_async();
                float c[20];
                {
                    const u64 dq = mkdesc(sb + OFF_Q + pb * 5120 + 1024, 128, 512), dk = mkdesc(sb + OFF_K + pb * 5120, 128, 1024);
                    wg_fence();
                    wgmma_n40_ss<0>(c, dq, dk);
#pragma unroll
                    for (int ks = 1; ks < 4; ks++) wgmma_n40_ss<1>(c, dq + ks * 16, dk + ks * 16);
                    wg_commit();
                    wg_wait<0>();
                }
                mbar_wait(bar + 8 * (B_X1 + pb), ph);
                if ((w >> 1) != rank) {
                    if (s >= 1) mbar_wait(bar + 8 * B_PXE, pb ^ 1);
                    const uint32_t pa = mapa(sb + OFF_PX + (w & 1) * 1280 + lane * 8, rank ^ 1), pf = mapa(bar + 8 * B_PXF, rank ^ 1);
#pragma unroll
                    for (int nt = 0; nt < 5; nt++)
                        if (nt < 3 || rank == 0) st_async2(pa + nt * 256, __float_as_uint(c[4 * nt]), __float_as_uint(c[4 * nt + 1]), pf);
                    if (w == wl && s + 1 < NSEG) {
                        const uint32_t tw = clk();
                        while (clk() - tw < (uint32_t)delay2) {}
                        if (lane == 0) loads(s);
                    }
                } else {
                    mbar_wait(bar + 8 * B_PXF, pb);
                    if (w == 0) PROFT(13);
                    const int tq = 8 * w + g;
                    float sc[10];
#pragma unroll
                    for (int nt = 0; nt < 5; nt++) {
                        float u0, u1;
                        lds64f(u0, u1, sb + OFF_PX + (w & 1) * 1280 + nt * 256 + lane * 8);
                        sc[2 * nt] = (8 * nt - 8 + 2 * q <= tq) ? (u0 + c[4 * nt]) * SM_SCALE : -INFINITY;
                        sc[2 * nt + 1] = (8 * nt - 7 + 2 * q <= tq) ? (u1 + c[4 * nt + 1]) * SM_SCALE : -INFINITY;
                    }
                    float mx = sc[0];
#pragma unroll
                    for (int i = 1; i < 10; i++) mx = fmaxf(mx, sc[i]);
                    mx = fmaxf(mx, __shfl_xor_sync(~0u, mx, 1));
                    mx = fmaxf(mx, __shfl_xor_sync(~0u, mx, 2));
                    if (lane == 0) mbar_arrive_remote(mapa(bar + 8 * B_PXE, rank ^ 1));
                    float sum = 0.f;
#pragma unroll
                    for (int i = 0; i < 10; i++) { sc[i] = ex2(sc[i] - mx); sum += sc[i]; }
                    sum += __shfl_xor_sync(~0u, sum, 1);
                    sum += __shfl_xor_sync(~0u, sum, 2);
                    sum = rcp(sum);
#pragma unroll
                    for (int nt = 0; nt < 5; nt++)
                        sts32(sb + OFF_PT + (w & 1) * 768 + (nt ? nt - 1 : 4) * 128 + lane * 4, pack2(sc[2 * nt] * sum, sc[2 * nt + 1] * sum));
                }
                mbar_wait(bar + 8 * (B_VX + pb), ph);
                fence_async();
                bar_sync(NB_X, 128);
                if (s < NSEG - 1) mbar_wait(bar + 8 * (B_WN + pb), ph);
                float acc[2][8];
                const u64 dv = mkdesc(sb + OFF_VX + pb * 8192, 128, 512), dp = mkdesc(sb + OFF_PT, 128, 768), dm = mkdesc(sb + OFF_VM + pb * 2048, 0, 128);
                wg_fence();
#pragma unroll
                for (int m = 0; m < 2; m++) {
                    wgmma_n16_ss<0>(acc[m], dv + m * 256, dp);
                    wgmma_n16_ss<1>(acc[m], dv + m * 256 + 16, dp + 16);
                    wgmma_n16_ss<1>(acc[m], dm + m * 64, dp + 32);
                }
                wg_commit();
                wg_wait<0>();
#pragma unroll
                for (int m = 0; m < 2; m++)
                    stsm4t(sb + OFF_OST + m * 2048 + (lane >> 4) * 1024 + w * 256 + (lane & 15) * 16, pack2(acc[m][0], acc[m][1]), pack2(acc[m][2], acc[m][3]),
                           pack2(acc[m][4], acc[m][5]), pack2(acc[m][6], acc[m][7]));
                fence_async();
                bar_sync(NB_X, 128);
                if (lane == 0) mbar_arrive_remote(mapa(bar + 8 * (B_XD + pb), 2));
                if (t0) {
                    unsigned char* op = g_o + (size_t)(s * H_ + h) * 8192 + rank * 2048;
                    bulk_s2g(op, sb + OFF_OST, 2048);
                    bulk_s2g(op + 4096, sb + OFF_OST + 2048, 2048);
                    bulk_commit();
                    bulk_wait<1>();
                    st_remote(mapa(sb + OFF_MX + 32 + 4 * rank, 2), s);
                }
                if (w == 0) PROFT(14);
            }
            if (t0) { bulk_wait<0>(); st_remote(mapa(sb + OFF_MX + 32 + 4 * rank, 2), NSEG); }
        }
    }
    __syncwarp();
    if (lane < 3) mbar_arrive_remote(mapa(bar + 8 * B_FIN, lane));
    mbar_wait(bar + 8 * B_FIN, 0);
    TLE(2 + 5 * layer);
}

int g_delay = 1050, g_layers = 2;

void make_map(CUtensorMap* m, CUtensorMapDataType dt, const void* p, const cuuint64_t* dim, const cuuint64_t* str, const cuuint32_t* box, CUtensorMapSwizzle sw) {
    typedef CUresult (*Fn)(CUtensorMap*, CUtensorMapDataType, cuuint32_t, void*, const cuuint64_t*, const cuuint64_t*, const cuuint32_t*,
                           const cuuint32_t*, CUtensorMapInterleave, CUtensorMapSwizzle, CUtensorMapL2promotion, CUtensorMapFloatOOBfill);
    static Fn fn = nullptr;
    if (!fn) {
        cudaDriverEntryPointQueryResult qr;
        cudaGetDriverEntryPoint("cuTensorMapEncodeTiled", (void**)&fn, cudaEnableDefault, &qr);
    }
    const cuuint32_t es[3] = {1, 1, 1};
    fn(m, dt, 3, (void*)p, dim, str, box, es, CU_TENSOR_MAP_INTERLEAVE_NONE, sw, CU_TENSOR_MAP_L2_PROMOTION_L2_128B, CU_TENSOR_MAP_FLOAT_OOB_FILL_NONE);
}
void map_weight(CUtensorMap* m, const bf16* p, int rows, int cols, int ng, int br = 64) {
    const cuuint64_t dim[3] = {64, (cuuint64_t)rows, (cuuint64_t)cols / 64}, str[2] = {(cuuint64_t)cols * 2, 128};
    const cuuint32_t box[3] = {64, (cuuint32_t)br, (cuuint32_t)ng};
    make_map(m, CU_TENSOR_MAP_DATA_TYPE_BFLOAT16, p, dim, str, box, CU_TENSOR_MAP_SWIZZLE_128B);
}
void map_pieces(CUtensorMap* m, const void* p, int np, int ns) {
    const cuuint64_t dim[3] = {256, (cuuint64_t)np * 2, NSEG}, str[2] = {2048, (cuuint64_t)np * 4096};
    const cuuint32_t box[3] = {256, 2, (cuuint32_t)ns};
    make_map(m, CU_TENSOR_MAP_DATA_TYPE_UINT64, p, dim, str, box, CU_TENSOR_MAP_SWIZZLE_NONE);
}

template <class... P, class... A> void launch(void (*k)(P...), int grid, int block, int smem, int cluster, bool pdl, A... args) {
    cudaLaunchConfig_t c = {};
    c.gridDim = dim3(grid); c.blockDim = dim3(block); c.dynamicSmemBytes = smem; c.stream = cudaStreamPerThread;
    cudaLaunchAttribute at[2];
    int n = 0;
    if (cluster > 1) { at[n].id = cudaLaunchAttributeClusterDimension; at[n].val.clusterDim.x = cluster; at[n].val.clusterDim.y = 1; at[n].val.clusterDim.z = 1; n++; }
    if (pdl) { at[n].id = cudaLaunchAttributeProgrammaticStreamSerialization; at[n].val.programmaticStreamSerializationAllowed = 1; n++; }
    c.attrs = at; c.numAttrs = n;
    cudaLaunchKernelEx(&c, k, args...);
}

int max_clusters() {
    cudaLaunchConfig_t c = {};
    c.gridDim = dim3(3 * H_); c.blockDim = dim3(512); c.dynamicSmemBytes = rec::SMEM;
    cudaLaunchAttribute at[1];
    at[0].id = cudaLaunchAttributeClusterDimension; at[0].val.clusterDim.x = 3; at[0].val.clusterDim.y = 1; at[0].val.clusterDim.z = 1;
    c.attrs = at; c.numAttrs = 1;
    int n = 0;
    cudaOccupancyMaxActiveClusters(&n, rec_kernel, &c);
    return n;
}

}

extern "C" void kernel_launch(void* const* d_in, const int* in_sizes, int n_in, void* d_out, int out_size) {
    const bf16* x = (const bf16*)d_in[0];
    const bf16* mem0 = (const bf16*)d_in[1];
    const bf16* Wq = (const bf16*)d_in[2];
    const bf16* Wk = (const bf16*)d_in[3];
    const bf16* Wv = (const bf16*)d_in[4];
    const bf16* Wo = (const bf16*)d_in[5];
    const bf16* wr = (const bf16*)d_in[8];
    const bf16* wi = (const bf16*)d_in[9];
    cudaFuncSetAttribute(rec_kernel, cudaFuncAttributeMaxDynamicSharedMemorySize, rec::SMEM);
    cudaFuncSetAttribute(side_kernel, cudaFuncAttributeMaxDynamicSharedMemorySize, wk::SMEM);
    cudaFuncSetAttribute(colfft_kernel, cudaFuncAttributeMaxDynamicSharedMemorySize, CF_SMEM);
    Maps maps;
    void *pxn, *po;
    cudaGetSymbolAddress(&pxn, g_xn);
    cudaGetSymbolAddress(&po, g_o);
    map_weight(&maps.wq2, Wq, D_, 4096, 2); map_weight(&maps.wv1, Wv, D_, 4096, 1);
    map_weight(&maps.wo2, Wo, 4096, D_, 2); map_weight(&maps.wo1, Wo, 4096, D_, 1, 192);
    map_pieces(&maps.x6, pxn, 10, 6); map_pieces(&maps.x2, pxn, 10, 2);
    map_pieces(&maps.o6, po, 64, 6); map_pieces(&maps.o2, po, 64, 2);
    bf16 *x1, *x2;
    cudaGetSymbolAddress((void**)&x1, g_x1);
    cudaGetSymbolAddress((void**)&x2, g_x2);
    constexpr int ONE_PER_SM = 120 * 1024;
    cudaFuncSetAttribute(rowfft_kernel, cudaFuncAttributeMaxDynamicSharedMemorySize, ONE_PER_SM);
    cudaFuncSetAttribute(rowifft_kernel, cudaFuncAttributeMaxDynamicSharedMemorySize, ONE_PER_SM);
    static int ncl = 0, nsm = 0;
    if (!ncl) { ncl = max_clusters(); cudaDeviceGetAttribute(&nsm, cudaDevAttrMultiProcessorCount, 0); }
    maps.wr = wr; maps.wi = wi;
    launch(prep_kernel, 128, 512, 0, 1, false, x, Wq, Wk, Wv, Wo);
    for (int layer = 0; layer < g_layers; layer++) {
        const bf16* xin = layer ? x2 : x;
        launch(rec_kernel, 3 * ncl, 512, rec::SMEM, 3, true, maps, xin, x1, mem0, Wq, Wk, Wv, Wo, layer, g_delay % 10000, g_delay / 10000);
        launch(side_kernel, nsm - 3 * (ncl - H_), 512, wk::SMEM, 1, true, maps, xin, x1, layer);
        launch(rowfft_kernel, 128, 256, ONE_PER_SM, 1, true, xin, x1, Wq, Wk, Wv, layer);
        launch(colfft_kernel, 107, 384, CF_SMEM, 1, true, layer);
        launch(rowifft_kernel, 128, 256, ONE_PER_SM, 1, true, (const bf16*)x1, layer ? (bf16*)d_out : x2, layer);
    }
}
```

```cpp
#include <cuda_runtime.h>
#include <cuda_bf16.h>
#include <cuda.h>
#include <stdint.h>

#define DEV __device__ __forceinline__
typedef unsigned long long u64;
typedef __nv_bfloat16 bf16;

namespace {

constexpr int S_ = 2048, D_ = 640, H_ = 32, E_ = 128, NSEG = 64;

__device__ __align__(1024) unsigned char g_xn[S_ * D_ * 2];
__device__ __align__(1024) unsigned char g_o[S_ * H_ * E_ * 2];
constexpr int ACC_LAYER = 32 * 5120;
__device__ __align__(4096) u64 g_acc[2 * ACC_LAYER];
__device__ __align__(16) float g_nrm[256];
__device__ __align__(1024) unsigned char g_p[NSEG * H_ * 3 * 4096];
constexpr int SYNC_LAYER = 1024 + 64 * 32;
__device__ __align__(128) uint32_t g_sync[2 * SYNC_LAYER];
__device__ __align__(1024) bf16 g_x1[S_ * D_];
__device__ __align__(1024) bf16 g_x2[S_ * D_];
constexpr int YT_ROWS = 128;
__device__ __align__(1024) float g_yt[2 * YT_ROWS * D_];
constexpr int NCOL = 321;
__device__ __align__(1024) unsigned char g_z[NCOL * 8192];
__device__ __align__(1024) unsigned char g_wt[NCOL * 8192];
__device__ __align__(1024) uint4 g_f128[2 * 8 * 256];
__device__ __align__(1024) uint4 g_f64[2 * 4 * 128];
__device__ __align__(1024) bf16 g_g32[2 * 4096];
#define TLI(id, k, v)
#define TLS(i)
#define TLE(i)

DEV uint32_t s2u(const void* p) { return (uint32_t)__cvta_generic_to_shared(p); }
DEV uint32_t clk() { uint32_t c; asm volatile("mov.u32 %0,%%clock;" : "=r"(c)::"memory"); return c; }
DEV uint32_t gtime32() { uint32_t t; asm volatile("mov.u32 %0,%%globaltimer_lo;" : "=r"(t)::"memory"); return t; }
DEV uint32_t cta_rank() { uint32_t r; asm volatile("mov.u32 %0,%%cluster_ctarank;" : "=r"(r)); return __shfl_sync(~0u, r, 0); }
DEV uint32_t mapa(uint32_t a, uint32_t r) { uint32_t o; asm("mapa.shared::cluster.u32 %0,%1,%2;" : "=r"(o) : "r"(a), "r"(r)); return o; }
DEV void mbar_init(uint32_t b, uint32_t n) { asm volatile("mbarrier.init.shared::cta.b64 [%0],%1;" ::"r"(b), "r"(n) : "memory"); }
DEV bool mbar_try(uint32_t b, uint32_t par) {
    uint32_t ok;
    asm volatile("{.reg .pred p; mbarrier.try_wait.parity.shared::cta.b64 p,[%1],%2; selp.u32 %0,1,0,p;}" : "=r"(ok) : "r"(b), "r"(par) : "memory");
    return ok;
}
constexpr uint32_t SPIN_LIMIT = 1u << 18;
DEV void die() { __trap(); }
DEV void mbar_wait(uint32_t b, uint32_t par) {
    uint32_t n = 0;
    while (!mbar_try(b, par)) if (++n > SPIN_LIMIT) die();
}
DEV uint32_t opaque(uint32_t x) { return __shfl_xor_sync(~0u, x, 0); }
#define SFENCE() asm volatile("{.reg .pred p; setp.ne.u32 p,%1,0; @p mov.u32 %0,%%clock;}" : "+r"(sfd) : "r"((uint32_t)never) : "memory")
DEV void mbar_arrive(uint32_t b) { asm volatile("mbarrier.arrive.shared::cta.b64 _,[%0];" ::"r"(b) : "memory"); }
DEV void mbar_arrive_elect(uint32_t b) { asm volatile("{.reg .pred p; elect.sync _|p, 0xffffffff; @p mbarrier.arrive.shared::cta.b64 _,[%0];}" ::"r"(b) : "memory"); }
DEV void mbar_expect_elect(uint32_t b, uint32_t tx) {
    asm volatile("{.reg .pred p; elect.sync _|p, 0xffffffff; @p mbarrier.arrive.expect_tx.shared::cta.b64 _,[%0],%1;}" ::"r"(b), "r"(tx) : "memory");
}
DEV bool elect() { uint32_t r; asm volatile("{.reg .pred p; elect.sync _|p, 0xffffffff; selp.u32 %0,1,0,p;}" : "=r"(r)); return r; }
DEV void mbar_arrive_remote(uint32_t b) { asm volatile("mbarrier.arrive.shared::cluster.b64 _,[%0];" ::"r"(b) : "memory"); }
DEV void mbar_expect(uint32_t b, uint32_t tx) { asm volatile("mbarrier.arrive.expect_tx.shared::cta.b64 _,[%0],%1;" ::"r"(b), "r"(tx) : "memory"); }
DEV void bar_sync(int id, int n) { asm volatile("bar.sync %0,%1;" ::"r"(id), "r"(n) : "memory"); }
DEV void bar_arrive(int id, int n) { asm volatile("bar.arrive %0,%1;" ::"r"(id), "r"(n) : "memory"); }
template <int ID, int N> DEV void bar_arrive_if(bool p) {
    asm volatile("{.reg .pred p; setp.ne.u32 p,%0,0; @p bar.arrive %1,%2;}" ::"r"((uint32_t)p), "n"(ID), "n"(N) : "memory");
}
DEV void prefetch_bulk(const void* p, uint32_t bytes) { asm volatile("cp.async.bulk.prefetch.L2.global [%0],%1;" ::"l"(p), "r"(bytes) : "memory"); }
DEV void prefetch_l2(const void* p) { asm volatile("prefetch.global.L2 [%0];" ::"l"(p) : "memory"); }
DEV void st_remote(uint32_t a, uint32_t x) { asm volatile("st.relaxed.cluster.shared::cluster.u32 [%0],%1;" ::"r"(a), "r"(x) : "memory"); }
DEV void st_async1(uint32_t a, uint32_t x, uint32_t b) {
    asm volatile("st.async.shared::cluster.mbarrier::complete_tx::bytes.u32 [%0],%1,[%2];" ::"r"(a), "r"(x), "r"(b) : "memory");
}
DEV void st_async2(uint32_t a, uint32_t x, uint32_t y, uint32_t b) {
    asm volatile("st.async.shared::cluster.mbarrier::complete_tx::bytes.v2.u32 [%0],{%1,%2},[%3];" ::"r"(a), "r"(x), "r"(y), "r"(b) : "memory");
}
DEV void st_async4(uint32_t a, uint32_t x, uint32_t y, uint32_t z, uint32_t w, uint32_t b) {
    asm volatile("st.async.shared::cluster.mbarrier::complete_tx::bytes.v4.u32 [%0],{%1,%2,%3,%4},[%5];" ::"r"(a), "r"(x), "r"(y), "r"(z), "r"(w), "r"(b) : "memory");
}
DEV void bulk_g2s(uint32_t dst, const void* src, uint32_t bytes, uint32_t b) {
    asm volatile("cp.async.bulk.shared::cluster.global.mbarrier::complete_tx::bytes [%0],[%1],%2,[%3];" ::"r"(dst), "l"(src), "r"(bytes), "r"(b) : "memory");
}
DEV void bulk_s2s(uint32_t dst, uint32_t src, uint32_t bytes, uint32_t b) {
    asm volatile("cp.async.bulk.shared::cluster.shared::cta.mbarrier::complete_tx::bytes [%0],[%1],%2,[%3];" ::"r"(dst), "r"(src), "r"(bytes), "r"(b) : "memory");
}
DEV void bulk_s2g(void* dst, uint32_t src, uint32_t bytes) {
    asm volatile("cp.async.bulk.global.shared::cta.bulk_group [%0],[%1],%2;" ::"l"(dst), "r"(src), "r"(bytes) : "memory");
}
DEV void tma3d(uint32_t dst, const CUtensorMap* m, int c0, int c1, int c2, uint32_t b) {
    asm volatile("cp.async.bulk.tensor.3d.shared::cluster.global.mbarrier::complete_tx::bytes [%0],[%1,{%3,%4,%5}],[%2];"
                 ::"r"(dst), "l"(m), "r"(b), "r"(c0), "r"(c1), "r"(c2) : "memory");
}
DEV void bulk_commit() { asm volatile("cp.async.bulk.commit_group;" ::: "memory"); }
template <int N> DEV void bulk_wait() { asm volatile("cp.async.bulk.wait_group %0;" ::"n"(N) : "memory"); }
template <int N> DEV void bulk_wait_read() { asm volatile("cp.async.bulk.wait_group.read %0;" ::"n"(N) : "memory"); }
DEV void fence_async_all() { asm volatile("fence.proxy.async;" ::: "memory"); }
DEV void flag_add(uint32_t* p) { fence_async_all(); asm volatile("red.release.gpu.global.add.u32 [%0],1;" ::"l"(p) : "memory"); }
template <bool BOUNDED = true> DEV void flag_wait(const uint32_t* p, uint32_t n) {
    uint32_t v, it = 0;
    for (;;) {
        asm volatile("ld.acquire.gpu.global.u32 %0,[%1];" : "=r"(v) : "l"(p) : "memory");
        if (v >= n) break;
        if (BOUNDED && ++it > (SPIN_LIMIT << 3)) die();
        __nanosleep(100);
    }
    fence_async_all();
}
DEV void cp16(uint32_t dst, const void* src) { asm volatile("cp.async.cg.shared.global [%0],[%1],16;" ::"r"(dst), "l"(src) : "memory"); }
DEV void cp_commit() { asm volatile("cp.async.commit_group;" ::: "memory"); }
template <int N> DEV void cp_wait() { asm volatile("cp.async.wait_group %0;" ::"n"(N) : "memory"); }
DEV uint32_t lds32(uint32_t a) { uint32_t x; asm volatile("ld.shared.u32 %0,[%1];" : "=r"(x) : "r"(a) : "memory"); return x; }
DEV void fence_async() { asm volatile("fence.proxy.async.shared::cta;" ::: "memory"); }
DEV uint32_t pack2(float lo, float hi) { uint32_t r; asm("cvt.rn.bf16x2.f32 %0,%1,%2;" : "=r"(r) : "f"(hi), "f"(lo)); return r; }
DEV uint32_t prmt(uint32_t a, uint32_t b, uint32_t s) { uint32_t r; asm("prmt.b32 %0,%1,%2,%3;" : "=r"(r) : "r"(a), "r"(b), "r"(s)); return r; }
DEV float ex2(float x) { float r; asm("ex2.approx.ftz.f32 %0,%1;" : "=f"(r) : "f"(x)); return r; }
DEV float rcp(float x) { float r; asm("rcp.approx.ftz.f32 %0,%1;" : "=f"(r) : "f"(x)); return r; }
DEV void lds128(uint32_t* r, uint32_t a) { asm volatile("ld.shared.v4.u32 {%0,%1,%2,%3},[%4];" : "=r"(r[0]), "=r"(r[1]), "=r"(r[2]), "=r"(r[3]) : "r"(a) : "memory"); }
DEV void lds64(uint32_t* r, uint32_t a) { asm volatile("ld.shared.v2.u32 {%0,%1},[%2];" : "=r"(r[0]), "=r"(r[1]) : "r"(a) : "memory"); }
DEV void lds64f(float& x, float& y, uint32_t a) { asm volatile("ld.shared.v2.f32 {%0,%1},[%2];" : "=f"(x), "=f"(y) : "r"(a) : "memory"); }
DEV void lds128f(float* r, uint32_t a) { asm volatile("ld.shared.v4.f32 {%0,%1,%2,%3},[%4];" : "=f"(r[0]), "=f"(r[1]), "=f"(r[2]), "=f"(r[3]) : "r"(a) : "memory"); }
DEV void sts128(uint32_t a, uint32_t x, uint32_t y, uint32_t z, uint32_t w) { asm volatile("st.shared.v4.u32 [%0],{%1,%2,%3,%4};" ::"r"(a), "r"(x), "r"(y), "r"(z), "r"(w) : "memory"); }
DEV void sts64(uint32_t a, uint32_t x, uint32_t y) { asm volatile("st.shared.v2.u32 [%0],{%1,%2};" ::"r"(a), "r"(x), "r"(y) : "memory"); }
DEV void sts32(uint32_t a, uint32_t x) { asm volatile("st.shared.u32 [%0],%1;" ::"r"(a), "r"(x) : "memory"); }
DEV void ldsm4(uint32_t* r, uint32_t a) { asm volatile("ldmatrix.sync.aligned.m8n8.x4.shared.b16 {%0,%1,%2,%3},[%4];" : "=r"(r[0]), "=r"(r[1]), "=r"(r[2]), "=r"(r[3]) : "r"(a) : "memory"); }
DEV void ldsm4t(uint32_t* r, uint32_t a) { asm volatile("ldmatrix.sync.aligned.m8n8.x4.trans.shared.b16 {%0,%1,%2,%3},[%4];" : "=r"(r[0]), "=r"(r[1]), "=r"(r[2]), "=r"(r[3]) : "r"(a) : "memory"); }
DEV void ldsm2(uint32_t* r, uint32_t a) { asm volatile("ldmatrix.sync.aligned.m8n8.x2.shared.b16 {%0,%1},[%2];" : "=r"(r[0]), "=r"(r[1]) : "r"(a) : "memory"); }
DEV void stsm4t(uint32_t a, uint32_t x, uint32_t y, uint32_t z, uint32_t w) { asm volatile("stmatrix.sync.aligned.m8n8.x4.trans.shared.b16 [%0],{%1,%2,%3,%4};" ::"r"(a), "r"(x), "r"(y), "r"(z), "r"(w) : "memory"); }
DEV void stsm4(uint32_t a, uint32_t x, uint32_t y, uint32_t z, uint32_t w) { asm volatile("stmatrix.sync.aligned.m8n8.x4.shared.b16 [%0],{%1,%2,%3,%4};" ::"r"(a), "r"(x), "r"(y), "r"(z), "r"(w) : "memory"); }
DEV void stsm2(uint32_t a, uint32_t x, uint32_t y) { asm volatile("stmatrix.sync.aligned.m8n8.x2.shared.b16 [%0],{%1,%2};" ::"r"(a), "r"(x), "r"(y) : "memory"); }
DEV void stsm2t(uint32_t a, uint32_t x, uint32_t y) { asm volatile("stmatrix.sync.aligned.m8n8.x2.trans.shared.b16 [%0],{%1,%2};" ::"r"(a), "r"(x), "r"(y) : "memory"); }
DEV void mma16(float* d, uint32_t a0, uint32_t a1, uint32_t a2, uint32_t a3, uint32_t b0, uint32_t b1) {
    asm volatile("mma.sync.aligned.m16n8k16.row.col.f32.bf16.bf16.f32 {%0,%1,%2,%3},{%4,%5,%6,%7},{%8,%9},{%0,%1,%2,%3};"
                 : "+f"(d[0]), "+f"(d[1]), "+f"(d[2]), "+f"(d[3]) : "r"(a0), "r"(a1), "r"(a2), "r"(a3), "r"(b0), "r"(b1));
}
DEV void mma8(float* d, uint32_t a0, uint32_t a1, uint32_t b0) {
    asm volatile("mma.sync.aligned.m16n8k8.row.col.f32.bf16.bf16.f32 {%0,%1,%2,%3},{%4,%5},{%6},{%0,%1,%2,%3};"
                 : "+f"(d[0]), "+f"(d[1]), "+f"(d[2]), "+f"(d[3]) : "r"(a0), "r"(a1), "r"(b0));
}
DEV u64 mkdesc(uint32_t a, uint32_t lbo, uint32_t sbo) { return (u64)((a & 0x3ffff) >> 4) | ((u64)(lbo >> 4) << 16) | ((u64)(sbo >> 4) << 32); }
constexpr u64 SW128 = 1ull << 62;
DEV void wg_fence() { asm volatile("wgmma.fence.sync.aligned;" ::: "memory"); }
DEV void wg_commit() { asm volatile("wgmma.commit_group.sync.aligned;" ::: "memory"); }
template <int N> DEV void wg_wait() { asm volatile("wgmma.wait_group.sync.aligned %0;" ::"n"(N) : "memory"); }
template <int ACC> DEV void wgmma_n32_rs(float* d, const uint32_t* a, u64 desc) {
    asm volatile("wgmma.mma_async.sync.aligned.m64n32k16.f32.bf16.bf16 {%0,%1,%2,%3,%4,%5,%6,%7,%8,%9,%10,%11,%12,%13,%14,%15},{%16,%17,%18,%19},%20,%21,1,1,0;"
                 : "+f"(d[0]), "+f"(d[1]), "+f"(d[2]), "+f"(d[3]), "+f"(d[4]), "+f"(d[5]), "+f"(d[6]), "+f"(d[7]),
                   "+f"(d[8]), "+f"(d[9]), "+f"(d[10]), "+f"(d[11]), "+f"(d[12]), "+f"(d[13]), "+f"(d[14]), "+f"(d[15])
                 : "r"(a[0]), "r"(a[1]), "r"(a[2]), "r"(a[3]), "l"(desc), "n"(ACC));
}
template <int ACC> DEV void wgmma_n32_ss(float* d, u64 da, u64 desc) {
    asm volatile("wgmma.mma_async.sync.aligned.m64n32k16.f32.bf16.bf16 {%0,%1,%2,%3,%4,%5,%6,%7,%8,%9,%10,%11,%12,%13,%14,%15},%16,%17,%18,1,1,0,0;"
                 : "+f"(d[0]), "+f"(d[1]), "+f"(d[2]), "+f"(d[3]), "+f"(d[4]), "+f"(d[5]), "+f"(d[6]), "+f"(d[7]),
                   "+f"(d[8]), "+f"(d[9]), "+f"(d[10]), "+f"(d[11]), "+f"(d[12]), "+f"(d[13]), "+f"(d[14]), "+f"(d[15])
                 : "l"(da), "l"(desc), "n"(ACC));
}
template <int ACC> DEV void wgmma_n16_ss(float* d, u64 da, u64 desc) {
    asm volatile("wgmma.mma_async.sync.aligned.m64n16k16.f32.bf16.bf16 {%0,%1,%2,%3,%4,%5,%6,%7},%8,%9,%10,1,1,0,0;"
                 : "+f"(d[0]), "+f"(d[1]), "+f"(d[2]), "+f"(d[3]), "+f"(d[4]), "+f"(d[5]), "+f"(d[6]), "+f"(d[7])
                 : "l"(da), "l"(desc), "n"(ACC));
}
#define ACC8(o) "+f"(d[o]), "+f"(d[o + 1]), "+f"(d[o + 2]), "+f"(d[o + 3]), "+f"(d[o + 4]), "+f"(d[o + 5]), "+f"(d[o + 6]), "+f"(d[o + 7])
template <int ACC, int TB> DEV void wgmma_n64_rs(float* d, const uint32_t* a, u64 desc) {
    asm volatile("wgmma.mma_async.sync.aligned.m64n64k16.f32.bf16.bf16 {%0,%1,%2,%3,%4,%5,%6,%7,%8,%9,%10,%11,%12,%13,%14,%15,"
                 "%16,%17,%18,%19,%20,%21,%22,%23,%24,%25,%26,%27,%28,%29,%30,%31},{%32,%33,%34,%35},%36,%37,1,1,%38;"
                 : ACC8(0), ACC8(8), ACC8(16), ACC8(24) : "r"(a[0]), "r"(a[1]), "r"(a[2]), "r"(a[3]), "l"(desc), "n"(ACC), "n"(TB));
}
template <int ACC, int TB> DEV void wgmma_n80_rs(float* d, const uint32_t* a, u64 desc) {
    asm volatile("wgmma.mma_async.sync.aligned.m64n80k16.f32.bf16.bf16 {%0,%1,%2,%3,%4,%5,%6,%7,%8,%9,%10,%11,%12,%13,%14,%15,"
                 "%16,%17,%18,%19,%20,%21,%22,%23,%24,%25,%26,%27,%28,%29,%30,%31,%32,%33,%34,%35,%36,%37,%38,%39},{%40,%41,%42,%43},%44,%45,1,1,%46;"
                 : ACC8(0), ACC8(8), ACC8(16), ACC8(24), ACC8(32) : "r"(a[0]), "r"(a[1]), "r"(a[2]), "r"(a[3]), "l"(desc), "n"(ACC), "n"(TB));
}
template <int TA, int TB> DEV void wgmma_n64_ss(float* d, u64 da, u64 db, int acc) {
    asm volatile("{.reg .pred p; setp.ne.b32 p,%34,0; wgmma.mma_async.sync.aligned.m64n64k16.f32.bf16.bf16 {%0,%1,%2,%3,%4,%5,%6,%7,%8,%9,%10,%11,%12,%13,%14,%15,%16,%17,%18,%19,%20,%21,%22,%23,%24,%25,%26,%27,%28,%29,%30,%31},%32,%33,p,1,1,%35,%36;}"
                 : ACC8(0), ACC8(8), ACC8(16), ACC8(24) : "l"(da), "l"(db), "r"(acc), "n"(TA), "n"(TB));
}
template <int TA, int TB> DEV void wgmma_n128_ss(float* d, u64 da, u64 db, int acc) {
    asm volatile("{.reg .pred p; setp.ne.b32 p,%66,0; wgmma.mma_async.sync.aligned.m64n128k16.f32.bf16.bf16 {%0,%1,%2,%3,%4,%5,%6,%7,%8,%9,%10,%11,%12,%13,%14,%15,%16,%17,%18,%19,%20,%21,%22,%23,%24,%25,%26,%27,%28,%29,%30,%31,%32,%33,%34,%35,%36,%37,%38,%39,%40,%41,%42,%43,%44,%45,%46,%47,%48,%49,%50,%51,%52,%53,%54,%55,%56,%57,%58,%59,%60,%61,%62,%63},%64,%65,p,1,1,%67,%68;}"
                 : ACC8(0), ACC8(8), ACC8(16), ACC8(24), ACC8(32), ACC8(40), ACC8(48), ACC8(56) : "l"(da), "l"(db), "r"(acc), "n"(TA), "n"(TB));
}
template <int TA, int TB> DEV void wgmma_n192_ss(float* d, u64 da, u64 db, int acc) {
    asm volatile("{.reg .pred p; setp.ne.b32 p,%98,0; wgmma.mma_async.sync.aligned.m64n192k16.f32.bf16.bf16 {%0,%1,%2,%3,%4,%5,%6,%7,%8,%9,%10,%11,%12,%13,%14,%15,%16,%17,%18,%19,%20,%21,%22,%23,%24,%25,%26,%27,%28,%29,%30,%31,%32,%33,%34,%35,%36,%37,%38,%39,%40,%41,%42,%43,%44,%45,%46,%47,%48,%49,%50,%51,%52,%53,%54,%55,%56,%57,%58,%59,%60,%61,%62,%63,%64,%65,%66,%67,%68,%69,%70,%71,%72,%73,%74,%75,%76,%77,%78,%79,%80,%81,%82,%83,%84,%85,%86,%87,%88,%89,%90,%91,%92,%93,%94,%95},%96,%97,p,1,1,%99,%100;}"
                 : ACC8(0), ACC8(8), ACC8(16), ACC8(24), ACC8(32), ACC8(40), ACC8(48), ACC8(56), ACC8(64), ACC8(72), ACC8(80), ACC8(88) : "l"(da), "l"(db), "r"(acc), "n"(TA), "n"(TB));
}
template <int ACC> DEV void wgmma_n40_ss(float* d, u64 da, u64 desc) {
    asm volatile("wgmma.mma_async.sync.aligned.m64n40k16.f32.bf16.bf16 {%0,%1,%2,%3,%4,%5,%6,%7,%8,%9,%10,%11,%12,%13,%14,%15,%16,%17,%18,%19},%20,%21,%22,1,1,0,0;"
                 : ACC8(0), ACC8(8), "+f"(d[16]), "+f"(d[17]), "+f"(d[18]), "+f"(d[19]) : "l"(da), "l"(desc), "n"(ACC));
}
DEV void pdl_wait() { asm volatile("griddepcontrol.wait;" ::: "memory"); }
DEV void pdl_launch() { asm volatile("griddepcontrol.launch_dependents;" ::: "memory"); }
DEV uint32_t ldg32(const void* p) { uint32_t v; asm volatile("ld.global.nc.u32 %0,[%1];" : "=r"(v) : "l"(p)); return v; }
DEV void ld_acc(u64& a, u64& b, const void* p) {
    const uint32_t done = (uint32_t)a & (uint32_t)b & 32u;
    asm volatile("{.reg .pred p; setp.eq.u32 p,%3,0;\n"
                 "@p ld.relaxed.gpu.global.v2.u64 {%0,%1},[%2];}" : "+l"(a), "+l"(b) : "l"(p), "r"(done) : "memory");
}
DEV void ld_acc0(u64& a, u64& b, const void* p) {
    asm volatile("ld.relaxed.gpu.global.v2.u64 {%0,%1},[%2];" : "=l"(a), "=l"(b) : "l"(p) : "memory");
}
DEV uint32_t and3(uint32_t a, uint32_t b, uint32_t c) { uint32_t r; asm volatile("lop3.b32 %0,%1,%2,%3,0x80;" : "=r"(r) : "r"(a), "r"(b), "r"(c)); return r; }
DEV uint32_t absmax2(uint32_t a, uint32_t b) { uint32_t r; asm("max.xorsign.abs.bf16x2 %0,%1,%2;" : "=r"(r) : "r"(a), "r"(b)); return r; }
DEV float lds32f(uint32_t a) { float x; asm volatile("ld.shared.f32 %0,[%1];" : "=f"(x) : "r"(a) : "memory"); return x; }
DEV void red_add64(u64* p, uint32_t lo, uint32_t hi) {
    asm volatile("{.reg .b64 v; mov.b64 v,{%1,%2}; red.relaxed.gpu.global.add.u64 [%0],v;}" ::"l"(p), "r"(lo), "r"(hi) : "memory");
}
DEV float bf_round(float x) { return __bfloat162float(__float2bfloat16_rn(x)); }
DEV float bf_lo(uint32_t u) { return __uint_as_float(u << 16); }
DEV float bf_hi(uint32_t u) { return __uint_as_float(u & 0xffff0000u); }

#define GPROF(i, n)
#define PROFT(i)
#define STAMP(i)

DEV void unpack8(float* v, uint4 u) {
    v[0] = bf_lo(u.x); v[1] = bf_hi(u.x); v[2] = bf_lo(u.y); v[3] = bf_hi(u.y);
    v[4] = bf_lo(u.z); v[5] = bf_hi(u.z); v[6] = bf_lo(u.w); v[7] = bf_hi(u.w);
}
DEV int xn_off(int row, int chunk) { return (row >> 5) * 40960 + (chunk >> 3) * 4096 + (row & 31) * 128 + (((chunk ^ row) & 7) << 4); }

DEV void ln_row(float (&v)[3][8], int lane) {
    float s = 0.f;
#pragma unroll
    for (int c = 0; c < 3; c++)
#pragma unroll
        for (int j = 0; j < 8; j++) s += v[c][j];
#pragma unroll
    for (int o = 16; o; o >>= 1) s += __shfl_xor_sync(~0u, s, o);
    float mean = s * (1.f / D_), q = 0.f;
#pragma unroll
    for (int c = 0; c < 3; c++)
        if (c < 2 || lane < 16)
#pragma unroll
            for (int j = 0; j < 8; j++) { float d = v[c][j] - mean; q += d * d; }
#pragma unroll
    for (int o = 16; o; o >>= 1) q += __shfl_xor_sync(~0u, q, o);
    float mb = bf_round(mean);
    float inv = 1.f / bf_round(sqrtf(bf_round(bf_round(q * (1.f / D_)) + 1e-5f)));
#pragma unroll
    for (int c = 0; c < 3; c++)
#pragma unroll
        for (int j = 0; j < 8; j++) v[c][j] = bf_round(v[c][j] - mb) * inv;
}

__host__ __device__ constexpr int col_freq(int c) {
    return c == 320 ? 320 : c < 192 ? (c >> 6) * 128 + (c & 63) : c == 192 ? 192 : c < 256 ? 448 - c : c == 256 ? 64 : 384 - c;
}
DEV float rdft(int n, int k, int sn, int N) {
    float s, c;
    sincospif((float)((n * k) & (N - 1)) * (2.f / N), &s, &c);
    return !sn ? c : k ? s : (n & 1 ? -1.f : 1.f);
}

__global__ void __launch_bounds__(512) prep_kernel(const bf16* __restrict__ x, const bf16* __restrict__ Wq, const bf16* __restrict__ Wk,
                                                   const bf16* __restrict__ Wv, const bf16* __restrict__ Wo) {
    __shared__ float red[32], col[4][640];
    const int tid = threadIdx.x, lane = tid & 31, warp = tid >> 5, b = blockIdx.x, row = b * 16 + warp;
    TLS(0);
    pdl_launch();
    uint4 ux[3], uv[5], uo[8];
#pragma unroll
    for (int c = 0; c < 3; c++) ux[c] = c < 2 || lane < 16 ? *(const uint4*)(x + row * D_ + (c * 32 + lane) * 8) : make_uint4(0, 0, 0, 0);
#pragma unroll
    for (int i = 0; i < 5; i++) uv[i] = *(const uint4*)(Wv + (size_t)((b & 3) * 160 + i * 32 + (tid >> 4)) * 4096 + (b >> 2) * E_ + (tid & 15) * 8);
    if (tid < 320) {
#pragma unroll
        for (int r = 0; r < 8; r++) uo[r] = *(const uint4*)(Wo + (size_t)(b * 32 + tid / 80 * 8 + r) * D_ + tid % 80 * 8);
    }
    if (tid >= 504) prefetch_bulk((const char*)(tid & 4 ? Wk : Wq) + (b * 4 + (tid & 3)) * 10240, 10240);
    if (b < 3) ((uint4*)g_sync)[b * 512 + tid] = make_uint4(0, 0, 0, 0);
    for (int i = b * 512 + tid; i < ACC_LAYER; i += 128 * 512) ((uint4*)g_acc)[i] = make_uint4(0, 0, 0, 0);
    if (tid < 2 * YT_ROWS * D_ / 4 / 128) ((uint4*)g_yt)[b * (2 * YT_ROWS * D_ / 4 / 128) + tid] = make_uint4(0, 0, 0, 0);
    const int gid = tid < 104 ? b * 104 + tid : 1 << 20;
    if (gid < 4096) {
        const int inv = gid >> 11, ks = (gid >> 8) & 7, t = gid & 255, g = (t & 31) >> 2, q = t & 3, tile = t >> 5;
        uint32_t v[4];
#pragma unroll
        for (int j = 0; j < 4; j++) {
            float x[2];
#pragma unroll
            for (int u = 0; u < 2; u++) {
                const int m = inv ? 16 * tile + 2 * g + (j & 1) : 16 * ks + 8 * (j >> 1) + 2 * q + u;
                const int k2 = inv ? 8 * ks + 2 * q + u : 8 * tile + g, sn = inv ? j >> 1 : j & 1;
                x[u] = rdft(m, k2, sn, 128);
                if (sn && k2) x[u] = -x[u];
            }
            v[j] = pack2(x[0], x[1]);
        }
        g_f128[gid] = make_uint4(v[0], v[1], v[2], v[3]);
    } else if (gid < 5120) {
        const int id = gid - 4096, inv = id >> 9, ks = (id >> 7) & 3, t = id & 127, g = (t & 31) >> 2, q = t & 3, tile = t >> 5;
        uint32_t v[4];
#pragma unroll
        for (int j = 0; j < 4; j++) {
            float x[2];
#pragma unroll
            for (int u = 0; u < 2; u++) {
                const int a = inv ? 16 * tile + g + 8 * (j & 1) : 16 * ks + 8 * (j >> 1) + 2 * q + u;
                const int ka = inv ? 8 * ks + 2 * q + u : 8 * tile + g, sn = inv ? j >> 1 : j & 1;
                x[u] = rdft(a, ka, sn, 64);
            }
            v[j] = pack2(x[0], x[1]);
        }
        g_f64[id] = make_uint4(v[0], v[1], v[2], v[3]);
    } else if (gid < 5120 + 8192) {
        const int id = gid - 5120, inv = id >> 12, n = ((id >> 9) & 7) * 8 + ((id >> 3) & 7), k = ((id >> 6) & 7) * 8 + (id & 7);
        float s, c;
        sincospif((float)(((n >> 1) * (k >> 1)) & 31) * (1.f / 16), &s, &c);
        if (inv) s = -s;
        g_g32[id] = __float2bfloat16_rn((n & 1) == (k & 1) ? c : (k & 1) ? s : -s);
    }
    {
        float v[3][8];
#pragma unroll
        for (int c = 0; c < 3; c++) unpack8(v[c], ux[c]);
        ln_row(v, lane);
#pragma unroll
        for (int c = 0; c < 3; c++)
            if (c < 2 || lane < 16)
                *(uint4*)(g_xn + xn_off(row, c * 32 + lane)) =
                    make_uint4(pack2(v[c][0], v[c][1]), pack2(v[c][2], v[c][3]), pack2(v[c][4], v[c][5]), pack2(v[c][6], v[c][7]));
    }
    float sv = 0.f;
#pragma unroll
    for (int i = 0; i < 5; i++) {
        float w[8];
        unpack8(w, uv[i]);
#pragma unroll
        for (int j = 0; j < 8; j++) sv += w[j] * w[j];
    }
    if (tid < 320) {
        float a[8] = {0.f, 0.f, 0.f, 0.f, 0.f, 0.f, 0.f, 0.f};
#pragma unroll
        for (int r = 0; r < 8; r++) {
            float w[8];
            unpack8(w, uo[r]);
#pragma unroll
            for (int j = 0; j < 8; j++) a[j] += w[j] * w[j];
        }
#pragma unroll
        for (int j = 0; j < 8; j++) col[tid / 80][tid % 80 * 8 + j] = a[j];
    }
    __syncthreads();
    float so = (col[0][tid] + col[1][tid]) + (col[2][tid] + col[3][tid]);
    if (tid < 128) so = fmaxf(so, (col[0][512 + tid] + col[1][512 + tid]) + (col[2][512 + tid] + col[3][512 + tid]));
#pragma unroll
    for (int o = 16; o; o >>= 1) { sv += __shfl_xor_sync(~0u, sv, o); so = fmaxf(so, __shfl_xor_sync(~0u, so, o)); }
    if (lane == 0) { red[warp] = sv; red[16 + warp] = so; }
    __syncthreads();
    if (tid == 0) {
        float a = 0.f, c = 0.f;
        for (int i = 0; i < 16; i++) { a += red[i]; c = fmaxf(c, red[16 + i]); }
        g_nrm[b] = a; g_nrm[128 + b] = c;
    }
    TLE(0);
}

DEV void filter_tile(const bf16* __restrict__ wr, const bf16* __restrict__ wi, int ka, int c) {
    const int kn = ka ? 2048 - ka : 32, kc = col_freq(c);
    const unsigned short* pr = (const unsigned short*)wr + kc;
    const unsigned short* pi = (const unsigned short*)wi + kc;
#pragma unroll 1
    for (int i = 0; i < 4; i += 2) {
        unsigned short a[32], b[32];
#pragma unroll
        for (int n = 0; n < 32; n++) {
            const int k = ((n & 1 ? kn : ka) + 64 * (4 * (2 * (i + (n >> 4)) + ((n >> 1) & 1)) + ((n >> 2) & 3))) & 2047;
            a[n] = __ldg(pr + k * NCOL); b[n] = __ldg(pi + k * NCOL);
        }
#pragma unroll
        for (int n = 0; n < 32; n += 4)
            *(uint4*)(g_wt + c * 8192 + (i + (n >> 4)) * 2048 + (ka * 4 + ((n >> 2) & 3)) * 16) =
                make_uint4(a[n] | ((uint32_t)b[n] << 16), a[n + 1] | ((uint32_t)b[n + 1] << 16), a[n + 2] | ((uint32_t)b[n + 2] << 16), a[n + 3] | ((uint32_t)b[n + 3] << 16));
    }
}

namespace wk {
constexpr int STAGE = 49152, NST = 4, OFF_OUT = 3 * STAGE, OFF_RED = 4 * STAGE, OFF_BAR = OFF_RED + 32768, SMEM = OFF_BAR + 128;
constexpr int NPB = 12;
DEV int pb_first(int n) { return n < 2 ? 0 : n == 2 ? 1 : n % 6 == 0 ? n / 6 + 1 : -1; }
__host__ __device__ constexpr int pb_start(int b) { return b == 0 ? 0 : b == 1 ? 2 : b < NPB ? 6 * b - 6 : 64; }
#define NOB 7
#define SPLIT_A 3
#define SPLIT_B 11
constexpr int N_P = NPB * H_, I_F = N_P, I_OB = I_F + 32, I_OT = I_OB + NOB * 5, I_SA = I_OT + (30 - 3 * NOB) * 10;
constexpr int I_SB = I_SA + 10 * SPLIT_A, N_ITEMS = I_SB + 10 * SPLIT_B;
DEV void ot_decode(int id, int& b, int& nt, int& k0, int& k1) {
    const int base = id < I_SA ? I_OT : id < I_SB ? I_SA : I_SB, j = (id - base) / 10;
    nt = (id - base) % 10;
    if (id < I_SA) { b = 3 * NOB + j; k0 = 0; k1 = 22; }
    else if (id < I_SB) { b = 30; k0 = 22 * j / SPLIT_A; k1 = 22 * (j + 1) / SPLIT_A; }
    else { b = 31; k0 = 22 * j / SPLIT_B; k1 = 22 * (j + 1) / SPLIT_B; }
}
enum { SY_TICKET = 0, SY_O = 32, SY_P = 128 };
}
struct Ring {
    int st; uint32_t ph;
    DEV uint32_t par() const { return (ph >> st) & 1; }
    DEV void next(int n) { ph ^= 1u << st; st = st + 1 >= n ? 0 : st + 1; }
};
struct Maps { CUtensorMap wq2, wv1, wo2, wo1, x6, x2, o6, o2; const bf16 *wr, *wi; };

template <int NSG> DEV void proj_tile(uint32_t sb, uint32_t bar, Ring& rg, int wg, int id) {
    using namespace wk;
    float acc[NSG * 16];
#pragma unroll
    for (int i = 0; i < NSG * 16; i++) acc[i] = 0.f;
    const int lane = threadIdx.x & 31, ww = (threadIdx.x >> 5) & 3;
    for (int kb = 0; kb < 10; kb++, rg.next(3)) {
        const int st = rg.st;
        if (kb) mbar_wait(bar + 8 * st, rg.par());
        const u64 da = mkdesc(sb + st * STAGE + wg * 8192, 0, 1024) | SW128, db = mkdesc(sb + st * STAGE + 24576, 0, 1024) | SW128;
        wg_fence();
#pragma unroll
        for (int ks = 0; ks < 4; ks++) {
            if (NSG == 2) wgmma_n64_ss<1, 0>(acc, da + ks * 128, db + ks * 2, 1);
            if (NSG == 4) wgmma_n128_ss<1, 0>(acc, da + ks * 128, db + ks * 2, 1);
            if (NSG == 6) wgmma_n192_ss<1, 0>(acc, da + ks * 128, db + ks * 2, 1);
        }
        wg_commit();
        wg_wait<0>();
        mbar_arrive_elect(bar + 8 * (NST + st));
    }
    const uint32_t out = sb + OFF_OUT + wg * 24576;
    bar_sync(5 + wg, 160);
    const uint32_t la = out + (wg < 2 ? (lane >> 4) * 1024 + ww * 256 + (lane & 15) * 16 : ww * 1024 + ((lane >> 3) & 1) * 512 + (lane >> 4) * 128 + (lane & 7) * 16);
#pragma unroll
    for (int j = 0; j < 2 * NSG; j++) {
        const float* c = acc + 8 * j;
        const uint32_t p0 = pack2(c[0], c[1]), p1 = pack2(c[2], c[3]), p2 = pack2(c[4], c[5]), p3 = pack2(c[6], c[7]);
        if (wg < 2) stsm4t(la + j * 2048, p0, p1, p2, p3);
        else stsm4(la + (j >> 1) * 4096 + (j & 1) * 256, p0, p1, p2, p3);
    }
    if ((threadIdx.x & 127) == 0) sts32(bar + 80 + 4 * wg, id);
    fence_async();
    bar_arrive(1 + wg, 160);
}

DEV uint32_t resid(uint32_t u, float a, float b) { return pack2(bf_lo(u) + bf_round(a), bf_hi(u) + bf_round(b)); }

DEV void worker(uint32_t sb, const Maps& maps, const bf16* __restrict__ x, bf16* __restrict__ x1, int layer) {
    using namespace wk;
    const uint32_t bar = sb + OFF_BAR, slot = bar + 64;
    const int tid = threadIdx.x, lane = tid & 31, warp = __shfl_sync(~0u, tid >> 5, 0);
    uint32_t* sy = g_sync + layer * SYNC_LAYER;
    if (tid == 0) {
        for (int i = 0; i < NST; i++) { mbar_init(bar + 8 * i, 1); mbar_init(bar + 8 * (NST + i), 12); }
        asm volatile("fence.mbarrier_init.release.cluster;" ::: "memory");
    }
    __syncthreads();
    if (warp > 12) {
        const int wg = warp - 13;
        bar_arrive(5 + wg, 160);
        for (;;) {
            bar_sync(1 + wg, 160);
            const int id = (int)lds32(bar + 80 + 4 * wg);
            if (id < 0) break;
            const int s0 = pb_start(id >> 5), ns = pb_start((id >> 5) + 1) - s0;
            if (lane == 0) {
                for (int j = 0; j < ns; j++)
                    bulk_s2g(g_p + (size_t)(((s0 + j) * H_ + (id & 31)) * 3 + wg) * 4096, sb + OFF_OUT + wg * 24576 + j * 4096, 4096);
                bulk_commit();
                bulk_wait<0>();
                flag_add(sy + SY_P + id);
            }
            __syncwarp();
            bar_arrive(5 + wg, 160);
        }
    } else if (warp == 12) {
        if (lane == 0) {
            Ring rg = {0, 7u};
            auto acquire = [&]() { mbar_wait(bar + 8 * (NST + rg.st), rg.par()); return sb + rg.st * STAGE; };
            for (;;) {
                int id = (int)atomicAdd(sy + SY_TICKET, 1u);
                if (layer && id >= I_F) id += I_OB - I_F;
                if (id >= N_ITEMS) id = -1;
                if (id >= 0) { TLI(id, 0, gtime()); TLI(id, 3, blockIdx.x + (gridDim.x % 3 == 0 && gridDim.x > 111 ? 0 : 1000)); }
                uint32_t d = acquire();
                sts32(slot + 4 * rg.st, id);
                if (id < 0) { mbar_arrive(bar + 8 * rg.st); break; }
                if (id < N_P) {
                    const int b = id >> 5, h = id & 31, s0 = pb_start(b), ns = pb_start(b + 1) - s0;
                    for (int kb = 0; kb < 10; kb++, rg.next(3)) {
                        if (kb) d = acquire();
                        const uint32_t fb = bar + 8 * rg.st;
                        mbar_expect(fb, 24576 + ns * 4096);
                        tma3d(d, &maps.wq2, 0, kb * 64, 2 * h, fb);
                        tma3d(d + 16384, &maps.wv1, 0, kb * 64, 2 * h, fb);
                        if (ns == 6) tma3d(d + 24576, &maps.x6, 0, 2 * kb, s0, fb);
                        else for (int j = 0; j < ns; j += 2) tma3d(d + 24576 + j * 4096, &maps.x2, 0, 2 * kb, s0 + j, fb);
                    }
                } else if (id < I_OB) {
                    mbar_arrive(bar + 8 * rg.st);
                    mbar_wait(bar + 8 * (NST + rg.st), rg.par() ^ 1);
                    rg.next(NST);
                } else if (id < I_OT) {
                    const int b = (id - I_OB) / 5, nt = (id - I_OB) % 5;
                    for (int j = 0; j < 6; j++) flag_wait(sy + SY_O + 6 * b + j, 32);
                    for (int kb = 0; kb < 64; kb++, rg.next(NST)) {
                        if (kb) d = acquire();
                        const uint32_t fb = bar + 8 * rg.st;
                        mbar_expect(fb, 40960);
                        tma3d(d, &maps.o6, 0, 2 * kb, 6 * b, fb);
                        tma3d(d + 24576, &maps.wo2, 0, kb * 64, 2 * nt, fb);
                    }
                } else {
                    int b, nt, k0, k1;
                    ot_decode(id, b, nt, k0, k1);
                    for (int kb = k0; kb < k1; kb++, rg.next(NST)) {
                        if (kb > k0) d = acquire();
                        const uint32_t fb = bar + 8 * rg.st;
                        mbar_expect(fb, 49152);
                        tma3d(d + 24576, &maps.wo1, 0, 3 * kb * 64, nt, fb);
                        if (kb == k0) for (int j = 0; j < 2; j++) flag_wait(sy + SY_O + 2 * b + j, 32);
                        for (int u = 0; u < 3; u++) tma3d(d + u * 8192, &maps.o2, 0, 2 * (3 * kb + u), 2 * b, fb);
                    }
                }
            }
        }
    } else {
        const int wg = warp >> 2, g = lane >> 2, q = lane & 3;
        Ring rg = {0, 0u};
        bool stores_done = false;
        for (;;) {
            mbar_wait(bar + 8 * rg.st, rg.par());
            const int id = (int)lds32(slot + 4 * rg.st);
            if ((id < 0 || id >= N_P) && !stores_done) {
                bar_sync(5 + wg, 160);
                if ((tid & 127) == 0) sts32(bar + 80 + 4 * wg, ~0u);
                bar_arrive(1 + wg, 160);
                stores_done = true;
                bar_sync(4, 384);
                mbar_arrive_elect(bar + 8 * (NST + 3));
            }
            if (id < 0) break;
            if (tid == 0) TLI(id, 1, gtime());
            if (id < N_P) {
                const int b = id >> 5;
                if (b == 0) proj_tile<2>(sb, bar, rg, wg, id);
                else if (b == 1 || b == NPB - 1) proj_tile<4>(sb, bar, rg, wg, id);
                else proj_tile<6>(sb, bar, rg, wg, id);
            } else if (id < I_OB) {
                if (tid < NCOL) filter_tile(maps.wr, maps.wi, id - I_F, tid);
                __syncwarp();
                mbar_arrive_elect(bar + 8 * (NST + rg.st));
                rg.next(NST);
            } else if (id < I_OT) {
                const int b = (id - I_OB) / 5, nt = (id - I_OB) % 5;
                const size_t o = (size_t)(192 * b + 16 * warp + g) * D_ + nt * 128 + 2 * q;
                float acc[64];
#pragma unroll
                for (int i = 0; i < 64; i++) acc[i] = 0.f;
                for (int kb = 0; kb < 64; kb++, rg.next(NST)) {
                    const int st = rg.st;
                    if (kb) mbar_wait(bar + 8 * st, rg.par());
                    const u64 da = mkdesc(sb + st * STAGE + wg * 8192, 128, 1024), db = mkdesc(sb + st * STAGE + 24576, 8192, 1024) | SW128;
                    wg_fence();
#pragma unroll
                    for (int ks = 0; ks < 4; ks++) wgmma_n128_ss<0, 1>(acc, da + ks * 16, db + ks * 128, 1);
                    wg_commit();
                    wg_wait<0>();
                    mbar_arrive_elect(bar + 8 * (NST + st));
                }
                uint32_t xr[32];
#pragma unroll
                for (int t = 0; t < 32; t++) xr[t] = ldg32(x + o + 8 * (t >> 1) + (t & 1) * 8 * D_);
#pragma unroll
                for (int t = 0; t < 32; t++) *(uint32_t*)(x1 + o + 8 * (t >> 1) + (t & 1) * 8 * D_) = resid(xr[t], acc[2 * t], acc[2 * t + 1]);
            } else {
                int b, nt, k0, k1;
                ot_decode(id, b, nt, k0, k1);
                const size_t o = (size_t)(64 * b + 16 * (warp & 3) + g) * D_ + nt * 64 + 2 * q;
                float acc[32];
                uint32_t xr[16];
#pragma unroll
                for (int t = 0; t < 16; t++) xr[t] = wg == 0 && id < I_SA ? ldg32(x + o + 8 * (t >> 1) + (t & 1) * 8 * D_) : 0;
#pragma unroll
                for (int i = 0; i < 32; i++) acc[i] = 0.f;
                for (int kb = k0; kb < k1; kb++, rg.next(NST)) {
                    const int st = rg.st;
                    if (kb > k0) mbar_wait(bar + 8 * st, rg.par());
                    const u64 da = mkdesc(sb + st * STAGE + wg * 8192, 128, 1024), db = mkdesc(sb + st * STAGE + 24576 + wg * 8192, 0, 1024) | SW128;
                    wg_fence();
#pragma unroll
                    for (int ks = 0; ks < 4; ks++) wgmma_n64_ss<0, 1>(acc, da + ks * 16, db + ks * 128, 1);
                    wg_commit();
                    wg_wait<0>();
                    mbar_arrive_elect(bar + 8 * (NST + st));
                }
                const uint32_t ra = sb + OFF_RED + (tid & 127) * 16;
                if (wg) {
#pragma unroll
                    for (int t = 0; t < 8; t++)
                        sts128(ra + (wg - 1) * 16384 + t * 2048, __float_as_uint(acc[4 * t]), __float_as_uint(acc[4 * t + 1]), __float_as_uint(acc[4 * t + 2]), __float_as_uint(acc[4 * t + 3]));
                }
                bar_sync(4, 384);
                if (wg == 0) {
#pragma unroll
                    for (int t = 0; t < 8; t++) {
                        float u[4], v[4];
                        lds128f(u, ra + t * 2048); lds128f(v, ra + 16384 + t * 2048);
#pragma unroll
                        for (int i = 0; i < 4; i++) acc[4 * t + i] += u[i] + v[i];
                    }
                }
                bar_sync(4, 384);
                if (wg == 0) {
                    if (id < I_SA) {
#pragma unroll
                        for (int t = 0; t < 16; t++) *(uint32_t*)(x1 + o + 8 * (t >> 1) + (t & 1) * 8 * D_) = resid(xr[t], acc[2 * t], acc[2 * t + 1]);
                    } else {
                        float* y = g_yt + (layer * YT_ROWS - (S_ - YT_ROWS)) * D_ + o;
#pragma unroll
                        for (int t = 0; t < 16; t++)
                            asm volatile("red.relaxed.gpu.global.add.v2.f32 [%0],{%1,%2};" ::"l"(y + 8 * (t >> 1) + (t & 1) * 8 * D_), "f"(acc[2 * t]), "f"(acc[2 * t + 1]) : "memory");
                    }
                }
            }
            if (tid == 0) TLI(id, 2, gtime());
        }
    }
}

__global__ void __launch_bounds__(512, 1) side_kernel(const __grid_constant__ Maps maps, const bf16* __restrict__ x, bf16* __restrict__ x1, int layer) {
    extern __shared__ __align__(1024) unsigned char smem[];
    pdl_launch();
    TLS(3 + 5 * layer);
    worker(s2u(smem), maps, x, x1, layer);
    __syncwarp();
    pdl_wait();
    TLE(3 + 5 * layer);
}

constexpr float C5A = 0.30901699437494742f, C5B = -0.80901699437494742f, S5A = 0.95105651629515357f, S5B = 0.58778525229247313f;
template <int SGN> DEV void dft5(const float (&tr)[5], const float (&ti)[5], float (&zr)[5], float (&zi)[5]) {
    const float ar = tr[1] + tr[4], ai = ti[1] + ti[4], br = tr[2] + tr[3], bi = ti[2] + ti[3];
    const float cr = tr[1] - tr[4], ci = ti[1] - ti[4], dr = tr[2] - tr[3], di = ti[2] - ti[3];
    zr[0] = tr[0] + ar + br; zi[0] = ti[0] + ai + bi;
    const float m1r = tr[0] + C5A * ar + C5B * br, m1i = ti[0] + C5A * ai + C5B * bi;
    const float m2r = tr[0] + C5B * ar + C5A * br, m2i = ti[0] + C5B * ai + C5A * bi;
    const float n1r = SGN * (S5A * cr + S5B * dr), n1i = SGN * (S5A * ci + S5B * di);
    const float n2r = SGN * (S5B * cr - S5A * dr), n2i = SGN * (S5B * ci - S5A * di);
    zr[1] = m1r + n1i; zi[1] = m1i - n1r; zr[4] = m1r - n1i; zi[4] = m1i + n1r;
    zr[2] = m2r + n2i; zi[2] = m2i - n2r; zr[3] = m2r - n2i; zi[3] = m2i + n2r;
}
DEV void ln40(float (&v)[40]) {
    float s = 0.f;
#pragma unroll
    for (int i = 0; i < 40; i++) s += v[i];
#pragma unroll
    for (int o = 8; o; o >>= 1) s += __shfl_xor_sync(~0u, s, o);
    const float mean = s * (1.f / D_);
    float q = 0.f;
#pragma unroll
    for (int i = 0; i < 40; i++) { const float d = v[i] - mean; q += d * d; }
#pragma unroll
    for (int o = 8; o; o >>= 1) q += __shfl_xor_sync(~0u, q, o);
    const float mb = bf_round(mean);
    const float inv = 1.f / bf_round(sqrtf(bf_round(bf_round(q * (1.f / D_)) + 1e-5f)));
#pragma unroll
    for (int i = 0; i < 40; i++) v[i] = bf_round(v[i] - mb) * inv;
}
__global__ void __launch_bounds__(256) rowfft_kernel(const bf16* __restrict__ x0, bf16* __restrict__ x, const bf16* __restrict__ Wq,
                                                     const bf16* __restrict__ Wk, const bf16* __restrict__ Wv, int layer) {
    extern __shared__ __align__(1024) unsigned char smem[];
    const uint32_t sb = s2u(smem), sx = sb + 23552, sy = sx + 20480, bar = sy + 40960;
    const int tid = threadIdx.x, lane = tid & 31, q = lane & 3, blk = blockIdx.x, k2 = tid >> 2;
    if (tid == 0) TLI(800 + blk, 0, gtime());
    float twr[5], twi[5];
#pragma unroll
    for (int r = 1; r < 5; r++) { sincospif((float)(r * k2) * (-1.f / 320), &twi[r], &twr[r]); }
    uint32_t f[8][4];
#pragma unroll
    for (int ks = 0; ks < 8; ks++) { const uint4 u = g_f128[ks * 256 + tid]; f[ks][0] = u.x; f[ks][1] = u.y; f[ks][2] = u.z; f[ks][3] = u.w; }
    const bool split = blk * 16 >= S_ - YT_ROWS;
    if (tid == 0) {
        mbar_init(bar, 1);
        asm volatile("fence.mbarrier_init.release.cluster;" ::: "memory");
        mbar_expect(bar, split ? 61440 : 20480);
        if (split) bulk_g2s(sx, x0 + (size_t)blk * 16 * D_, 20480, bar);
    }
    __syncthreads();
    pdl_wait();
    pdl_launch();
    TLS(4 + 5 * layer);
    if (tid == 0) TLI(800 + blk, 1, gtime());
    if (tid == 0) {
        if (split) bulk_g2s(sy, g_yt + (layer * YT_ROWS + blk * 16 - (S_ - YT_ROWS)) * D_, 40960, bar);
        else bulk_g2s(sx, x + (size_t)blk * 16 * D_, 20480, bar);
    }
    mbar_wait(bar, 0);
    {
        const int rho = tid >> 4, j = tid & 15;
        float v[40];
#pragma unroll
        for (int i = 0; i < 5; i++) {
            uint32_t u[4];
            lds128(u, sx + tid * 80 + i * 16);
            if (split) {
                float p[8];
                lds128f(p, sy + tid * 160 + i * 32); lds128f(p + 4, sy + tid * 160 + i * 32 + 16);
#pragma unroll
                for (int k = 0; k < 4; k++) u[k] = resid(u[k], p[2 * k], p[2 * k + 1]);
                sts128(sx + tid * 80 + i * 16, u[0], u[1], u[2], u[3]);
            }
            unpack8(v + 8 * i, make_uint4(u[0], u[1], u[2], u[3]));
        }
        if (layer == 0 && tid < 12) prefetch_bulk((const char*)(tid < 4 ? Wk : tid < 8 ? Wq : Wv) + (blk * 4 + (tid & 3)) * 10240, 10240);
        ln40(v);
        const uint32_t a = sb + ((rho >> 1) & 1) * 2304 + j * 144 + (2 * (rho >> 2) + (rho & 1)) * 16;
#pragma unroll
        for (int r = 0; r < 5; r++)
            sts128(a + r * 4608, pack2(v[r], v[5 + r]), pack2(v[10 + r], v[15 + r]), pack2(v[20 + r], v[25 + r]), pack2(v[30 + r], v[35 + r]));
    }
    fence_async();
    __syncthreads();
    if (tid == 0) TLI(800 + blk, 2, gtime());
    if (tid == 0 && split) { bulk_s2g(x + (size_t)blk * 16 * D_, sx, 20480); bulk_commit(); }
    float acc[40];
    const u64 db = mkdesc(sb, 144, 2304);
    wg_fence();
    wgmma_n80_rs<0, 0>(acc, f[0], db);
#pragma unroll
    for (int ks = 1; ks < 8; ks++) wgmma_n80_rs<1, 0>(acc, f[ks], db + ks * 18);
    wg_commit();
    wg_wait<0>();
    unsigned char* zp = g_z + (blk >> 1) * 128 + ((((blk & 1) * 4 + q) ^ ((blk >> 1) & 7)) << 4);
    uint32_t o[5][4];
#pragma unroll
    for (int u = 0; u < 4; u++) {
        float tr[5], ti[5], zr[5], zi[5];
#pragma unroll
        for (int r = 0; r < 5; r++) {
            const float yr = acc[8 * r + 4 * (u >> 1) + (u & 1)], yi = k2 ? acc[8 * r + 4 * (u >> 1) + 2 + (u & 1)] : 0.f;
            tr[r] = r ? yr * twr[r] - yi * twi[r] : yr;
            ti[r] = r ? yr * twi[r] + yi * twr[r] : yi;
        }
        dft5<1>(tr, ti, zr, zi);
#pragma unroll
        for (int j = 0; j < 5; j++) o[j][u] = pack2(zr[j], j < 3 ? zi[j] : -zi[j]);
    }
#pragma unroll
    for (int j = 0; j < 5; j++)
        if (j < 3 || k2) *(uint4*)(zp + (64 * j + k2) * 8192) = make_uint4(o[j][0], o[j][1], o[j][2], o[j][3]);
    if (k2 == 0) {
#pragma unroll
        for (int u = 0; u < 4; u++) {
            float tr[5], ti[5], zr[5], zi[5];
            const float cr[5] = {1.f, -C5B, C5A, -C5A, C5B}, ci[5] = {0.f, -S5B, -S5A, -S5A, -S5B};
#pragma unroll
            for (int r = 0; r < 5; r++) { const float y = acc[8 * r + 4 * (u >> 1) + 2 + (u & 1)]; tr[r] = y * cr[r]; ti[r] = y * ci[r]; }
            dft5<1>(tr, ti, zr, zi);
            o[0][u] = pack2(zr[0], zi[0]); o[1][u] = pack2(zr[1], zi[1]); o[2][u] = pack2(zr[2], 0.f);
        }
        *(uint4*)(zp + 256 * 8192) = make_uint4(o[0][0], o[0][1], o[0][2], o[0][3]);
        *(uint4*)(zp + 192 * 8192) = make_uint4(o[1][0], o[1][1], o[1][2], o[1][3]);
        *(uint4*)(zp + 320 * 8192) = make_uint4(o[2][0], o[2][1], o[2][2], o[2][3]);
    }
    if (tid == 0) bulk_wait<0>();
    TLE(4 + 5 * layer);
    if (tid == 0) TLI(800 + blk, 3, gtime());
}

constexpr int CF_SMEM = 16384 + 3 * 16384 + 64;
__global__ void __launch_bounds__(384) colfft_kernel(int layer) {
    extern __shared__ __align__(1024) unsigned char smem[];
    const uint32_t sb = s2u(smem), bar = sb + 65536;
    const int tid = threadIdx.x, lane = tid & 31, q = lane & 3, wg = __shfl_sync(~0u, tid >> 7, 0), t = tid & 127, ka = t >> 2;
    const int col = blockIdx.x * 3 + wg;
    const uint32_t d0 = sb + 16384 + wg * 16384, d1 = d0 + 8192;
    if (tid == 0) {
        for (int i = 0; i < 4; i++) mbar_init(bar + 8 * i, 1);
        asm volatile("fence.mbarrier_init.release.cluster;" ::: "memory");
    }
    float twr[8], twi[8];
#pragma unroll
    for (int i = 0; i < 8; i++) sincospif((float)((4 * i + q) * (ka ? ka : -32)) * (1.f / 1024), &twi[i], &twr[i]);
    __syncthreads();
    if (tid == 0) { mbar_expect(bar + 24, 16384); bulk_g2s(sb, g_g32, 16384, bar + 24); }
    uint32_t f[4][4], w[16];
#pragma unroll
    for (int ks = 0; ks < 4; ks++) { const uint4 u = g_f64[ks * 128 + t]; f[ks][0] = u.x; f[ks][1] = u.y; f[ks][2] = u.z; f[ks][3] = u.w; }
#pragma unroll
    for (int i = 0; i < 4; i++) { const uint4 u = *(const uint4*)(g_wt + col * 8192 + i * 2048 + t * 16); w[4 * i] = u.x; w[4 * i + 1] = u.y; w[4 * i + 2] = u.z; w[4 * i + 3] = u.w; }
    pdl_wait();
    pdl_launch();
    TLS(5 + 5 * layer);
    if (t == 0) {
        mbar_expect(bar + 8 * wg, 8192);
        bulk_g2s(d0, g_z + col * 8192, 8192, bar + 8 * wg);
    }
    float acc[32];
    uint32_t a[4][4];
    mbar_wait(bar + 8 * wg, 0);
    {
        const u64 db = mkdesc(d0, 0, 1024) | SW128;
        wg_fence();
        wgmma_n64_rs<0, 1>(acc, f[0], db);
#pragma unroll
        for (int ks = 1; ks < 4; ks++) wgmma_n64_rs<1, 1>(acc, f[ks], db + ks * 128);
        wg_commit();
        wg_wait<0>();
    }
#pragma unroll
    for (int ks = 0; ks < 4; ks++) { const uint4 u = g_f64[512 + ks * 128 + t]; f[ks][0] = u.x; f[ks][1] = u.y; f[ks][2] = u.z; f[ks][3] = u.w; }
#pragma unroll
    for (int i = 0; i < 8; i++) {
        const float c0 = acc[4 * i], c1 = acc[4 * i + 1], c2 = acc[4 * i + 2], c3 = acc[4 * i + 3];
        const float pr = c0 + c3, pi = c1 - c2, nr = ka ? c0 - c3 : c2, ni = ka ? c1 + c2 : c3;
        a[i >> 1][2 * (i & 1)] = ka ? pack2(pr * twr[i] + pi * twi[i], pi * twr[i] - pr * twi[i]) : pack2(c0, c1);
        a[i >> 1][2 * (i & 1) + 1] = pack2(nr * twr[i] - ni * twi[i], ni * twr[i] + nr * twi[i]);
    }
    mbar_wait(bar + 24, 0);
    {
        const u64 db = mkdesc(sb, 128, 1024);
        wg_fence();
        wgmma_n64_rs<0, 0>(acc, a[0], db);
#pragma unroll
        for (int ks = 1; ks < 4; ks++) wgmma_n64_rs<1, 0>(acc, a[ks], db + ks * 16);
        wg_commit();
        wg_wait<0>();
    }
    constexpr float NORM = 1.f / (2048.f * 640.f);
#pragma unroll
    for (int i = 0; i < 16; i++) {
        const float zr = acc[2 * i] * NORM, zi = acc[2 * i + 1] * NORM, wr = bf_lo(w[i]), wi = bf_hi(w[i]);
        a[i >> 2][i & 3] = pack2(zr * wr - zi * wi, zr * wi + zi * wr);
    }
    {
        const u64 db = mkdesc(sb + 8192, 128, 1024);
        wg_fence();
        wgmma_n64_rs<0, 0>(acc, a[0], db);
#pragma unroll
        for (int ks = 1; ks < 4; ks++) wgmma_n64_rs<1, 0>(acc, a[ks], db + ks * 16);
        wg_commit();
        wg_wait<0>();
    }
    const uint32_t row = (t >> 5) * 2048 + (lane & 15) * 128;
#pragma unroll
    for (int i = 0; i < 8; i++) {
        const float c0 = acc[4 * i], c1 = acc[4 * i + 1], c2 = acc[4 * i + 2], c3 = acc[4 * i + 3];
        const float pr = c0 * twr[i] - c1 * twi[i], pi = c1 * twr[i] + c0 * twi[i];
        const float nr = c2 * twr[i] + c3 * twi[i], ni = c3 * twr[i] - c2 * twi[i];
        a[i >> 1][2 * (i & 1)] = ka ? pack2(pr + nr, pi + ni) : pack2(c0, c1);
        a[i >> 1][2 * (i & 1) + 1] = ka ? pack2(ni - pi, pr - nr) : pack2(nr, ni);
    }
#pragma unroll
    for (int i = 0; i < 4; i++) stsm4(d1 + row + (((2 * i + (lane >> 4)) ^ (lane & 7)) << 4), a[i][0], a[i][1], a[i][2], a[i][3]);
    fence_async();
    bar_sync(1 + wg, 128);
    {
        const u64 db = mkdesc(d1, 0, 1024) | SW128;
        wg_fence();
        wgmma_n64_rs<0, 1>(acc, f[0], db);
#pragma unroll
        for (int ks = 1; ks < 4; ks++) wgmma_n64_rs<1, 1>(acc, f[ks], db + ks * 128);
        wg_commit();
        wg_wait<0>();
    }
#pragma unroll
    for (int i = 0; i < 4; i++)
        stsm4(d0 + row + (((2 * i + (lane >> 4)) ^ (lane & 7)) << 4), pack2(acc[8 * i], acc[8 * i + 1]), pack2(acc[8 * i + 2], acc[8 * i + 3]),
              pack2(acc[8 * i + 4], acc[8 * i + 5]), pack2(acc[8 * i + 6], acc[8 * i + 7]));
    fence_async();
    bar_sync(1 + wg, 128);
    if (t == 0) {
        bulk_s2g(g_z + col * 8192, d0, 8192);
        asm volatile("cp.async.bulk.commit_group;" ::: "memory");
        asm volatile("cp.async.bulk.wait_group 0;" ::: "memory");
    }
    TLE(5 + 5 * layer);
}

__global__ void __launch_bounds__(256) rowifft_kernel(const bf16* __restrict__ x, bf16* __restrict__ out, int last) {
    extern __shared__ __align__(1024) unsigned char smem[];
    const uint32_t sb = s2u(smem), sx = sb + 20480, sy = sx + 20480, bar = sy + 16 * 1296;
    const int tid = threadIdx.x, lane = tid & 31, q = lane & 3, blk = blockIdx.x, k2 = tid >> 2, warp = tid >> 5;
    float twr[5], twi[5];
#pragma unroll
    for (int r = 1; r < 5; r++) { sincospif((float)(r * k2) * (1.f / 320), &twi[r], &twr[r]); twr[r] *= 2.f; twi[r] *= 2.f; }
    uint32_t f[8][4];
#pragma unroll
    for (int ks = 0; ks < 8; ks++) { const uint4 u = g_f128[2048 + ks * 256 + tid]; f[ks][0] = u.x; f[ks][1] = u.y; f[ks][2] = u.z; f[ks][3] = u.w; }
    if (tid == 0) {
        mbar_init(bar, 1);
        asm volatile("fence.mbarrier_init.release.cluster;" ::: "memory");
        mbar_expect(bar, 20480);
        bulk_g2s(sx, x + (size_t)blk * 16 * D_, 20480, bar);
    }
    pdl_wait();
    pdl_launch();
    TLS(6 + 5 * last);
    const unsigned char* zp = g_z + (blk >> 1) * 128 + ((((blk & 1) * 4 + q) ^ ((blk >> 1) & 7)) << 4);
    uint4 z[6];
#pragma unroll
    for (int j = 0; j < 5; j++) z[j] = *(const uint4*)(zp + (64 * j + k2) * 8192);
    z[5] = k2 ? make_uint4(0, 0, 0, 0) : *(const uint4*)(zp + 320 * 8192);
    float acc[40];
#pragma unroll
    for (int u = 0; u < 4; u++) {
        float yr[6], yi[6], tr[5], ti[5], zr[5], zi[5];
#pragma unroll
        for (int j = 0; j < 6; j++) { const uint32_t v = u == 0 ? z[j].x : u == 1 ? z[j].y : u == 2 ? z[j].z : z[j].w; yr[j] = bf_lo(v); yi[j] = bf_hi(v); }
#pragma unroll
        for (int j = 0; j < 5; j++) { tr[j] = yr[j]; ti[j] = j < 3 ? yi[j] : -yi[j]; }
        dft5<-1>(tr, ti, zr, zi);
        const float c1[5] = {1.f, C5A, C5B, C5B, C5A}, s1[5] = {0.f, S5A, S5B, -S5B, -S5A};
        const float c2[5] = {1.f, C5B, C5A, C5A, C5B}, s2[5] = {0.f, S5B, -S5A, S5A, -S5B};
        const float c3[5] = {1.f, -C5B, C5A, -C5A, C5B}, s3[5] = {0.f, S5B, S5A, S5A, S5B};
        const float c4[5] = {1.f, -C5A, C5B, -C5B, C5A}, s4[5] = {0.f, S5A, -S5B, -S5B, S5A};
#pragma unroll
        for (int r = 0; r < 5; r++) {
            float er = r ? zr[r] * twr[r] - zi[r] * twi[r] : 2.f * zr[0], ei = r ? zr[r] * twi[r] + zi[r] * twr[r] : 2.f * zi[0];
            if (k2 == 0) {
                er = yr[0] + 2.f * (yr[1] * c1[r] - yi[1] * s1[r] + yr[2] * c2[r] - yi[2] * s2[r]);
                ei = (r & 1 ? -yr[5] : yr[5]) + 2.f * (yr[4] * c3[r] - yi[4] * s3[r] + yr[3] * c4[r] - yi[3] * s4[r]);
            }
            acc[8 * r + 4 * (u >> 1) + (u & 1)] = er;
            acc[8 * r + 4 * (u >> 1) + 2 + (u & 1)] = ei;
        }
    }
#pragma unroll
    for (int r = 0; r < 5; r++)
        stsm4(sb + (2 * warp + ((lane >> 3) & 1)) * 1280 + (2 * r + (lane >> 4)) * 128 + (lane & 7) * 16, pack2(acc[8 * r], acc[8 * r + 1]),
              pack2(acc[8 * r + 2], acc[8 * r + 3]), pack2(acc[8 * r + 4], acc[8 * r + 5]), pack2(acc[8 * r + 6], acc[8 * r + 7]));
    fence_async();
    __syncthreads();
    const u64 db = mkdesc(sb, 1280, 128);
    wg_fence();
    wgmma_n80_rs<0, 1>(acc, f[0], db);
#pragma unroll
    for (int ks = 1; ks < 8; ks++) wgmma_n80_rs<1, 1>(acc, f[ks], db + ks * 160);
    wg_commit();
    wg_wait<0>();
#pragma unroll
    for (int u = 0; u < 4; u++) {
        float e[10];
#pragma unroll
        for (int r = 0; r < 5; r++) { e[r] = acc[8 * r + 4 * (u >> 1) + (u & 1)]; e[5 + r] = acc[8 * r + 4 * (u >> 1) + 2 + (u & 1)]; }
#pragma unroll
        for (int i = 0; i < 5; i++) sts32(sy + (4 * q + u) * 1296 + k2 * 20 + i * 4, pack2(e[2 * i], e[2 * i + 1]));
    }
    __syncthreads();
    const int rho = tid >> 4, j = tid & 15;
    float v[40];
    mbar_wait(bar, 0);
#pragma unroll
    for (int i = 0; i < 5; i++) {
        uint32_t y[4], u[4];
        lds128(y, sy + rho * 1296 + j * 80 + i * 16);
        lds128(u, sx + tid * 80 + i * 16);
#pragma unroll
        for (int k = 0; k < 4; k++) u[k] = pack2(bf_lo(u[k]) + bf_lo(y[k]), bf_hi(u[k]) + bf_hi(y[k]));
        sts128(sx + tid * 80 + i * 16, u[0], u[1], u[2], u[3]);
        unpack8(v + 8 * i, make_uint4(u[0], u[1], u[2], u[3]));
    }
    if (!last) {
        ln40(v);
#pragma unroll
        for (int i = 0; i < 5; i++) {
            const int c = j * 5 + i;
            sts128(sb + (c >> 3) * 2048 + rho * 128 + (((c ^ rho) & 7) << 4), pack2(v[8 * i], v[8 * i + 1]), pack2(v[8 * i + 2], v[8 * i + 3]),
                   pack2(v[8 * i + 4], v[8 * i + 5]), pack2(v[8 * i + 6], v[8 * i + 7]));
        }
    }
    fence_async();
    __syncthreads();
    if (lane == 0) {
        if (warp == 7) bulk_s2g(out + (size_t)blk * 16 * D_, sx, 20480);
        else if (!last && warp < 5) {
            unsigned char* p = g_xn + (blk >> 1) * 40960 + warp * 8192 + (blk & 1) * 2048;
            bulk_s2g(p, sb + warp * 4096, 2048);
            bulk_s2g(p + 4096, sb + warp * 4096 + 2048, 2048);
        }
        bulk_commit();
        bulk_wait<0>();
    }
    TLE(6 + 5 * last);
}

namespace rec {
#define NSA 5
#define NSB 2
#define REG0 184
#define REG1 184
constexpr int NS = NSA, NS0 = NSB;
constexpr int OFF_X = 0;
constexpr int OFF_WO = 81920;
constexpr int OFF_WS = OFF_WO + 65536;
constexpr int OFF_MEMB = OFF_WS + (NS + NS0) * 2048;
constexpr int OFF_VX = OFF_MEMB + 10240;
constexpr int OFF_VM = OFF_VX + 16384;
constexpr int OFF_Q = OFF_VM + 8192;
constexpr int OFF_K = OFF_Q + 10240;
constexpr int OFF_OST = OFF_WO + 49152;
constexpr int OFF_PX = OFF_OST + 8192;
constexpr int OFF_PT = OFF_PX + 2560;
constexpr int OFF_PS = OFF_K + 10240;
constexpr int OFF_OB = OFF_PS + 1280;
constexpr int OFF_MX = OFF_OB + 2048;
constexpr int OFF_BAR = OFF_MX + 64;
constexpr int OFF_PROF = OFF_BAR + 256;
constexpr int SMEM = OFF_PROF + 4096 > wk::SMEM ? OFF_PROF + 4096 : wk::SMEM;
enum { B_XT = 0, B_KX = 2, B_VX = 4, B_XD = 6, B_X1 = 8, B_PXF = 12, B_PXE = 13, B_FIN = 14, B_ST = 15 };
enum { NB_W2 = 0, NB_GO = 1, NB_QK = 2, NB_WIN = 3, NB_ATT = 4, NB_X = 5, NB_PRO = 6, NB_W1 = 7, NB_MEM = 8  , NB_LD = 13  , NB_KX = 15 };
#define NOX 0
#define NW1 10
#define NW1B 0
#define LDX1 0
#define RING 8
template <int N> struct IC { static constexpr int value = N; };
template <int N, int I = 0, class F> DEV void static_for(F&& f) { if constexpr (I < N) { f(IC<I>{}); static_for<N, I + 1>(f); } }
constexpr float SM_SCALE = 0.08838834764831845f * 1.4426950408889634f;
}

__global__ void __launch_bounds__(512, 1) rec_kernel(const __grid_constant__ Maps maps, const bf16* __restrict__ x, bf16* __restrict__ x1, const bf16* __restrict__ mem0, const bf16* __restrict__ Wq, const bf16* __restrict__ Wk,
                                                     const bf16* __restrict__ Wv, const bf16* __restrict__ Wo, int layer, int delay, int delay2) {
    using namespace rec;
    extern __shared__ __align__(1024) unsigned char smem[];
    const uint32_t sb = s2u(smem);
    if (blockIdx.x >= 3 * H_) {
        pdl_wait();
        pdl_launch();
        worker(sb, maps, x, x1, layer);
        return;
    }
    const int tid = threadIdx.x, lane = tid & 31, warp = __shfl_sync(~0u, tid >> 5, 0);
    const int g = lane >> 2, q = lane & 3;
    const int h = blockIdx.x / 3;
    const uint32_t bar = sb + OFF_BAR;
    STAMP(2 * layer);
    TLS(2 + 5 * layer);
    if (tid == 0) {
        for (int i = 0; i < 2; i++) {
            mbar_init(bar + 8 * (B_XT + i), 1); mbar_init(bar + 8 * (B_KX + i), 4); mbar_init(bar + 8 * (B_VX + i), 1);
            mbar_init(bar + 8 * (B_XD + i), 8); mbar_init(bar + 8 * (B_X1 + i), 1);
        }
        mbar_init(bar + 8 * B_PXF, 1); mbar_init(bar + 8 * B_PXE, 2); mbar_init(bar + 8 * B_ST, 2);
        mbar_init(bar + 8 * B_FIN, 48);
        sts32(sb + OFF_MX + 32, 0); sts32(sb + OFF_MX + 36, 0);
        asm volatile("fence.mbarrier_init.release.cluster;" ::: "memory");
    }
    asm volatile("barrier.cluster.arrive.aligned; barrier.cluster.wait.aligned;" ::: "memory");
    const bool never = delay < 0;

    if (warp < 8) {
        auto role = [&](auto XP) {
            constexpr int wg = XP.value, NSW = wg ? NS : NS0;
            asm volatile("setmaxnreg.inc.sync.aligned.u32 %0;" ::"n"(wg ? REG1 : REG0));
            const uint32_t rank = cta_rank();
            uint32_t a[40 - NSW][4];
            const uint32_t l16 = opaque(sb + lane * 16);
            uint32_t wsa = wg ? opaque(sb + OFF_WS + (warp & 3) * 512 + (lane & 7) * 16 + ((lane >> 3) & 1) * 256 + (lane >> 4) * 128) : 0;
            uint32_t dst = opaque(rank < 2 ? sb + OFF_Q + wg * 10240 + (warp & 3) * 256 + (lane & 15) * 16 + (lane >> 4) * 1024
                                           : sb + OFF_VM + warp * 256 + lane * 4);
            uint32_t& sfd = wg ? wsa : dst;
            auto ws_addr = [&](int ks) { return wg ? wsa + ks * 2048 : l16 + OFF_WS + (NS + ks) * 2048 + warp * 512; };
            {
                const int t = tid & 127;
                const bf16* src = (rank == 2 ? Wv + wg * 64 : (wg ? Wk : Wq) + rank * 64) + h * E_ + (size_t)(t >> 3) * 4096 + (t & 7) * 8;
                const uint32_t stg = sb + (wg ? OFF_VX : OFF_X + 40960);
                const uint32_t sdst = stg + (t >> 3) * 128 + (((t & 7) ^ ((t >> 3) & 7)) << 4);
                const uint32_t ra = stg + ((lane >> 4) * 8 + (lane & 7)) * 128 + (((2 * (warp & 3) + ((lane >> 3) & 1)) ^ (lane & 7)) << 4);
                auto issue = [&](int rd) {
#pragma unroll
                    for (int i = 0; i < 10; i++) cp16(sdst + (rd & 1) * 20480 + i * 2048, src + (size_t)(rd * 160 + i * 16) * 4096);
                    cp_commit();
                };
                issue(0); issue(1);
                pdl_wait();
                pdl_launch();
#pragma unroll
                for (int rd = 0; rd < 4; rd++) {
                    if (rd < 3) cp_wait<1>(); else cp_wait<0>();
                    bar_sync(NB_LD + wg, 128);
#pragma unroll
                    for (int i = 0; i < 10; i++) {
                        const int ks = rd * 10 + i;
                        if (ks < NSW) {
                            uint32_t f[4];
                            ldsm4t(f, ra + i * 2048);
                            stsm4(ws_addr(ks), f[0], f[1], f[2], f[3]);
                        } else ldsm4t(a[ks - NSW], ra + (rd & 1) * 20480 + i * 2048);
                    }
                    if (rd < 2) { bar_sync(NB_LD + wg, 128); issue(rd + 2); }
                }
                fence_async();
                bar_sync(NB_PRO, 288);
            }
            float acc[16];
            uint32_t xlo = (uint32_t)mkdesc(sb + OFF_X, 0, 0);
            const uint32_t xtog = xlo ^ (uint32_t)mkdesc(sb + OFF_X + 40960, 0, 0);
            uint32_t p8 = 0;
            auto xproj = [&](auto K1, auto K0) {
                const u64 desc = (u64)xlo | (64ull << 32) | SW128, da = mkdesc(sb + OFF_WS, 128, 256);
                wg_fence();
#pragma unroll
                for (int ks = K1.value - 1; ks >= K0.value; ks--) {
                    const u64 db = desc + (ks >> 2) * 256 + (ks & 3) * 2;
                    if (ks == 39) wgmma_n32_rs<0>(acc, a[ks - NSW], db);
                    else if (NOX) {}
                    else if (ks < NSW) wgmma_n32_ss<1>(acc, da + ks * 128, db);
                    else wgmma_n32_rs<1>(acc, a[ks - NSW], db);
                }
                wg_commit();
            };
            auto xstore = [&]() {
                wg_wait<0>();
                uint32_t pk[8];
#pragma unroll
                for (int i = 0; i < 8; i++) pk[i] = pack2(acc[2 * i], acc[2 * i + 1]);
                if (rank < 2) {
                    stsm4t(dst + 1024, pk[0], pk[1], pk[2], pk[3]);
                    stsm4t(dst + 3072, pk[4], pk[5], pk[6], pk[7]);
                    bar_arrive(NB_KX, 256);
                } else {
                    const uint32_t la = wsa + (wsa & 256) + (OFF_VX + 4096 - OFF_WS) + (warp & 3) * 512 + p8 * 1024;
                    stsm4(la, pk[0], pk[1], pk[2], pk[3]);
                    stsm4(la + 256, pk[4], pk[5], pk[6], pk[7]);
                    fence_async();
                    mbar_arrive_elect(bar + 8 * B_KX + p8);
                }
            };
            bar_sync(NB_LD, 288);
            if (wg) {
                xproj(IC<40>{}, IC<0>{});
                xstore();
            }
            for (int s = 0;; s++) {
                float d0[4] = {0.f, 0.f, 0.f, 0.f}, d1[4] = {0.f, 0.f, 0.f, 0.f};
                uint32_t t[NSW][4], b[20][4];
#pragma unroll
                for (int ks = 0; ks < NSW; ks++) ldsm4(t[ks], ws_addr(ks));
                bar_sync(NB_MEM, 384);
                lds128(b[0], l16 + OFF_MEMB); lds128(b[1], l16 + OFF_MEMB + 512); lds128(b[2], l16 + OFF_MEMB + 1024);
                xlo ^= xtog;
                const uint32_t xb0 = mapa(bar + 8 * B_X1 + p8, 0), xb1 = mapa(bar + 8 * B_X1 + p8, 1);
                SFENCE();
                float is;
#pragma unroll
                for (int kp = 0; kp < 20; kp++) {
#pragma unroll
                    for (int j = 0; j < 2; j++) {
                        const int ks = 2 * kp + j;
                        const uint32_t* f = ks < NSW ? t[ks] : a[ks - NSW];
                        mma16(j ? d1 : d0, f[0], f[1], f[2], f[3], b[kp][2 * j], b[kp][2 * j + 1]);
                    }
                    if (kp == 0 && warp == 4) PROFT(0);
                    if (kp < 16 && (kp & 3) == 1) bar_sync(NB_MEM + 1 + (kp >> 2), 384);
                    if (kp + 3 < 20) lds128(b[kp + 3], l16 + OFF_MEMB + (kp + 3) * 512);
                    if (kp == 17) is = lds32f(sb + OFF_MX + 16);
                    if (kp < 18) SFENCE();
                }
                const uint32_t p0 = pack2((d0[0] + d1[0]) * is, (d0[1] + d1[1]) * is), p1 = pack2((d0[2] + d1[2]) * is, (d0[3] + d1[3]) * is);
                if (rank < 2) {
                    stsm2t(dst, p0, p1);
                } else {
                    st_async1(mapa(dst, 0), p0, xb0); st_async1(mapa(dst, 1), p0, xb1);
                    st_async1(mapa(dst + 128, 0), p1, xb0); st_async1(mapa(dst + 128, 1), p1, xb1);
                    sts32(dst, p0); sts32(dst + 128, p1);
                }
                bar_arrive(NB_QK, 384);
                if (warp == 4) PROFT(1);
                dst += rank < 2 ? (p8 ? -5120 : 5120) : ((s & 3) == 3 ? -6144 : 2048);
                p8 ^= 8;
                if (wg) {
                    if (rank < 2) bar_sync(NB_W1, 416); else bar_sync(NB_W1, 352);
                    if (s == NSEG - 1) break;
                    xproj(IC<40>{}, IC<40 - NW1>{});
                    wg_wait<0>();
                    if (warp == 4) PROFT(15);
                    if (rank < 2) bar_sync(NB_W2, 256);
                    if (NW1B > 0) {
                        xproj(IC<40 - NW1>{}, IC<40 - NW1 - NW1B>{});
                        wg_wait<0>();
                    }
                    if (rank == 2) bar_sync(NB_WIN, 256);
                    xproj(IC<40 - NW1 - NW1B>{}, IC<0>{});
                    xstore();
                    if (warp == 4) PROFT(3);
                } else {
                    const unsigned char* pn = g_p + (size_t)((s + 1) * H_ + h) * 12288;
                    if (warp == 1) {
                        if (s + 1 < NSEG && elect()) {
                            const uint32_t xt = bar + 8 * B_XT + (p8 ^ 8);
                            if (LDX1) while (!mbar_try(bar + 8 * B_X1 + (p8 ^ 8), (s >> 1) & 1)) {}
                            mbar_expect(xt, (s + 2 < NSEG ? 40960 : 0) + (rank < 2 ? 4096 : 0));
                            if (s + 2 < NSEG) bulk_g2s(sb + OFF_X + (p8 ^ 8) * 5120, g_xn + (s + 2) * 40960, 40960, xt);
                            const int blk = wk::pb_first(s + 1);
                            if (blk >= 0) flag_wait<false>(g_sync + layer * SYNC_LAYER + wk::SY_P + blk * H_ + h, 3);
                            if (rank < 2) bulk_g2s(sb + OFF_Q + p8 * 640 + 1024, pn + rank * 4096, 4096, xt);
                            else if (s + 2 < NSEG) bulk_g2s(sb + OFF_VX + p8 * 1024, pn + 8192, 4096, bar + 8 * B_VX + p8);
                        }
                        __syncwarp();
                        if (rank < 2 && s + 1 < NSEG) {
                            if (s) bar_sync(NB_X, 160);
                            if (elect()) bulk_g2s(sb + OFF_VX + p8 * 1024, pn + 8192, 4096, bar + 8 * B_VX + p8);
                            __syncwarp();
                        }
                    } else if (warp == 2 && rank < 2) {
                        bar_sync(NB_W1, 416);
                        for (int n = s - 2; n < (s + 1 < NSEG ? s - 1 : NSEG); n++) {
                            if (n > s - 2) { bulk_wait<0>(); __syncwarp(); bar_sync(NB_W1, 160); }
                            if (lane == 0 && n >= 0) {
                                unsigned char* op = g_o + (size_t)(n * H_ + h) * 8192 + rank * 2048;
                                bulk_s2g(op, sb + OFF_OST + (n & 1) * 4096, 2048);
                                bulk_s2g(op + 4096, sb + OFF_OST + (n & 1) * 4096 + 2048, 2048);
                                bulk_commit();
                                bulk_wait<0>();
                                st_remote(mapa(sb + OFF_MX + 32 + 4 * rank, 2), n + 1);
                            }
                            __syncwarp();
                        }
                    }
                    if (warp == 1) PROFT(2);
                    if (warp == 2) PROFT(5);
                    if (s == NSEG - 1) break;
                    if (warp == 0) {
                        uint32_t* hp = g_sync + layer * SYNC_LAYER + 1024 + s * 32;
                        for (int n = 0; n < 1000 && !mbar_try(bar + 8 * B_X1 + (p8 ^ 8), (s >> 1) & 1); n++) {}
                        uint32_t t = gtime32();
                        if (rank == 0 && lane == 0) {
                            asm volatile("red.relaxed.gpu.global.max.u32 [%0],%1;" ::"l"(hp + 1), "r"(t) : "memory");
                            asm volatile("red.relaxed.gpu.global.add.u32 [%0],1;" ::"l"(hp) : "memory");
                        }
                        while (gtime32() - t < 150u) {}
                        for (int n = 0; n < 1000; n++) {
                            uint32_t c;
                            asm volatile("ld.relaxed.gpu.global.v2.u32 {%0,%1},[%2];" : "=r"(c), "=r"(t) : "l"(hp) : "memory");
                            if (c == H_) break;
                        }
                        while (gtime32() - t < (uint32_t)delay) {}
                        bar_arrive(NB_GO, 160);
                        t = clk();
                        while (clk() - t < (uint32_t)delay2) {}
                        bar_arrive(NB_PRO, 160);
                        while (clk() - t < 2 * (uint32_t)delay2) {}
                        bar_arrive(NB_LD, 160);
                        while (clk() - t < 3 * (uint32_t)delay2) {}
                        bar_arrive(NB_LD + 1, 160);
                    }
                }
            }
        };
        if (warp < 4) role(IC<0>{}); else role(IC<1>{});
    } else if (warp < 12) {
        asm volatile("setmaxnreg.dec.sync.aligned.u32 96;");
        const uint32_t rank = cta_rank();
        const int w = warp - 8;
        uint32_t amax = 0;
#pragma unroll
        for (int it = 0; it < 5; it++) {
            const int kp = it * 4 + w;
            const bf16* p = mem0 + g * D_ + kp * 32 + 2 * q;
            uint32_t b0 = ldg32(p), b1 = ldg32(p + 8), b2 = ldg32(p + 16), b3 = ldg32(p + 24);
            sts128(sb + OFF_MEMB + kp * 512 + lane * 16, b0, b1, b2, b3);
            amax = absmax2(amax, absmax2(absmax2(b0, b1), absmax2(b2, b3)));
        }
        if (tid == 256) { sts32(sb + OFF_MX + 16, 0x3f800000u); sts128(sb + OFF_MX + 48, 0x3f803f80u, 0x3f803f80u, 0x3f803f80u, 0x3f803f80u); }
        bar_arrive(NB_MEM, 384); bar_arrive(NB_MEM + 1, 384); bar_arrive(NB_MEM + 2, 384); bar_arrive(NB_MEM + 3, 384); bar_arrive(NB_MEM + 4, 384);
        {
            const int t = tid & 127, nr = rank == 2 ? 4 : 3;
            for (int r = 0; r < nr; r++) {
                const bf16* src = Wo + (size_t)(h * E_) * D_ + (r < 3 ? 192 * r + 64 * rank : 576);
#pragma unroll
                for (int i = 0; i < 8; i++) {
                    const int e = i * 16 + (t >> 3);
                    cp16(sb + OFF_WO + r * 16384 + e * 128 + (((t & 7) ^ (e & 6)) << 4), src + e * D_ + (t & 7) * 8);
                }
            }
            cp_commit();
            pdl_wait();
            pdl_launch();
            cp_wait<0>();
            bar_sync(NB_ATT, 128);
            for (int r = 0; r < nr; r++) {
                uint32_t u[8][4];
                const uint32_t p = sb + OFF_WO + r * 16384 + 2 * q * 128 + (((2 * w + (g & 1)) ^ (2 * q)) << 4) + (g >> 1) * 4;
#pragma unroll
                for (int ks = 0; ks < 8; ks++)
#pragma unroll
                    for (int j = 0; j < 4; j++) u[ks][j] = lds32(p + (16 * ks + (j & 1) * 8 + (j >> 1)) * 128);
                bar_sync(NB_ATT, 128);
#pragma unroll
                for (int ks = 0; ks < 8; ks++)
                    sts128(sb + OFF_WO + (r * 4 + w) * 4096 + ks * 512 + lane * 16, prmt(u[ks][0], u[ks][2], 0x5410), prmt(u[ks][0], u[ks][2], 0x7632),
                           prmt(u[ks][1], u[ks][3], 0x5410), prmt(u[ks][1], u[ks][3], 0x7632));
            }
        }
        float cw;
        {
            const float4 a = ((const float4*)g_nrm)[lane], c = ((const float4*)g_nrm)[32 + lane];
            float sm = sqrtf((a.x + a.y) + (a.z + a.w)) * sqrtf((c.x + c.y) + (c.z + c.w)), mxv = sm;
#pragma unroll
            for (int o = 16; o; o >>= 1) { sm += __shfl_xor_sync(~0u, sm, o); mxv = fmaxf(mxv, __shfl_xor_sync(~0u, mxv, o)); }
            cw = 26.5f * fmaxf(sm, 8.f * mxv);
        }
        if (w == 0) {
            mbar_expect_elect(bar + 8 * B_X1, rank < 2 ? 3328 : 1280);
            mbar_expect_elect(bar + 8 * B_VX, rank < 2 ? 8192 : 4096);
        }
        auto steps = [&](auto KIND) {
            constexpr int kind = KIND.value, NT = kind == 2 ? 4 : 3;
            const uint32_t l16 = opaque(sb + lane * 16), lw = opaque(sb + lane * 16 + w * 512);
            const uint32_t pa = opaque(sb + OFF_PS + rank * 512 + lane * 4 + w * 128);
            uint32_t lq = opaque(sb + OFF_Q + (lane & 7) * 16 + ((lane >> 3) & 1) * 256 + (lane >> 4) * 128);
            const uint32_t lv = opaque(sb + OFF_VX + w * 2048 + (lane & 7) * 16 + ((lane >> 3) & 1) * 512 + (lane >> 4) * 128);
            const uint32_t lo = opaque(sb + OFF_WO + w * 4096 + lane * 16);
            uint32_t& sfd = lq;
            const char* rp = (const char*)(g_acc + layer * ACC_LAYER) + (4 * rank + w) * 4096 + opaque((q >> 1) * 1024 + ((q & 1) * 8 + g) * 8);
            const char* lp = (const char*)(g_acc + layer * ACC_LAYER) + opaque(w * 8192 + (2 * (g & 1) + (g >> 2)) * 1024 + (((g >> 1) & 1) * 8 + 2 * q) * 8);
            float isig = 1.f;
            uint32_t kf[8];
            if (kind < 2) {
                bar_sync(NB_KX, 256);
                ldsm4(kf, l16 + OFF_K + (1 + w) * 1024); ldsm4(kf + 4, l16 + OFF_K + (1 + w) * 1024 + 512);
            }
            for (int s = 0; s < NSEG - 1; s++) {
                const uint32_t pb = s & 1, ph = (s >> 1) & 1, x1 = bar + 8 * (B_X1 + pb);
                sts32(sb + OFF_MX + w * 4, __reduce_max_sync(~0u, max(amax & 0x7fff0000u, (amax << 16) & 0x7fff0000u)));
                mbar_wait(bar + 8 * (B_VX + pb), ph);
                const uint32_t va = lv + pb * 8192, vma = lw + OFF_VM + (s & 3) * 2048;
                uint32_t wf[RING][4], vf[2][2][4], vm[4], one[4];
                auto scores = [&](auto MM) {
                    constexpr int mm = MM.value;
                    uint32_t qf[8], mf[8];
                    const uint32_t qa = lq + pb * 5120, ka = l16 + OFF_K + pb * 5120;
                    const uint32_t pa0 = mapa(pa, rank ^ 1), pa1 = mapa(pa, 2), pa2 = mapa(pa, rank);
                    const uint32_t xb0 = mapa(x1, rank ^ 1), xb1 = mapa(x1, 2), xb2 = mapa(x1, rank);
                    const uint32_t pm = 640 - rank * 384;
                    SFENCE();
                    bar_sync(NB_QK, 384);
                    ldsm4(qf, qa); ldsm4(qf + 4, qa + 512);
                    if (mm) { ldsm4(mf, ka); ldsm4(mf + 4, ka + 512); }
                    SFENCE();
                    float c[8][4];
#pragma unroll
                    for (int i = 0; i < (mm ? 8 : 4); i++) {
                        const uint32_t* f = (i < 4 ? kf : mf) + 2 * (i & 3);
                        c[i][0] = c[i][1] = c[i][2] = c[i][3] = 0.f;
                        mma16(c[i], qf[i & 2 ? 4 : 0], qf[i & 2 ? 5 : 1], qf[i & 2 ? 6 : 2], qf[i & 2 ? 7 : 3], f[0], f[1]);
                    }
                    SFENCE();
                    const uint32_t y = pack2((c[0][0] + c[1][2]) + (c[2][0] + c[3][2]), (c[0][1] + c[1][3]) + (c[2][1] + c[3][3]));
                    st_async1(pa0, y, xb0); st_async1(pa1, y, xb1);
                    if (mm) {
                        const uint32_t z = pack2((c[4][0] + c[5][2]) + (c[6][0] + c[7][2]), (c[4][1] + c[5][3]) + (c[6][1] + c[7][3]));
                        st_async1(pa0 + pm, z, xb0); st_async1(pa1 + pm, z, xb1); st_async1(pa2 + pm, z, xb2);
                    }
                    st_async1(pa2, y, xb2);
                };
                if (kind == 2) bar_sync(NB_QK, 384);
                else if (w == 3) scores(IC<1>{});
                else scores(IC<0>{});
#pragma unroll
                for (int t = 0; t < 2; t++)
#pragma unroll
                    for (int j = 0; j < 2; j++) ldsm4(vf[t][j], va + t * 1024 + j * 256);
                float m4[4];
                lds128f(m4, sb + OFF_MX);
                bar_arrive(NB_W1, kind < 2 ? 416 : 352);
                lds128(one, sb + OFF_MX + 48);
                if (w == 0) PROFT(4);
                mbar_wait(x1, ph);
                if (w == 0) PROFT(6);
                float sc[10];
                {
                    uint32_t u[4], v[4], m[2];
                    ldsm4(u, l16 + OFF_PS); ldsm4(v, l16 + OFF_PS + 512); ldsm2(m, l16 + OFF_PS + 1024);
                    ldsm4(vm, vma);
                    SFENCE();
                    m4[0] = fmaxf(fmaxf(m4[0], m4[1]), fmaxf(m4[2], m4[3])) * isig;
                    SFENCE();
#pragma unroll
                    for (int i = 0; i < 4; i++) { sc[2 * i] = bf_lo(u[i]) + bf_lo(v[i]); sc[2 * i + 1] = bf_hi(u[i]) + bf_hi(v[i]); }
                    sc[8] = bf_lo(m[0]) + bf_lo(m[1]); sc[9] = bf_hi(m[0]) + bf_hi(m[1]);
                }
                float mx = fmaxf(fmaxf(fmaxf(fmaxf(sc[0], sc[1]), fmaxf(sc[2], sc[3])), fmaxf(fmaxf(sc[4], sc[5]), fmaxf(sc[6], sc[7]))), fmaxf(sc[8], sc[9]));
                auto fetch = [&](int i) { if (i < 8 * NT) lds128(wf[i % RING], lo + (i >> 3) * 16384 + (i & 7) * 512); };
                {
                    float m1 = __shfl_xor_sync(~0u, mx, 1), m2 = __shfl_xor_sync(~0u, mx, 2), m3 = __shfl_xor_sync(~0u, mx, 3);
                    SFENCE();
#pragma unroll
                    for (int i = 0; i < 4; i++) fetch(i);
                    SFENCE();
                    mx = fmaxf(fmaxf(mx, m1), fmaxf(m2, m3)) * SM_SCALE;
                }
#pragma unroll
                for (int i = 0; i < 10; i++) sc[i] = fmaf(sc[i], SM_SCALE, -mx);
                float o0[4] = {0.f, 0.f, 0.f, 0.f}, o1[4] = {0.f, 0.f, 0.f, 0.f}, rs[4] = {0.f, 0.f, 0.f, 0.f};
                sc[8] = ex2(sc[8]); sc[9] = ex2(sc[9]);
                SFENCE();
                sc[0] = ex2(sc[0]); fetch(4); sc[1] = ex2(sc[1]); fetch(5); sc[2] = ex2(sc[2]); fetch(6);
                SFENCE();
                {
                    const uint32_t p = pack2(sc[8], sc[9]);
                    sc[3] = ex2(sc[3]); fetch(7);
                    mma8(o0, vm[0], vm[1], p);
                    mma8(o1, vm[2], vm[3], p);
                    sc[4] = ex2(sc[4]);
                    mma8(rs, one[0], one[1], p);
                    sc[5] = ex2(sc[5]);
                }
                SFENCE();
                {
                    const uint32_t p0 = pack2(sc[0], sc[1]), p1 = pack2(sc[2], sc[3]);
                    sc[6] = ex2(sc[6]);
                    mma16(o0, vf[0][0][0], vf[0][0][1], vf[0][0][2], vf[0][0][3], p0, p1);
                    SFENCE();
                    sc[7] = ex2(sc[7]);
                    mma16(o1, vf[1][0][0], vf[1][0][1], vf[1][0][2], vf[1][0][3], p0, p1);
                    SFENCE();
                    mma16(rs, one[0], one[1], one[2], one[3], p0, p1);
                    SFENCE();
                }
                {
                    const uint32_t p0 = pack2(sc[4], sc[5]), p1 = pack2(sc[6], sc[7]);
                    mma16(o0, vf[0][1][0], vf[0][1][1], vf[0][1][2], vf[0][1][3], p0, p1);
                    mma16(o1, vf[1][1][0], vf[1][1][1], vf[1][1][2], vf[1][1][3], p0, p1);
                    SFENCE();
                    mma16(rs, one[0], one[1], one[2], one[3], p0, p1);
                }
                const uint32_t e = max((__float_as_uint(cw * fmaxf(m4[0], 1.f)) >> 23) & 255u, 31u);
                SFENCE();
                stsm4t(lw + OFF_OB, pack2(o0[0], o0[1]), pack2(o0[2], o0[3]), pack2(o1[0], o1[1]), pack2(o1[2], o1[3]));
                bar_sync(NB_ATT, 128);
                uint32_t ob[16];
#pragma unroll
                for (int j = 0; j < 4; j++) ldsm4(ob + 4 * j, l16 + OFF_OB + j * 512);
                SFENCE();
                const float sig = __uint_as_float((278u - e) << 23);
                isig = __uint_as_float((e - 30u) << 23);
                const float sg0 = rcp(rs[0]) * sig, sg1 = rcp(rs[1]) * sig;
#pragma unroll
                for (int i = 8; i < RING; i++) fetch(i);
                SFENCE();
#pragma unroll
                for (int r = 0; r < NT; r++) {
                    float c[4][4];
#pragma unroll
                    for (int i = 0; i < 4; i++) c[i][0] = c[i][1] = c[i][2] = c[i][3] = 0.f;
#pragma unroll
                    for (int ks = 0; ks < 8; ks++) {
                        const uint32_t* f = wf[(8 * r + ks) % RING];
                        mma16(c[ks & 3], f[0], f[1], f[2], f[3], ob[2 * ks], ob[2 * ks + 1]);
                        if ((ks & 3) == 3) {
                            SFENCE();
#pragma unroll
                            for (int i = 8 * r + ks - 3 + RING; i <= 8 * r + ks + RING; i++) fetch(i);
                        }
                    }
                    if (r == NT - 1) bar_arrive(NB_WIN, 256);
                    SFENCE();
                    uint32_t v[4];
#pragma unroll
                    for (int i = 0; i < 4; i++)
                        v[i] = (__float_as_uint(fmaf((c[0][i] + c[1][i]) + (c[2][i] + c[3][i]), i & 1 ? sg1 : sg0, 12582912.f)) << 6) + (i < 2);
                    const char* p = rp + (r < 3 ? r * 49152 : 28 * 4096);
                    red_add64((u64*)p, v[0], v[2]);
                    red_add64((u64*)(p + 2048), v[1], v[3]);
                    if (r == 0) {
                        if (w == 0) PROFT(7);
                        if (w == 0) GPROF(4, 0);
                    }
                }
                if (w == 0) PROFT(8);
                sts32(sb + OFF_MX + 16, __float_as_uint(isig));
                if (w == 0) {
                    if (kind < 2 || s < NSEG - 2) mbar_expect_elect(bar + 8 * (B_VX + (pb ^ 1)), kind < 2 ? 8192 : 4096);
                    mbar_expect_elect(bar + 8 * (B_X1 + (pb ^ 1)), (kind < 2 ? 2048 : 0) + (s < NSEG - 2 ? 1280 : 0));
                }
                u64 y[20];
                const uint32_t kn = lw + OFF_K + 1024 + w * 512 + (pb ^ 1) * 5120;
#pragma unroll
                for (int i = 0; i < 10; i++) {
                    if (i == 0 || i == 2 || i == 4 || i == 7) bar_sync(i == 0 ? NB_GO : i == 2 ? NB_PRO : i == 4 ? NB_LD : NB_LD + 1, 160);
                    ld_acc0(y[2 * i], y[2 * i + 1], lp + (i >> 1) * 32768 + (i & 1) * 4096);
                }
                if (w == 0) PROFT(9);
                uint32_t nretry = 0, b[20];
                bool done[5] = {false, false, false, false, false};
                auto publish = [&](auto FIRST) {
                    uint32_t ok = 32u, late = 32u;
                    static_for<5>([&](auto IT) {
                        constexpr int it = IT.value;
                        if (it == 2) late = and3((uint32_t)y[8], (uint32_t)y[10], (uint32_t)y[12]);
                        else if (it == 3) late &= and3((uint32_t)y[14], (uint32_t)y[16], (uint32_t)y[18]);
                        else ok = and3(ok, (uint32_t)y[4 * it], it == 4 ? late : (uint32_t)y[4 * it + 2]);
                        if (FIRST.value && it < 4) SFENCE();
                        if (it == 2 || it == 3) ok = and3(ok, (uint32_t)y[4 * it], (uint32_t)y[4 * it + 2]);
                        ok = and3(ok, (uint32_t)y[4 * it + 1], (uint32_t)y[4 * it + 3]);
                        const bool all = __all_sync(~0u, ok);
#pragma unroll
                        for (int j = 0; j < 4; j++) {
                            const u64 z = y[4 * it + j];
                            b[4 * it + j] = pack2((float)(int)(uint32_t)z, (float)(int)(uint32_t)(z >> 32));
                        }
                        sts128(lw + OFF_MEMB + it * 2048, b[4 * it], b[4 * it + 1], b[4 * it + 2], b[4 * it + 3]);
                        bar_arrive_if<NB_MEM + it, 384>(all && (FIRST.value || !done[it]));
                        done[it] = all;
                        if (FIRST.value) SFENCE();
                        if (FIRST.value && it == 0) {
                            if (w == 0) PROFT(10);
                            if (kind < 2) {
                                bar_sync(NB_KX, 256);
                                ldsm4(kf, kn); ldsm4(kf + 4, kn + 512);
                                SFENCE();
                            }
                        }
                    });
                };
                publish(IC<1>{});
                while (!done[4]) {
                    if (++nretry > SPIN_LIMIT) die();
#pragma unroll
                    for (int i = 0; i < 10; i++) ld_acc(y[2 * i], y[2 * i + 1], lp + (i >> 1) * 32768 + (i & 1) * 4096);
                    publish(IC<0>{});
                }
                if (w == 0) PROFT(11);
                GPROF(w, nretry);
                amax = b[0];
#pragma unroll
                for (int i = 1; i < 19; i += 2) amax = absmax2(amax, absmax2(b[i], b[i + 1]));
                amax = absmax2(amax, b[19]);
                const int adv = (s & 7) == 7 ? 163840 - 896 : 128;
                rp += adv; lp += adv;
            }
        };
        if (rank == 2) steps(IC<2>{}); else steps(IC<0>{});
        bar_sync(NB_QK, 384);
        if (rank < 2) bar_arrive(NB_W1, 416); else bar_arrive(NB_W1, 352);
    } else {
        asm volatile("setmaxnreg.dec.sync.aligned.u32 %0;" ::"n"(416 - REG0 - REG1));
        const uint32_t rank = cta_rank();
        const int w = warp - 12;
        pdl_wait();
        pdl_launch();
        uint32_t* sy = g_sync + layer * SYNC_LAYER;
        if (w == 1) {
            if (lane == 0) {
                mbar_expect(bar + 8 * B_XT, 40960);
                bulk_g2s(sb + OFF_X, g_xn, 40960, bar + 8 * B_XT);
            }
            __syncwarp();
            bar_sync(NB_PRO, 288);
            if (rank == 2) mbar_wait(bar + 8 * B_ST, 0);
            else if (lane == 0) mbar_arrive_remote(mapa(bar + 8 * B_ST, 2));
            mbar_wait(bar + 8 * B_XT, 0);
            __syncwarp();
            bar_arrive(NB_LD, 288);
            if (lane == 0) {
                mbar_expect(bar + 8 * (B_XT + 1), rank < 2 ? 45056 : 40960);
                bulk_g2s(sb + OFF_X + 40960, g_xn + 40960, 40960, bar + 8 * (B_XT + 1));
                flag_wait(sy + wk::SY_P + h, 3);
                if (rank < 2) bulk_g2s(sb + OFF_Q + 1024, g_p + h * 12288 + rank * 4096, 4096, bar + 8 * (B_XT + 1));
                bulk_g2s(sb + OFF_VX, g_p + h * 12288 + 8192, 4096, bar + 8 * B_VX);
            }
            __syncwarp();
        }
        if (rank == 2 && w == 3) {
            if (lane == 0) {
                for (uint32_t s = 0, n = 0; s < NSEG; s++) {
                    uint32_t c[2];
                    for (;;) {
                        asm volatile("ld.acquire.cluster.shared::cta.v2.u32 {%0,%1},[%2];" : "=r"(c[0]), "=r"(c[1]) : "r"(sb + OFF_MX + 32) : "memory");
                        if (min(c[0], c[1]) > s) break;
                        if (++n > (SPIN_LIMIT << 3)) die();
                        __nanosleep(s < NSEG - 2 ? 400 : 50);
                    }
                    flag_add(sy + wk::SY_O + s);
                }
            }
        } else if (rank == 2) {
            const char* pf = (const char*)(g_acc + layer * ACC_LAYER) + (5 * h + lane % 5) * 1024;
            if (w == 2 && lane < 20) prefetch_l2(pf + lane / 5 * 128);
            if (w == 2 && lane < 4 && h == 0) prefetch_l2(sy + 1024 + lane * 32);
            for (int s = 0; s < NSEG; s++) {
                const int pb = s & 1, ph = (s >> 1) & 1;
                if (w == 0) {
                    mbar_wait(bar + 8 * (B_KX + pb), ph);
                    if (s >= 2) mbar_wait(bar + 8 * (B_XD + pb), ph ^ 1);
                    if (lane < 2) bulk_s2s(mapa(sb + OFF_VX + pb * 8192 + 4096, lane), sb + OFF_VX + pb * 8192 + 4096, 4096, mapa(bar + 8 * (B_VX + pb), lane));
                }
                if (w == 1) mbar_wait(bar + 8 * (B_XT + (pb ^ 1)), ((s + 1) >> 1) & 1);
                __syncwarp();
                bar_sync(NB_W1, 352);
                if (w == 2 && lane < 5 && s + 4 < NSEG) prefetch_l2(pf + ((s + 4) >> 3) * 163840 + ((s + 4) & 7) * 128);
                if (w == 2 && lane == 5 && h == 0 && s + 4 < NSEG) prefetch_l2(sy + 1024 + (s + 4) * 32);
            }
        } else {
            if (w < 2) sts32(sb + OFF_PT + w * 768 + 640 + lane * 4, 0u);
            const uint32_t px = opaque(sb + OFF_PX + (w & 1) * 1280 + lane * 8);
            for (int s = 0; s <= NSEG; s++) {
                const uint32_t pb = s & 1, ph = (s >> 1) & 1;
                float own[10];
                if (s < NSEG) {
                    if (w == 2 * rank) mbar_expect_elect(bar + 8 * B_PXF, rank ? 2560 : 1536);
                    if (w == 1) mbar_wait(bar + 8 * (B_XT + (pb ^ 1)), ((s + 1) >> 1) & 1);
                    const u64 dq = mkdesc(sb + OFF_Q + pb * 5120 + 1024, 128, 512), dk = mkdesc(sb + OFF_K + pb * 5120, 128, 1024);
                    __syncwarp();
                    bar_sync(NB_W1, 416);
                    fence_async();
                    float c[20];
                    wg_fence();
                    wgmma_n40_ss<0>(c, dq, dk);
#pragma unroll
                    for (int ks = 1; ks < 4; ks++) wgmma_n40_ss<1>(c, dq + ks * 16, dk + ks * 16);
                    wg_commit();
                    wg_wait<0>();
#pragma unroll
                    for (int i = 0; i < 10; i++) own[i] = c[4 * (i >> 1) + (i & 1)];
                    mbar_wait(bar + 8 * (B_X1 + pb), ph);
                    if ((w >> 1) != rank) {
                        if (s >= 1) mbar_wait(bar + 8 * B_PXE, pb ^ 1);
                        const uint32_t pa = mapa(px, rank ^ 1), pf = mapa(bar + 8 * B_PXF, rank ^ 1);
#pragma unroll
                        for (int nt = 0; nt < 5; nt++)
                            if (nt < 3 || rank == 0) st_async2(pa + nt * 256, __float_as_uint(own[2 * nt]), __float_as_uint(own[2 * nt + 1]), pf);
                    }
                } else {
                    bar_sync(NB_X, 128);
                }
                if (s == 0) { bar_sync(NB_WIN, 256); bar_arrive(NB_W2, 256); }
                if (s >= 1) {
                    float acc[2][8];
                    const u64 dv = mkdesc(sb + OFF_VX + (pb ^ 1) * 8192, 128, 512), dp = mkdesc(sb + OFF_PT, 128, 768);
                    const u64 dm = mkdesc(sb + OFF_VM + ((s - 1) & 3) * 2048, 0, 128);
                    if (s < NSEG - 1) { bar_sync(NB_WIN, 256); bar_arrive(NB_W2, 256); }
                    wg_fence();
#pragma unroll
                    for (int m = 0; m < 2; m++) {
                        wgmma_n16_ss<0>(acc[m], dv + m * 256, dp);
                        wgmma_n16_ss<1>(acc[m], dv + m * 256 + 16, dp + 16);
                        wgmma_n16_ss<1>(acc[m], dm + m * 64, dp + 32);
                    }
                    wg_commit();
                    wg_wait<0>();
                    if (s < NSEG - 1) bar_sync(NB_X, 160);
                    if (w == 0 && s < NSEG) PROFT(12);
                    if (lane == 0) mbar_arrive_remote(mapa(bar + 8 * (B_XD + (pb ^ 1)), 2));
#pragma unroll
                    for (int m = 0; m < 2; m++)
                        stsm4t(sb + OFF_OST + (pb ^ 1) * 4096 + m * 2048 + (lane >> 4) * 1024 + w * 256 + (lane & 15) * 16, pack2(acc[m][0], acc[m][1]), pack2(acc[m][2], acc[m][3]),
                               pack2(acc[m][4], acc[m][5]), pack2(acc[m][6], acc[m][7]));
                    if (s >= NSEG - 1) { fence_async(); bar_sync(NB_W1, 160); }
                }
                if (s == NSEG) break;
                if ((w >> 1) == rank) {
                    mbar_wait(bar + 8 * B_PXF, pb);
                    if (w == 0) PROFT(13);
                    const int tq = 8 * w + g;
                    float u[10];
#pragma unroll
                    for (int nt = 0; nt < 5; nt++) lds64f(u[2 * nt], u[2 * nt + 1], px + nt * 256);
#pragma unroll
                    for (int i = 0; i < 10; i++) own[i] = (8 * (i >> 1) - 8 + (i & 1) + 2 * q <= tq) ? (u[i] + own[i]) * SM_SCALE : -INFINITY;
                    float mx = own[0];
#pragma unroll
                    for (int i = 1; i < 10; i++) mx = fmaxf(mx, own[i]);
                    mx = fmaxf(mx, __shfl_xor_sync(~0u, mx, 1));
                    mx = fmaxf(mx, __shfl_xor_sync(~0u, mx, 2));
                    if (lane == 0) mbar_arrive_remote(mapa(bar + 8 * B_PXE, rank ^ 1));
                    float sum = 0.f;
#pragma unroll
                    for (int i = 0; i < 10; i++) { own[i] = ex2(own[i] - mx); sum += own[i]; }
                    sum += __shfl_xor_sync(~0u, sum, 1);
                    sum += __shfl_xor_sync(~0u, sum, 2);
                    sum = rcp(sum);
#pragma unroll
                    for (int nt = 0; nt < 5; nt++)
                        sts32(sb + OFF_PT + (w & 1) * 768 + (nt ? nt - 1 : 4) * 128 + lane * 4, pack2(own[2 * nt] * sum, own[2 * nt + 1] * sum));
                }
                __syncwarp();
                mbar_wait(bar + 8 * (B_VX + pb), ph);
                fence_async();
                if (w == 0) PROFT(14);
            }
        }
    }
    __syncwarp();
    if (lane < 3) mbar_arrive_remote(mapa(bar + 8 * B_FIN, lane));
    mbar_wait(bar + 8 * B_FIN, 0);
    TLE(2 + 5 * layer);
}

int g_delay = 1000650, g_layers = 2;

void make_map(CUtensorMap* m, CUtensorMapDataType dt, const void* p, const cuuint64_t* dim, const cuuint64_t* str, const cuuint32_t* box, CUtensorMapSwizzle sw) {
    typedef CUresult (*Fn)(CUtensorMap*, CUtensorMapDataType, cuuint32_t, void*, const cuuint64_t*, const cuuint64_t*, const cuuint32_t*,
                           const cuuint32_t*, CUtensorMapInterleave, CUtensorMapSwizzle, CUtensorMapL2promotion, CUtensorMapFloatOOBfill);
    static Fn fn = nullptr;
    if (!fn) {
        cudaDriverEntryPointQueryResult qr;
        cudaGetDriverEntryPoint("cuTensorMapEncodeTiled", (void**)&fn, cudaEnableDefault, &qr);
    }
    const cuuint32_t es[3] = {1, 1, 1};
    fn(m, dt, 3, (void*)p, dim, str, box, es, CU_TENSOR_MAP_INTERLEAVE_NONE, sw, CU_TENSOR_MAP_L2_PROMOTION_L2_128B, CU_TENSOR_MAP_FLOAT_OOB_FILL_NONE);
}
void map_weight(CUtensorMap* m, const bf16* p, int rows, int cols, int ng, int br = 64) {
    const cuuint64_t dim[3] = {64, (cuuint64_t)rows, (cuuint64_t)cols / 64}, str[2] = {(cuuint64_t)cols * 2, 128};
    const cuuint32_t box[3] = {64, (cuuint32_t)br, (cuuint32_t)ng};
    make_map(m, CU_TENSOR_MAP_DATA_TYPE_BFLOAT16, p, dim, str, box, CU_TENSOR_MAP_SWIZZLE_128B);
}
void map_pieces(CUtensorMap* m, const void* p, int np, int ns) {
    const cuuint64_t dim[3] = {256, (cuuint64_t)np * 2, NSEG}, str[2] = {2048, (cuuint64_t)np * 4096};
    const cuuint32_t box[3] = {256, 2, (cuuint32_t)ns};
    make_map(m, CU_TENSOR_MAP_DATA_TYPE_UINT64, p, dim, str, box, CU_TENSOR_MAP_SWIZZLE_NONE);
}

template <class... P, class... A> void launch(void (*k)(P...), int grid, int block, int smem, int cluster, bool pdl, A... args) {
    cudaLaunchConfig_t c = {};
    c.gridDim = dim3(grid); c.blockDim = dim3(block); c.dynamicSmemBytes = smem; c.stream = cudaStreamPerThread;
    cudaLaunchAttribute at[2];
    int n = 0;
    if (cluster > 1) { at[n].id = cudaLaunchAttributeClusterDimension; at[n].val.clusterDim.x = cluster; at[n].val.clusterDim.y = 1; at[n].val.clusterDim.z = 1; n++; }
    if (pdl) { at[n].id = cudaLaunchAttributeProgrammaticStreamSerialization; at[n].val.programmaticStreamSerializationAllowed = 1; n++; }
    c.attrs = at; c.numAttrs = n;
    cudaLaunchKernelEx(&c, k, args...);
}

int max_clusters() {
    cudaLaunchConfig_t c = {};
    c.gridDim = dim3(3 * H_); c.blockDim = dim3(512); c.dynamicSmemBytes = rec::SMEM;
    cudaLaunchAttribute at[1];
    at[0].id = cudaLaunchAttributeClusterDimension; at[0].val.clusterDim.x = 3; at[0].val.clusterDim.y = 1; at[0].val.clusterDim.z = 1;
    c.attrs = at; c.numAttrs = 1;
    int n = 0;
    cudaOccupancyMaxActiveClusters(&n, rec_kernel, &c);
    return n;
}

}

extern "C" void kernel_launch(void* const* d_in, const int* in_sizes, int n_in, void* d_out, int out_size) {
    const bf16* x = (const bf16*)d_in[0];
    const bf16* mem0 = (const bf16*)d_in[1];
    const bf16* Wq = (const bf16*)d_in[2];
    const bf16* Wk = (const bf16*)d_in[3];
    const bf16* Wv = (const bf16*)d_in[4];
    const bf16* Wo = (const bf16*)d_in[5];
    const bf16* wr = (const bf16*)d_in[8];
    const bf16* wi = (const bf16*)d_in[9];
    cudaFuncSetAttribute(rec_kernel, cudaFuncAttributeMaxDynamicSharedMemorySize, rec::SMEM);
    cudaFuncSetAttribute(side_kernel, cudaFuncAttributeMaxDynamicSharedMemorySize, wk::SMEM);
    cudaFuncSetAttribute(colfft_kernel, cudaFuncAttributeMaxDynamicSharedMemorySize, CF_SMEM);
    Maps maps;
    void *pxn, *po;
    cudaGetSymbolAddress(&pxn, g_xn);
    cudaGetSymbolAddress(&po, g_o);
    map_weight(&maps.wq2, Wq, D_, 4096, 2); map_weight(&maps.wv1, Wv, D_, 4096, 1);
    map_weight(&maps.wo2, Wo, 4096, D_, 2); map_weight(&maps.wo1, Wo, 4096, D_, 1, 192);
    map_pieces(&maps.x6, pxn, 10, 6); map_pieces(&maps.x2, pxn, 10, 2);
    map_pieces(&maps.o6, po, 64, 6); map_pieces(&maps.o2, po, 64, 2);
    bf16 *x1, *x2;
    cudaGetSymbolAddress((void**)&x1, g_x1);
    cudaGetSymbolAddress((void**)&x2, g_x2);
    constexpr int ONE_PER_SM = 120 * 1024;
    cudaFuncSetAttribute(rowfft_kernel, cudaFuncAttributeMaxDynamicSharedMemorySize, ONE_PER_SM);
    cudaFuncSetAttribute(rowifft_kernel, cudaFuncAttributeMaxDynamicSharedMemorySize, ONE_PER_SM);
    static int ncl = 0, nsm = 0;
    if (!ncl) { ncl = max_clusters(); cudaDeviceGetAttribute(&nsm, cudaDevAttrMultiProcessorCount, 0); }
    maps.wr = wr; maps.wi = wi;
    launch(prep_kernel, 128, 512, 0, 1, false, x, Wq, Wk, Wv, Wo);
    for (int layer = 0; layer < g_layers; layer++) {
        const bf16* xin = layer ? x2 : x;
        launch(rec_kernel, 3 * ncl, 512, rec::SMEM, 3, true, maps, xin, x1, mem0, Wq, Wk, Wv, Wo, layer, g_delay % 10000, g_delay / 10000);
        launch(side_kernel, nsm - 3 * (ncl - H_), 512, wk::SMEM, 1, true, maps, xin, x1, layer);
        launch(rowfft_kernel, 128, 256, ONE_PER_SM, 1, true, xin, x1, Wq, Wk, Wv, layer);
        launch(colfft_kernel, 107, 384, CF_SMEM, 1, true, layer);
        launch(rowifft_kernel, 128, 256, ONE_PER_SM, 1, true, (const bf16*)x1, layer ? (bf16*)d_out : x2, layer);
    }
}
```

```cpp
#include <cuda_runtime.h>
#include <cuda_bf16.h>
#include <cuda.h>
#include <stdint.h>

#define DEV __device__ __forceinline__
typedef unsigned long long u64;
typedef __nv_bfloat16 bf16;

namespace {

constexpr int S_ = 2048, D_ = 640, H_ = 32, E_ = 128, NSEG = 64;

__device__ __align__(1024) unsigned char g_xn[S_ * D_ * 2];
__device__ __align__(1024) unsigned char g_o[S_ * H_ * E_ * 2];
constexpr int ACC_LAYER = 32 * 5120;
__device__ __align__(4096) u64 g_acc[2 * ACC_LAYER];
__device__ __align__(16) float g_nrm[256];
__device__ __align__(1024) unsigned char g_p[NSEG * H_ * 3 * 4096];
constexpr int SYNC_LAYER = 1024 + 64 * 32;
__device__ __align__(128) uint32_t g_sync[2 * SYNC_LAYER];
__device__ __align__(1024) bf16 g_x1[S_ * D_];
__device__ __align__(1024) bf16 g_x2[S_ * D_];
constexpr int YT_ROWS = 128;
__device__ __align__(1024) float g_yt[2 * YT_ROWS * D_];
constexpr int NCOL = 321;
__device__ __align__(1024) unsigned char g_z[NCOL * 8192];
__device__ __align__(1024) unsigned char g_wt[NCOL * 8192];
__device__ __align__(1024) uint4 g_f128[2 * 8 * 256];
__device__ __align__(1024) uint4 g_f64[2 * 4 * 128];
__device__ __align__(1024) bf16 g_g32[2 * 4096];
#define TLI(id, k, v)
#define TLS(i)
#define TLE(i)

DEV uint32_t s2u(const void* p) { return (uint32_t)__cvta_generic_to_shared(p); }
DEV uint32_t clk() { uint32_t c; asm volatile("mov.u32 %0,%%clock;" : "=r"(c)::"memory"); return c; }
DEV uint32_t gtime32() { uint32_t t; asm volatile("mov.u32 %0,%%globaltimer_lo;" : "=r"(t)::"memory"); return t; }
DEV uint32_t cta_rank() { uint32_t r; asm volatile("mov.u32 %0,%%cluster_ctarank;" : "=r"(r)); return __shfl_sync(~0u, r, 0); }
DEV uint32_t mapa(uint32_t a, uint32_t r) { uint32_t o; asm("mapa.shared::cluster.u32 %0,%1,%2;" : "=r"(o) : "r"(a), "r"(r)); return o; }
DEV void mbar_init(uint32_t b, uint32_t n) { asm volatile("mbarrier.init.shared::cta.b64 [%0],%1;" ::"r"(b), "r"(n) : "memory"); }
DEV bool mbar_try(uint32_t b, uint32_t par, int) {
    uint32_t ok;
    asm volatile("{.reg .pred p; mbarrier.test_wait.parity.shared::cta.b64 p,[%1],%2; selp.u32 %0,1,0,p;}" : "=r"(ok) : "r"(b), "r"(par) : "memory");
    return ok;
}
DEV bool mbar_try(uint32_t b, uint32_t par) {
    uint32_t ok;
    asm volatile("{.reg .pred p; mbarrier.try_wait.parity.shared::cta.b64 p,[%1],%2; selp.u32 %0,1,0,p;}" : "=r"(ok) : "r"(b), "r"(par) : "memory");
    return ok;
}
constexpr uint32_t SPIN_LIMIT = 1u << 18;
DEV void die() { __trap(); }
DEV void mbar_wait(uint32_t b, uint32_t par) {
    uint32_t n = 0;
    while (!mbar_try(b, par)) if (++n > SPIN_LIMIT) die();
}
DEV uint32_t opaque(uint32_t x) { return __shfl_xor_sync(~0u, x, 0); }
#define SFENCE() asm volatile("{.reg .pred p; setp.ne.u32 p,%1,0; @p mov.u32 %0,%%clock;}" : "+r"(sfd) : "r"((uint32_t)never) : "memory")
DEV void mbar_arrive(uint32_t b) { asm volatile("mbarrier.arrive.shared::cta.b64 _,[%0];" ::"r"(b) : "memory"); }
DEV void mbar_arrive_elect(uint32_t b) { asm volatile("{.reg .pred p; elect.sync _|p, 0xffffffff; @p mbarrier.arrive.shared::cta.b64 _,[%0];}" ::"r"(b) : "memory"); }
DEV void mbar_expect_elect(uint32_t b, uint32_t tx) {
    asm volatile("{.reg .pred p; elect.sync _|p, 0xffffffff; @p mbarrier.arrive.expect_tx.shared::cta.b64 _,[%0],%1;}" ::"r"(b), "r"(tx) : "memory");
}
DEV bool elect() { uint32_t r; asm volatile("{.reg .pred p; elect.sync _|p, 0xffffffff; selp.u32 %0,1,0,p;}" : "=r"(r)); return r; }
DEV void mbar_arrive_remote(uint32_t b) { asm volatile("mbarrier.arrive.shared::cluster.b64 _,[%0];" ::"r"(b) : "memory"); }
DEV void mbar_expect(uint32_t b, uint32_t tx) { asm volatile("mbarrier.arrive.expect_tx.shared::cta.b64 _,[%0],%1;" ::"r"(b), "r"(tx) : "memory"); }
DEV void bar_sync(int id, int n) { asm volatile("bar.sync %0,%1;" ::"r"(id), "r"(n) : "memory"); }
DEV void bar_arrive(int id, int n) { asm volatile("bar.arrive %0,%1;" ::"r"(id), "r"(n) : "memory"); }
template <int ID, int N> DEV void bar_arrive_if(bool p) {
    asm volatile("{.reg .pred p; setp.ne.u32 p,%0,0; @p bar.arrive %1,%2;}" ::"r"((uint32_t)p), "n"(ID), "n"(N) : "memory");
}
DEV void prefetch_bulk(const void* p, uint32_t bytes) { asm volatile("cp.async.bulk.prefetch.L2.global [%0],%1;" ::"l"(p), "r"(bytes) : "memory"); }
DEV void prefetch_l2(const void* p) { asm volatile("prefetch.global.L2 [%0];" ::"l"(p) : "memory"); }
template <int ID, int N> DEV void bar_sync_if(bool p) {
    asm volatile("{.reg .pred p; setp.ne.u32 p,%0,0; @p bar.sync %1,%2;}" ::"r"((uint32_t)p), "n"(ID), "n"(N) : "memory");
}
DEV void st_remote(uint32_t a, uint32_t x) { asm volatile("st.relaxed.cluster.shared::cluster.u32 [%0],%1;" ::"r"(a), "r"(x) : "memory"); }
DEV void st_async1(uint32_t a, uint32_t x, uint32_t b) {
    asm volatile("st.async.shared::cluster.mbarrier::complete_tx::bytes.u32 [%0],%1,[%2];" ::"r"(a), "r"(x), "r"(b) : "memory");
}
DEV void st_async2(uint32_t a, uint32_t x, uint32_t y, uint32_t b) {
    asm volatile("st.async.shared::cluster.mbarrier::complete_tx::bytes.v2.u32 [%0],{%1,%2},[%3];" ::"r"(a), "r"(x), "r"(y), "r"(b) : "memory");
}
DEV void st_async4(uint32_t a, uint32_t x, uint32_t y, uint32_t z, uint32_t w, uint32_t b) {
    asm volatile("st.async.shared::cluster.mbarrier::complete_tx::bytes.v4.u32 [%0],{%1,%2,%3,%4},[%5];" ::"r"(a), "r"(x), "r"(y), "r"(z), "r"(w), "r"(b) : "memory");
}
DEV void bulk_g2s(uint32_t dst, const void* src, uint32_t bytes, uint32_t b) {
    asm volatile("cp.async.bulk.shared::cluster.global.mbarrier::complete_tx::bytes [%0],[%1],%2,[%3];" ::"r"(dst), "l"(src), "r"(bytes), "r"(b) : "memory");
}
DEV void bulk_s2s(uint32_t dst, uint32_t src, uint32_t bytes, uint32_t b) {
    asm volatile("cp.async.bulk.shared::cluster.shared::cta.mbarrier::complete_tx::bytes [%0],[%1],%2,[%3];" ::"r"(dst), "r"(src), "r"(bytes), "r"(b) : "memory");
}
DEV void bulk_s2g(void* dst, uint32_t src, uint32_t bytes) {
    asm volatile("cp.async.bulk.global.shared::cta.bulk_group [%0],[%1],%2;" ::"l"(dst), "r"(src), "r"(bytes) : "memory");
}
DEV void tma3d(uint32_t dst, const CUtensorMap* m, int c0, int c1, int c2, uint32_t b) {
    asm volatile("cp.async.bulk.tensor.3d.shared::cluster.global.mbarrier::complete_tx::bytes [%0],[%1,{%3,%4,%5}],[%2];"
                 ::"r"(dst), "l"(m), "r"(b), "r"(c0), "r"(c1), "r"(c2) : "memory");
}
DEV void bulk_commit() { asm volatile("cp.async.bulk.commit_group;" ::: "memory"); }
template <int N> DEV void bulk_wait() { asm volatile("cp.async.bulk.wait_group %0;" ::"n"(N) : "memory"); }
template <int N> DEV void bulk_wait_read() { asm volatile("cp.async.bulk.wait_group.read %0;" ::"n"(N) : "memory"); }
DEV void fence_async_all() { asm volatile("fence.proxy.async;" ::: "memory"); }
DEV void flag_add(uint32_t* p) { fence_async_all(); asm volatile("red.release.gpu.global.add.u32 [%0],1;" ::"l"(p) : "memory"); }
template <bool BOUNDED = true> DEV void flag_wait(const uint32_t* p, uint32_t n) {
    uint32_t v, it = 0;
    for (;;) {
        asm volatile("ld.acquire.gpu.global.u32 %0,[%1];" : "=r"(v) : "l"(p) : "memory");
        if (v >= n) break;
        if (BOUNDED && ++it > (SPIN_LIMIT << 3)) die();
        __nanosleep(100);
    }
    fence_async_all();
}
DEV void cp16(uint32_t dst, const void* src) { asm volatile("cp.async.cg.shared.global [%0],[%1],16;" ::"r"(dst), "l"(src) : "memory"); }
DEV void cp_commit() { asm volatile("cp.async.commit_group;" ::: "memory"); }
template <int N> DEV void cp_wait() { asm volatile("cp.async.wait_group %0;" ::"n"(N) : "memory"); }
DEV uint32_t lds32(uint32_t a) { uint32_t x; asm volatile("ld.shared.u32 %0,[%1];" : "=r"(x) : "r"(a) : "memory"); return x; }
DEV void fence_async() { asm volatile("fence.proxy.async.shared::cta;" ::: "memory"); }
DEV uint32_t pack2(float lo, float hi) { uint32_t r; asm("cvt.rn.bf16x2.f32 %0,%1,%2;" : "=r"(r) : "f"(hi), "f"(lo)); return r; }
DEV uint32_t prmt(uint32_t a, uint32_t b, uint32_t s) { uint32_t r; asm("prmt.b32 %0,%1,%2,%3;" : "=r"(r) : "r"(a), "r"(b), "r"(s)); return r; }
DEV float ex2(float x) { float r; asm("ex2.approx.ftz.f32 %0,%1;" : "=f"(r) : "f"(x)); return r; }
DEV float rcp(float x) { float r; asm("rcp.approx.ftz.f32 %0,%1;" : "=f"(r) : "f"(x)); return r; }
DEV void lds128(uint32_t* r, uint32_t a) { asm volatile("ld.shared.v4.u32 {%0,%1,%2,%3},[%4];" : "=r"(r[0]), "=r"(r[1]), "=r"(r[2]), "=r"(r[3]) : "r"(a) : "memory"); }
DEV void lds64(uint32_t* r, uint32_t a) { asm volatile("ld.shared.v2.u32 {%0,%1},[%2];" : "=r"(r[0]), "=r"(r[1]) : "r"(a) : "memory"); }
DEV void lds64f(float& x, float& y, uint32_t a) { asm volatile("ld.shared.v2.f32 {%0,%1},[%2];" : "=f"(x), "=f"(y) : "r"(a) : "memory"); }
DEV void lds128f(float* r, uint32_t a) { asm volatile("ld.shared.v4.f32 {%0,%1,%2,%3},[%4];" : "=f"(r[0]), "=f"(r[1]), "=f"(r[2]), "=f"(r[3]) : "r"(a) : "memory"); }
DEV void sts128(uint32_t a, uint32_t x, uint32_t y, uint32_t z, uint32_t w) { asm volatile("st.shared.v4.u32 [%0],{%1,%2,%3,%4};" ::"r"(a), "r"(x), "r"(y), "r"(z), "r"(w) : "memory"); }
DEV void sts64(uint32_t a, uint32_t x, uint32_t y) { asm volatile("st.shared.v2.u32 [%0],{%1,%2};" ::"r"(a), "r"(x), "r"(y) : "memory"); }
DEV void sts32(uint32_t a, uint32_t x) { asm volatile("st.shared.u32 [%0],%1;" ::"r"(a), "r"(x) : "memory"); }
DEV void ldsm4(uint32_t* r, uint32_t a) { asm volatile("ldmatrix.sync.aligned.m8n8.x4.shared.b16 {%0,%1,%2,%3},[%4];" : "=r"(r[0]), "=r"(r[1]), "=r"(r[2]), "=r"(r[3]) : "r"(a) : "memory"); }
DEV void ldsm4t(uint32_t* r, uint32_t a) { asm volatile("ldmatrix.sync.aligned.m8n8.x4.trans.shared.b16 {%0,%1,%2,%3},[%4];" : "=r"(r[0]), "=r"(r[1]), "=r"(r[2]), "=r"(r[3]) : "r"(a) : "memory"); }
DEV void ldsm2(uint32_t* r, uint32_t a) { asm volatile("ldmatrix.sync.aligned.m8n8.x2.shared.b16 {%0,%1},[%2];" : "=r"(r[0]), "=r"(r[1]) : "r"(a) : "memory"); }
DEV void stsm4t(uint32_t a, uint32_t x, uint32_t y, uint32_t z, uint32_t w) { asm volatile("stmatrix.sync.aligned.m8n8.x4.trans.shared.b16 [%0],{%1,%2,%3,%4};" ::"r"(a), "r"(x), "r"(y), "r"(z), "r"(w) : "memory"); }
DEV void stsm4(uint32_t a, uint32_t x, uint32_t y, uint32_t z, uint32_t w) { asm volatile("stmatrix.sync.aligned.m8n8.x4.shared.b16 [%0],{%1,%2,%3,%4};" ::"r"(a), "r"(x), "r"(y), "r"(z), "r"(w) : "memory"); }
DEV void stsm2(uint32_t a, uint32_t x, uint32_t y) { asm volatile("stmatrix.sync.aligned.m8n8.x2.shared.b16 [%0],{%1,%2};" ::"r"(a), "r"(x), "r"(y) : "memory"); }
DEV void stsm2t_if(uint32_t a, uint32_t x, uint32_t y, bool p) {
    asm volatile("{.reg .pred p; setp.ne.u32 p,%3,0; @p stmatrix.sync.aligned.m8n8.x2.trans.shared.b16 [%0],{%1,%2};}" ::"r"(a), "r"(x), "r"(y), "r"((uint32_t)p) : "memory");
}
DEV void stsm2t(uint32_t a, uint32_t x, uint32_t y) { asm volatile("stmatrix.sync.aligned.m8n8.x2.trans.shared.b16 [%0],{%1,%2};" ::"r"(a), "r"(x), "r"(y) : "memory"); }
DEV void mma16(float* d, uint32_t a0, uint32_t a1, uint32_t a2, uint32_t a3, uint32_t b0, uint32_t b1) {
    asm volatile("mma.sync.aligned.m16n8k16.row.col.f32.bf16.bf16.f32 {%0,%1,%2,%3},{%4,%5,%6,%7},{%8,%9},{%0,%1,%2,%3};"
                 : "+f"(d[0]), "+f"(d[1]), "+f"(d[2]), "+f"(d[3]) : "r"(a0), "r"(a1), "r"(a2), "r"(a3), "r"(b0), "r"(b1));
}
DEV void mma8(float* d, uint32_t a0, uint32_t a1, uint32_t b0) {
    asm volatile("mma.sync.aligned.m16n8k8.row.col.f32.bf16.bf16.f32 {%0,%1,%2,%3},{%4,%5},{%6},{%0,%1,%2,%3};"
                 : "+f"(d[0]), "+f"(d[1]), "+f"(d[2]), "+f"(d[3]) : "r"(a0), "r"(a1), "r"(b0));
}
DEV u64 mkdesc(uint32_t a, uint32_t lbo, uint32_t sbo) { return (u64)((a & 0x3ffff) >> 4) | ((u64)(lbo >> 4) << 16) | ((u64)(sbo >> 4) << 32); }
constexpr u64 SW128 = 1ull << 62;
DEV void wg_fence() { asm volatile("wgmma.fence.sync.aligned;" ::: "memory"); }
DEV void wg_commit() { asm volatile("wgmma.commit_group.sync.aligned;" ::: "memory"); }
template <int N> DEV void wg_wait() { asm volatile("wgmma.wait_group.sync.aligned %0;" ::"n"(N) : "memory"); }
template <int ACC> DEV void wgmma_n32_rs(float* d, const uint32_t* a, u64 desc) {
    asm volatile("wgmma.mma_async.sync.aligned.m64n32k16.f32.bf16.bf16 {%0,%1,%2,%3,%4,%5,%6,%7,%8,%9,%10,%11,%12,%13,%14,%15},{%16,%17,%18,%19},%20,%21,1,1,0;"
                 : "+f"(d[0]), "+f"(d[1]), "+f"(d[2]), "+f"(d[3]), "+f"(d[4]), "+f"(d[5]), "+f"(d[6]), "+f"(d[7]),
                   "+f"(d[8]), "+f"(d[9]), "+f"(d[10]), "+f"(d[11]), "+f"(d[12]), "+f"(d[13]), "+f"(d[14]), "+f"(d[15])
                 : "r"(a[0]), "r"(a[1]), "r"(a[2]), "r"(a[3]), "l"(desc), "n"(ACC));
}
template <int ACC> DEV void wgmma_n32_ss(float* d, u64 da, u64 desc) {
    asm volatile("wgmma.mma_async.sync.aligned.m64n32k16.f32.bf16.bf16 {%0,%1,%2,%3,%4,%5,%6,%7,%8,%9,%10,%11,%12,%13,%14,%15},%16,%17,%18,1,1,0,0;"
                 : "+f"(d[0]), "+f"(d[1]), "+f"(d[2]), "+f"(d[3]), "+f"(d[4]), "+f"(d[5]), "+f"(d[6]), "+f"(d[7]),
                   "+f"(d[8]), "+f"(d[9]), "+f"(d[10]), "+f"(d[11]), "+f"(d[12]), "+f"(d[13]), "+f"(d[14]), "+f"(d[15])
                 : "l"(da), "l"(desc), "n"(ACC));
}
template <int ACC> DEV void wgmma_n16_ss(float* d, u64 da, u64 desc) {
    asm volatile("wgmma.mma_async.sync.aligned.m64n16k16.f32.bf16.bf16 {%0,%1,%2,%3,%4,%5,%6,%7},%8,%9,%10,1,1,0,0;"
                 : "+f"(d[0]), "+f"(d[1]), "+f"(d[2]), "+f"(d[3]), "+f"(d[4]), "+f"(d[5]), "+f"(d[6]), "+f"(d[7])
                 : "l"(da), "l"(desc), "n"(ACC));
}
#define ACC8(o) "+f"(d[o]), "+f"(d[o + 1]), "+f"(d[o + 2]), "+f"(d[o + 3]), "+f"(d[o + 4]), "+f"(d[o + 5]), "+f"(d[o + 6]), "+f"(d[o + 7])
template <int ACC, int TB> DEV void wgmma_n64_rs(float* d, const uint32_t* a, u64 desc) {
    asm volatile("wgmma.mma_async.sync.aligned.m64n64k16.f32.bf16.bf16 {%0,%1,%2,%3,%4,%5,%6,%7,%8,%9,%10,%11,%12,%13,%14,%15,"
                 "%16,%17,%18,%19,%20,%21,%22,%23,%24,%25,%26,%27,%28,%29,%30,%31},{%32,%33,%34,%35},%36,%37,1,1,%38;"
                 : ACC8(0), ACC8(8), ACC8(16), ACC8(24) : "r"(a[0]), "r"(a[1]), "r"(a[2]), "r"(a[3]), "l"(desc), "n"(ACC), "n"(TB));
}
template <int ACC, int TB> DEV void wgmma_n80_rs(float* d, const uint32_t* a, u64 desc) {
    asm volatile("wgmma.mma_async.sync.aligned.m64n80k16.f32.bf16.bf16 {%0,%1,%2,%3,%4,%5,%6,%7,%8,%9,%10,%11,%12,%13,%14,%15,"
                 "%16,%17,%18,%19,%20,%21,%22,%23,%24,%25,%26,%27,%28,%29,%30,%31,%32,%33,%34,%35,%36,%37,%38,%39},{%40,%41,%42,%43},%44,%45,1,1,%46;"
                 : ACC8(0), ACC8(8), ACC8(16), ACC8(24), ACC8(32) : "r"(a[0]), "r"(a[1]), "r"(a[2]), "r"(a[3]), "l"(desc), "n"(ACC), "n"(TB));
}
template <int TA, int TB> DEV void wgmma_n64_ss(float* d, u64 da, u64 db, int acc) {
    asm volatile("{.reg .pred p; setp.ne.b32 p,%34,0; wgmma.mma_async.sync.aligned.m64n64k16.f32.bf16.bf16 {%0,%1,%2,%3,%4,%5,%6,%7,%8,%9,%10,%11,%12,%13,%14,%15,%16,%17,%18,%19,%20,%21,%22,%23,%24,%25,%26,%27,%28,%29,%30,%31},%32,%33,p,1,1,%35,%36;}"
                 : ACC8(0), ACC8(8), ACC8(16), ACC8(24) : "l"(da), "l"(db), "r"(acc), "n"(TA), "n"(TB));
}
template <int TA, int TB> DEV void wgmma_n128_ss(float* d, u64 da, u64 db, int acc) {
    asm volatile("{.reg .pred p; setp.ne.b32 p,%66,0; wgmma.mma_async.sync.aligned.m64n128k16.f32.bf16.bf16 {%0,%1,%2,%3,%4,%5,%6,%7,%8,%9,%10,%11,%12,%13,%14,%15,%16,%17,%18,%19,%20,%21,%22,%23,%24,%25,%26,%27,%28,%29,%30,%31,%32,%33,%34,%35,%36,%37,%38,%39,%40,%41,%42,%43,%44,%45,%46,%47,%48,%49,%50,%51,%52,%53,%54,%55,%56,%57,%58,%59,%60,%61,%62,%63},%64,%65,p,1,1,%67,%68;}"
                 : ACC8(0), ACC8(8), ACC8(16), ACC8(24), ACC8(32), ACC8(40), ACC8(48), ACC8(56) : "l"(da), "l"(db), "r"(acc), "n"(TA), "n"(TB));
}
template <int TA, int TB> DEV void wgmma_n192_ss(float* d, u64 da, u64 db, int acc) {
    asm volatile("{.reg .pred p; setp.ne.b32 p,%98,0; wgmma.mma_async.sync.aligned.m64n192k16.f32.bf16.bf16 {%0,%1,%2,%3,%4,%5,%6,%7,%8,%9,%10,%11,%12,%13,%14,%15,%16,%17,%18,%19,%20,%21,%22,%23,%24,%25,%26,%27,%28,%29,%30,%31,%32,%33,%34,%35,%36,%37,%38,%39,%40,%41,%42,%43,%44,%45,%46,%47,%48,%49,%50,%51,%52,%53,%54,%55,%56,%57,%58,%59,%60,%61,%62,%63,%64,%65,%66,%67,%68,%69,%70,%71,%72,%73,%74,%75,%76,%77,%78,%79,%80,%81,%82,%83,%84,%85,%86,%87,%88,%89,%90,%91,%92,%93,%94,%95},%96,%97,p,1,1,%99,%100;}"
                 : ACC8(0), ACC8(8), ACC8(16), ACC8(24), ACC8(32), ACC8(40), ACC8(48), ACC8(56), ACC8(64), ACC8(72), ACC8(80), ACC8(88) : "l"(da), "l"(db), "r"(acc), "n"(TA), "n"(TB));
}
template <int ACC> DEV void wgmma_n40_ss(float* d, u64 da, u64 desc) {
    asm volatile("wgmma.mma_async.sync.aligned.m64n40k16.f32.bf16.bf16 {%0,%1,%2,%3,%4,%5,%6,%7,%8,%9,%10,%11,%12,%13,%14,%15,%16,%17,%18,%19},%20,%21,%22,1,1,0,0;"
                 : ACC8(0), ACC8(8), "+f"(d[16]), "+f"(d[17]), "+f"(d[18]), "+f"(d[19]) : "l"(da), "l"(desc), "n"(ACC));
}
DEV void pdl_wait() { asm volatile("griddepcontrol.wait;" ::: "memory"); }
DEV void pdl_launch() { asm volatile("griddepcontrol.launch_dependents;" ::: "memory"); }
DEV uint32_t ldg32(const void* p) { uint32_t v; asm volatile("ld.global.nc.u32 %0,[%1];" : "=r"(v) : "l"(p)); return v; }
DEV void ld_acc(u64& a, u64& b, const void* p) {
    const uint32_t done = (uint32_t)a & (uint32_t)b & 32u;
    asm volatile("{.reg .pred p; setp.eq.u32 p,%3,0;\n"
                 "@p ld.relaxed.gpu.global.v2.u64 {%0,%1},[%2];}" : "+l"(a), "+l"(b) : "l"(p), "r"(done) : "memory");
}
DEV void ld_acc0(u64& a, u64& b, const void* p) {
    asm volatile("ld.relaxed.gpu.global.v2.u64 {%0,%1},[%2];" : "=l"(a), "=l"(b) : "l"(p) : "memory");
}
DEV uint32_t and3(uint32_t a, uint32_t b, uint32_t c) { uint32_t r; asm volatile("lop3.b32 %0,%1,%2,%3,0x80;" : "=r"(r) : "r"(a), "r"(b), "r"(c)); return r; }
DEV uint32_t absmax2(uint32_t a, uint32_t b) { uint32_t r; asm("max.xorsign.abs.bf16x2 %0,%1,%2;" : "=r"(r) : "r"(a), "r"(b)); return r; }
DEV float lds32f(uint32_t a) { float x; asm volatile("ld.shared.f32 %0,[%1];" : "=f"(x) : "r"(a) : "memory"); return x; }
DEV void red_add64(u64* p, uint32_t lo, uint32_t hi) {
    asm volatile("{.reg .b64 v; mov.b64 v,{%1,%2}; red.relaxed.gpu.global.add.u64 [%0],v;}" ::"l"(p), "r"(lo), "r"(hi) : "memory");
}
DEV float bf_round(float x) { return __bfloat162float(__float2bfloat16_rn(x)); }
DEV float bf_lo(uint32_t u) { return __uint_as_float(u << 16); }
DEV float bf_hi(uint32_t u) { return __uint_as_float(u & 0xffff0000u); }

#define GPROF(i, n)
#define PROFT(i)
#define STAMP(i)

DEV void unpack8(float* v, uint4 u) {
    v[0] = bf_lo(u.x); v[1] = bf_hi(u.x); v[2] = bf_lo(u.y); v[3] = bf_hi(u.y);
    v[4] = bf_lo(u.z); v[5] = bf_hi(u.z); v[6] = bf_lo(u.w); v[7] = bf_hi(u.w);
}
DEV int xn_off(int row, int chunk) { return (row >> 5) * 40960 + (chunk >> 3) * 4096 + (row & 31) * 128 + (((chunk ^ row) & 7) << 4); }

DEV void ln_row(float (&v)[3][8], int lane) {
    float s = 0.f;
#pragma unroll
    for (int c = 0; c < 3; c++)
#pragma unroll
        for (int j = 0; j < 8; j++) s += v[c][j];
#pragma unroll
    for (int o = 16; o; o >>= 1) s += __shfl_xor_sync(~0u, s, o);
    float mean = s * (1.f / D_), q = 0.f;
#pragma unroll
    for (int c = 0; c < 3; c++)
        if (c < 2 || lane < 16)
#pragma unroll
            for (int j = 0; j < 8; j++) { float d = v[c][j] - mean; q += d * d; }
#pragma unroll
    for (int o = 16; o; o >>= 1) q += __shfl_xor_sync(~0u, q, o);
    float mb = bf_round(mean);
    float inv = 1.f / bf_round(sqrtf(bf_round(bf_round(q * (1.f / D_)) + 1e-5f)));
#pragma unroll
    for (int c = 0; c < 3; c++)
#pragma unroll
        for (int j = 0; j < 8; j++) v[c][j] = bf_round(v[c][j] - mb) * inv;
}

__host__ __device__ constexpr int col_freq(int c) {
    return c == 320 ? 320 : c < 192 ? (c >> 6) * 128 + (c & 63) : c == 192 ? 192 : c < 256 ? 448 - c : c == 256 ? 64 : 384 - c;
}
DEV float rdft(int n, int k, int sn, int N) {
    float s, c;
    sincospif((float)((n * k) & (N - 1)) * (2.f / N), &s, &c);
    return !sn ? c : k ? s : (n & 1 ? -1.f : 1.f);
}

__global__ void __launch_bounds__(512) prep_kernel(const bf16* __restrict__ x, const bf16* __restrict__ Wq, const bf16* __restrict__ Wk,
                                                   const bf16* __restrict__ Wv, const bf16* __restrict__ Wo) {
    __shared__ float red[32], col[4][640];
    const int tid = threadIdx.x, lane = tid & 31, warp = tid >> 5, b = blockIdx.x, row = b * 16 + warp;
    TLS(0);
    pdl_launch();
    uint4 ux[3], uv[5], uo[8];
#pragma unroll
    for (int c = 0; c < 3; c++) ux[c] = c < 2 || lane < 16 ? *(const uint4*)(x + row * D_ + (c * 32 + lane) * 8) : make_uint4(0, 0, 0, 0);
#pragma unroll
    for (int i = 0; i < 5; i++) uv[i] = *(const uint4*)(Wv + (size_t)((b & 3) * 160 + i * 32 + (tid >> 4)) * 4096 + (b >> 2) * E_ + (tid & 15) * 8);
    if (tid < 320) {
#pragma unroll
        for (int r = 0; r < 8; r++) uo[r] = *(const uint4*)(Wo + (size_t)(b * 32 + tid / 80 * 8 + r) * D_ + tid % 80 * 8);
    }
    if (tid >= 504) prefetch_bulk((const char*)(tid & 4 ? Wk : Wq) + (b * 4 + (tid & 3)) * 10240, 10240);
    if (b < 3) ((uint4*)g_sync)[b * 512 + tid] = make_uint4(0, 0, 0, 0);
    for (int i = b * 512 + tid; i < ACC_LAYER; i += 128 * 512) ((uint4*)g_acc)[i] = make_uint4(0, 0, 0, 0);
    if (tid < 2 * YT_ROWS * D_ / 4 / 128) ((uint4*)g_yt)[b * (2 * YT_ROWS * D_ / 4 / 128) + tid] = make_uint4(0, 0, 0, 0);
    const int gid = tid < 104 ? b * 104 + tid : 1 << 20;
    if (gid < 4096) {
        const int inv = gid >> 11, ks = (gid >> 8) & 7, t = gid & 255, g = (t & 31) >> 2, q = t & 3, tile = t >> 5;
        uint32_t v[4];
#pragma unroll
        for (int j = 0; j < 4; j++) {
            float x[2];
#pragma unroll
            for (int u = 0; u < 2; u++) {
                const int m = inv ? 16 * tile + 2 * g + (j & 1) : 16 * ks + 8 * (j >> 1) + 2 * q + u;
                const int k2 = inv ? 8 * ks + 2 * q + u : 8 * tile + g, sn = inv ? j >> 1 : j & 1;
                x[u] = rdft(m, k2, sn, 128);
                if (sn && k2) x[u] = -x[u];
            }
            v[j] = pack2(x[0], x[1]);
        }
        g_f128[gid] = make_uint4(v[0], v[1], v[2], v[3]);
    } else if (gid < 5120) {
        const int id = gid - 4096, inv = id >> 9, ks = (id >> 7) & 3, t = id & 127, g = (t & 31) >> 2, q = t & 3, tile = t >> 5;
        uint32_t v[4];
#pragma unroll
        for (int j = 0; j < 4; j++) {
            float x[2];
#pragma unroll
            for (int u = 0; u < 2; u++) {
                const int a = inv ? 16 * tile + g + 8 * (j & 1) : 16 * ks + 8 * (j >> 1) + 2 * q + u;
                const int ka = inv ? 8 * ks + 2 * q + u : 8 * tile + g, sn = inv ? j >> 1 : j & 1;
                x[u] = rdft(a, ka, sn, 64);
            }
            v[j] = pack2(x[0], x[1]);
        }
        g_f64[id] = make_uint4(v[0], v[1], v[2], v[3]);
    } else if (gid < 5120 + 8192) {
        const int id = gid - 5120, inv = id >> 12, n = ((id >> 9) & 7) * 8 + ((id >> 3) & 7), k = ((id >> 6) & 7) * 8 + (id & 7);
        float s, c;
        sincospif((float)(((n >> 1) * (k >> 1)) & 31) * (1.f / 16), &s, &c);
        if (inv) s = -s;
        g_g32[id] = __float2bfloat16_rn((n & 1) == (k & 1) ? c : (k & 1) ? s : -s);
    }
    {
        float v[3][8];
#pragma unroll
        for (int c = 0; c < 3; c++) unpack8(v[c], ux[c]);
        ln_row(v, lane);
#pragma unroll
        for (int c = 0; c < 3; c++)
            if (c < 2 || lane < 16)
                *(uint4*)(g_xn + xn_off(row, c * 32 + lane)) =
                    make_uint4(pack2(v[c][0], v[c][1]), pack2(v[c][2], v[c][3]), pack2(v[c][4], v[c][5]), pack2(v[c][6], v[c][7]));
    }
    float sv = 0.f;
#pragma unroll
    for (int i = 0; i < 5; i++) {
        float w[8];
        unpack8(w, uv[i]);
#pragma unroll
        for (int j = 0; j < 8; j++) sv += w[j] * w[j];
    }
    if (tid < 320) {
        float a[8] = {0.f, 0.f, 0.f, 0.f, 0.f, 0.f, 0.f, 0.f};
#pragma unroll
        for (int r = 0; r < 8; r++) {
            float w[8];
            unpack8(w, uo[r]);
#pragma unroll
            for (int j = 0; j < 8; j++) a[j] += w[j] * w[j];
        }
#pragma unroll
        for (int j = 0; j < 8; j++) col[tid / 80][tid % 80 * 8 + j] = a[j];
    }
    __syncthreads();
    float so = (col[0][tid] + col[1][tid]) + (col[2][tid] + col[3][tid]);
    if (tid < 128) so = fmaxf(so, (col[0][512 + tid] + col[1][512 + tid]) + (col[2][512 + tid] + col[3][512 + tid]));
#pragma unroll
    for (int o = 16; o; o >>= 1) { sv += __shfl_xor_sync(~0u, sv, o); so = fmaxf(so, __shfl_xor_sync(~0u, so, o)); }
    if (lane == 0) { red[warp] = sv; red[16 + warp] = so; }
    __syncthreads();
    if (tid == 0) {
        float a = 0.f, c = 0.f;
        for (int i = 0; i < 16; i++) { a += red[i]; c = fmaxf(c, red[16 + i]); }
        g_nrm[b] = a; g_nrm[128 + b] = c;
    }
    TLE(0);
}

DEV void filter_tile(const bf16* __restrict__ wr, const bf16* __restrict__ wi, int ka, int c) {
    const int kn = ka ? 2048 - ka : 32, kc = col_freq(c);
    const unsigned short* pr = (const unsigned short*)wr + kc;
    const unsigned short* pi = (const unsigned short*)wi + kc;
#pragma unroll 1
    for (int i = 0; i < 4; i += 2) {
        unsigned short a[32], b[32];
#pragma unroll
        for (int n = 0; n < 32; n++) {
            const int k = ((n & 1 ? kn : ka) + 64 * (4 * (2 * (i + (n >> 4)) + ((n >> 1) & 1)) + ((n >> 2) & 3))) & 2047;
            a[n] = __ldg(pr + k * NCOL); b[n] = __ldg(pi + k * NCOL);
        }
#pragma unroll
        for (int n = 0; n < 32; n += 4)
            *(uint4*)(g_wt + c * 8192 + (i + (n >> 4)) * 2048 + (ka * 4 + ((n >> 2) & 3)) * 16) =
                make_uint4(a[n] | ((uint32_t)b[n] << 16), a[n + 1] | ((uint32_t)b[n + 1] << 16), a[n + 2] | ((uint32_t)b[n + 2] << 16), a[n + 3] | ((uint32_t)b[n + 3] << 16));
    }
}

namespace wk {
constexpr int STAGE = 49152, NST = 4, OFF_OUT = 3 * STAGE, OFF_RED = 4 * STAGE, OFF_BAR = OFF_RED + 32768, SMEM = OFF_BAR + 128;
constexpr int NPB = 12;
DEV int pb_first(int n) { return n < 2 ? 0 : n == 2 ? 1 : n % 6 == 0 ? n / 6 + 1 : -1; }
__host__ __device__ constexpr int pb_start(int b) { return b == 0 ? 0 : b == 1 ? 2 : b < NPB ? 6 * b - 6 : 64; }
#define NOB 7
#define SPLIT_A 3
#define SPLIT_B 11
constexpr int N_P = NPB * H_, I_F = N_P, I_OB = I_F + 32, I_OT = I_OB + NOB * 5, I_SA = I_OT + (30 - 3 * NOB) * 10;
constexpr int I_SB = I_SA + 10 * SPLIT_A, N_ITEMS = I_SB + 10 * SPLIT_B;
DEV void ot_decode(int id, int& b, int& nt, int& k0, int& k1) {
    const int base = id < I_SA ? I_OT : id < I_SB ? I_SA : I_SB, j = (id - base) / 10;
    nt = (id - base) % 10;
    if (id < I_SA) { b = 3 * NOB + j; k0 = 0; k1 = 22; }
    else if (id < I_SB) { b = 30; k0 = 22 * j / SPLIT_A; k1 = 22 * (j + 1) / SPLIT_A; }
    else { b = 31; k0 = 22 * j / SPLIT_B; k1 = 22 * (j + 1) / SPLIT_B; }
}
enum { SY_TICKET = 0, SY_O = 32, SY_P = 128 };
}
struct Ring {
    int st; uint32_t ph;
    DEV uint32_t par() const { return (ph >> st) & 1; }
    DEV void next(int n) { ph ^= 1u << st; st = st + 1 >= n ? 0 : st + 1; }
};
struct Maps { CUtensorMap wq2, wv1, wo2, wo1, x6, x2, o6, o2; const bf16 *wr, *wi; };

template <int NSG> DEV void proj_tile(uint32_t sb, uint32_t bar, Ring& rg, int wg, int id) {
    using namespace wk;
    float acc[NSG * 16];
#pragma unroll
    for (int i = 0; i < NSG * 16; i++) acc[i] = 0.f;
    const int lane = threadIdx.x & 31, ww = (threadIdx.x >> 5) & 3;
    for (int kb = 0; kb < 10; kb++, rg.next(3)) {
        const int st = rg.st;
        if (kb) mbar_wait(bar + 8 * st, rg.par());
        const u64 da = mkdesc(sb + st * STAGE + wg * 8192, 0, 1024) | SW128, db = mkdesc(sb + st * STAGE + 24576, 0, 1024) | SW128;
        wg_fence();
#pragma unroll
        for (int ks = 0; ks < 4; ks++) {
            if (NSG == 2) wgmma_n64_ss<1, 0>(acc, da + ks * 128, db + ks * 2, 1);
            if (NSG == 4) wgmma_n128_ss<1, 0>(acc, da + ks * 128, db + ks * 2, 1);
            if (NSG == 6) wgmma_n192_ss<1, 0>(acc, da + ks * 128, db + ks * 2, 1);
        }
        wg_commit();
        wg_wait<0>();
        mbar_arrive_elect(bar + 8 * (NST + st));
    }
    const uint32_t out = sb + OFF_OUT + wg * 24576;
    bar_sync(5 + wg, 160);
    const uint32_t la = out + (wg < 2 ? (lane >> 4) * 1024 + ww * 256 + (lane & 15) * 16 : ww * 1024 + ((lane >> 3) & 1) * 512 + (lane >> 4) * 128 + (lane & 7) * 16);
#pragma unroll
    for (int j = 0; j < 2 * NSG; j++) {
        const float* c = acc + 8 * j;
        const uint32_t p0 = pack2(c[0], c[1]), p1 = pack2(c[2], c[3]), p2 = pack2(c[4], c[5]), p3 = pack2(c[6], c[7]);
        if (wg < 2) stsm4t(la + j * 2048, p0, p1, p2, p3);
        else stsm4(la + (j >> 1) * 4096 + (j & 1) * 256, p0, p1, p2, p3);
    }
    if ((threadIdx.x & 127) == 0) sts32(bar + 80 + 4 * wg, id);
    fence_async();
    bar_arrive(1 + wg, 160);
}

DEV uint32_t resid(uint32_t u, float a, float b) { return pack2(bf_lo(u) + bf_round(a), bf_hi(u) + bf_round(b)); }

DEV void worker(uint32_t sb, const Maps& maps, const bf16* __restrict__ x, bf16* __restrict__ x1, int layer) {
    using namespace wk;
    const uint32_t bar = sb + OFF_BAR, slot = bar + 64;
    const int tid = threadIdx.x, lane = tid & 31, warp = __shfl_sync(~0u, tid >> 5, 0);
    uint32_t* sy = g_sync + layer * SYNC_LAYER;
    if (tid == 0) {
        for (int i = 0; i < NST; i++) { mbar_init(bar + 8 * i, 1); mbar_init(bar + 8 * (NST + i), 12); }
        asm volatile("fence.mbarrier_init.release.cluster;" ::: "memory");
    }
    __syncthreads();
    if (warp > 12) {
        const int wg = warp - 13;
        bar_arrive(5 + wg, 160);
        for (;;) {
            bar_sync(1 + wg, 160);
            const int id = (int)lds32(bar + 80 + 4 * wg);
            if (id < 0) break;
            const int s0 = pb_start(id >> 5), ns = pb_start((id >> 5) + 1) - s0;
            if (lane == 0) {
                for (int j = 0; j < ns; j++)
                    bulk_s2g(g_p + (size_t)(((s0 + j) * H_ + (id & 31)) * 3 + wg) * 4096, sb + OFF_OUT + wg * 24576 + j * 4096, 4096);
                bulk_commit();
                bulk_wait<0>();
                flag_add(sy + SY_P + id);
            }
            __syncwarp();
            bar_arrive(5 + wg, 160);
        }
    } else if (warp == 12) {
        if (lane == 0) {
            Ring rg = {0, 7u};
            auto acquire = [&]() { mbar_wait(bar + 8 * (NST + rg.st), rg.par()); return sb + rg.st * STAGE; };
            for (;;) {
                int id = (int)atomicAdd(sy + SY_TICKET, 1u);
                if (layer && id >= I_F) id += I_OB - I_F;
                if (id >= N_ITEMS) id = -1;
                if (id >= 0) { TLI(id, 0, gtime()); TLI(id, 3, blockIdx.x + (gridDim.x % 3 == 0 && gridDim.x > 111 ? 0 : 1000)); }
                uint32_t d = acquire();
                sts32(slot + 4 * rg.st, id);
                if (id < 0) { mbar_arrive(bar + 8 * rg.st); break; }
                if (id < N_P) {
                    const int b = id >> 5, h = id & 31, s0 = pb_start(b), ns = pb_start(b + 1) - s0;
                    for (int kb = 0; kb < 10; kb++, rg.next(3)) {
                        if (kb) d = acquire();
                        const uint32_t fb = bar + 8 * rg.st;
                        mbar_expect(fb, 24576 + ns * 4096);
                        tma3d(d, &maps.wq2, 0, kb * 64, 2 * h, fb);
                        tma3d(d + 16384, &maps.wv1, 0, kb * 64, 2 * h, fb);
                        if (ns == 6) tma3d(d + 24576, &maps.x6, 0, 2 * kb, s0, fb);
                        else for (int j = 0; j < ns; j += 2) tma3d(d + 24576 + j * 4096, &maps.x2, 0, 2 * kb, s0 + j, fb);
                    }
                } else if (id < I_OB) {
                    mbar_arrive(bar + 8 * rg.st);
                    mbar_wait(bar + 8 * (NST + rg.st), rg.par() ^ 1);
                    rg.next(NST);
                } else if (id < I_OT) {
                    const int b = (id - I_OB) / 5, nt = (id - I_OB) % 5;
                    for (int j = 0; j < 6; j++) flag_wait(sy + SY_O + 6 * b + j, 32);
                    for (int kb = 0; kb < 64; kb++, rg.next(NST)) {
                        if (kb) d = acquire();
                        const uint32_t fb = bar + 8 * rg.st;
                        mbar_expect(fb, 40960);
                        tma3d(d, &maps.o6, 0, 2 * kb, 6 * b, fb);
                        tma3d(d + 24576, &maps.wo2, 0, kb * 64, 2 * nt, fb);
                    }
                } else {
                    int b, nt, k0, k1;
                    ot_decode(id, b, nt, k0, k1);
                    for (int kb = k0; kb < k1; kb++, rg.next(NST)) {
                        if (kb > k0) d = acquire();
                        const uint32_t fb = bar + 8 * rg.st;
                        mbar_expect(fb, 49152);
                        tma3d(d + 24576, &maps.wo1, 0, 3 * kb * 64, nt, fb);
                        if (kb == k0) for (int j = 0; j < 2; j++) flag_wait(sy + SY_O + 2 * b + j, 32);
                        for (int u = 0; u < 3; u++) tma3d(d + u * 8192, &maps.o2, 0, 2 * (3 * kb + u), 2 * b, fb);
                    }
                }
            }
        }
    } else {
        const int wg = warp >> 2, g = lane >> 2, q = lane & 3;
        Ring rg = {0, 0u};
        bool stores_done = false;
        for (;;) {
            mbar_wait(bar + 8 * rg.st, rg.par());
            const int id = (int)lds32(slot + 4 * rg.st);
            if ((id < 0 || id >= N_P) && !stores_done) {
                bar_sync(5 + wg, 160);
                if ((tid & 127) == 0) sts32(bar + 80 + 4 * wg, ~0u);
                bar_arrive(1 + wg, 160);
                stores_done = true;
                bar_sync(4, 384);
                mbar_arrive_elect(bar + 8 * (NST + 3));
            }
            if (id < 0) break;
            if (tid == 0) TLI(id, 1, gtime());
            if (id < N_P) {
                const int b = id >> 5;
                if (b == 0) proj_tile<2>(sb, bar, rg, wg, id);
                else if (b == 1 || b == NPB - 1) proj_tile<4>(sb, bar, rg, wg, id);
                else proj_tile<6>(sb, bar, rg, wg, id);
            } else if (id < I_OB) {
                if (tid < NCOL) filter_tile(maps.wr, maps.wi, id - I_F, tid);
                __syncwarp();
                mbar_arrive_elect(bar + 8 * (NST + rg.st));
                rg.next(NST);
            } else if (id < I_OT) {
                const int b = (id - I_OB) / 5, nt = (id - I_OB) % 5;
                const size_t o = (size_t)(192 * b + 16 * warp + g) * D_ + nt * 128 + 2 * q;
                float acc[64];
#pragma unroll
                for (int i = 0; i < 64; i++) acc[i] = 0.f;
                for (int kb = 0; kb < 64; kb++, rg.next(NST)) {
                    const int st = rg.st;
                    if (kb) mbar_wait(bar + 8 * st, rg.par());
                    const u64 da = mkdesc(sb + st * STAGE + wg * 8192, 128, 1024), db = mkdesc(sb + st * STAGE + 24576, 8192, 1024) | SW128;
                    wg_fence();
#pragma unroll
                    for (int ks = 0; ks < 4; ks++) wgmma_n128_ss<0, 1>(acc, da + ks * 16, db + ks * 128, 1);
                    wg_commit();
                    wg_wait<0>();
                    mbar_arrive_elect(bar + 8 * (NST + st));
                }
                uint32_t xr[32];
#pragma unroll
                for (int t = 0; t < 32; t++) xr[t] = ldg32(x + o + 8 * (t >> 1) + (t & 1) * 8 * D_);
#pragma unroll
                for (int t = 0; t < 32; t++) *(uint32_t*)(x1 + o + 8 * (t >> 1) + (t & 1) * 8 * D_) = resid(xr[t], acc[2 * t], acc[2 * t + 1]);
            } else {
                int b, nt, k0, k1;
                ot_decode(id, b, nt, k0, k1);
                const size_t o = (size_t)(64 * b + 16 * (warp & 3) + g) * D_ + nt * 64 + 2 * q;
                float acc[32];
                uint32_t xr[16];
#pragma unroll
                for (int t = 0; t < 16; t++) xr[t] = wg == 0 && id < I_SA ? ldg32(x + o + 8 * (t >> 1) + (t & 1) * 8 * D_) : 0;
#pragma unroll
                for (int i = 0; i < 32; i++) acc[i] = 0.f;
                for (int kb = k0; kb < k1; kb++, rg.next(NST)) {
                    const int st = rg.st;
                    if (kb > k0) mbar_wait(bar + 8 * st, rg.par());
                    const u64 da = mkdesc(sb + st * STAGE + wg * 8192, 128, 1024), db = mkdesc(sb + st * STAGE + 24576 + wg * 8192, 0, 1024) | SW128;
                    wg_fence();
#pragma unroll
                    for (int ks = 0; ks < 4; ks++) wgmma_n64_ss<0, 1>(acc, da + ks * 16, db + ks * 128, 1);
                    wg_commit();
                    wg_wait<0>();
                    mbar_arrive_elect(bar + 8 * (NST + st));
                }
                const uint32_t ra = sb + OFF_RED + (tid & 127) * 16;
                if (wg) {
#pragma unroll
                    for (int t = 0; t < 8; t++)
                        sts128(ra + (wg - 1) * 16384 + t * 2048, __float_as_uint(acc[4 * t]), __float_as_uint(acc[4 * t + 1]), __float_as_uint(acc[4 * t + 2]), __float_as_uint(acc[4 * t + 3]));
                }
                bar_sync(4, 384);
                if (wg == 0) {
#pragma unroll
                    for (int t = 0; t < 8; t++) {
                        float u[4], v[4];
                        lds128f(u, ra + t * 2048); lds128f(v, ra + 16384 + t * 2048);
#pragma unroll
                        for (int i = 0; i < 4; i++) acc[4 * t + i] += u[i] + v[i];
                    }
                }
                bar_sync(4, 384);
                if (wg == 0) {
                    if (id < I_SA) {
#pragma unroll
                        for (int t = 0; t < 16; t++) *(uint32_t*)(x1 + o + 8 * (t >> 1) + (t & 1) * 8 * D_) = resid(xr[t], acc[2 * t], acc[2 * t + 1]);
                    } else {
                        float* y = g_yt + (layer * YT_ROWS - (S_ - YT_ROWS)) * D_ + o;
#pragma unroll
                        for (int t = 0; t < 16; t++)
                            asm volatile("red.relaxed.gpu.global.add.v2.f32 [%0],{%1,%2};" ::"l"(y + 8 * (t >> 1) + (t & 1) * 8 * D_), "f"(acc[2 * t]), "f"(acc[2 * t + 1]) : "memory");
                    }
                }
            }
            if (tid == 0) TLI(id, 2, gtime());
        }
    }
}

__global__ void __launch_bounds__(512, 1) side_kernel(const __grid_constant__ Maps maps, const bf16* __restrict__ x, bf16* __restrict__ x1, int layer) {
    extern __shared__ __align__(1024) unsigned char smem[];
    pdl_launch();
    TLS(3 + 5 * layer);
    worker(s2u(smem), maps, x, x1, layer);
    __syncwarp();
    pdl_wait();
    TLE(3 + 5 * layer);
}

constexpr float C5A = 0.30901699437494742f, C5B = -0.80901699437494742f, S5A = 0.95105651629515357f, S5B = 0.58778525229247313f;
template <int SGN> DEV void dft5(const float (&tr)[5], const float (&ti)[5], float (&zr)[5], float (&zi)[5]) {
    const float ar = tr[1] + tr[4], ai = ti[1] + ti[4], br = tr[2] + tr[3], bi = ti[2] + ti[3];
    const float cr = tr[1] - tr[4], ci = ti[1] - ti[4], dr = tr[2] - tr[3], di = ti[2] - ti[3];
    zr[0] = tr[0] + ar + br; zi[0] = ti[0] + ai + bi;
    const float m1r = tr[0] + C5A * ar + C5B * br, m1i = ti[0] + C5A * ai + C5B * bi;
    const float m2r = tr[0] + C5B * ar + C5A * br, m2i = ti[0] + C5B * ai + C5A * bi;
    const float n1r = SGN * (S5A * cr + S5B * dr), n1i = SGN * (S5A * ci + S5B * di);
    const float n2r = SGN * (S5B * cr - S5A * dr), n2i = SGN * (S5B * ci - S5A * di);
    zr[1] = m1r + n1i; zi[1] = m1i - n1r; zr[4] = m1r - n1i; zi[4] = m1i + n1r;
    zr[2] = m2r + n2i; zi[2] = m2i - n2r; zr[3] = m2r - n2i; zi[3] = m2i + n2r;
}
DEV void ln40(float (&v)[40]) {
    float s = 0.f;
#pragma unroll
    for (int i = 0; i < 40; i++) s += v[i];
#pragma unroll
    for (int o = 8; o; o >>= 1) s += __shfl_xor_sync(~0u, s, o);
    const float mean = s * (1.f / D_);
    float q = 0.f;
#pragma unroll
    for (int i = 0; i < 40; i++) { const float d = v[i] - mean; q += d * d; }
#pragma unroll
    for (int o = 8; o; o >>= 1) q += __shfl_xor_sync(~0u, q, o);
    const float mb = bf_round(mean);
    const float inv = 1.f / bf_round(sqrtf(bf_round(bf_round(q * (1.f / D_)) + 1e-5f)));
#pragma unroll
    for (int i = 0; i < 40; i++) v[i] = bf_round(v[i] - mb) * inv;
}
__global__ void __launch_bounds__(256) rowfft_kernel(const bf16* __restrict__ x0, bf16* __restrict__ x, const bf16* __restrict__ Wq,
                                                     const bf16* __restrict__ Wk, const bf16* __restrict__ Wv, int layer) {
    extern __shared__ __align__(1024) unsigned char smem[];
    const uint32_t sb = s2u(smem), sx = sb + 23552, sy = sx + 20480, bar = sy + 40960;
    const int tid = threadIdx.x, lane = tid & 31, q = lane & 3, blk = blockIdx.x, k2 = tid >> 2;
    if (tid == 0) TLI(800 + blk, 0, gtime());
    float twr[5], twi[5];
#pragma unroll
    for (int r = 1; r < 5; r++) { sincospif((float)(r * k2) * (-1.f / 320), &twi[r], &twr[r]); }
    uint32_t f[8][4];
#pragma unroll
    for (int ks = 0; ks < 8; ks++) { const uint4 u = g_f128[ks * 256 + tid]; f[ks][0] = u.x; f[ks][1] = u.y; f[ks][2] = u.z; f[ks][3] = u.w; }
    const bool split = blk * 16 >= S_ - YT_ROWS;
    if (tid == 0) {
        mbar_init(bar, 1);
        asm volatile("fence.mbarrier_init.release.cluster;" ::: "memory");
        mbar_expect(bar, split ? 61440 : 20480);
        if (split) bulk_g2s(sx, x0 + (size_t)blk * 16 * D_, 20480, bar);
    }
    __syncthreads();
    pdl_wait();
    pdl_launch();
    TLS(4 + 5 * layer);
    if (tid == 0) TLI(800 + blk, 1, gtime());
    if (tid == 0) {
        if (split) bulk_g2s(sy, g_yt + (layer * YT_ROWS + blk * 16 - (S_ - YT_ROWS)) * D_, 40960, bar);
        else bulk_g2s(sx, x + (size_t)blk * 16 * D_, 20480, bar);
    }
    mbar_wait(bar, 0);
    {
        const int rho = tid >> 4, j = tid & 15;
        float v[40];
#pragma unroll
        for (int i = 0; i < 5; i++) {
            uint32_t u[4];
            lds128(u, sx + tid * 80 + i * 16);
            if (split) {
                float p[8];
                lds128f(p, sy + tid * 160 + i * 32); lds128f(p + 4, sy + tid * 160 + i * 32 + 16);
#pragma unroll
                for (int k = 0; k < 4; k++) u[k] = resid(u[k], p[2 * k], p[2 * k + 1]);
                sts128(sx + tid * 80 + i * 16, u[0], u[1], u[2], u[3]);
            }
            unpack8(v + 8 * i, make_uint4(u[0], u[1], u[2], u[3]));
        }
        if (layer == 0 && tid < 12) prefetch_bulk((const char*)(tid < 4 ? Wk : tid < 8 ? Wq : Wv) + (blk * 4 + (tid & 3)) * 10240, 10240);
        ln40(v);
        const uint32_t a = sb + ((rho >> 1) & 1) * 2304 + j * 144 + (2 * (rho >> 2) + (rho & 1)) * 16;
#pragma unroll
        for (int r = 0; r < 5; r++)
            sts128(a + r * 4608, pack2(v[r], v[5 + r]), pack2(v[10 + r], v[15 + r]), pack2(v[20 + r], v[25 + r]), pack2(v[30 + r], v[35 + r]));
    }
    fence_async();
    __syncthreads();
    if (tid == 0) TLI(800 + blk, 2, gtime());
    if (tid == 0 && split) { bulk_s2g(x + (size_t)blk * 16 * D_, sx, 20480); bulk_commit(); }
    float acc[40];
    const u64 db = mkdesc(sb, 144, 2304);
    wg_fence();
    wgmma_n80_rs<0, 0>(acc, f[0], db);
#pragma unroll
    for (int ks = 1; ks < 8; ks++) wgmma_n80_rs<1, 0>(acc, f[ks], db + ks * 18);
    wg_commit();
    wg_wait<0>();
    unsigned char* zp = g_z + (blk >> 1) * 128 + ((((blk & 1) * 4 + q) ^ ((blk >> 1) & 7)) << 4);
    uint32_t o[5][4];
#pragma unroll
    for (int u = 0; u < 4; u++) {
        float tr[5], ti[5], zr[5], zi[5];
#pragma unroll
        for (int r = 0; r < 5; r++) {
            const float yr = acc[8 * r + 4 * (u >> 1) + (u & 1)], yi = k2 ? acc[8 * r + 4 * (u >> 1) + 2 + (u & 1)] : 0.f;
            tr[r] = r ? yr * twr[r] - yi * twi[r] : yr;
            ti[r] = r ? yr * twi[r] + yi * twr[r] : yi;
        }
        dft5<1>(tr, ti, zr, zi);
#pragma unroll
        for (int j = 0; j < 5; j++) o[j][u] = pack2(zr[j], j < 3 ? zi[j] : -zi[j]);
    }
#pragma unroll
    for (int j = 0; j < 5; j++)
        if (j < 3 || k2) *(uint4*)(zp + (64 * j + k2) * 8192) = make_uint4(o[j][0], o[j][1], o[j][2], o[j][3]);
    if (k2 == 0) {
#pragma unroll
        for (int u = 0; u < 4; u++) {
            float tr[5], ti[5], zr[5], zi[5];
            const float cr[5] = {1.f, -C5B, C5A, -C5A, C5B}, ci[5] = {0.f, -S5B, -S5A, -S5A, -S5B};
#pragma unroll
            for (int r = 0; r < 5; r++) { const float y = acc[8 * r + 4 * (u >> 1) + 2 + (u & 1)]; tr[r] = y * cr[r]; ti[r] = y * ci[r]; }
            dft5<1>(tr, ti, zr, zi);
            o[0][u] = pack2(zr[0], zi[0]); o[1][u] = pack2(zr[1], zi[1]); o[2][u] = pack2(zr[2], 0.f);
        }
        *(uint4*)(zp + 256 * 8192) = make_uint4(o[0][0], o[0][1], o[0][2], o[0][3]);
        *(uint4*)(zp + 192 * 8192) = make_uint4(o[1][0], o[1][1], o[1][2], o[1][3]);
        *(uint4*)(zp + 320 * 8192) = make_uint4(o[2][0], o[2][1], o[2][2], o[2][3]);
    }
    if (tid == 0) bulk_wait<0>();
    TLE(4 + 5 * layer);
    if (tid == 0) TLI(800 + blk, 3, gtime());
}

constexpr int CF_SMEM = 16384 + 3 * 16384 + 64;
__global__ void __launch_bounds__(384) colfft_kernel(int layer) {
    extern __shared__ __align__(1024) unsigned char smem[];
    const uint32_t sb = s2u(smem), bar = sb + 65536;
    const int tid = threadIdx.x, lane = tid & 31, q = lane & 3, wg = __shfl_sync(~0u, tid >> 7, 0), t = tid & 127, ka = t >> 2;
    const int col = blockIdx.x * 3 + wg;
    const uint32_t d0 = sb + 16384 + wg * 16384, d1 = d0 + 8192;
    if (tid == 0) {
        for (int i = 0; i < 4; i++) mbar_init(bar + 8 * i, 1);
        asm volatile("fence.mbarrier_init.release.cluster;" ::: "memory");
    }
    float twr[8], twi[8];
#pragma unroll
    for (int i = 0; i < 8; i++) sincospif((float)((4 * i + q) * (ka ? ka : -32)) * (1.f / 1024), &twi[i], &twr[i]);
    __syncthreads();
    if (tid == 0) { mbar_expect(bar + 24, 16384); bulk_g2s(sb, g_g32, 16384, bar + 24); }
    uint32_t f[4][4], w[16];
#pragma unroll
    for (int ks = 0; ks < 4; ks++) { const uint4 u = g_f64[ks * 128 + t]; f[ks][0] = u.x; f[ks][1] = u.y; f[ks][2] = u.z; f[ks][3] = u.w; }
#pragma unroll
    for (int i = 0; i < 4; i++) { const uint4 u = *(const uint4*)(g_wt + col * 8192 + i * 2048 + t * 16); w[4 * i] = u.x; w[4 * i + 1] = u.y; w[4 * i + 2] = u.z; w[4 * i + 3] = u.w; }
    pdl_wait();
    pdl_launch();
    TLS(5 + 5 * layer);
    if (t == 0) {
        mbar_expect(bar + 8 * wg, 8192);
        bulk_g2s(d0, g_z + col * 8192, 8192, bar + 8 * wg);
    }
    float acc[32];
    uint32_t a[4][4];
    mbar_wait(bar + 8 * wg, 0);
    {
        const u64 db = mkdesc(d0, 0, 1024) | SW128;
        wg_fence();
        wgmma_n64_rs<0, 1>(acc, f[0], db);
#pragma unroll
        for (int ks = 1; ks < 4; ks++) wgmma_n64_rs<1, 1>(acc, f[ks], db + ks * 128);
        wg_commit();
        wg_wait<0>();
    }
#pragma unroll
    for (int ks = 0; ks < 4; ks++) { const uint4 u = g_f64[512 + ks * 128 + t]; f[ks][0] = u.x; f[ks][1] = u.y; f[ks][2] = u.z; f[ks][3] = u.w; }
#pragma unroll
    for (int i = 0; i < 8; i++) {
        const float c0 = acc[4 * i], c1 = acc[4 * i + 1], c2 = acc[4 * i + 2], c3 = acc[4 * i + 3];
        const float pr = c0 + c3, pi = c1 - c2, nr = ka ? c0 - c3 : c2, ni = ka ? c1 + c2 : c3;
        a[i >> 1][2 * (i & 1)] = ka ? pack2(pr * twr[i] + pi * twi[i], pi * twr[i] - pr * twi[i]) : pack2(c0, c1);
        a[i >> 1][2 * (i & 1) + 1] = pack2(nr * twr[i] - ni * twi[i], ni * twr[i] + nr * twi[i]);
    }
    mbar_wait(bar + 24, 0);
    {
        const u64 db = mkdesc(sb, 128, 1024);
        wg_fence();
        wgmma_n64_rs<0, 0>(acc, a[0], db);
#pragma unroll
        for (int ks = 1; ks < 4; ks++) wgmma_n64_rs<1, 0>(acc, a[ks], db + ks * 16);
        wg_commit();
        wg_wait<0>();
    }
    constexpr float NORM = 1.f / (2048.f * 640.f);
#pragma unroll
    for (int i = 0; i < 16; i++) {
        const float zr = acc[2 * i] * NORM, zi = acc[2 * i + 1] * NORM, wr = bf_lo(w[i]), wi = bf_hi(w[i]);
        a[i >> 2][i & 3] = pack2(zr * wr - zi * wi, zr * wi + zi * wr);
    }
    {
        const u64 db = mkdesc(sb + 8192, 128, 1024);
        wg_fence();
        wgmma_n64_rs<0, 0>(acc, a[0], db);
#pragma unroll
        for (int ks = 1; ks < 4; ks++) wgmma_n64_rs<1, 0>(acc, a[ks], db + ks * 16);
        wg_commit();
        wg_wait<0>();
    }
    const uint32_t row = (t >> 5) * 2048 + (lane & 15) * 128;
#pragma unroll
    for (int i = 0; i < 8; i++) {
        const float c0 = acc[4 * i], c1 = acc[4 * i + 1], c2 = acc[4 * i + 2], c3 = acc[4 * i + 3];
        const float pr = c0 * twr[i] - c1 * twi[i], pi = c1 * twr[i] + c0 * twi[i];
        const float nr = c2 * twr[i] + c3 * twi[i], ni = c3 * twr[i] - c2 * twi[i];
        a[i >> 1][2 * (i & 1)] = ka ? pack2(pr + nr, pi + ni) : pack2(c0, c1);
        a[i >> 1][2 * (i & 1) + 1] = ka ? pack2(ni - pi, pr - nr) : pack2(nr, ni);
    }
#pragma unroll
    for (int i = 0; i < 4; i++) stsm4(d1 + row + (((2 * i + (lane >> 4)) ^ (lane & 7)) << 4), a[i][0], a[i][1], a[i][2], a[i][3]);
    fence_async();
    bar_sync(1 + wg, 128);
    {
        const u64 db = mkdesc(d1, 0, 1024) | SW128;
        wg_fence();
        wgmma_n64_rs<0, 1>(acc, f[0], db);
#pragma unroll
        for (int ks = 1; ks < 4; ks++) wgmma_n64_rs<1, 1>(acc, f[ks], db + ks * 128);
        wg_commit();
        wg_wait<0>();
    }
#pragma unroll
    for (int i = 0; i < 4; i++)
        stsm4(d0 + row + (((2 * i + (lane >> 4)) ^ (lane & 7)) << 4), pack2(acc[8 * i], acc[8 * i + 1]), pack2(acc[8 * i + 2], acc[8 * i + 3]),
              pack2(acc[8 * i + 4], acc[8 * i + 5]), pack2(acc[8 * i + 6], acc[8 * i + 7]));
    fence_async();
    bar_sync(1 + wg, 128);
    if (t == 0) {
        bulk_s2g(g_z + col * 8192, d0, 8192);
        asm volatile("cp.async.bulk.commit_group;" ::: "memory");
        asm volatile("cp.async.bulk.wait_group 0;" ::: "memory");
    }
    TLE(5 + 5 * layer);
}

__global__ void __launch_bounds__(256) rowifft_kernel(const bf16* __restrict__ x, bf16* __restrict__ out, int last) {
    extern __shared__ __align__(1024) unsigned char smem[];
    const uint32_t sb = s2u(smem), sx = sb + 20480, sy = sx + 20480, bar = sy + 16 * 1296;
    const int tid = threadIdx.x, lane = tid & 31, q = lane & 3, blk = blockIdx.x, k2 = tid >> 2, warp = tid >> 5;
    float twr[5], twi[5];
#pragma unroll
    for (int r = 1; r < 5; r++) { sincospif((float)(r * k2) * (1.f / 320), &twi[r], &twr[r]); twr[r] *= 2.f; twi[r] *= 2.f; }
    uint32_t f[8][4];
#pragma unroll
    for (int ks = 0; ks < 8; ks++) { const uint4 u = g_f128[2048 + ks * 256 + tid]; f[ks][0] = u.x; f[ks][1] = u.y; f[ks][2] = u.z; f[ks][3] = u.w; }
    if (tid == 0) {
        mbar_init(bar, 1);
        asm volatile("fence.mbarrier_init.release.cluster;" ::: "memory");
        mbar_expect(bar, 20480);
        bulk_g2s(sx, x + (size_t)blk * 16 * D_, 20480, bar);
    }
    pdl_wait();
    pdl_launch();
    TLS(6 + 5 * last);
    const unsigned char* zp = g_z + (blk >> 1) * 128 + ((((blk & 1) * 4 + q) ^ ((blk >> 1) & 7)) << 4);
    uint4 z[6];
#pragma unroll
    for (int j = 0; j < 5; j++) z[j] = *(const uint4*)(zp + (64 * j + k2) * 8192);
    z[5] = k2 ? make_uint4(0, 0, 0, 0) : *(const uint4*)(zp + 320 * 8192);
    float acc[40];
#pragma unroll
    for (int u = 0; u < 4; u++) {
        float yr[6], yi[6], tr[5], ti[5], zr[5], zi[5];
#pragma unroll
        for (int j = 0; j < 6; j++) { const uint32_t v = u == 0 ? z[j].x : u == 1 ? z[j].y : u == 2 ? z[j].z : z[j].w; yr[j] = bf_lo(v); yi[j] = bf_hi(v); }
#pragma unroll
        for (int j = 0; j < 5; j++) { tr[j] = yr[j]; ti[j] = j < 3 ? yi[j] : -yi[j]; }
        dft5<-1>(tr, ti, zr, zi);
        const float c1[5] = {1.f, C5A, C5B, C5B, C5A}, s1[5] = {0.f, S5A, S5B, -S5B, -S5A};
        const float c2[5] = {1.f, C5B, C5A, C5A, C5B}, s2[5] = {0.f, S5B, -S5A, S5A, -S5B};
        const float c3[5] = {1.f, -C5B, C5A, -C5A, C5B}, s3[5] = {0.f, S5B, S5A, S5A, S5B};
        const float c4[5] = {1.f, -C5A, C5B, -C5B, C5A}, s4[5] = {0.f, S5A, -S5B, -S5B, S5A};
#pragma unroll
        for (int r = 0; r < 5; r++) {
            float er = r ? zr[r] * twr[r] - zi[r] * twi[r] : 2.f * zr[0], ei = r ? zr[r] * twi[r] + zi[r] * twr[r] : 2.f * zi[0];
            if (k2 == 0) {
                er = yr[0] + 2.f * (yr[1] * c1[r] - yi[1] * s1[r] + yr[2] * c2[r] - yi[2] * s2[r]);
                ei = (r & 1 ? -yr[5] : yr[5]) + 2.f * (yr[4] * c3[r] - yi[4] * s3[r] + yr[3] * c4[r] - yi[3] * s4[r]);
            }
            acc[8 * r + 4 * (u >> 1) + (u & 1)] = er;
            acc[8 * r + 4 * (u >> 1) + 2 + (u & 1)] = ei;
        }
    }
#pragma unroll
    for (int r = 0; r < 5; r++)
        stsm4(sb + (2 * warp + ((lane >> 3) & 1)) * 1280 + (2 * r + (lane >> 4)) * 128 + (lane & 7) * 16, pack2(acc[8 * r], acc[8 * r + 1]),
              pack2(acc[8 * r + 2], acc[8 * r + 3]), pack2(acc[8 * r + 4], acc[8 * r + 5]), pack2(acc[8 * r + 6], acc[8 * r + 7]));
    fence_async();
    __syncthreads();
    const u64 db = mkdesc(sb, 1280, 128);
    wg_fence();
    wgmma_n80_rs<0, 1>(acc, f[0], db);
#pragma unroll
    for (int ks = 1; ks < 8; ks++) wgmma_n80_rs<1, 1>(acc, f[ks], db + ks * 160);
    wg_commit();
    wg_wait<0>();
#pragma unroll
    for (int u = 0; u < 4; u++) {
        float e[10];
#pragma unroll
        for (int r = 0; r < 5; r++) { e[r] = acc[8 * r + 4 * (u >> 1) + (u & 1)]; e[5 + r] = acc[8 * r + 4 * (u >> 1) + 2 + (u & 1)]; }
#pragma unroll
        for (int i = 0; i < 5; i++) sts32(sy + (4 * q + u) * 1296 + k2 * 20 + i * 4, pack2(e[2 * i], e[2 * i + 1]));
    }
    __syncthreads();
    const int rho = tid >> 4, j = tid & 15;
    float v[40];
    mbar_wait(bar, 0);
#pragma unroll
    for (int i = 0; i < 5; i++) {
        uint32_t y[4], u[4];
        lds128(y, sy + rho * 1296 + j * 80 + i * 16);
        lds128(u, sx + tid * 80 + i * 16);
#pragma unroll
        for (int k = 0; k < 4; k++) u[k] = pack2(bf_lo(u[k]) + bf_lo(y[k]), bf_hi(u[k]) + bf_hi(y[k]));
        sts128(sx + tid * 80 + i * 16, u[0], u[1], u[2], u[3]);
        unpack8(v + 8 * i, make_uint4(u[0], u[1], u[2], u[3]));
    }
    if (!last) {
        ln40(v);
#pragma unroll
        for (int i = 0; i < 5; i++) {
            const int c = j * 5 + i;
            sts128(sb + (c >> 3) * 2048 + rho * 128 + (((c ^ rho) & 7) << 4), pack2(v[8 * i], v[8 * i + 1]), pack2(v[8 * i + 2], v[8 * i + 3]),
                   pack2(v[8 * i + 4], v[8 * i + 5]), pack2(v[8 * i + 6], v[8 * i + 7]));
        }
    }
    fence_async();
    __syncthreads();
    if (lane == 0) {
        if (warp == 7) bulk_s2g(out + (size_t)blk * 16 * D_, sx, 20480);
        else if (!last && warp < 5) {
            unsigned char* p = g_xn + (blk >> 1) * 40960 + warp * 8192 + (blk & 1) * 2048;
            bulk_s2g(p, sb + warp * 4096, 2048);
            bulk_s2g(p + 4096, sb + warp * 4096 + 2048, 2048);
        }
        bulk_commit();
        bulk_wait<0>();
    }
    TLE(6 + 5 * last);
}

namespace rec {
constexpr int NS = 5;
constexpr int OFF_X = 0;
constexpr int OFF_WO = 81920;
constexpr int OFF_WS = OFF_WO + 65536;
constexpr int OFF_MEMB = OFF_WS + NS * 4096;
constexpr int OFF_VX = OFF_MEMB + 10240;
constexpr int OFF_VM = OFF_VX + 16384;
constexpr int OFF_Q = OFF_VM + 4096;
constexpr int OFF_K = OFF_Q + 10240;
constexpr int OFF_OST = OFF_WO + 49152;
constexpr int OFF_PX = OFF_OST + 8192;
constexpr int OFF_PT = OFF_PX + 2560;
constexpr int OFF_PS = OFF_K + 10240;
constexpr int OFF_OB = OFF_PS + 1280;
constexpr int OFF_MX = OFF_OB + 2048;
constexpr int OFF_BAR = OFF_MX + 64;
constexpr int OFF_PROF = OFF_BAR + 256;
constexpr int SMEM = OFF_PROF + 4096 > wk::SMEM ? OFF_PROF + 4096 : wk::SMEM;
enum { B_XT = 0, B_KX = 2, B_VX = 4, B_XD = 6, B_X1 = 8, B_PXF = 12, B_PXE = 13, B_FIN = 14, B_ST = 15 };
enum { NB_W2 = 0, NB_GO = 1, NB_QK = 2, NB_WIN = 3, NB_ATT = 4, NB_X = 5, NB_PRO = 6, NB_W1 = 7, NB_MEM = 8  , NB_LD = 13  , NB_KX = 15 };
#define NOX 0
#define NW1 7
#define NW1B 9
template <int N> struct IC { static constexpr int value = N; };
template <int N, int I = 0, class F> DEV void static_for(F&& f) { if constexpr (I < N) { f(IC<I>{}); static_for<N, I + 1>(f); } }
constexpr float SM_SCALE = 0.08838834764831845f * 1.4426950408889634f;
}

__global__ void __launch_bounds__(512, 1) rec_kernel(const __grid_constant__ Maps maps, const bf16* __restrict__ x, bf16* __restrict__ x1, const bf16* __restrict__ mem0, const bf16* __restrict__ Wq, const bf16* __restrict__ Wk,
                                                     const bf16* __restrict__ Wv, const bf16* __restrict__ Wo, int layer, int delay, int delay2) {
    using namespace rec;
    extern __shared__ __align__(1024) unsigned char smem[];
    const uint32_t sb = s2u(smem);
    if (blockIdx.x >= 3 * H_) {
        pdl_wait();
        pdl_launch();
        worker(sb, maps, x, x1, layer);
        return;
    }
    const int tid = threadIdx.x, lane = tid & 31, warp = __shfl_sync(~0u, tid >> 5, 0);
    const int g = lane >> 2, q = lane & 3;
    const int h = blockIdx.x / 3;
    const uint32_t bar = sb + OFF_BAR;
    STAMP(2 * layer);
    TLS(2 + 5 * layer);
    if (tid == 0) {
        for (int i = 0; i < 2; i++) {
            mbar_init(bar + 8 * (B_XT + i), 1); mbar_init(bar + 8 * (B_KX + i), 4); mbar_init(bar + 8 * (B_VX + i), 1);
            mbar_init(bar + 8 * (B_XD + i), 8); mbar_init(bar + 8 * (B_X1 + i), 1);
        }
        mbar_init(bar + 8 * B_PXF, 1); mbar_init(bar + 8 * B_PXE, 2); mbar_init(bar + 8 * B_ST, 2);
        mbar_init(bar + 8 * B_FIN, 48);
        sts32(sb + OFF_MX + 32, 0); sts32(sb + OFF_MX + 36, 0);
        asm volatile("fence.mbarrier_init.release.cluster;" ::: "memory");
    }
    asm volatile("barrier.cluster.arrive.aligned; barrier.cluster.wait.aligned;" ::: "memory");
    const bool never = delay < 0;

    if (warp < 8) {
        asm volatile("setmaxnreg.inc.sync.aligned.u32 184;");
        const uint32_t rank = cta_rank();
        const int wg = warp >> 2;
        uint32_t a[40 - NS][4];
        const uint32_t l16 = opaque(sb + lane * 16);
        uint32_t wsa = opaque(sb + OFF_WS + warp * 512 + (lane & 7) * 16 + ((lane >> 3) & 1) * 256 + (lane >> 4) * 128);
        uint32_t dst = opaque(rank < 2 ? sb + OFF_Q + wg * 10240 + (warp & 3) * 256 + (lane & 15) * 16 + (lane >> 4) * 1024
                                       : sb + OFF_VM + warp * 256 + lane * 4);
        int dstep = rank < 2 ? 5120 : 2048;
        uint32_t& sfd = wsa;
        {
            const int t = tid & 127;
            const bf16* src = (rank == 2 ? Wv + wg * 64 : (wg ? Wk : Wq) + rank * 64) + h * E_ + (size_t)(t >> 3) * 4096 + (t & 7) * 8;
            const uint32_t stg = sb + (wg ? OFF_VX : OFF_X + 40960);
            const uint32_t sdst = stg + (t >> 3) * 128 + (((t & 7) ^ ((t >> 3) & 7)) << 4);
            const uint32_t ra = stg + ((lane >> 4) * 8 + (lane & 7)) * 128 + (((2 * (warp & 3) + ((lane >> 3) & 1)) ^ (lane & 7)) << 4);
            auto issue = [&](int rd) {
#pragma unroll
                for (int i = 0; i < 10; i++) cp16(sdst + (rd & 1) * 20480 + i * 2048, src + (size_t)(rd * 160 + i * 16) * 4096);
                cp_commit();
            };
            issue(0); issue(1);
#pragma unroll
            for (int rd = 0; rd < 4; rd++) {
                if (rd < 3) cp_wait<1>(); else cp_wait<0>();
                bar_sync(NB_LD + wg, 128);
#pragma unroll
                for (int i = 0; i < 10; i++) {
                    const int ks = rd * 10 + i;
                    if (ks < NS) {
                        uint32_t f[4];
                        ldsm4t(f, ra + i * 2048);
                        stsm4(wsa + ks * 4096, f[0], f[1], f[2], f[3]);
                    } else ldsm4t(a[ks - NS], ra + (rd & 1) * 20480 + i * 2048);
                }
                if (rd < 2) { bar_sync(NB_LD + wg, 128); issue(rd + 2); }
            }
            fence_async();
            bar_sync(NB_PRO, 288);
        }
        uint32_t xlo = (uint32_t)mkdesc(sb + OFF_X, 0, 0);
        const uint32_t xtog = xlo ^ (uint32_t)mkdesc(sb + OFF_X + 40960, 0, 0);
        uint32_t p8 = 0;
        bar_sync(NB_LD, 288);
        for (int s = -1;; s++) {
            if (wg) {
                float acc[16];
                auto xproj = [&](auto K1, auto K0) {
                    const u64 desc = (u64)xlo | (64ull << 32) | SW128, da = mkdesc(sb + OFF_WS + 2048, 128, 256);
                    wg_fence();
#pragma unroll
                    for (int ks = K1.value - 1; ks >= K0.value; ks--) {
                        const u64 db = desc + (ks >> 2) * 256 + (ks & 3) * 2;
                        if (ks == 39) wgmma_n32_rs<0>(acc, a[ks - NS], db);
                        else if (NOX) {}
                        else if (ks < NS) wgmma_n32_ss<1>(acc, da + ks * 256, db);
                        else wgmma_n32_rs<1>(acc, a[ks - NS], db);
                    }
                    wg_commit();
                    wg_wait<0>();
                };
                bar_sync_if<NB_X, 320>(s >= 0 && rank < 2);
                bar_sync_if<NB_W1, 352>(s >= 0 && rank == 2);
                if (s == NSEG - 1) break;
                xproj(IC<40>{}, IC<40 - NW1>{});
                if (warp == 4 && s >= 0) PROFT(15);
                bar_sync_if<NB_W2, 256>(s >= 0 && rank < 2);
                if (NW1B > 0) xproj(IC<40 - NW1>{}, IC<40 - NW1 - NW1B>{});
                bar_sync_if<NB_WIN, 256>(s >= 0 && rank == 2);
                xproj(IC<40 - NW1 - NW1B>{}, IC<0>{});
                uint32_t pk[8];
#pragma unroll
                for (int i = 0; i < 8; i++) pk[i] = pack2(acc[2 * i], acc[2 * i + 1]);
                if (rank < 2) {
                    stsm4t(dst + 1024, pk[0], pk[1], pk[2], pk[3]);
                    stsm4t(dst + 3072, pk[4], pk[5], pk[6], pk[7]);
                    bar_arrive(NB_KX, 256);
                } else {
                    const uint32_t la = wsa + (wsa & 256) + (OFF_VX - OFF_WS) + warp * 512 + p8 * 1024;
                    stsm4(la, pk[0], pk[1], pk[2], pk[3]);
                    stsm4(la + 256, pk[4], pk[5], pk[6], pk[7]);
                    fence_async();
                    mbar_arrive_elect(bar + 8 * B_KX + p8);
                }
                xlo ^= xtog;
                if (warp == 4 && s >= 0) PROFT(3);
            } else if (s >= 0) {
                if (warp == 1) {
                    bar_sync_if<NB_X, 320>(rank < 2);
                    if (s + 1 < NSEG && elect()) {
                        const uint32_t xt = bar + 8 * B_XT + (p8 ^ 8);
                        const unsigned char* pn = g_p + (size_t)((s + 1) * H_ + h) * 12288;
                        mbar_expect(xt, (s + 2 < NSEG ? 40960 : 0) + (rank < 2 ? 4096 : 0));
                        if (s + 2 < NSEG) bulk_g2s(sb + OFF_X + (p8 ^ 8) * 5120, g_xn + (s + 2) * 40960, 40960, xt);
                        const int blk = wk::pb_first(s + 1);
                        if (blk >= 0) flag_wait<false>(g_sync + layer * SYNC_LAYER + wk::SY_P + blk * H_ + h, 3);
                        if (rank < 2) bulk_g2s(sb + OFF_Q + p8 * 640 + 1024, pn + rank * 4096, 4096, xt);
                        if (rank < 2 || s + 2 < NSEG) bulk_g2s(sb + OFF_VX + p8 * 1024, pn + 8192, 4096, bar + 8 * B_VX + p8);
                    }
                    __syncwarp();
                } else if (warp == 2 && rank < 2) {
                    bar_sync(NB_X, 320);
#pragma unroll 1
                    for (int n = s - 1; n < (s + 1 < NSEG ? s : NSEG); n++) {
                        bar_sync_if<NB_W2, 160>(n == s);
                        if (n >= 0 && elect()) {
                            unsigned char* op = g_o + (size_t)(n * H_ + h) * 8192 + rank * 2048;
                            bulk_s2g(op, sb + OFF_OST + (n & 1) * 4096, 2048);
                            bulk_s2g(op + 4096, sb + OFF_OST + (n & 1) * 4096 + 2048, 2048);
                            bulk_commit();
                            bulk_wait<0>();
                            st_remote(mapa(sb + OFF_MX + 32 + 4 * rank, 2), n + 1);
                        }
                        __syncwarp();
                    }
                }
                if (s == NSEG - 1) break;
                if (warp == 0) {
                    uint32_t* hp = g_sync + layer * SYNC_LAYER + 1024 + s * 32;
                    while (!mbar_try(bar + 8 * B_X1 + (p8 ^ 8), (s >> 1) & 1)) {}
                    uint32_t t = gtime32(), c;
                    if (rank == 0 && elect()) {
                        asm volatile("red.relaxed.gpu.global.max.u32 [%0],%1;" ::"l"(hp + 1), "r"(t) : "memory");
                        asm volatile("red.relaxed.gpu.global.add.u32 [%0],1;" ::"l"(hp) : "memory");
                    }
                    __syncwarp();
                    while (gtime32() - t < 150u) {}
                    do asm volatile("ld.relaxed.gpu.global.v2.u32 {%0,%1},[%2];" : "=r"(c), "=r"(t) : "l"(hp) : "memory"); while (c != H_);
                    while (gtime32() - t < (uint32_t)delay) {}
                    bar_arrive(NB_GO, 160);
                    t = clk();
                    while (clk() - t < (uint32_t)delay2) {}
                    bar_arrive(NB_PRO, 160);
                    while (clk() - t < 2 * (uint32_t)delay2) {}
                    bar_arrive(NB_LD, 160);
                    while (clk() - t < 3 * (uint32_t)delay2) {}
                    bar_arrive(NB_LD + 1, 160);
                }
            }
            float d0[4] = {0.f, 0.f, 0.f, 0.f}, d1[4] = {0.f, 0.f, 0.f, 0.f};
            uint32_t t[NS][4], b[20][4];
#pragma unroll
            for (int ks = 0; ks < NS; ks++) ldsm4(t[ks], wsa + ks * 4096);
            bar_sync(NB_MEM, 384);
            lds128(b[0], l16 + OFF_MEMB); lds128(b[1], l16 + OFF_MEMB + 512); lds128(b[2], l16 + OFF_MEMB + 1024);
            const uint32_t xb0 = mapa(bar + 8 * B_X1 + p8, 0), xb1 = mapa(bar + 8 * B_X1 + p8, 1);
            SFENCE();
            float is;
#pragma unroll
            for (int kp = 0; kp < 20; kp++) {
#pragma unroll
                for (int j = 0; j < 2; j++) {
                    const int ks = 2 * kp + j;
                    const uint32_t* f = ks < NS ? t[ks] : a[ks - NS];
                    mma16(j ? d1 : d0, f[0], f[1], f[2], f[3], b[kp][2 * j], b[kp][2 * j + 1]);
                }
                if (kp == 0 && warp == 4) PROFT(16);
                if (kp < 16 && (kp & 3) == 1) bar_sync(NB_MEM + 1 + (kp >> 2), 384);
                if (kp + 3 < 20) lds128(b[kp + 3], l16 + OFF_MEMB + (kp + 3) * 512);
                if (kp == 17) is = lds32f(sb + OFF_MX + 16);
                if (kp < 18) SFENCE();
            }
            const uint32_t p0 = pack2((d0[0] + d1[0]) * is, (d0[1] + d1[1]) * is), p1 = pack2((d0[2] + d1[2]) * is, (d0[3] + d1[3]) * is);
            stsm2t_if(dst, p0, p1, rank < 2);
            bar_arrive_if<NB_QK, 384>(rank < 2);
            if (rank == 2) {
                st_async1(mapa(dst, 0), p0, xb0); st_async1(mapa(dst, 1), p0, xb1);
                st_async1(mapa(dst + 128, 0), p1, xb0); st_async1(mapa(dst + 128, 1), p1, xb1);
                sts32(dst, p0); sts32(dst + 128, p1);
                bar_arrive(NB_QK, 384);
            }
            if (warp == 4) PROFT(17);
            dst += dstep; dstep = -dstep; p8 ^= 8;
        }
    } else if (warp < 12) {
        asm volatile("setmaxnreg.dec.sync.aligned.u32 96;");
        const uint32_t rank = cta_rank();
        const int w = warp - 8;
        uint32_t amax = 0;
#pragma unroll
        for (int it = 0; it < 5; it++) {
            const int kp = it * 4 + w;
            const bf16* p = mem0 + g * D_ + kp * 32 + 2 * q;
            uint32_t b0 = ldg32(p), b1 = ldg32(p + 8), b2 = ldg32(p + 16), b3 = ldg32(p + 24);
            sts128(sb + OFF_MEMB + kp * 512 + lane * 16, b0, b1, b2, b3);
            amax = absmax2(amax, absmax2(absmax2(b0, b1), absmax2(b2, b3)));
        }
        if (tid == 256) { sts32(sb + OFF_MX + 16, 0x3f800000u); sts128(sb + OFF_MX + 48, 0x3f803f80u, 0x3f803f80u, 0x3f803f80u, 0x3f803f80u); }
        bar_arrive(NB_MEM, 384); bar_arrive(NB_MEM + 1, 384); bar_arrive(NB_MEM + 2, 384); bar_arrive(NB_MEM + 3, 384); bar_arrive(NB_MEM + 4, 384);
        {
            const int t = tid & 127, nr = rank == 2 ? 4 : 3;
            for (int r = 0; r < nr; r++) {
                const bf16* src = Wo + (size_t)(h * E_) * D_ + (r < 3 ? 192 * r + 64 * rank : 576);
#pragma unroll
                for (int i = 0; i < 8; i++) {
                    const int e = i * 16 + (t >> 3);
                    cp16(sb + OFF_WO + r * 16384 + e * 128 + (((t & 7) ^ (e & 6)) << 4), src + e * D_ + (t & 7) * 8);
                }
            }
            cp_commit();
            pdl_wait();
            pdl_launch();
            cp_wait<0>();
            bar_sync(NB_ATT, 128);
            for (int r = 0; r < nr; r++) {
                uint32_t u[8][4];
                const uint32_t p = sb + OFF_WO + r * 16384 + 2 * q * 128 + (((2 * w + (g & 1)) ^ (2 * q)) << 4) + (g >> 1) * 4;
#pragma unroll
                for (int ks = 0; ks < 8; ks++)
#pragma unroll
                    for (int j = 0; j < 4; j++) u[ks][j] = lds32(p + (16 * ks + (j & 1) * 8 + (j >> 1)) * 128);
                bar_sync(NB_ATT, 128);
#pragma unroll
                for (int ks = 0; ks < 8; ks++)
                    sts128(sb + OFF_WO + (r * 4 + w) * 4096 + ks * 512 + lane * 16, prmt(u[ks][0], u[ks][2], 0x5410), prmt(u[ks][0], u[ks][2], 0x7632),
                           prmt(u[ks][1], u[ks][3], 0x5410), prmt(u[ks][1], u[ks][3], 0x7632));
            }
        }
        float cw;
        {
            const float4 a = ((const float4*)g_nrm)[lane], c = ((const float4*)g_nrm)[32 + lane];
            float sm = sqrtf((a.x + a.y) + (a.z + a.w)) * sqrtf((c.x + c.y) + (c.z + c.w)), mxv = sm;
#pragma unroll
            for (int o = 16; o; o >>= 1) { sm += __shfl_xor_sync(~0u, sm, o); mxv = fmaxf(mxv, __shfl_xor_sync(~0u, mxv, o)); }
            cw = 26.5f * fmaxf(sm, 8.f * mxv);
        }
        if (w == 0) {
            mbar_expect_elect(bar + 8 * B_X1, rank < 2 ? 3328 : 1280);
            mbar_expect_elect(bar + 8 * B_VX, rank < 2 ? 8192 : 4096);
        }
        {
            const int kind = rank;
            const uint32_t l16 = opaque(sb + lane * 16), lw = opaque(sb + lane * 16 + w * 512);
            const uint32_t pa = opaque(sb + OFF_PS + rank * 512 + lane * 4 + w * 128);
            uint32_t lq = opaque(sb + OFF_Q + (lane & 7) * 16 + ((lane >> 3) & 1) * 256 + (lane >> 4) * 128);
            const uint32_t lv = opaque(sb + OFF_VX + w * 2048 + (lane & 7) * 16 + ((lane >> 3) & 1) * 512 + (lane >> 4) * 128);
            const uint32_t lo = opaque(sb + OFF_WO + w * 4096 + lane * 16);
            uint32_t& sfd = lq;
            const char* rp = (const char*)(g_acc + layer * ACC_LAYER) + (4 * rank + w) * 4096 + opaque((q >> 1) * 1024 + ((q & 1) * 8 + g) * 8);
            const char* lp = (const char*)(g_acc + layer * ACC_LAYER) + opaque(w * 8192 + (2 * (g & 1) + (g >> 2)) * 1024 + (((g >> 1) & 1) * 8 + 2 * q) * 8);
            float isig = 1.f;
            uint32_t kf[8];
            bar_sync_if<NB_KX, 256>(kind < 2);
            ldsm4(kf, l16 + OFF_K + (1 + w) * 1024); ldsm4(kf + 4, l16 + OFF_K + (1 + w) * 1024 + 512);
            for (int s = 0; s < NSEG - 1; s++) {
                const uint32_t pb = s & 1, ph = (s >> 1) & 1, x1 = bar + 8 * (B_X1 + pb);
                sts32(sb + OFF_MX + w * 4, __reduce_max_sync(~0u, max(amax & 0x7fff0000u, (amax << 16) & 0x7fff0000u)));
                const bool vok = mbar_try(bar + 8 * (B_VX + pb), ph, 1);
                const uint32_t va = lv + pb * 8192, vma = lw + OFF_VM + pb * 2048;
                uint32_t wf[8][4], vf[2][2][4], vm[4], one[4];
                auto scores = [&](auto MM) {
                    constexpr int mm = MM.value;
                    uint32_t qf[8], mf[8];
                    const uint32_t qa = lq + pb * 5120, ka = l16 + OFF_K + pb * 5120;
                    const uint32_t pa0 = mapa(pa, rank ^ 1), pa1 = mapa(pa, 2), pa2 = mapa(pa, rank);
                    const uint32_t xb0 = mapa(x1, rank ^ 1), xb1 = mapa(x1, 2), xb2 = mapa(x1, rank);
                    const uint32_t pm = 640 - rank * 384;
                    SFENCE();
                    if (w == 0) PROFT(2);
                    bar_sync(NB_QK, 384);
                    ldsm4(qf, qa); ldsm4(qf + 4, qa + 512);
                    if (mm) { ldsm4(mf, ka); ldsm4(mf + 4, ka + 512); }
                    SFENCE();
                    float c[8][4];
#pragma unroll
                    for (int i = 0; i < (mm ? 8 : 4); i++) {
                        const uint32_t* f = (i < 4 ? kf : mf) + 2 * (i & 3);
                        c[i][0] = c[i][1] = c[i][2] = c[i][3] = 0.f;
                        mma16(c[i], qf[i & 2 ? 4 : 0], qf[i & 2 ? 5 : 1], qf[i & 2 ? 6 : 2], qf[i & 2 ? 7 : 3], f[0], f[1]);
                    }
                    SFENCE();
                    const uint32_t y = pack2((c[0][0] + c[1][2]) + (c[2][0] + c[3][2]), (c[0][1] + c[1][3]) + (c[2][1] + c[3][3]));
                    st_async1(pa0, y, xb0); st_async1(pa1, y, xb1);
                    if (mm) {
                        const uint32_t z = pack2((c[4][0] + c[5][2]) + (c[6][0] + c[7][2]), (c[4][1] + c[5][3]) + (c[6][1] + c[7][3]));
                        st_async1(pa0 + pm, z, xb0); st_async1(pa1 + pm, z, xb1); st_async1(pa2 + pm, z, xb2);
                    }
                    st_async1(pa2, y, xb2);
                    if (w == 0) PROFT(5);
                };
                if (kind == 2) bar_sync(NB_QK, 384);
                else if (w == 3) scores(IC<1>{});
                else scores(IC<0>{});
                if (!vok) mbar_wait(bar + 8 * (B_VX + pb), ph);
#pragma unroll
                for (int t = 0; t < 2; t++)
#pragma unroll
                    for (int j = 0; j < 2; j++) ldsm4(vf[t][j], va + t * 1024 + j * 256);
                float m4[4];
                lds128f(m4, sb + OFF_MX);
                bar_arrive_if<NB_W1, 256>(kind < 2);
                bar_arrive_if<NB_W1, 352>(kind == 2);
                lds128(one, sb + OFF_MX + 48);
                if (w == 0) PROFT(4);
                mbar_wait(x1, ph);
                if (w == 0) PROFT(6);
                float sc[10];
                {
                    uint32_t u[4], v[4], m[2];
                    ldsm4(u, l16 + OFF_PS); ldsm4(v, l16 + OFF_PS + 512); ldsm2(m, l16 + OFF_PS + 1024);
                    ldsm4(vm, vma);
                    SFENCE();
                    m4[0] = fmaxf(fmaxf(m4[0], m4[1]), fmaxf(m4[2], m4[3])) * isig;
                    SFENCE();
#pragma unroll
                    for (int i = 0; i < 4; i++) { sc[2 * i] = bf_lo(u[i]) + bf_lo(v[i]); sc[2 * i + 1] = bf_hi(u[i]) + bf_hi(v[i]); }
                    sc[8] = bf_lo(m[0]) + bf_lo(m[1]); sc[9] = bf_hi(m[0]) + bf_hi(m[1]);
                }
                float mx = fmaxf(fmaxf(fmaxf(fmaxf(sc[0], sc[1]), fmaxf(sc[2], sc[3])), fmaxf(fmaxf(sc[4], sc[5]), fmaxf(sc[6], sc[7]))), fmaxf(sc[8], sc[9]));
                auto fetch = [&](int i) { lds128(wf[i], lo + i * 512); };
                {
                    float m1 = __shfl_xor_sync(~0u, mx, 1), m2 = __shfl_xor_sync(~0u, mx, 2), m3 = __shfl_xor_sync(~0u, mx, 3);
                    SFENCE();
#pragma unroll
                    for (int i = 0; i < 4; i++) fetch(i);
                    SFENCE();
                    mx = fmaxf(fmaxf(mx, m1), fmaxf(m2, m3)) * SM_SCALE;
                }
#pragma unroll
                for (int i = 0; i < 10; i++) sc[i] = fmaf(sc[i], SM_SCALE, -mx);
                float o0[4] = {0.f, 0.f, 0.f, 0.f}, o1[4] = {0.f, 0.f, 0.f, 0.f}, rs[4] = {0.f, 0.f, 0.f, 0.f};
                sc[8] = ex2(sc[8]); sc[9] = ex2(sc[9]);
                SFENCE();
                sc[0] = ex2(sc[0]); fetch(4); sc[1] = ex2(sc[1]); fetch(5); sc[2] = ex2(sc[2]); fetch(6);
                SFENCE();
                {
                    const uint32_t p = pack2(sc[8], sc[9]);
                    sc[3] = ex2(sc[3]); fetch(7);
                    mma8(o0, vm[0], vm[1], p);
                    mma8(o1, vm[2], vm[3], p);
                    sc[4] = ex2(sc[4]);
                    mma8(rs, one[0], one[1], p);
                    sc[5] = ex2(sc[5]);
                }
                SFENCE();
                {
                    const uint32_t p0 = pack2(sc[0], sc[1]), p1 = pack2(sc[2], sc[3]);
                    sc[6] = ex2(sc[6]);
                    mma16(o0, vf[0][0][0], vf[0][0][1], vf[0][0][2], vf[0][0][3], p0, p1);
                    SFENCE();
                    sc[7] = ex2(sc[7]);
                    mma16(o1, vf[1][0][0], vf[1][0][1], vf[1][0][2], vf[1][0][3], p0, p1);
                    SFENCE();
                    mma16(rs, one[0], one[1], one[2], one[3], p0, p1);
                    SFENCE();
                }
                {
                    const uint32_t p0 = pack2(sc[4], sc[5]), p1 = pack2(sc[6], sc[7]);
                    mma16(o0, vf[0][1][0], vf[0][1][1], vf[0][1][2], vf[0][1][3], p0, p1);
                    mma16(o1, vf[1][1][0], vf[1][1][1], vf[1][1][2], vf[1][1][3], p0, p1);
                    SFENCE();
                    mma16(rs, one[0], one[1], one[2], one[3], p0, p1);
                }
                const uint32_t e = max((__float_as_uint(cw * fmaxf(m4[0], 1.f)) >> 23) & 255u, 31u);
                SFENCE();
                stsm4t(lw + OFF_OB, pack2(o0[0], o0[1]), pack2(o0[2], o0[3]), pack2(o1[0], o1[1]), pack2(o1[2], o1[3]));
                bar_sync(NB_ATT, 128);
                uint32_t ob[16];
#pragma unroll
                for (int j = 0; j < 4; j++) ldsm4(ob + 4 * j, l16 + OFF_OB + j * 512);
                SFENCE();
                const float sig = __uint_as_float((278u - e) << 23);
                isig = __uint_as_float((e - 30u) << 23);
                const float sg0 = rcp(rs[0]) * sig, sg1 = rcp(rs[1]) * sig;
                SFENCE();
                auto tile = [&](uint32_t next, const char* p, auto LAST) {
                    float c[4][4];
#pragma unroll
                    for (int i = 0; i < 4; i++) c[i][0] = c[i][1] = c[i][2] = c[i][3] = 0.f;
#pragma unroll
                    for (int ks = 0; ks < 8; ks++) {
                        mma16(c[ks & 3], wf[ks][0], wf[ks][1], wf[ks][2], wf[ks][3], ob[2 * ks], ob[2 * ks + 1]);
                        if ((ks & 3) == 3 && !LAST.value) {
                            SFENCE();
#pragma unroll
                            for (int i = ks - 3; i <= ks; i++) lds128(wf[i], next + i * 512);
                        }
                    }
                    SFENCE();
                    if (LAST.value) bar_arrive(NB_WIN, 256);
                    uint32_t v[4];
#pragma unroll
                    for (int i = 0; i < 4; i++)
                        v[i] = (__float_as_uint(fmaf((c[0][i] + c[1][i]) + (c[2][i] + c[3][i]), i & 1 ? sg1 : sg0, 12582912.f)) << 6) + (i < 2);
                    red_add64((u64*)p, v[0], v[2]);
                    red_add64((u64*)(p + 2048), v[1], v[3]);
                };
                tile(lo + 16384, rp, IC<0>{});
                if (w == 0) PROFT(7);
                if (w == 0) GPROF(4, 0);
                tile(lo + 32768, rp + 49152, IC<0>{});
                if (kind == 2) tile(lo + 49152, rp + 98304, IC<0>{});
                tile(0, rp + (kind == 2 ? 28 * 4096 : 98304), IC<1>{});
                if (w == 0) PROFT(8);
                sts32(sb + OFF_MX + 16, __float_as_uint(isig));
                if (w == 0) {
                    if (kind < 2 || s < NSEG - 2) mbar_expect_elect(bar + 8 * (B_VX + (pb ^ 1)), kind < 2 ? 8192 : 4096);
                    mbar_expect_elect(bar + 8 * (B_X1 + (pb ^ 1)), (kind < 2 ? 2048 : 0) + (s < NSEG - 2 ? 1280 : 0));
                }
                u64 y[20];
                const uint32_t kn = lw + OFF_K + 1024 + w * 512 + (pb ^ 1) * 5120;
#pragma unroll
                for (int i = 0; i < 10; i++) {
                    if (i == 0 || i == 2 || i == 4 || i == 7) bar_sync(i == 0 ? NB_GO : i == 2 ? NB_PRO : i == 4 ? NB_LD : NB_LD + 1, 160);
                    ld_acc0(y[2 * i], y[2 * i + 1], lp + (i >> 1) * 32768 + (i & 1) * 4096);
                }
                if (w == 0) PROFT(9);
                uint32_t nretry = 0, b[20];
                bool done[5] = {false, false, false, false, false};
                auto publish = [&](auto FIRST) {
                    uint32_t ok = 32u, late = 32u;
                    static_for<5>([&](auto IT) {
                        constexpr int it = IT.value;
                        if (it == 2) late = and3((uint32_t)y[8], (uint32_t)y[10], (uint32_t)y[12]);
                        else if (it == 3) late &= and3((uint32_t)y[14], (uint32_t)y[16], (uint32_t)y[18]);
                        else ok = and3(ok, (uint32_t)y[4 * it], it == 4 ? late : (uint32_t)y[4 * it + 2]);
                        if (FIRST.value && it < 4) SFENCE();
                        if (it == 2 || it == 3) ok = and3(ok, (uint32_t)y[4 * it], (uint32_t)y[4 * it + 2]);
                        ok = and3(ok, (uint32_t)y[4 * it + 1], (uint32_t)y[4 * it + 3]);
                        const bool all = __all_sync(~0u, ok);
#pragma unroll
                        for (int j = 0; j < 4; j++) {
                            const u64 z = y[4 * it + j];
                            b[4 * it + j] = pack2((float)(int)(uint32_t)z, (float)(int)(uint32_t)(z >> 32));
                        }
                        sts128(lw + OFF_MEMB + it * 2048, b[4 * it], b[4 * it + 1], b[4 * it + 2], b[4 * it + 3]);
                        bar_arrive_if<NB_MEM + it, 384>(all && (FIRST.value || !done[it]));
                        done[it] = all;
                        if (FIRST.value) SFENCE();
                        if (FIRST.value && it == 0) {
                            if (w == 0) PROFT(10);
                            bar_sync_if<NB_KX, 256>(kind < 2);
                            ldsm4(kf, kn); ldsm4(kf + 4, kn + 512);
                            SFENCE();
                        }
                    });
                };
                publish(IC<1>{});
                while (!done[4]) {
                    if (++nretry > SPIN_LIMIT) die();
#pragma unroll
                    for (int i = 0; i < 10; i++) ld_acc(y[2 * i], y[2 * i + 1], lp + (i >> 1) * 32768 + (i & 1) * 4096);
                    publish(IC<0>{});
                }
                if (w == 0) PROFT(11);
                GPROF(w, nretry);
                amax = b[0];
#pragma unroll
                for (int i = 1; i < 19; i += 2) amax = absmax2(amax, absmax2(b[i], b[i + 1]));
                amax = absmax2(amax, b[19]);
                const int adv = (s & 7) == 7 ? 163840 - 896 : 128;
                rp += adv; lp += adv;
            }
        }
        bar_sync(NB_QK, 384);
        if (rank < 2) bar_arrive(NB_W1, 256); else bar_arrive(NB_W1, 352);
    } else {
        asm volatile("setmaxnreg.dec.sync.aligned.u32 %0;" ::"n"(48));
        const uint32_t rank = cta_rank();
        const int w = warp - 12;
        pdl_wait();
        pdl_launch();
        uint32_t* sy = g_sync + layer * SYNC_LAYER;
        if (w == 1) {
            if (lane == 0) {
                mbar_expect(bar + 8 * B_XT, 40960);
                bulk_g2s(sb + OFF_X, g_xn, 40960, bar + 8 * B_XT);
            }
            __syncwarp();
            bar_sync(NB_PRO, 288);
            if (rank == 2) mbar_wait(bar + 8 * B_ST, 0);
            else if (lane == 0) mbar_arrive_remote(mapa(bar + 8 * B_ST, 2));
            mbar_wait(bar + 8 * B_XT, 0);
            __syncwarp();
            bar_arrive(NB_LD, 288);
            if (lane == 0) {
                mbar_expect(bar + 8 * (B_XT + 1), rank < 2 ? 45056 : 40960);
                bulk_g2s(sb + OFF_X + 40960, g_xn + 40960, 40960, bar + 8 * (B_XT + 1));
                flag_wait(sy + wk::SY_P + h, 3);
                if (rank < 2) bulk_g2s(sb + OFF_Q + 1024, g_p + h * 12288 + rank * 4096, 4096, bar + 8 * (B_XT + 1));
                bulk_g2s(sb + OFF_VX, g_p + h * 12288 + 8192, 4096, bar + 8 * B_VX);
            }
            __syncwarp();
        }
        if (rank == 2 && w == 3) {
            if (lane == 0) {
                for (uint32_t s = 0, n = 0; s < NSEG; s++) {
                    uint32_t c[2];
                    for (;;) {
                        asm volatile("ld.acquire.cluster.shared::cta.v2.u32 {%0,%1},[%2];" : "=r"(c[0]), "=r"(c[1]) : "r"(sb + OFF_MX + 32) : "memory");
                        if (min(c[0], c[1]) > s) break;
                        if (++n > (SPIN_LIMIT << 3)) die();
                        __nanosleep(s < NSEG - 2 ? 400 : 50);
                    }
                    if (h == 0) TLI(940 + s, 0, gtime());
                    flag_add(sy + wk::SY_O + s);
                }
            }
        } else if (rank == 2) {
            const char* pf = (const char*)(g_acc + layer * ACC_LAYER) + (5 * h + lane % 5) * 1024;
            if (w == 2 && lane < 20) prefetch_l2(pf + lane / 5 * 128);
            if (w == 2 && lane < 4 && h == 0) prefetch_l2(sy + 1024 + lane * 32);
            for (int s = 0; s < NSEG; s++) {
                const int pb = s & 1, ph = (s >> 1) & 1;
                if (w == 0) {
                    mbar_wait(bar + 8 * (B_KX + pb), ph);
                    if (lane < 2) bulk_s2s(mapa(sb + OFF_VX + pb * 8192 + 4096, lane), sb + OFF_VX + pb * 8192 + 4096, 4096, mapa(bar + 8 * (B_VX + pb), lane));
                }
                if (w == 1) mbar_wait(bar + 8 * (B_XT + (pb ^ 1)), ((s + 1) >> 1) & 1);
                if (w == 2 && s >= 1) mbar_wait(bar + 8 * (B_XD + (pb ^ 1)), ((s - 1) >> 1) & 1);
                __syncwarp();
                bar_sync(NB_W1, 352);
                if (w == 2 && lane < 5 && s + 4 < NSEG) prefetch_l2(pf + ((s + 4) >> 3) * 163840 + ((s + 4) & 7) * 128);
                if (w == 2 && lane == 5 && h == 0 && s + 4 < NSEG) prefetch_l2(sy + 1024 + (s + 4) * 32);
            }
        } else {
            if (w < 2) sts32(sb + OFF_PT + w * 768 + 640 + lane * 4, 0u);
            const uint32_t px = opaque(sb + OFF_PX + (w & 1) * 1280 + lane * 8);
            const uint32_t pt = opaque(sb + OFF_PT + (w & 1) * 768 + lane * 4);
            const uint32_t os = opaque(sb + OFF_OST + (lane >> 4) * 1024 + w * 256 + (lane & 15) * 16);
            const int lim = opaque(8 * w + g + 8 - 2 * q);
            for (int s = 0; s < NSEG; s++) {
                const uint32_t pb = s & 1, ph = (s >> 1) & 1;
                if ((w >> 1) != rank) { if (s >= 1) mbar_wait(bar + 8 * B_PXE, pb ^ 1); }
                else if (w & 1) mbar_wait(bar + 8 * (B_XT + (pb ^ 1)), ((s + 1) >> 1) & 1);
                else mbar_expect_elect(bar + 8 * B_PXF, rank ? 2560 : 1536);
                const u64 dq = mkdesc(sb + OFF_Q + pb * 5120 + 1024, 128, 512), dk = mkdesc(sb + OFF_K + pb * 5120, 128, 1024);
                bar_sync(NB_W1, 256);
                fence_async();
                bar_arrive(NB_X, 320);
                float c[20];
                wg_fence();
                wgmma_n40_ss<0>(c, dq, dk);
#pragma unroll
                for (int ks = 1; ks < 4; ks++) wgmma_n40_ss<1>(c, dq + ks * 16, dk + ks * 16);
                wg_commit();
                wg_wait<0>();
                if ((w >> 1) != rank) {
                    const uint32_t pa = mapa(px, rank ^ 1), pf = mapa(bar + 8 * B_PXF, rank ^ 1);
#pragma unroll
                    for (int nt = 0; nt < 5; nt++)
                        if (nt < 3 || rank == 0) st_async2(pa + nt * 256, __float_as_uint(c[4 * nt]), __float_as_uint(c[4 * nt + 1]), pf);
                } else {
                    mbar_wait(bar + 8 * B_PXF, pb);
                    float u[10];
#pragma unroll
                    for (int nt = 0; nt < 5; nt++) lds64f(u[2 * nt], u[2 * nt + 1], px + nt * 256);
#pragma unroll
                    for (int i = 0; i < 10; i++) u[i] = 8 * (i >> 1) + (i & 1) <= lim ? u[i] + c[4 * (i >> 1) + (i & 1)] : -INFINITY;
                    float mx = fmaxf(fmaxf(fmaxf(fmaxf(u[0], u[1]), fmaxf(u[2], u[3])), fmaxf(fmaxf(u[4], u[5]), fmaxf(u[6], u[7]))), fmaxf(u[8], u[9]));
                    const float m1 = __shfl_xor_sync(~0u, mx, 1), m2 = __shfl_xor_sync(~0u, mx, 2), m3 = __shfl_xor_sync(~0u, mx, 3);
                    mx = fmaxf(fmaxf(mx, m1), fmaxf(m2, m3)) * SM_SCALE;
#pragma unroll
                    for (int i = 0; i < 10; i++) u[i] = ex2(fmaf(u[i], SM_SCALE, -mx));
                    float sum = (((u[0] + u[1]) + (u[2] + u[3])) + ((u[4] + u[5]) + (u[6] + u[7]))) + (u[8] + u[9]);
                    const float s1 = __shfl_xor_sync(~0u, sum, 1), s2 = __shfl_xor_sync(~0u, sum, 2), s3 = __shfl_xor_sync(~0u, sum, 3);
                    sum = rcp((sum + s1) + (s2 + s3));
#pragma unroll
                    for (int nt = 0; nt < 5; nt++) sts32(pt + (nt ? nt - 1 : 4) * 128, pack2(u[2 * nt] * sum, u[2 * nt + 1] * sum));
                    if (w == 0) PROFT(14);
                }
                float acc[2][8];
                const u64 dv = mkdesc(sb + OFF_VX + pb * 8192, 128, 512), dp = mkdesc(sb + OFF_PT, 128, 768);
                const u64 dm = mkdesc(sb + OFF_VM + pb * 2048, 0, 128);
                if (s < NSEG - 1) {
                    bar_sync(NB_WIN, 256);
                    fence_async();
                    bar_arrive(NB_W2, 256);
                } else {
                    mbar_wait(bar + 8 * (B_X1 + pb), ph);
                    mbar_wait(bar + 8 * (B_VX + pb), ph);
                    bar_sync(NB_WIN, 128);
                    fence_async();
                }
                wg_fence();
#pragma unroll
                for (int m = 0; m < 2; m++) {
                    wgmma_n16_ss<0>(acc[m], dv + m * 256, dp);
                    wgmma_n16_ss<1>(acc[m], dv + m * 256 + 16, dp + 16);
                    wgmma_n16_ss<1>(acc[m], dm + m * 64, dp + 32);
                }
                wg_commit();
                wg_wait<0>();
                if (w == 0) PROFT(12);
#pragma unroll
                for (int m = 0; m < 2; m++)
                    stsm4t(os + pb * 4096 + m * 2048, pack2(acc[m][0], acc[m][1]), pack2(acc[m][2], acc[m][3]), pack2(acc[m][4], acc[m][5]), pack2(acc[m][6], acc[m][7]));
                if (elect()) {
                    mbar_arrive_remote(mapa(bar + 8 * (B_XD + pb), 2));
                    if ((w >> 1) == rank) mbar_arrive_remote(mapa(bar + 8 * B_PXE, rank ^ 1));
                }
                __syncwarp();
            }
            fence_async();
            bar_sync(NB_W2, 160);
        }
    }
    __syncwarp();
    if (lane < 3) mbar_arrive_remote(mapa(bar + 8 * B_FIN, lane));
    mbar_wait(bar + 8 * B_FIN, 0);
    TLE(2 + 5 * layer);
}

int g_delay = 1000650, g_layers = 2;

void make_map(CUtensorMap* m, CUtensorMapDataType dt, const void* p, const cuuint64_t* dim, const cuuint64_t* str, const cuuint32_t* box, CUtensorMapSwizzle sw) {
    typedef CUresult (*Fn)(CUtensorMap*, CUtensorMapDataType, cuuint32_t, void*, const cuuint64_t*, const cuuint64_t*, const cuuint32_t*,
                           const cuuint32_t*, CUtensorMapInterleave, CUtensorMapSwizzle, CUtensorMapL2promotion, CUtensorMapFloatOOBfill);
    static Fn fn = nullptr;
    if (!fn) {
        cudaDriverEntryPointQueryResult qr;
        cudaGetDriverEntryPoint("cuTensorMapEncodeTiled", (void**)&fn, cudaEnableDefault, &qr);
    }
    const cuuint32_t es[3] = {1, 1, 1};
    fn(m, dt, 3, (void*)p, dim, str, box, es, CU_TENSOR_MAP_INTERLEAVE_NONE, sw, CU_TENSOR_MAP_L2_PROMOTION_L2_128B, CU_TENSOR_MAP_FLOAT_OOB_FILL_NONE);
}
void map_weight(CUtensorMap* m, const bf16* p, int rows, int cols, int ng, int br = 64) {
    const cuuint64_t dim[3] = {64, (cuuint64_t)rows, (cuuint64_t)cols / 64}, str[2] = {(cuuint64_t)cols * 2, 128};
    const cuuint32_t box[3] = {64, (cuuint32_t)br, (cuuint32_t)ng};
    make_map(m, CU_TENSOR_MAP_DATA_TYPE_BFLOAT16, p, dim, str, box, CU_TENSOR_MAP_SWIZZLE_128B);
}
void map_pieces(CUtensorMap* m, const void* p, int np, int ns) {
    const cuuint64_t dim[3] = {256, (cuuint64_t)np * 2, NSEG}, str[2] = {2048, (cuuint64_t)np * 4096};
    const cuuint32_t box[3] = {256, 2, (cuuint32_t)ns};
    make_map(m, CU_TENSOR_MAP_DATA_TYPE_UINT64, p, dim, str, box, CU_TENSOR_MAP_SWIZZLE_NONE);
}

template <class... P, class... A> void launch(void (*k)(P...), int grid, int block, int smem, int cluster, bool pdl, A... args) {
    cudaLaunchConfig_t c = {};
    c.gridDim = dim3(grid); c.blockDim = dim3(block); c.dynamicSmemBytes = smem; c.stream = cudaStreamPerThread;
    cudaLaunchAttribute at[2];
    int n = 0;
    if (cluster > 1) { at[n].id = cudaLaunchAttributeClusterDimension; at[n].val.clusterDim.x = cluster; at[n].val.clusterDim.y = 1; at[n].val.clusterDim.z = 1; n++; }
    if (pdl) { at[n].id = cudaLaunchAttributeProgrammaticStreamSerialization; at[n].val.programmaticStreamSerializationAllowed = 1; n++; }
    c.attrs = at; c.numAttrs = n;
    cudaLaunchKernelEx(&c, k, args...);
}

int max_clusters() {
    cudaLaunchConfig_t c = {};
    c.gridDim = dim3(3 * H_); c.blockDim = dim3(512); c.dynamicSmemBytes = rec::SMEM;
    cudaLaunchAttribute at[1];
    at[0].id = cudaLaunchAttributeClusterDimension; at[0].val.clusterDim.x = 3; at[0].val.clusterDim.y = 1; at[0].val.clusterDim.z = 1;
    c.attrs = at; c.numAttrs = 1;
    int n = 0;
    cudaOccupancyMaxActiveClusters(&n, rec_kernel, &c);
    return n;
}

}

extern "C" void kernel_launch(void* const* d_in, const int* in_sizes, int n_in, void* d_out, int out_size) {
    const bf16* x = (const bf16*)d_in[0];
    const bf16* mem0 = (const bf16*)d_in[1];
    const bf16* Wq = (const bf16*)d_in[2];
    const bf16* Wk = (const bf16*)d_in[3];
    const bf16* Wv = (const bf16*)d_in[4];
    const bf16* Wo = (const bf16*)d_in[5];
    const bf16* wr = (const bf16*)d_in[8];
    const bf16* wi = (const bf16*)d_in[9];
    cudaFuncSetAttribute(rec_kernel, cudaFuncAttributeMaxDynamicSharedMemorySize, rec::SMEM);
    cudaFuncSetAttribute(side_kernel, cudaFuncAttributeMaxDynamicSharedMemorySize, wk::SMEM);
    cudaFuncSetAttribute(colfft_kernel, cudaFuncAttributeMaxDynamicSharedMemorySize, CF_SMEM);
    Maps maps;
    void *pxn, *po;
    cudaGetSymbolAddress(&pxn, g_xn);
    cudaGetSymbolAddress(&po, g_o);
    map_weight(&maps.wq2, Wq, D_, 4096, 2); map_weight(&maps.wv1, Wv, D_, 4096, 1);
    map_weight(&maps.wo2, Wo, 4096, D_, 2); map_weight(&maps.wo1, Wo, 4096, D_, 1, 192);
    map_pieces(&maps.x6, pxn, 10, 6); map_pieces(&maps.x2, pxn, 10, 2);
    map_pieces(&maps.o6, po, 64, 6); map_pieces(&maps.o2, po, 64, 2);
    bf16 *x1, *x2;
    cudaGetSymbolAddress((void**)&x1, g_x1);
    cudaGetSymbolAddress((void**)&x2, g_x2);
    constexpr int ONE_PER_SM = 120 * 1024;
    cudaFuncSetAttribute(rowfft_kernel, cudaFuncAttributeMaxDynamicSharedMemorySize, ONE_PER_SM);
    cudaFuncSetAttribute(rowifft_kernel, cudaFuncAttributeMaxDynamicSharedMemorySize, ONE_PER_SM);
    static int ncl = 0, nsm = 0;
    if (!ncl) { ncl = max_clusters(); cudaDeviceGetAttribute(&nsm, cudaDevAttrMultiProcessorCount, 0); }
    maps.wr = wr; maps.wi = wi;
    launch(prep_kernel, 128, 512, 0, 1, false, x, Wq, Wk, Wv, Wo);
    for (int layer = 0; layer < g_layers; layer++) {
        const bf16* xin = layer ? x2 : x;
        launch(rec_kernel, 3 * ncl, 512, rec::SMEM, 3, true, maps, xin, x1, mem0, Wq, Wk, Wv, Wo, layer, g_delay % 10000, g_delay / 10000);
        launch(side_kernel, nsm - 3 * (ncl - H_), 512, wk::SMEM, 1, true, maps, xin, x1, layer);
        launch(rowfft_kernel, 128, 256, ONE_PER_SM, 1, true, xin, x1, Wq, Wk, Wv, layer);
        launch(colfft_kernel, 107, 384, CF_SMEM, 1, true, layer);
        launch(rowifft_kernel, 128, 256, ONE_PER_SM, 1, true, (const bf16*)x1, layer ? (bf16*)d_out : x2, layer);
    }
}
```

```cpp
#include <cuda_runtime.h>
#include <cuda_bf16.h>
#include <cuda.h>
#include <stdint.h>

#define DEV __device__ __forceinline__
typedef unsigned long long u64;
typedef __nv_bfloat16 bf16;

namespace {

constexpr int S_ = 2048, D_ = 640, H_ = 32, E_ = 128, NSEG = 64;

__device__ __align__(1024) unsigned char g_xn[S_ * D_ * 2];
__device__ __align__(1024) unsigned char g_o[S_ * H_ * E_ * 2];
constexpr int ACC_LAYER = 32 * 5120;
__device__ __align__(4096) u64 g_acc[2 * ACC_LAYER];
__device__ __align__(16) float g_nrm[256];
__device__ __align__(1024) unsigned char g_p[NSEG * H_ * 3 * 4096];
constexpr int SYNC_LAYER = 1024 + 64 * 32;
__device__ __align__(128) uint32_t g_sync[2 * SYNC_LAYER];
__device__ __align__(1024) bf16 g_x1[S_ * D_];
__device__ __align__(1024) bf16 g_x2[S_ * D_];
constexpr int YT_ROWS = 128;
__device__ __align__(1024) float g_yt[2 * YT_ROWS * D_];
constexpr int NCOL = 321;
__device__ __align__(1024) unsigned char g_z[NCOL * 8192];
__device__ __align__(1024) unsigned char g_wt[NCOL * 8192];
__device__ __align__(1024) uint4 g_f128[2 * 8 * 256];
__device__ __align__(1024) uint4 g_f64[2 * 4 * 128];
__device__ __align__(1024) bf16 g_g32[2 * 4096];
#define TLI(id, k, v)
#define TLS(i)
#define TLE(i)

DEV uint32_t s2u(const void* p) { return (uint32_t)__cvta_generic_to_shared(p); }
DEV uint32_t clk() { uint32_t c; asm volatile("mov.u32 %0,%%clock;" : "=r"(c)::"memory"); return c; }
DEV uint32_t gtime32() { uint32_t t; asm volatile("mov.u32 %0,%%globaltimer_lo;" : "=r"(t)::"memory"); return t; }
DEV uint32_t cta_rank() { uint32_t r; asm volatile("mov.u32 %0,%%cluster_ctarank;" : "=r"(r)); return __shfl_sync(~0u, r, 0); }
DEV uint32_t mapa(uint32_t a, uint32_t r) { uint32_t o; asm("mapa.shared::cluster.u32 %0,%1,%2;" : "=r"(o) : "r"(a), "r"(r)); return o; }
DEV void mbar_init(uint32_t b, uint32_t n) { asm volatile("mbarrier.init.shared::cta.b64 [%0],%1;" ::"r"(b), "r"(n) : "memory"); }
DEV bool mbar_try(uint32_t b, uint32_t par, int) {
    uint32_t ok;
    asm volatile("{.reg .pred p; mbarrier.test_wait.parity.shared::cta.b64 p,[%1],%2; selp.u32 %0,1,0,p;}" : "=r"(ok) : "r"(b), "r"(par) : "memory");
    return ok;
}
DEV bool mbar_try(uint32_t b, uint32_t par) {
    uint32_t ok;
    asm volatile("{.reg .pred p; mbarrier.try_wait.parity.shared::cta.b64 p,[%1],%2; selp.u32 %0,1,0,p;}" : "=r"(ok) : "r"(b), "r"(par) : "memory");
    return ok;
}
constexpr uint32_t SPIN_LIMIT = 1u << 18;
DEV void die() { __trap(); }
DEV void mbar_wait(uint32_t b, uint32_t par) {
    uint32_t n = 0;
    while (!mbar_try(b, par)) if (++n > SPIN_LIMIT) die();
}
DEV uint32_t opaque(uint32_t x) { return __shfl_xor_sync(~0u, x, 0); }
#define SFENCE() asm volatile("{.reg .pred p; setp.ne.u32 p,%1,0; @p mov.u32 %0,%%clock;}" : "+r"(sfd) : "r"((uint32_t)never) : "memory")
DEV void mbar_arrive(uint32_t b) { asm volatile("mbarrier.arrive.shared::cta.b64 _,[%0];" ::"r"(b) : "memory"); }
DEV void mbar_arrive_elect(uint32_t b) { asm volatile("{.reg .pred p; elect.sync _|p, 0xffffffff; @p mbarrier.arrive.shared::cta.b64 _,[%0];}" ::"r"(b) : "memory"); }
DEV void mbar_expect_elect(uint32_t b, uint32_t tx) {
    asm volatile("{.reg .pred p; elect.sync _|p, 0xffffffff; @p mbarrier.arrive.expect_tx.shared::cta.b64 _,[%0],%1;}" ::"r"(b), "r"(tx) : "memory");
}
DEV void mbar_arrive_remote_elect(uint32_t b) { asm volatile("{.reg .pred p; elect.sync _|p, 0xffffffff; @p mbarrier.arrive.shared::cluster.b64 _,[%0];}" ::"r"(b) : "memory"); }
DEV bool elect() { uint32_t r; asm volatile("{.reg .pred p; elect.sync _|p, 0xffffffff; selp.u32 %0,1,0,p;}" : "=r"(r)); return r; }
DEV void mbar_arrive_remote(uint32_t b) { asm volatile("mbarrier.arrive.shared::cluster.b64 _,[%0];" ::"r"(b) : "memory"); }
DEV void mbar_expect(uint32_t b, uint32_t tx) { asm volatile("mbarrier.arrive.expect_tx.shared::cta.b64 _,[%0],%1;" ::"r"(b), "r"(tx) : "memory"); }
DEV void bar_sync(int id, int n) { asm volatile("bar.sync %0,%1;" ::"r"(id), "r"(n) : "memory"); }
DEV void bar_arrive(int id, int n) { asm volatile("bar.arrive %0,%1;" ::"r"(id), "r"(n) : "memory"); }
template <int ID, int N> DEV void bar_arrive_if(bool p) {
    asm volatile("{.reg .pred p; setp.ne.u32 p,%0,0; @p bar.arrive %1,%2;}" ::"r"((uint32_t)p), "n"(ID), "n"(N) : "memory");
}
DEV void prefetch_bulk(const void* p, uint32_t bytes) { asm volatile("cp.async.bulk.prefetch.L2.global [%0],%1;" ::"l"(p), "r"(bytes) : "memory"); }
DEV void prefetch_l2(const void* p) { asm volatile("prefetch.global.L2 [%0];" ::"l"(p) : "memory"); }
template <int ID, int N> DEV void bar_sync_if(bool p) {
    asm volatile("{.reg .pred p; setp.ne.u32 p,%0,0; @p bar.sync %1,%2;}" ::"r"((uint32_t)p), "n"(ID), "n"(N) : "memory");
}
DEV void st_remote(uint32_t a, uint32_t x) { asm volatile("st.relaxed.cluster.shared::cluster.u32 [%0],%1;" ::"r"(a), "r"(x) : "memory"); }
DEV void st_async1(uint32_t a, uint32_t x, uint32_t b) {
    asm volatile("st.async.shared::cluster.mbarrier::complete_tx::bytes.u32 [%0],%1,[%2];" ::"r"(a), "r"(x), "r"(b) : "memory");
}
DEV void st_async2(uint32_t a, uint32_t x, uint32_t y, uint32_t b) {
    asm volatile("st.async.shared::cluster.mbarrier::complete_tx::bytes.v2.u32 [%0],{%1,%2},[%3];" ::"r"(a), "r"(x), "r"(y), "r"(b) : "memory");
}
DEV void st_async4(uint32_t a, uint32_t x, uint32_t y, uint32_t z, uint32_t w, uint32_t b) {
    asm volatile("st.async.shared::cluster.mbarrier::complete_tx::bytes.v4.u32 [%0],{%1,%2,%3,%4},[%5];" ::"r"(a), "r"(x), "r"(y), "r"(z), "r"(w), "r"(b) : "memory");
}
DEV void bulk_g2s(uint32_t dst, const void* src, uint32_t bytes, uint32_t b) {
    asm volatile("cp.async.bulk.shared::cluster.global.mbarrier::complete_tx::bytes [%0],[%1],%2,[%3];" ::"r"(dst), "l"(src), "r"(bytes), "r"(b) : "memory");
}
DEV void bulk_g2s_elect(uint32_t dst, const void* src, uint32_t bytes, uint32_t b) {
    asm volatile("{.reg .pred p; elect.sync _|p, 0xffffffff; @p cp.async.bulk.shared::cluster.global.mbarrier::complete_tx::bytes [%0],[%1],%2,[%3];}"
                 ::"r"(dst), "l"(src), "r"(bytes), "r"(b) : "memory");
}
DEV void bulk_s2s_elect(uint32_t dst, uint32_t src, uint32_t bytes, uint32_t b) {
    asm volatile("{.reg .pred p; elect.sync _|p, 0xffffffff; @p cp.async.bulk.shared::cluster.shared::cta.mbarrier::complete_tx::bytes [%0],[%1],%2,[%3];}"
                 ::"r"(dst), "r"(src), "r"(bytes), "r"(b) : "memory");
}
DEV void bulk_s2g_elect(void* dst, uint32_t src, uint32_t bytes) {
    asm volatile("{.reg .pred p; elect.sync _|p, 0xffffffff; @p cp.async.bulk.global.shared::cta.bulk_group [%0],[%1],%2;}" ::"l"(dst), "r"(src), "r"(bytes) : "memory");
}
DEV void bulk_s2s(uint32_t dst, uint32_t src, uint32_t bytes, uint32_t b) {
    asm volatile("cp.async.bulk.shared::cluster.shared::cta.mbarrier::complete_tx::bytes [%0],[%1],%2,[%3];" ::"r"(dst), "r"(src), "r"(bytes), "r"(b) : "memory");
}
DEV void bulk_s2g(void* dst, uint32_t src, uint32_t bytes) {
    asm volatile("cp.async.bulk.global.shared::cta.bulk_group [%0],[%1],%2;" ::"l"(dst), "r"(src), "r"(bytes) : "memory");
}
DEV void tma3d(uint32_t dst, const CUtensorMap* m, int c0, int c1, int c2, uint32_t b) {
    asm volatile("cp.async.bulk.tensor.3d.shared::cluster.global.mbarrier::complete_tx::bytes [%0],[%1,{%3,%4,%5}],[%2];"
                 ::"r"(dst), "l"(m), "r"(b), "r"(c0), "r"(c1), "r"(c2) : "memory");
}
DEV void bulk_commit() { asm volatile("cp.async.bulk.commit_group;" ::: "memory"); }
template <int N> DEV void bulk_wait() { asm volatile("cp.async.bulk.wait_group %0;" ::"n"(N) : "memory"); }
template <int N> DEV void bulk_wait_read() { asm volatile("cp.async.bulk.wait_group.read %0;" ::"n"(N) : "memory"); }
DEV void fence_async_all() { asm volatile("fence.proxy.async;" ::: "memory"); }
DEV void flag_add(uint32_t* p) { fence_async_all(); asm volatile("red.release.gpu.global.add.u32 [%0],1;" ::"l"(p) : "memory"); }
template <bool BOUNDED = true, bool UNIFORM = false> DEV void flag_wait(const uint32_t* p, uint32_t n) {
    uint32_t v, it = 0;
    for (;;) {
        asm volatile("ld.acquire.gpu.global.u32 %0,[%1];" : "=r"(v) : "l"(p) : "memory");
        if (UNIFORM ? __all_sync(~0u, v >= n) : v >= n) break;
        if (BOUNDED && ++it > (SPIN_LIMIT << 3)) die();
        __nanosleep(100);
    }
    fence_async_all();
}
DEV void cp16(uint32_t dst, const void* src) { asm volatile("cp.async.cg.shared.global [%0],[%1],16;" ::"r"(dst), "l"(src) : "memory"); }
DEV void cp_commit() { asm volatile("cp.async.commit_group;" ::: "memory"); }
template <int N> DEV void cp_wait() { asm volatile("cp.async.wait_group %0;" ::"n"(N) : "memory"); }
DEV uint32_t lds32(uint32_t a) { uint32_t x; asm volatile("ld.shared.u32 %0,[%1];" : "=r"(x) : "r"(a) : "memory"); return x; }
DEV void fence_async() { asm volatile("fence.proxy.async.shared::cta;" ::: "memory"); }
DEV uint32_t pack2(float lo, float hi) { uint32_t r; asm("cvt.rn.bf16x2.f32 %0,%1,%2;" : "=r"(r) : "f"(hi), "f"(lo)); return r; }
DEV uint32_t prmt(uint32_t a, uint32_t b, uint32_t s) { uint32_t r; asm("prmt.b32 %0,%1,%2,%3;" : "=r"(r) : "r"(a), "r"(b), "r"(s)); return r; }
DEV float ex2(float x) { float r; asm("ex2.approx.ftz.f32 %0,%1;" : "=f"(r) : "f"(x)); return r; }
DEV float rcp(float x) { float r; asm("rcp.approx.ftz.f32 %0,%1;" : "=f"(r) : "f"(x)); return r; }
DEV void lds128(uint32_t* r, uint32_t a) { asm volatile("ld.shared.v4.u32 {%0,%1,%2,%3},[%4];" : "=r"(r[0]), "=r"(r[1]), "=r"(r[2]), "=r"(r[3]) : "r"(a) : "memory"); }
DEV void lds64(uint32_t* r, uint32_t a) { asm volatile("ld.shared.v2.u32 {%0,%1},[%2];" : "=r"(r[0]), "=r"(r[1]) : "r"(a) : "memory"); }
DEV void lds64f(float& x, float& y, uint32_t a) { asm volatile("ld.shared.v2.f32 {%0,%1},[%2];" : "=f"(x), "=f"(y) : "r"(a) : "memory"); }
DEV void lds128f(float* r, uint32_t a) { asm volatile("ld.shared.v4.f32 {%0,%1,%2,%3},[%4];" : "=f"(r[0]), "=f"(r[1]), "=f"(r[2]), "=f"(r[3]) : "r"(a) : "memory"); }
DEV void sts128(uint32_t a, uint32_t x, uint32_t y, uint32_t z, uint32_t w) { asm volatile("st.shared.v4.u32 [%0],{%1,%2,%3,%4};" ::"r"(a), "r"(x), "r"(y), "r"(z), "r"(w) : "memory"); }
DEV void sts64(uint32_t a, uint32_t x, uint32_t y) { asm volatile("st.shared.v2.u32 [%0],{%1,%2};" ::"r"(a), "r"(x), "r"(y) : "memory"); }
DEV void sts32(uint32_t a, uint32_t x) { asm volatile("st.shared.u32 [%0],%1;" ::"r"(a), "r"(x) : "memory"); }
DEV void ldsm4(uint32_t* r, uint32_t a) { asm volatile("ldmatrix.sync.aligned.m8n8.x4.shared.b16 {%0,%1,%2,%3},[%4];" : "=r"(r[0]), "=r"(r[1]), "=r"(r[2]), "=r"(r[3]) : "r"(a) : "memory"); }
DEV void ldsm4t(uint32_t* r, uint32_t a) { asm volatile("ldmatrix.sync.aligned.m8n8.x4.trans.shared.b16 {%0,%1,%2,%3},[%4];" : "=r"(r[0]), "=r"(r[1]), "=r"(r[2]), "=r"(r[3]) : "r"(a) : "memory"); }
DEV void ldsm2(uint32_t* r, uint32_t a) { asm volatile("ldmatrix.sync.aligned.m8n8.x2.shared.b16 {%0,%1},[%2];" : "=r"(r[0]), "=r"(r[1]) : "r"(a) : "memory"); }
DEV void stsm4t(uint32_t a, uint32_t x, uint32_t y, uint32_t z, uint32_t w) { asm volatile("stmatrix.sync.aligned.m8n8.x4.trans.shared.b16 [%0],{%1,%2,%3,%4};" ::"r"(a), "r"(x), "r"(y), "r"(z), "r"(w) : "memory"); }
DEV void stsm4(uint32_t a, uint32_t x, uint32_t y, uint32_t z, uint32_t w) { asm volatile("stmatrix.sync.aligned.m8n8.x4.shared.b16 [%0],{%1,%2,%3,%4};" ::"r"(a), "r"(x), "r"(y), "r"(z), "r"(w) : "memory"); }
DEV void stsm2(uint32_t a, uint32_t x, uint32_t y) { asm volatile("stmatrix.sync.aligned.m8n8.x2.shared.b16 [%0],{%1,%2};" ::"r"(a), "r"(x), "r"(y) : "memory"); }
DEV void stsm2t_if(uint32_t a, uint32_t x, uint32_t y, bool p) {
    asm volatile("{.reg .pred p; setp.ne.u32 p,%3,0; @p stmatrix.sync.aligned.m8n8.x2.trans.shared.b16 [%0],{%1,%2};}" ::"r"(a), "r"(x), "r"(y), "r"((uint32_t)p) : "memory");
}
DEV void stsm2t(uint32_t a, uint32_t x, uint32_t y) { asm volatile("stmatrix.sync.aligned.m8n8.x2.trans.shared.b16 [%0],{%1,%2};" ::"r"(a), "r"(x), "r"(y) : "memory"); }
DEV void mma16(float* d, uint32_t a0, uint32_t a1, uint32_t a2, uint32_t a3, uint32_t b0, uint32_t b1) {
    asm volatile("mma.sync.aligned.m16n8k16.row.col.f32.bf16.bf16.f32 {%0,%1,%2,%3},{%4,%5,%6,%7},{%8,%9},{%0,%1,%2,%3};"
                 : "+f"(d[0]), "+f"(d[1]), "+f"(d[2]), "+f"(d[3]) : "r"(a0), "r"(a1), "r"(a2), "r"(a3), "r"(b0), "r"(b1));
}
DEV void mma8(float* d, uint32_t a0, uint32_t a1, uint32_t b0) {
    asm volatile("mma.sync.aligned.m16n8k8.row.col.f32.bf16.bf16.f32 {%0,%1,%2,%3},{%4,%5},{%6},{%0,%1,%2,%3};"
                 : "+f"(d[0]), "+f"(d[1]), "+f"(d[2]), "+f"(d[3]) : "r"(a0), "r"(a1), "r"(b0));
}
DEV u64 mkdesc(uint32_t a, uint32_t lbo, uint32_t sbo) { return (u64)((a & 0x3ffff) >> 4) | ((u64)(lbo >> 4) << 16) | ((u64)(sbo >> 4) << 32); }
constexpr u64 SW128 = 1ull << 62;
DEV void wg_fence() { asm volatile("wgmma.fence.sync.aligned;" ::: "memory"); }
DEV void wg_commit() { asm volatile("wgmma.commit_group.sync.aligned;" ::: "memory"); }
template <int N> DEV void wg_wait() { asm volatile("wgmma.wait_group.sync.aligned %0;" ::"n"(N) : "memory"); }
template <int ACC> DEV void wgmma_n32_rs(float* d, const uint32_t* a, u64 desc) {
    asm volatile("wgmma.mma_async.sync.aligned.m64n32k16.f32.bf16.bf16 {%0,%1,%2,%3,%4,%5,%6,%7,%8,%9,%10,%11,%12,%13,%14,%15},{%16,%17,%18,%19},%20,%21,1,1,0;"
                 : "+f"(d[0]), "+f"(d[1]), "+f"(d[2]), "+f"(d[3]), "+f"(d[4]), "+f"(d[5]), "+f"(d[6]), "+f"(d[7]),
                   "+f"(d[8]), "+f"(d[9]), "+f"(d[10]), "+f"(d[11]), "+f"(d[12]), "+f"(d[13]), "+f"(d[14]), "+f"(d[15])
                 : "r"(a[0]), "r"(a[1]), "r"(a[2]), "r"(a[3]), "l"(desc), "n"(ACC));
}
template <int ACC> DEV void wgmma_n32_ss(float* d, u64 da, u64 desc) {
    asm volatile("wgmma.mma_async.sync.aligned.m64n32k16.f32.bf16.bf16 {%0,%1,%2,%3,%4,%5,%6,%7,%8,%9,%10,%11,%12,%13,%14,%15},%16,%17,%18,1,1,0,0;"
                 : "+f"(d[0]), "+f"(d[1]), "+f"(d[2]), "+f"(d[3]), "+f"(d[4]), "+f"(d[5]), "+f"(d[6]), "+f"(d[7]),
                   "+f"(d[8]), "+f"(d[9]), "+f"(d[10]), "+f"(d[11]), "+f"(d[12]), "+f"(d[13]), "+f"(d[14]), "+f"(d[15])
                 : "l"(da), "l"(desc), "n"(ACC));
}
template <int ACC> DEV void wgmma_n16_ss(float* d, u64 da, u64 desc) {
    asm volatile("wgmma.mma_async.sync.aligned.m64n16k16.f32.bf16.bf16 {%0,%1,%2,%3,%4,%5,%6,%7},%8,%9,%10,1,1,0,0;"
                 : "+f"(d[0]), "+f"(d[1]), "+f"(d[2]), "+f"(d[3]), "+f"(d[4]), "+f"(d[5]), "+f"(d[6]), "+f"(d[7])
                 : "l"(da), "l"(desc), "n"(ACC));
}
#define ACC8(o) "+f"(d[o]), "+f"(d[o + 1]), "+f"(d[o + 2]), "+f"(d[o + 3]), "+f"(d[o + 4]), "+f"(d[o + 5]), "+f"(d[o + 6]), "+f"(d[o + 7])
template <int ACC, int TB> DEV void wgmma_n64_rs(float* d, const uint32_t* a, u64 desc) {
    asm volatile("wgmma.mma_async.sync.aligned.m64n64k16.f32.bf16.bf16 {%0,%1,%2,%3,%4,%5,%6,%7,%8,%9,%10,%11,%12,%13,%14,%15,"
                 "%16,%17,%18,%19,%20,%21,%22,%23,%24,%25,%26,%27,%28,%29,%30,%31},{%32,%33,%34,%35},%36,%37,1,1,%38;"
                 : ACC8(0), ACC8(8), ACC8(16), ACC8(24) : "r"(a[0]), "r"(a[1]), "r"(a[2]), "r"(a[3]), "l"(desc), "n"(ACC), "n"(TB));
}
template <int ACC, int TB> DEV void wgmma_n80_rs(float* d, const uint32_t* a, u64 desc) {
    asm volatile("wgmma.mma_async.sync.aligned.m64n80k16.f32.bf16.bf16 {%0,%1,%2,%3,%4,%5,%6,%7,%8,%9,%10,%11,%12,%13,%14,%15,"
                 "%16,%17,%18,%19,%20,%21,%22,%23,%24,%25,%26,%27,%28,%29,%30,%31,%32,%33,%34,%35,%36,%37,%38,%39},{%40,%41,%42,%43},%44,%45,1,1,%46;"
                 : ACC8(0), ACC8(8), ACC8(16), ACC8(24), ACC8(32) : "r"(a[0]), "r"(a[1]), "r"(a[2]), "r"(a[3]), "l"(desc), "n"(ACC), "n"(TB));
}
template <int TA, int TB> DEV void wgmma_n64_ss(float* d, u64 da, u64 db, int acc) {
    asm volatile("{.reg .pred p; setp.ne.b32 p,%34,0; wgmma.mma_async.sync.aligned.m64n64k16.f32.bf16.bf16 {%0,%1,%2,%3,%4,%5,%6,%7,%8,%9,%10,%11,%12,%13,%14,%15,%16,%17,%18,%19,%20,%21,%22,%23,%24,%25,%26,%27,%28,%29,%30,%31},%32,%33,p,1,1,%35,%36;}"
                 : ACC8(0), ACC8(8), ACC8(16), ACC8(24) : "l"(da), "l"(db), "r"(acc), "n"(TA), "n"(TB));
}
template <int TA, int TB> DEV void wgmma_n128_ss(float* d, u64 da, u64 db, int acc) {
    asm volatile("{.reg .pred p; setp.ne.b32 p,%66,0; wgmma.mma_async.sync.aligned.m64n128k16.f32.bf16.bf16 {%0,%1,%2,%3,%4,%5,%6,%7,%8,%9,%10,%11,%12,%13,%14,%15,%16,%17,%18,%19,%20,%21,%22,%23,%24,%25,%26,%27,%28,%29,%30,%31,%32,%33,%34,%35,%36,%37,%38,%39,%40,%41,%42,%43,%44,%45,%46,%47,%48,%49,%50,%51,%52,%53,%54,%55,%56,%57,%58,%59,%60,%61,%62,%63},%64,%65,p,1,1,%67,%68;}"
                 : ACC8(0), ACC8(8), ACC8(16), ACC8(24), ACC8(32), ACC8(40), ACC8(48), ACC8(56) : "l"(da), "l"(db), "r"(acc), "n"(TA), "n"(TB));
}
template <int TA, int TB> DEV void wgmma_n192_ss(float* d, u64 da, u64 db, int acc) {
    asm volatile("{.reg .pred p; setp.ne.b32 p,%98,0; wgmma.mma_async.sync.aligned.m64n192k16.f32.bf16.bf16 {%0,%1,%2,%3,%4,%5,%6,%7,%8,%9,%10,%11,%12,%13,%14,%15,%16,%17,%18,%19,%20,%21,%22,%23,%24,%25,%26,%27,%28,%29,%30,%31,%32,%33,%34,%35,%36,%37,%38,%39,%40,%41,%42,%43,%44,%45,%46,%47,%48,%49,%50,%51,%52,%53,%54,%55,%56,%57,%58,%59,%60,%61,%62,%63,%64,%65,%66,%67,%68,%69,%70,%71,%72,%73,%74,%75,%76,%77,%78,%79,%80,%81,%82,%83,%84,%85,%86,%87,%88,%89,%90,%91,%92,%93,%94,%95},%96,%97,p,1,1,%99,%100;}"
                 : ACC8(0), ACC8(8), ACC8(16), ACC8(24), ACC8(32), ACC8(40), ACC8(48), ACC8(56), ACC8(64), ACC8(72), ACC8(80), ACC8(88) : "l"(da), "l"(db), "r"(acc), "n"(TA), "n"(TB));
}
template <int ACC> DEV void wgmma_n40_ss(float* d, u64 da, u64 desc) {
    asm volatile("wgmma.mma_async.sync.aligned.m64n40k16.f32.bf16.bf16 {%0,%1,%2,%3,%4,%5,%6,%7,%8,%9,%10,%11,%12,%13,%14,%15,%16,%17,%18,%19},%20,%21,%22,1,1,0,0;"
                 : ACC8(0), ACC8(8), "+f"(d[16]), "+f"(d[17]), "+f"(d[18]), "+f"(d[19]) : "l"(da), "l"(desc), "n"(ACC));
}
DEV void pdl_wait() { asm volatile("griddepcontrol.wait;" ::: "memory"); }
DEV void pdl_launch() { asm volatile("griddepcontrol.launch_dependents;" ::: "memory"); }
DEV uint32_t ldg32(const void* p) { uint32_t v; asm volatile("ld.global.nc.u32 %0,[%1];" : "=r"(v) : "l"(p)); return v; }
DEV void ld_acc(u64& a, u64& b, const void* p) {
    const uint32_t done = (uint32_t)a & (uint32_t)b & 32u;
    asm volatile("{.reg .pred p; setp.eq.u32 p,%3,0;\n"
                 "@p ld.relaxed.gpu.global.v2.u64 {%0,%1},[%2];}" : "+l"(a), "+l"(b) : "l"(p), "r"(done) : "memory");
}
DEV void ld_acc0(u64& a, u64& b, const void* p) {
    asm volatile("ld.relaxed.gpu.global.v2.u64 {%0,%1},[%2];" : "=l"(a), "=l"(b) : "l"(p) : "memory");
}
DEV uint32_t and3(uint32_t a, uint32_t b, uint32_t c) { uint32_t r; asm volatile("lop3.b32 %0,%1,%2,%3,0x80;" : "=r"(r) : "r"(a), "r"(b), "r"(c)); return r; }
DEV uint32_t absmax2(uint32_t a, uint32_t b) { uint32_t r; asm("max.xorsign.abs.bf16x2 %0,%1,%2;" : "=r"(r) : "r"(a), "r"(b)); return r; }
DEV float lds32f(uint32_t a) { float x; asm volatile("ld.shared.f32 %0,[%1];" : "=f"(x) : "r"(a) : "memory"); return x; }
DEV void red_add64(u64* p, uint32_t lo, uint32_t hi) {
    asm volatile("{.reg .b64 v; mov.b64 v,{%1,%2}; red.relaxed.gpu.global.add.u64 [%0],v;}" ::"l"(p), "r"(lo), "r"(hi) : "memory");
}
DEV float bf_round(float x) { return __bfloat162float(__float2bfloat16_rn(x)); }
DEV float bf_lo(uint32_t u) { return __uint_as_float(u << 16); }
DEV float bf_hi(uint32_t u) { return __uint_as_float(u & 0xffff0000u); }

#define GPROF(i, n)
#define PROFT(i)
#define STAMP(i)

DEV void unpack8(float* v, uint4 u) {
    v[0] = bf_lo(u.x); v[1] = bf_hi(u.x); v[2] = bf_lo(u.y); v[3] = bf_hi(u.y);
    v[4] = bf_lo(u.z); v[5] = bf_hi(u.z); v[6] = bf_lo(u.w); v[7] = bf_hi(u.w);
}
DEV int xn_off(int row, int chunk) { return (row >> 5) * 40960 + (chunk >> 3) * 4096 + (row & 31) * 128 + (((chunk ^ row) & 7) << 4); }

DEV void ln_row(float (&v)[3][8], int lane) {
    float s = 0.f;
#pragma unroll
    for (int c = 0; c < 3; c++)
#pragma unroll
        for (int j = 0; j < 8; j++) s += v[c][j];
#pragma unroll
    for (int o = 16; o; o >>= 1) s += __shfl_xor_sync(~0u, s, o);
    float mean = s * (1.f / D_), q = 0.f;
#pragma unroll
    for (int c = 0; c < 3; c++)
        if (c < 2 || lane < 16)
#pragma unroll
            for (int j = 0; j < 8; j++) { float d = v[c][j] - mean; q += d * d; }
#pragma unroll
    for (int o = 16; o; o >>= 1) q += __shfl_xor_sync(~0u, q, o);
    float mb = bf_round(mean);
    float inv = 1.f / bf_round(sqrtf(bf_round(bf_round(q * (1.f / D_)) + 1e-5f)));
#pragma unroll
    for (int c = 0; c < 3; c++)
#pragma unroll
        for (int j = 0; j < 8; j++) v[c][j] = bf_round(v[c][j] - mb) * inv;
}

__host__ __device__ constexpr int col_freq(int c) {
    return c == 320 ? 320 : c < 192 ? (c >> 6) * 128 + (c & 63) : c == 192 ? 192 : c < 256 ? 448 - c : c == 256 ? 64 : 384 - c;
}
DEV float rdft(int n, int k, int sn, int N) {
    float s, c;
    sincospif((float)((n * k) & (N - 1)) * (2.f / N), &s, &c);
    return !sn ? c : k ? s : (n & 1 ? -1.f : 1.f);
}

__global__ void __launch_bounds__(512) prep_kernel(const bf16* __restrict__ x, const bf16* __restrict__ Wq, const bf16* __restrict__ Wk,
                                                   const bf16* __restrict__ Wv, const bf16* __restrict__ Wo) {
    __shared__ float red[32], col[4][640];
    const int tid = threadIdx.x, lane = tid & 31, warp = tid >> 5, b = blockIdx.x, row = b * 16 + warp;
    TLS(0);
    pdl_launch();
    uint4 ux[3], uv[5], uo[8];
#pragma unroll
    for (int c = 0; c < 3; c++) ux[c] = c < 2 || lane < 16 ? *(const uint4*)(x + row * D_ + (c * 32 + lane) * 8) : make_uint4(0, 0, 0, 0);
#pragma unroll
    for (int i = 0; i < 5; i++) uv[i] = *(const uint4*)(Wv + (size_t)((b & 3) * 160 + i * 32 + (tid >> 4)) * 4096 + (b >> 2) * E_ + (tid & 15) * 8);
    if (tid < 320) {
#pragma unroll
        for (int r = 0; r < 8; r++) uo[r] = *(const uint4*)(Wo + (size_t)(b * 32 + tid / 80 * 8 + r) * D_ + tid % 80 * 8);
    }
    if (tid >= 504) prefetch_bulk((const char*)(tid & 4 ? Wk : Wq) + (b * 4 + (tid & 3)) * 10240, 10240);
    if (b < 3) ((uint4*)g_sync)[b * 512 + tid] = make_uint4(0, 0, 0, 0);
    for (int i = b * 512 + tid; i < ACC_LAYER; i += 128 * 512) ((uint4*)g_acc)[i] = make_uint4(0, 0, 0, 0);
    if (tid < 2 * YT_ROWS * D_ / 4 / 128) ((uint4*)g_yt)[b * (2 * YT_ROWS * D_ / 4 / 128) + tid] = make_uint4(0, 0, 0, 0);
    const int gid = tid < 104 ? b * 104 + tid : 1 << 20;
    if (gid < 4096) {
        const int inv = gid >> 11, ks = (gid >> 8) & 7, t = gid & 255, g = (t & 31) >> 2, q = t & 3, tile = t >> 5;
        uint32_t v[4];
#pragma unroll
        for (int j = 0; j < 4; j++) {
            float x[2];
#pragma unroll
            for (int u = 0; u < 2; u++) {
                const int m = inv ? 16 * tile + 2 * g + (j & 1) : 16 * ks + 8 * (j >> 1) + 2 * q + u;
                const int k2 = inv ? 8 * ks + 2 * q + u : 8 * tile + g, sn = inv ? j >> 1 : j & 1;
                x[u] = rdft(m, k2, sn, 128);
                if (sn && k2) x[u] = -x[u];
            }
            v[j] = pack2(x[0], x[1]);
        }
        g_f128[gid] = make_uint4(v[0], v[1], v[2], v[3]);
    } else if (gid < 5120) {
        const int id = gid - 4096, inv = id >> 9, ks = (id >> 7) & 3, t = id & 127, g = (t & 31) >> 2, q = t & 3, tile = t >> 5;
        uint32_t v[4];
#pragma unroll
        for (int j = 0; j < 4; j++) {
            float x[2];
#pragma unroll
            for (int u = 0; u < 2; u++) {
                const int a = inv ? 16 * tile + g + 8 * (j & 1) : 16 * ks + 8 * (j >> 1) + 2 * q + u;
                const int ka = inv ? 8 * ks + 2 * q + u : 8 * tile + g, sn = inv ? j >> 1 : j & 1;
                x[u] = rdft(a, ka, sn, 64);
            }
            v[j] = pack2(x[0], x[1]);
        }
        g_f64[id] = make_uint4(v[0], v[1], v[2], v[3]);
    } else if (gid < 5120 + 8192) {
        const int id = gid - 5120, inv = id >> 12, n = ((id >> 9) & 7) * 8 + ((id >> 3) & 7), k = ((id >> 6) & 7) * 8 + (id & 7);
        float s, c;
        sincospif((float)(((n >> 1) * (k >> 1)) & 31) * (1.f / 16), &s, &c);
        if (inv) s = -s;
        g_g32[id] = __float2bfloat16_rn((n & 1) == (k & 1) ? c : (k & 1) ? s : -s);
    }
    {
        float v[3][8];
#pragma unroll
        for (int c = 0; c < 3; c++) unpack8(v[c], ux[c]);
        ln_row(v, lane);
#pragma unroll
        for (int c = 0; c < 3; c++)
            if (c < 2 || lane < 16)
                *(uint4*)(g_xn + xn_off(row, c * 32 + lane)) =
                    make_uint4(pack2(v[c][0], v[c][1]), pack2(v[c][2], v[c][3]), pack2(v[c][4], v[c][5]), pack2(v[c][6], v[c][7]));
    }
    float sv = 0.f;
#pragma unroll
    for (int i = 0; i < 5; i++) {
        float w[8];
        unpack8(w, uv[i]);
#pragma unroll
        for (int j = 0; j < 8; j++) sv += w[j] * w[j];
    }
    if (tid < 320) {
        float a[8] = {0.f, 0.f, 0.f, 0.f, 0.f, 0.f, 0.f, 0.f};
#pragma unroll
        for (int r = 0; r < 8; r++) {
            float w[8];
            unpack8(w, uo[r]);
#pragma unroll
            for (int j = 0; j < 8; j++) a[j] += w[j] * w[j];
        }
#pragma unroll
        for (int j = 0; j < 8; j++) col[tid / 80][tid % 80 * 8 + j] = a[j];
    }
    __syncthreads();
    float so = (col[0][tid] + col[1][tid]) + (col[2][tid] + col[3][tid]);
    if (tid < 128) so = fmaxf(so, (col[0][512 + tid] + col[1][512 + tid]) + (col[2][512 + tid] + col[3][512 + tid]));
#pragma unroll
    for (int o = 16; o; o >>= 1) { sv += __shfl_xor_sync(~0u, sv, o); so = fmaxf(so, __shfl_xor_sync(~0u, so, o)); }
    if (lane == 0) { red[warp] = sv; red[16 + warp] = so; }
    __syncthreads();
    if (tid == 0) {
        float a = 0.f, c = 0.f;
        for (int i = 0; i < 16; i++) { a += red[i]; c = fmaxf(c, red[16 + i]); }
        g_nrm[b] = a; g_nrm[128 + b] = c;
    }
    TLE(0);
}

DEV void filter_tile(const bf16* __restrict__ wr, const bf16* __restrict__ wi, int ka, int c) {
    const int kn = ka ? 2048 - ka : 32, kc = col_freq(c);
    const unsigned short* pr = (const unsigned short*)wr + kc;
    const unsigned short* pi = (const unsigned short*)wi + kc;
#pragma unroll 1
    for (int i = 0; i < 4; i += 2) {
        unsigned short a[32], b[32];
#pragma unroll
        for (int n = 0; n < 32; n++) {
            const int k = ((n & 1 ? kn : ka) + 64 * (4 * (2 * (i + (n >> 4)) + ((n >> 1) & 1)) + ((n >> 2) & 3))) & 2047;
            a[n] = __ldg(pr + k * NCOL); b[n] = __ldg(pi + k * NCOL);
        }
#pragma unroll
        for (int n = 0; n < 32; n += 4)
            *(uint4*)(g_wt + c * 8192 + (i + (n >> 4)) * 2048 + (ka * 4 + ((n >> 2) & 3)) * 16) =
                make_uint4(a[n] | ((uint32_t)b[n] << 16), a[n + 1] | ((uint32_t)b[n + 1] << 16), a[n + 2] | ((uint32_t)b[n + 2] << 16), a[n + 3] | ((uint32_t)b[n + 3] << 16));
    }
}

namespace wk {
constexpr int STAGE = 49152, NST = 4, OFF_OUT = 3 * STAGE, OFF_RED = 4 * STAGE, OFF_BAR = OFF_RED + 32768, SMEM = OFF_BAR + 128;
constexpr int NPB = 12;
DEV int pb_first(int n) { return n < 2 ? 0 : n == 2 ? 1 : n % 6 == 0 ? n / 6 + 1 : -1; }
__host__ __device__ constexpr int pb_start(int b) { return b == 0 ? 0 : b == 1 ? 2 : b < NPB ? 6 * b - 6 : 64; }
#define NOB 7
#define SPLIT_A 3
#define SPLIT_B 11
constexpr int N_P = NPB * H_, I_F = N_P, I_OB = I_F + 32, I_OT = I_OB + NOB * 5, I_SA = I_OT + (30 - 3 * NOB) * 10;
constexpr int I_SB = I_SA + 10 * SPLIT_A, N_ITEMS = I_SB + 10 * SPLIT_B;
DEV void ot_decode(int id, int& b, int& nt, int& k0, int& k1) {
    const int base = id < I_SA ? I_OT : id < I_SB ? I_SA : I_SB, j = (id - base) / 10;
    nt = (id - base) % 10;
    if (id < I_SA) { b = 3 * NOB + j; k0 = 0; k1 = 22; }
    else if (id < I_SB) { b = 30; k0 = 22 * j / SPLIT_A; k1 = 22 * (j + 1) / SPLIT_A; }
    else { b = 31; k0 = 22 * j / SPLIT_B; k1 = 22 * (j + 1) / SPLIT_B; }
}
enum { SY_TICKET = 0, SY_O = 32, SY_P = 128 };
}
struct Ring {
    int st; uint32_t ph;
    DEV uint32_t par() const { return (ph >> st) & 1; }
    DEV void next(int n) { ph ^= 1u << st; st = st + 1 >= n ? 0 : st + 1; }
};
struct Maps { CUtensorMap wq2, wv1, wo2, wo1, x6, x2, o6, o2; const bf16 *wr, *wi; };

template <int NSG> DEV void proj_tile(uint32_t sb, uint32_t bar, Ring& rg, int wg, int id) {
    using namespace wk;
    float acc[NSG * 16];
#pragma unroll
    for (int i = 0; i < NSG * 16; i++) acc[i] = 0.f;
    const int lane = threadIdx.x & 31, ww = (threadIdx.x >> 5) & 3;
    for (int kb = 0; kb < 10; kb++, rg.next(3)) {
        const int st = rg.st;
        if (kb) mbar_wait(bar + 8 * st, rg.par());
        const u64 da = mkdesc(sb + st * STAGE + wg * 8192, 0, 1024) | SW128, db = mkdesc(sb + st * STAGE + 24576, 0, 1024) | SW128;
        wg_fence();
#pragma unroll
        for (int ks = 0; ks < 4; ks++) {
            if (NSG == 2) wgmma_n64_ss<1, 0>(acc, da + ks * 128, db + ks * 2, 1);
            if (NSG == 4) wgmma_n128_ss<1, 0>(acc, da + ks * 128, db + ks * 2, 1);
            if (NSG == 6) wgmma_n192_ss<1, 0>(acc, da + ks * 128, db + ks * 2, 1);
        }
        wg_commit();
        wg_wait<0>();
        mbar_arrive_elect(bar + 8 * (NST + st));
    }
    const uint32_t out = sb + OFF_OUT + wg * 24576;
    bar_sync(5 + wg, 160);
    const uint32_t la = out + (wg < 2 ? (lane >> 4) * 1024 + ww * 256 + (lane & 15) * 16 : ww * 1024 + ((lane >> 3) & 1) * 512 + (lane >> 4) * 128 + (lane & 7) * 16);
#pragma unroll
    for (int j = 0; j < 2 * NSG; j++) {
        const float* c = acc + 8 * j;
        const uint32_t p0 = pack2(c[0], c[1]), p1 = pack2(c[2], c[3]), p2 = pack2(c[4], c[5]), p3 = pack2(c[6], c[7]);
        if (wg < 2) stsm4t(la + j * 2048, p0, p1, p2, p3);
        else stsm4(la + (j >> 1) * 4096 + (j & 1) * 256, p0, p1, p2, p3);
    }
    if ((threadIdx.x & 127) == 0) sts32(bar + 80 + 4 * wg, id);
    fence_async();
    bar_arrive(1 + wg, 160);
}

DEV uint32_t resid(uint32_t u, float a, float b) { return pack2(bf_lo(u) + bf_round(a), bf_hi(u) + bf_round(b)); }

DEV void worker(uint32_t sb, const Maps& maps, const bf16* __restrict__ x, bf16* __restrict__ x1, int layer) {
    using namespace wk;
    const uint32_t bar = sb + OFF_BAR, slot = bar + 64;
    const int tid = threadIdx.x, lane = tid & 31, warp = __shfl_sync(~0u, tid >> 5, 0);
    uint32_t* sy = g_sync + layer * SYNC_LAYER;
    if (tid == 0) {
        for (int i = 0; i < NST; i++) { mbar_init(bar + 8 * i, 1); mbar_init(bar + 8 * (NST + i), 12); }
        asm volatile("fence.mbarrier_init.release.cluster;" ::: "memory");
    }
    __syncthreads();
    if (warp > 12) {
        const int wg = warp - 13;
        bar_arrive(5 + wg, 160);
        for (;;) {
            bar_sync(1 + wg, 160);
            const int id = (int)lds32(bar + 80 + 4 * wg);
            if (id < 0) break;
            const int s0 = pb_start(id >> 5), ns = pb_start((id >> 5) + 1) - s0;
            if (lane == 0) {
                for (int j = 0; j < ns; j++)
                    bulk_s2g(g_p + (size_t)(((s0 + j) * H_ + (id & 31)) * 3 + wg) * 4096, sb + OFF_OUT + wg * 24576 + j * 4096, 4096);
                bulk_commit();
                bulk_wait<0>();
                flag_add(sy + SY_P + id);
            }
            __syncwarp();
            bar_arrive(5 + wg, 160);
        }
    } else if (warp == 12) {
        if (lane == 0) {
            Ring rg = {0, 7u};
            auto acquire = [&]() { mbar_wait(bar + 8 * (NST + rg.st), rg.par()); return sb + rg.st * STAGE; };
            for (;;) {
                int id = (int)atomicAdd(sy + SY_TICKET, 1u);
                if (layer && id >= I_F) id += I_OB - I_F;
                if (id >= N_ITEMS) id = -1;
                if (id >= 0) { TLI(id, 0, gtime()); TLI(id, 3, blockIdx.x + (gridDim.x % 3 == 0 && gridDim.x > 111 ? 0 : 1000)); }
                uint32_t d = acquire();
                sts32(slot + 4 * rg.st, id);
                if (id < 0) { mbar_arrive(bar + 8 * rg.st); break; }
                if (id < N_P) {
                    const int b = id >> 5, h = id & 31, s0 = pb_start(b), ns = pb_start(b + 1) - s0;
                    for (int kb = 0; kb < 10; kb++, rg.next(3)) {
                        if (kb) d = acquire();
                        const uint32_t fb = bar + 8 * rg.st;
                        mbar_expect(fb, 24576 + ns * 4096);
                        tma3d(d, &maps.wq2, 0, kb * 64, 2 * h, fb);
                        tma3d(d + 16384, &maps.wv1, 0, kb * 64, 2 * h, fb);
                        if (ns == 6) tma3d(d + 24576, &maps.x6, 0, 2 * kb, s0, fb);
                        else for (int j = 0; j < ns; j += 2) tma3d(d + 24576 + j * 4096, &maps.x2, 0, 2 * kb, s0 + j, fb);
                    }
                } else if (id < I_OB) {
                    mbar_arrive(bar + 8 * rg.st);
                    mbar_wait(bar + 8 * (NST + rg.st), rg.par() ^ 1);
                    rg.next(NST);
                } else if (id < I_OT) {
                    const int b = (id - I_OB) / 5, nt = (id - I_OB) % 5;
                    for (int j = 0; j < 6; j++) flag_wait(sy + SY_O + 6 * b + j, 32);
                    for (int kb = 0; kb < 64; kb++, rg.next(NST)) {
                        if (kb) d = acquire();
                        const uint32_t fb = bar + 8 * rg.st;
                        mbar_expect(fb, 40960);
                        tma3d(d, &maps.o6, 0, 2 * kb, 6 * b, fb);
                        tma3d(d + 24576, &maps.wo2, 0, kb * 64, 2 * nt, fb);
                    }
                } else {
                    int b, nt, k0, k1;
                    ot_decode(id, b, nt, k0, k1);
                    for (int kb = k0; kb < k1; kb++, rg.next(NST)) {
                        if (kb > k0) d = acquire();
                        const uint32_t fb = bar + 8 * rg.st;
                        mbar_expect(fb, 49152);
                        tma3d(d + 24576, &maps.wo1, 0, 3 * kb * 64, nt, fb);
                        if (kb == k0) for (int j = 0; j < 2; j++) flag_wait(sy + SY_O + 2 * b + j, 32);
                        for (int u = 0; u < 3; u++) tma3d(d + u * 8192, &maps.o2, 0, 2 * (3 * kb + u), 2 * b, fb);
                    }
                }
            }
        }
    } else {
        const int wg = warp >> 2, g = lane >> 2, q = lane & 3;
        Ring rg = {0, 0u};
        bool stores_done = false;
        for (;;) {
            mbar_wait(bar + 8 * rg.st, rg.par());
            const int id = (int)lds32(slot + 4 * rg.st);
            if ((id < 0 || id >= N_P) && !stores_done) {
                bar_sync(5 + wg, 160);
                if ((tid & 127) == 0) sts32(bar + 80 + 4 * wg, ~0u);
                bar_arrive(1 + wg, 160);
                stores_done = true;
                bar_sync(4, 384);
                mbar_arrive_elect(bar + 8 * (NST + 3));
            }
            if (id < 0) break;
            if (tid == 0) TLI(id, 1, gtime());
            if (id < N_P) {
                const int b = id >> 5;
                if (b == 0) proj_tile<2>(sb, bar, rg, wg, id);
                else if (b == 1 || b == NPB - 1) proj_tile<4>(sb, bar, rg, wg, id);
                else proj_tile<6>(sb, bar, rg, wg, id);
            } else if (id < I_OB) {
                if (tid < NCOL) filter_tile(maps.wr, maps.wi, id - I_F, tid);
                __syncwarp();
                mbar_arrive_elect(bar + 8 * (NST + rg.st));
                rg.next(NST);
            } else if (id < I_OT) {
                const int b = (id - I_OB) / 5, nt = (id - I_OB) % 5;
                const size_t o = (size_t)(192 * b + 16 * warp + g) * D_ + nt * 128 + 2 * q;
                float acc[64];
#pragma unroll
                for (int i = 0; i < 64; i++) acc[i] = 0.f;
                for (int kb = 0; kb < 64; kb++, rg.next(NST)) {
                    const int st = rg.st;
                    if (kb) mbar_wait(bar + 8 * st, rg.par());
                    const u64 da = mkdesc(sb + st * STAGE + wg * 8192, 128, 1024), db = mkdesc(sb + st * STAGE + 24576, 8192, 1024) | SW128;
                    wg_fence();
#pragma unroll
                    for (int ks = 0; ks < 4; ks++) wgmma_n128_ss<0, 1>(acc, da + ks * 16, db + ks * 128, 1);
                    wg_commit();
                    wg_wait<0>();
                    mbar_arrive_elect(bar + 8 * (NST + st));
                }
                uint32_t xr[32];
#pragma unroll
                for (int t = 0; t < 32; t++) xr[t] = ldg32(x + o + 8 * (t >> 1) + (t & 1) * 8 * D_);
#pragma unroll
                for (int t = 0; t < 32; t++) *(uint32_t*)(x1 + o + 8 * (t >> 1) + (t & 1) * 8 * D_) = resid(xr[t], acc[2 * t], acc[2 * t + 1]);
            } else {
                int b, nt, k0, k1;
                ot_decode(id, b, nt, k0, k1);
                const size_t o = (size_t)(64 * b + 16 * (warp & 3) + g) * D_ + nt * 64 + 2 * q;
                float acc[32];
                uint32_t xr[16];
#pragma unroll
                for (int t = 0; t < 16; t++) xr[t] = wg == 0 && id < I_SA ? ldg32(x + o + 8 * (t >> 1) + (t & 1) * 8 * D_) : 0;
#pragma unroll
                for (int i = 0; i < 32; i++) acc[i] = 0.f;
                for (int kb = k0; kb < k1; kb++, rg.next(NST)) {
                    const int st = rg.st;
                    if (kb > k0) mbar_wait(bar + 8 * st, rg.par());
                    const u64 da = mkdesc(sb + st * STAGE + wg * 8192, 128, 1024), db = mkdesc(sb + st * STAGE + 24576 + wg * 8192, 0, 1024) | SW128;
                    wg_fence();
#pragma unroll
                    for (int ks = 0; ks < 4; ks++) wgmma_n64_ss<0, 1>(acc, da + ks * 16, db + ks * 128, 1);
                    wg_commit();
                    wg_wait<0>();
                    mbar_arrive_elect(bar + 8 * (NST + st));
                }
                const uint32_t ra = sb + OFF_RED + (tid & 127) * 16;
                if (wg) {
#pragma unroll
                    for (int t = 0; t < 8; t++)
                        sts128(ra + (wg - 1) * 16384 + t * 2048, __float_as_uint(acc[4 * t]), __float_as_uint(acc[4 * t + 1]), __float_as_uint(acc[4 * t + 2]), __float_as_uint(acc[4 * t + 3]));
                }
                bar_sync(4, 384);
                if (wg == 0) {
#pragma unroll
                    for (int t = 0; t < 8; t++) {
                        float u[4], v[4];
                        lds128f(u, ra + t * 2048); lds128f(v, ra + 16384 + t * 2048);
#pragma unroll
                        for (int i = 0; i < 4; i++) acc[4 * t + i] += u[i] + v[i];
                    }
                }
                bar_sync(4, 384);
                if (wg == 0) {
                    if (id < I_SA) {
#pragma unroll
                        for (int t = 0; t < 16; t++) *(uint32_t*)(x1 + o + 8 * (t >> 1) + (t & 1) * 8 * D_) = resid(xr[t], acc[2 * t], acc[2 * t + 1]);
                    } else {
                        float* y = g_yt + (layer * YT_ROWS - (S_ - YT_ROWS)) * D_ + o;
#pragma unroll
                        for (int t = 0; t < 16; t++)
                            asm volatile("red.relaxed.gpu.global.add.v2.f32 [%0],{%1,%2};" ::"l"(y + 8 * (t >> 1) + (t & 1) * 8 * D_), "f"(acc[2 * t]), "f"(acc[2 * t + 1]) : "memory");
                    }
                }
            }
            if (tid == 0) TLI(id, 2, gtime());
        }
    }
}

__global__ void __launch_bounds__(512, 1) side_kernel(const __grid_constant__ Maps maps, const bf16* __restrict__ x, bf16* __restrict__ x1, int layer) {
    extern __shared__ __align__(1024) unsigned char smem[];
    pdl_launch();
    TLS(3 + 5 * layer);
    worker(s2u(smem), maps, x, x1, layer);
    __syncwarp();
    pdl_wait();
    TLE(3 + 5 * layer);
}

constexpr float C5A = 0.30901699437494742f, C5B = -0.80901699437494742f, S5A = 0.95105651629515357f, S5B = 0.58778525229247313f;
template <int SGN> DEV void dft5(const float (&tr)[5], const float (&ti)[5], float (&zr)[5], float (&zi)[5]) {
    const float ar = tr[1] + tr[4], ai = ti[1] + ti[4], br = tr[2] + tr[3], bi = ti[2] + ti[3];
    const float cr = tr[1] - tr[4], ci = ti[1] - ti[4], dr = tr[2] - tr[3], di = ti[2] - ti[3];
    zr[0] = tr[0] + ar + br; zi[0] = ti[0] + ai + bi;
    const float m1r = tr[0] + C5A * ar + C5B * br, m1i = ti[0] + C5A * ai + C5B * bi;
    const float m2r = tr[0] + C5B * ar + C5A * br, m2i = ti[0] + C5B * ai + C5A * bi;
    const float n1r = SGN * (S5A * cr + S5B * dr), n1i = SGN * (S5A * ci + S5B * di);
    const float n2r = SGN * (S5B * cr - S5A * dr), n2i = SGN * (S5B * ci - S5A * di);
    zr[1] = m1r + n1i; zi[1] = m1i - n1r; zr[4] = m1r - n1i; zi[4] = m1i + n1r;
    zr[2] = m2r + n2i; zi[2] = m2i - n2r; zr[3] = m2r - n2i; zi[3] = m2i + n2r;
}
DEV void ln40(float (&v)[40]) {
    float s = 0.f;
#pragma unroll
    for (int i = 0; i < 40; i++) s += v[i];
#pragma unroll
    for (int o = 8; o; o >>= 1) s += __shfl_xor_sync(~0u, s, o);
    const float mean = s * (1.f / D_);
    float q = 0.f;
#pragma unroll
    for (int i = 0; i < 40; i++) { const float d = v[i] - mean; q += d * d; }
#pragma unroll
    for (int o = 8; o; o >>= 1) q += __shfl_xor_sync(~0u, q, o);
    const float mb = bf_round(mean);
    const float inv = 1.f / bf_round(sqrtf(bf_round(bf_round(q * (1.f / D_)) + 1e-5f)));
#pragma unroll
    for (int i = 0; i < 40; i++) v[i] = bf_round(v[i] - mb) * inv;
}
__global__ void __launch_bounds__(256) rowfft_kernel(const bf16* __restrict__ x0, bf16* __restrict__ x, const bf16* __restrict__ Wq,
                                                     const bf16* __restrict__ Wk, const bf16* __restrict__ Wv, int layer) {
    extern __shared__ __align__(1024) unsigned char smem[];
    const uint32_t sb = s2u(smem), sx = sb + 23552, sy = sx + 20480, bar = sy + 40960;
    const int tid = threadIdx.x, lane = tid & 31, q = lane & 3, blk = blockIdx.x, k2 = tid >> 2;
    if (tid == 0) TLI(800 + blk, 0, gtime());
    float twr[5], twi[5];
#pragma unroll
    for (int r = 1; r < 5; r++) { sincospif((float)(r * k2) * (-1.f / 320), &twi[r], &twr[r]); }
    uint32_t f[8][4];
#pragma unroll
    for (int ks = 0; ks < 8; ks++) { const uint4 u = g_f128[ks * 256 + tid]; f[ks][0] = u.x; f[ks][1] = u.y; f[ks][2] = u.z; f[ks][3] = u.w; }
    const bool split = blk * 16 >= S_ - YT_ROWS;
    if (tid == 0) {
        mbar_init(bar, 1);
        asm volatile("fence.mbarrier_init.release.cluster;" ::: "memory");
        mbar_expect(bar, split ? 61440 : 20480);
        if (split) bulk_g2s(sx, x0 + (size_t)blk * 16 * D_, 20480, bar);
    }
    __syncthreads();
    pdl_wait();
    pdl_launch();
    TLS(4 + 5 * layer);
    if (tid == 0) TLI(800 + blk, 1, gtime());
    if (tid == 0) {
        if (split) bulk_g2s(sy, g_yt + (layer * YT_ROWS + blk * 16 - (S_ - YT_ROWS)) * D_, 40960, bar);
        else bulk_g2s(sx, x + (size_t)blk * 16 * D_, 20480, bar);
    }
    mbar_wait(bar, 0);
    {
        const int rho = tid >> 4, j = tid & 15;
        float v[40];
#pragma unroll
        for (int i = 0; i < 5; i++) {
            uint32_t u[4];
            lds128(u, sx + tid * 80 + i * 16);
            if (split) {
                float p[8];
                lds128f(p, sy + tid * 160 + i * 32); lds128f(p + 4, sy + tid * 160 + i * 32 + 16);
#pragma unroll
                for (int k = 0; k < 4; k++) u[k] = resid(u[k], p[2 * k], p[2 * k + 1]);
                sts128(sx + tid * 80 + i * 16, u[0], u[1], u[2], u[3]);
            }
            unpack8(v + 8 * i, make_uint4(u[0], u[1], u[2], u[3]));
        }
        if (layer == 0 && tid < 12) prefetch_bulk((const char*)(tid < 4 ? Wk : tid < 8 ? Wq : Wv) + (blk * 4 + (tid & 3)) * 10240, 10240);
        ln40(v);
        const uint32_t a = sb + ((rho >> 1) & 1) * 2304 + j * 144 + (2 * (rho >> 2) + (rho & 1)) * 16;
#pragma unroll
        for (int r = 0; r < 5; r++)
            sts128(a + r * 4608, pack2(v[r], v[5 + r]), pack2(v[10 + r], v[15 + r]), pack2(v[20 + r], v[25 + r]), pack2(v[30 + r], v[35 + r]));
    }
    fence_async();
    __syncthreads();
    if (tid == 0) TLI(800 + blk, 2, gtime());
    if (tid == 0 && split) { bulk_s2g(x + (size_t)blk * 16 * D_, sx, 20480); bulk_commit(); }
    float acc[40];
    const u64 db = mkdesc(sb, 144, 2304);
    wg_fence();
    wgmma_n80_rs<0, 0>(acc, f[0], db);
#pragma unroll
    for (int ks = 1; ks < 8; ks++) wgmma_n80_rs<1, 0>(acc, f[ks], db + ks * 18);
    wg_commit();
    wg_wait<0>();
    unsigned char* zp = g_z + (blk >> 1) * 128 + ((((blk & 1) * 4 + q) ^ ((blk >> 1) & 7)) << 4);
    uint32_t o[5][4];
#pragma unroll
    for (int u = 0; u < 4; u++) {
        float tr[5], ti[5], zr[5], zi[5];
#pragma unroll
        for (int r = 0; r < 5; r++) {
            const float yr = acc[8 * r + 4 * (u >> 1) + (u & 1)], yi = k2 ? acc[8 * r + 4 * (u >> 1) + 2 + (u & 1)] : 0.f;
            tr[r] = r ? yr * twr[r] - yi * twi[r] : yr;
            ti[r] = r ? yr * twi[r] + yi * twr[r] : yi;
        }
        dft5<1>(tr, ti, zr, zi);
#pragma unroll
        for (int j = 0; j < 5; j++) o[j][u] = pack2(zr[j], j < 3 ? zi[j] : -zi[j]);
    }
#pragma unroll
    for (int j = 0; j < 5; j++)
        if (j < 3 || k2) *(uint4*)(zp + (64 * j + k2) * 8192) = make_uint4(o[j][0], o[j][1], o[j][2], o[j][3]);
    if (k2 == 0) {
#pragma unroll
        for (int u = 0; u < 4; u++) {
            float tr[5], ti[5], zr[5], zi[5];
            const float cr[5] = {1.f, -C5B, C5A, -C5A, C5B}, ci[5] = {0.f, -S5B, -S5A, -S5A, -S5B};
#pragma unroll
            for (int r = 0; r < 5; r++) { const float y = acc[8 * r + 4 * (u >> 1) + 2 + (u & 1)]; tr[r] = y * cr[r]; ti[r] = y * ci[r]; }
            dft5<1>(tr, ti, zr, zi);
            o[0][u] = pack2(zr[0], zi[0]); o[1][u] = pack2(zr[1], zi[1]); o[2][u] = pack2(zr[2], 0.f);
        }
        *(uint4*)(zp + 256 * 8192) = make_uint4(o[0][0], o[0][1], o[0][2], o[0][3]);
        *(uint4*)(zp + 192 * 8192) = make_uint4(o[1][0], o[1][1], o[1][2], o[1][3]);
        *(uint4*)(zp + 320 * 8192) = make_uint4(o[2][0], o[2][1], o[2][2], o[2][3]);
    }
    if (tid == 0) bulk_wait<0>();
    TLE(4 + 5 * layer);
    if (tid == 0) TLI(800 + blk, 3, gtime());
}

constexpr int CF_SMEM = 16384 + 3 * 16384 + 64;
__global__ void __launch_bounds__(384) colfft_kernel(int layer) {
    extern __shared__ __align__(1024) unsigned char smem[];
    const uint32_t sb = s2u(smem), bar = sb + 65536;
    const int tid = threadIdx.x, lane = tid & 31, q = lane & 3, wg = __shfl_sync(~0u, tid >> 7, 0), t = tid & 127, ka = t >> 2;
    const int col = blockIdx.x * 3 + wg;
    const uint32_t d0 = sb + 16384 + wg * 16384, d1 = d0 + 8192;
    if (tid == 0) {
        for (int i = 0; i < 4; i++) mbar_init(bar + 8 * i, 1);
        asm volatile("fence.mbarrier_init.release.cluster;" ::: "memory");
    }
    float twr[8], twi[8];
#pragma unroll
    for (int i = 0; i < 8; i++) sincospif((float)((4 * i + q) * (ka ? ka : -32)) * (1.f / 1024), &twi[i], &twr[i]);
    __syncthreads();
    if (tid == 0) { mbar_expect(bar + 24, 16384); bulk_g2s(sb, g_g32, 16384, bar + 24); }
    uint32_t f[4][4], w[16];
#pragma unroll
    for (int ks = 0; ks < 4; ks++) { const uint4 u = g_f64[ks * 128 + t]; f[ks][0] = u.x; f[ks][1] = u.y; f[ks][2] = u.z; f[ks][3] = u.w; }
#pragma unroll
    for (int i = 0; i < 4; i++) { const uint4 u = *(const uint4*)(g_wt + col * 8192 + i * 2048 + t * 16); w[4 * i] = u.x; w[4 * i + 1] = u.y; w[4 * i + 2] = u.z; w[4 * i + 3] = u.w; }
    pdl_wait();
    pdl_launch();
    TLS(5 + 5 * layer);
    if (t == 0) {
        mbar_expect(bar + 8 * wg, 8192);
        bulk_g2s(d0, g_z + col * 8192, 8192, bar + 8 * wg);
    }
    float acc[32];
    uint32_t a[4][4];
    mbar_wait(bar + 8 * wg, 0);
    {
        const u64 db = mkdesc(d0, 0, 1024) | SW128;
        wg_fence();
        wgmma_n64_rs<0, 1>(acc, f[0], db);
#pragma unroll
        for (int ks = 1; ks < 4; ks++) wgmma_n64_rs<1, 1>(acc, f[ks], db + ks * 128);
        wg_commit();
        wg_wait<0>();
    }
#pragma unroll
    for (int ks = 0; ks < 4; ks++) { const uint4 u = g_f64[512 + ks * 128 + t]; f[ks][0] = u.x; f[ks][1] = u.y; f[ks][2] = u.z; f[ks][3] = u.w; }
#pragma unroll
    for (int i = 0; i < 8; i++) {
        const float c0 = acc[4 * i], c1 = acc[4 * i + 1], c2 = acc[4 * i + 2], c3 = acc[4 * i + 3];
        const float pr = c0 + c3, pi = c1 - c2, nr = ka ? c0 - c3 : c2, ni = ka ? c1 + c2 : c3;
        a[i >> 1][2 * (i & 1)] = ka ? pack2(pr * twr[i] + pi * twi[i], pi * twr[i] - pr * twi[i]) : pack2(c0, c1);
        a[i >> 1][2 * (i & 1) + 1] = pack2(nr * twr[i] - ni * twi[i], ni * twr[i] + nr * twi[i]);
    }
    mbar_wait(bar + 24, 0);
    {
        const u64 db = mkdesc(sb, 128, 1024);
        wg_fence();
        wgmma_n64_rs<0, 0>(acc, a[0], db);
#pragma unroll
        for (int ks = 1; ks < 4; ks++) wgmma_n64_rs<1, 0>(acc, a[ks], db + ks * 16);
        wg_commit();
        wg_wait<0>();
    }
    constexpr float NORM = 1.f / (2048.f * 640.f);
#pragma unroll
    for (int i = 0; i < 16; i++) {
        const float zr = acc[2 * i] * NORM, zi = acc[2 * i + 1] * NORM, wr = bf_lo(w[i]), wi = bf_hi(w[i]);
        a[i >> 2][i & 3] = pack2(zr * wr - zi * wi, zr * wi + zi * wr);
    }
    {
        const u64 db = mkdesc(sb + 8192, 128, 1024);
        wg_fence();
        wgmma_n64_rs<0, 0>(acc, a[0], db);
#pragma unroll
        for (int ks = 1; ks < 4; ks++) wgmma_n64_rs<1, 0>(acc, a[ks], db + ks * 16);
        wg_commit();
        wg_wait<0>();
    }
    const uint32_t row = (t >> 5) * 2048 + (lane & 15) * 128;
#pragma unroll
    for (int i = 0; i < 8; i++) {
        const float c0 = acc[4 * i], c1 = acc[4 * i + 1], c2 = acc[4 * i + 2], c3 = acc[4 * i + 3];
        const float pr = c0 * twr[i] - c1 * twi[i], pi = c1 * twr[i] + c0 * twi[i];
        const float nr = c2 * twr[i] + c3 * twi[i], ni = c3 * twr[i] - c2 * twi[i];
        a[i >> 1][2 * (i & 1)] = ka ? pack2(pr + nr, pi + ni) : pack2(c0, c1);
        a[i >> 1][2 * (i & 1) + 1] = ka ? pack2(ni - pi, pr - nr) : pack2(nr, ni);
    }
#pragma unroll
    for (int i = 0; i < 4; i++) stsm4(d1 + row + (((2 * i + (lane >> 4)) ^ (lane & 7)) << 4), a[i][0], a[i][1], a[i][2], a[i][3]);
    fence_async();
    bar_sync(1 + wg, 128);
    {
        const u64 db = mkdesc(d1, 0, 1024) | SW128;
        wg_fence();
        wgmma_n64_rs<0, 1>(acc, f[0], db);
#pragma unroll
        for (int ks = 1; ks < 4; ks++) wgmma_n64_rs<1, 1>(acc, f[ks], db + ks * 128);
        wg_commit();
        wg_wait<0>();
    }
#pragma unroll
    for (int i = 0; i < 4; i++)
        stsm4(d0 + row + (((2 * i + (lane >> 4)) ^ (lane & 7)) << 4), pack2(acc[8 * i], acc[8 * i + 1]), pack2(acc[8 * i + 2], acc[8 * i + 3]),
              pack2(acc[8 * i + 4], acc[8 * i + 5]), pack2(acc[8 * i + 6], acc[8 * i + 7]));
    fence_async();
    bar_sync(1 + wg, 128);
    if (t == 0) {
        bulk_s2g(g_z + col * 8192, d0, 8192);
        asm volatile("cp.async.bulk.commit_group;" ::: "memory");
        asm volatile("cp.async.bulk.wait_group 0;" ::: "memory");
    }
    TLE(5 + 5 * layer);
}

__global__ void __launch_bounds__(256) rowifft_kernel(const bf16* __restrict__ x, bf16* __restrict__ out, int last) {
    extern __shared__ __align__(1024) unsigned char smem[];
    const uint32_t sb = s2u(smem), sx = sb + 20480, sy = sx + 20480, bar = sy + 16 * 1296;
    const int tid = threadIdx.x, lane = tid & 31, q = lane & 3, blk = blockIdx.x, k2 = tid >> 2, warp = tid >> 5;
    float twr[5], twi[5];
#pragma unroll
    for (int r = 1; r < 5; r++) { sincospif((float)(r * k2) * (1.f / 320), &twi[r], &twr[r]); twr[r] *= 2.f; twi[r] *= 2.f; }
    uint32_t f[8][4];
#pragma unroll
    for (int ks = 0; ks < 8; ks++) { const uint4 u = g_f128[2048 + ks * 256 + tid]; f[ks][0] = u.x; f[ks][1] = u.y; f[ks][2] = u.z; f[ks][3] = u.w; }
    if (tid == 0) {
        mbar_init(bar, 1);
        asm volatile("fence.mbarrier_init.release.cluster;" ::: "memory");
        mbar_expect(bar, 20480);
        bulk_g2s(sx, x + (size_t)blk * 16 * D_, 20480, bar);
    }
    pdl_wait();
    pdl_launch();
    TLS(6 + 5 * last);
    const unsigned char* zp = g_z + (blk >> 1) * 128 + ((((blk & 1) * 4 + q) ^ ((blk >> 1) & 7)) << 4);
    uint4 z[6];
#pragma unroll
    for (int j = 0; j < 5; j++) z[j] = *(const uint4*)(zp + (64 * j + k2) * 8192);
    z[5] = k2 ? make_uint4(0, 0, 0, 0) : *(const uint4*)(zp + 320 * 8192);
    float acc[40];
#pragma unroll
    for (int u = 0; u < 4; u++) {
        float yr[6], yi[6], tr[5], ti[5], zr[5], zi[5];
#pragma unroll
        for (int j = 0; j < 6; j++) { const uint32_t v = u == 0 ? z[j].x : u == 1 ? z[j].y : u == 2 ? z[j].z : z[j].w; yr[j] = bf_lo(v); yi[j] = bf_hi(v); }
#pragma unroll
        for (int j = 0; j < 5; j++) { tr[j] = yr[j]; ti[j] = j < 3 ? yi[j] : -yi[j]; }
        dft5<-1>(tr, ti, zr, zi);
        const float c1[5] = {1.f, C5A, C5B, C5B, C5A}, s1[5] = {0.f, S5A, S5B, -S5B, -S5A};
        const float c2[5] = {1.f, C5B, C5A, C5A, C5B}, s2[5] = {0.f, S5B, -S5A, S5A, -S5B};
        const float c3[5] = {1.f, -C5B, C5A, -C5A, C5B}, s3[5] = {0.f, S5B, S5A, S5A, S5B};
        const float c4[5] = {1.f, -C5A, C5B, -C5B, C5A}, s4[5] = {0.f, S5A, -S5B, -S5B, S5A};
#pragma unroll
        for (int r = 0; r < 5; r++) {
            float er = r ? zr[r] * twr[r] - zi[r] * twi[r] : 2.f * zr[0], ei = r ? zr[r] * twi[r] + zi[r] * twr[r] : 2.f * zi[0];
            if (k2 == 0) {
                er = yr[0] + 2.f * (yr[1] * c1[r] - yi[1] * s1[r] + yr[2] * c2[r] - yi[2] * s2[r]);
                ei = (r & 1 ? -yr[5] : yr[5]) + 2.f * (yr[4] * c3[r] - yi[4] * s3[r] + yr[3] * c4[r] - yi[3] * s4[r]);
            }
            acc[8 * r + 4 * (u >> 1) + (u & 1)] = er;
            acc[8 * r + 4 * (u >> 1) + 2 + (u & 1)] = ei;
        }
    }
#pragma unroll
    for (int r = 0; r < 5; r++)
        stsm4(sb + (2 * warp + ((lane >> 3) & 1)) * 1280 + (2 * r + (lane >> 4)) * 128 + (lane & 7) * 16, pack2(acc[8 * r], acc[8 * r + 1]),
              pack2(acc[8 * r + 2], acc[8 * r + 3]), pack2(acc[8 * r + 4], acc[8 * r + 5]), pack2(acc[8 * r + 6], acc[8 * r + 7]));
    fence_async();
    __syncthreads();
    const u64 db = mkdesc(sb, 1280, 128);
    wg_fence();
    wgmma_n80_rs<0, 1>(acc, f[0], db);
#pragma unroll
    for (int ks = 1; ks < 8; ks++) wgmma_n80_rs<1, 1>(acc, f[ks], db + ks * 160);
    wg_commit();
    wg_wait<0>();
#pragma unroll
    for (int u = 0; u < 4; u++) {
        float e[10];
#pragma unroll
        for (int r = 0; r < 5; r++) { e[r] = acc[8 * r + 4 * (u >> 1) + (u & 1)]; e[5 + r] = acc[8 * r + 4 * (u >> 1) + 2 + (u & 1)]; }
#pragma unroll
        for (int i = 0; i < 5; i++) sts32(sy + (4 * q + u) * 1296 + k2 * 20 + i * 4, pack2(e[2 * i], e[2 * i + 1]));
    }
    __syncthreads();
    const int rho = tid >> 4, j = tid & 15;
    float v[40];
    mbar_wait(bar, 0);
#pragma unroll
    for (int i = 0; i < 5; i++) {
        uint32_t y[4], u[4];
        lds128(y, sy + rho * 1296 + j * 80 + i * 16);
        lds128(u, sx + tid * 80 + i * 16);
#pragma unroll
        for (int k = 0; k < 4; k++) u[k] = pack2(bf_lo(u[k]) + bf_lo(y[k]), bf_hi(u[k]) + bf_hi(y[k]));
        sts128(sx + tid * 80 + i * 16, u[0], u[1], u[2], u[3]);
        unpack8(v + 8 * i, make_uint4(u[0], u[1], u[2], u[3]));
    }
    if (!last) {
        ln40(v);
#pragma unroll
        for (int i = 0; i < 5; i++) {
            const int c = j * 5 + i;
            sts128(sb + (c >> 3) * 2048 + rho * 128 + (((c ^ rho) & 7) << 4), pack2(v[8 * i], v[8 * i + 1]), pack2(v[8 * i + 2], v[8 * i + 3]),
                   pack2(v[8 * i + 4], v[8 * i + 5]), pack2(v[8 * i + 6], v[8 * i + 7]));
        }
    }
    fence_async();
    __syncthreads();
    if (lane == 0) {
        if (warp == 7) bulk_s2g(out + (size_t)blk * 16 * D_, sx, 20480);
        else if (!last && warp < 5) {
            unsigned char* p = g_xn + (blk >> 1) * 40960 + warp * 8192 + (blk & 1) * 2048;
            bulk_s2g(p, sb + warp * 4096, 2048);
            bulk_s2g(p + 4096, sb + warp * 4096 + 2048, 2048);
        }
        bulk_commit();
        bulk_wait<0>();
    }
    TLE(6 + 5 * last);
}

namespace rec {
constexpr int NS = 5;
constexpr int OFF_X = 0;
constexpr int OFF_WO = 81920;
constexpr int OFF_WS = OFF_WO + 65536;
constexpr int OFF_MEMB = OFF_WS + NS * 4096;
constexpr int OFF_VX = OFF_MEMB + 10240;
constexpr int OFF_VM = OFF_VX + 16384;
constexpr int OFF_Q = OFF_VM + 4096;
constexpr int OFF_K = OFF_Q + 10240;
constexpr int OFF_OST = OFF_WO + 49152;
constexpr int OFF_PX = OFF_OST + 8192;
constexpr int OFF_PT = OFF_PX + 2560;
constexpr int OFF_PS = OFF_K + 10240;
constexpr int OFF_OB = OFF_PS + 1280;
constexpr int OFF_MX = OFF_OB + 2048;
constexpr int OFF_BAR = OFF_MX + 64;
constexpr int OFF_PROF = OFF_BAR + 256;
constexpr int SMEM = OFF_PROF + 4096 > wk::SMEM ? OFF_PROF + 4096 : wk::SMEM;
enum { B_XT = 0, B_KX = 2, B_VX = 4, B_XD = 6, B_X1 = 8, B_PXF = 12, B_PXE = 13, B_FIN = 14, B_ST = 15 };
enum { NB_W2 = 0, NB_GO = 1, NB_QK = 2, NB_WIN = 3, NB_ATT = 4, NB_X = 5, NB_PRO = 6, NB_W1 = 7, NB_MEM = 8  , NB_LD = 13  , NB_KX = 15 };
#define NOX 0
#define NW1 9
#define NW1B 0
template <int N> struct IC { static constexpr int value = N; };
template <int N, int I = 0, class F> DEV void static_for(F&& f) { if constexpr (I < N) { f(IC<I>{}); static_for<N, I + 1>(f); } }
constexpr float SM_SCALE = 0.08838834764831845f * 1.4426950408889634f;
}

__global__ void __launch_bounds__(512, 1) rec_kernel(const __grid_constant__ Maps maps, const bf16* __restrict__ x, bf16* __restrict__ x1, const bf16* __restrict__ mem0, const bf16* __restrict__ Wq, const bf16* __restrict__ Wk,
                                                     const bf16* __restrict__ Wv, const bf16* __restrict__ Wo, int layer, int delay, int delay2) {
    using namespace rec;
    extern __shared__ __align__(1024) unsigned char smem[];
    const uint32_t sb = s2u(smem);
    if (blockIdx.x >= 3 * H_) {
        pdl_wait();
        pdl_launch();
        worker(sb, maps, x, x1, layer);
        return;
    }
    const int tid = threadIdx.x, lane = tid & 31, warp = __shfl_sync(~0u, tid >> 5, 0);
    const int g = lane >> 2, q = lane & 3;
    const int h = blockIdx.x / 3;
    const uint32_t bar = sb + OFF_BAR;
    STAMP(2 * layer);
    TLS(2 + 5 * layer);
    if (tid == 0) {
        for (int i = 0; i < 2; i++) {
            mbar_init(bar + 8 * (B_XT + i), 1); mbar_init(bar + 8 * (B_KX + i), 4); mbar_init(bar + 8 * (B_VX + i), 1);
            mbar_init(bar + 8 * (B_XD + i), 8); mbar_init(bar + 8 * (B_X1 + i), 1);
        }
        mbar_init(bar + 8 * B_PXF, 1); mbar_init(bar + 8 * B_PXE, 2); mbar_init(bar + 8 * B_ST, 2);
        mbar_init(bar + 8 * B_FIN, 48);
        sts32(sb + OFF_MX + 32, 0); sts32(sb + OFF_MX + 36, 0);
        asm volatile("fence.mbarrier_init.release.cluster;" ::: "memory");
    }
    asm volatile("barrier.cluster.arrive.aligned; barrier.cluster.wait.aligned;" ::: "memory");
    const bool never = delay < 0;

    if (warp < 8) {
        asm volatile("setmaxnreg.inc.sync.aligned.u32 184;");
        const uint32_t rank = cta_rank();
        const int wg = warp >> 2;
        uint32_t a[40 - NS][4];
        const uint32_t l16 = opaque(sb + lane * 16);
        uint32_t wsa = opaque(sb + OFF_WS + warp * 512 + (lane & 7) * 16 + ((lane >> 3) & 1) * 256 + (lane >> 4) * 128);
        uint32_t dst = opaque(rank < 2 ? sb + OFF_Q + wg * 10240 + (warp & 3) * 256 + (lane & 15) * 16 + (lane >> 4) * 1024
                                       : sb + OFF_VM + warp * 256 + lane * 4);
        int dstep = rank < 2 ? 5120 : 2048;
        uint32_t& sfd = wsa;
        {
            const int t = tid & 127;
            const bf16* src = (rank == 2 ? Wv + wg * 64 : (wg ? Wk : Wq) + rank * 64) + h * E_ + (size_t)(t >> 3) * 4096 + (t & 7) * 8;
            const uint32_t stg = sb + (wg ? OFF_VX : OFF_X + 40960);
            const uint32_t sdst = stg + (t >> 3) * 128 + (((t & 7) ^ ((t >> 3) & 7)) << 4);
            const uint32_t ra = stg + ((lane >> 4) * 8 + (lane & 7)) * 128 + (((2 * (warp & 3) + ((lane >> 3) & 1)) ^ (lane & 7)) << 4);
            auto issue = [&](int rd) {
#pragma unroll
                for (int i = 0; i < 10; i++) cp16(sdst + (rd & 1) * 20480 + i * 2048, src + (size_t)(rd * 160 + i * 16) * 4096);
                cp_commit();
            };
            issue(0); issue(1);
#pragma unroll
            for (int rd = 0; rd < 4; rd++) {
                if (rd < 3) cp_wait<1>(); else cp_wait<0>();
                bar_sync(NB_LD + wg, 128);
#pragma unroll
                for (int i = 0; i < 10; i++) {
                    const int ks = rd * 10 + i;
                    if (ks < NS) {
                        uint32_t f[4];
                        ldsm4t(f, ra + i * 2048);
                        stsm4(wsa + ks * 4096, f[0], f[1], f[2], f[3]);
                    } else ldsm4t(a[ks - NS], ra + (rd & 1) * 20480 + i * 2048);
                }
                if (rd < 2) { bar_sync(NB_LD + wg, 128); issue(rd + 2); }
            }
            fence_async();
            bar_sync(NB_PRO, 288);
        }
        uint32_t xlo = (uint32_t)mkdesc(sb + OFF_X, 0, 0);
        const uint32_t xtog = xlo ^ (uint32_t)mkdesc(sb + OFF_X + 40960, 0, 0);
        uint32_t p8 = 0;
        bar_sync(NB_LD, 288);
        for (int s = -1;; s++) {
            uint32_t t[NS][4];
            if (wg) {
                float acc[16];
                auto xproj = [&](auto K1, auto K0) {
                    const u64 desc = (u64)xlo | (64ull << 32) | SW128, da = mkdesc(sb + OFF_WS + 2048, 128, 256);
                    wg_fence();
#pragma unroll
                    for (int ks = K1.value - 1; ks >= K0.value; ks--) {
                        const u64 db = desc + (ks >> 2) * 256 + (ks & 3) * 2;
                        if (ks == 39) wgmma_n32_rs<0>(acc, a[ks - NS], db);
                        else if (NOX) {}
                        else if (ks < NS) wgmma_n32_ss<1>(acc, da + ks * 256, db);
                        else wgmma_n32_rs<1>(acc, a[ks - NS], db);
                    }
                    wg_commit();
                    wg_wait<0>();
                };
                if (s >= 0 && rank < 2) { fence_async(); bar_arrive(NB_W1, 384); bar_sync(NB_X, 320); }
                bar_sync_if<NB_W1, 352>(s >= 0 && rank == 2);
                if (s == NSEG - 1) break;
                xproj(IC<40>{}, IC<40 - NW1>{});
                bar_sync_if<NB_W2, 256>(s >= 0 && rank < 2);
                if (NW1B > 0) xproj(IC<40 - NW1>{}, IC<40 - NW1 - NW1B>{});
                bar_sync_if<NB_WIN, 256>(s >= 0 && rank == 2);
                xproj(IC<40 - NW1 - NW1B>{}, IC<0>{});
                if (warp == 4 && s >= 0) PROFT(12);
                uint32_t pk[8];
#pragma unroll
                for (int i = 0; i < 8; i++) pk[i] = pack2(acc[2 * i], acc[2 * i + 1]);
                if (rank < 2) {
                    stsm4t(dst + 1024, pk[0], pk[1], pk[2], pk[3]);
                    stsm4t(dst + 3072, pk[4], pk[5], pk[6], pk[7]);
                    bar_arrive(NB_KX, 256);
                } else {
                    const uint32_t la = wsa + (wsa & 256) + (OFF_VX - OFF_WS) + warp * 512 + p8 * 1024;
                    stsm4(la, pk[0], pk[1], pk[2], pk[3]);
                    stsm4(la + 256, pk[4], pk[5], pk[6], pk[7]);
                    fence_async();
                    mbar_arrive_elect(bar + 8 * B_KX + p8);
                }
#pragma unroll
                for (int ks = 0; ks < NS; ks++) ldsm4(t[ks], wsa + ks * 4096);
                xlo ^= xtog;
                if (warp == 4 && s >= 0) PROFT(3);
            } else {
                if (s < 0) {
                } else if (warp == 1) {
                    bar_sync_if<NB_X, 320>(rank < 2);
                    if (s + 1 < NSEG) {
                        const uint32_t xt = bar + 8 * B_XT + (p8 ^ 8);
                        const unsigned char* pn = g_p + (size_t)((s + 1) * H_ + h) * 12288;
                        mbar_expect_elect(xt, (s + 2 < NSEG ? 40960 : 0) + (rank < 2 ? 4096 : 0));
                        if (s + 2 < NSEG) bulk_g2s_elect(sb + OFF_X + (p8 ^ 8) * 5120, g_xn + (s + 2) * 40960, 40960, xt);
                        const int blk = wk::pb_first(s + 1);
                        if (blk >= 0) flag_wait<false, true>(g_sync + layer * SYNC_LAYER + wk::SY_P + blk * H_ + h, 3);
                        if (rank < 2) bulk_g2s_elect(sb + OFF_Q + p8 * 640 + 1024, pn + rank * 4096, 4096, xt);
                        if (rank < 2 || s + 2 < NSEG) bulk_g2s_elect(sb + OFF_VX + p8 * 1024, pn + 8192, 4096, bar + 8 * B_VX + p8);
                    }
                } else if (warp == 2 && rank < 2) {
                    bar_sync(NB_X, 320);
#pragma unroll 1
                    for (int n = s - 1; n < (s + 1 < NSEG ? s : NSEG); n++) {
                        bar_sync_if<NB_W2, 160>(n == s);
                        if (n >= 0) {
                            unsigned char* op = g_o + (size_t)(n * H_ + h) * 8192 + rank * 2048;
                            bulk_s2g_elect(op, sb + OFF_OST + (n & 1) * 4096, 2048);
                            bulk_s2g_elect(op + 4096, sb + OFF_OST + (n & 1) * 4096 + 2048, 2048);
                            bulk_commit();
                            bulk_wait<0>();
                            __syncwarp();
                            st_remote(mapa(sb + OFF_MX + 32 + 4 * rank, 2), n + 1);
                        }
                    }
                }
                if (s == NSEG - 1) break;
                const uint32_t xb = bar + 8 * B_X1 + (p8 ^ 8);
                if (s >= 0) while (!mbar_try(xb, (s >> 1) & 1)) {}
                uint32_t tm = gtime32(), c;
#pragma unroll
                for (int ks = 0; ks < NS; ks++) ldsm4(t[ks], wsa + ks * 4096);
                if (warp == 0 && s >= 0) {
                    uint32_t* hp = g_sync + layer * SYNC_LAYER + 1024 + s * 32;
                    uint32_t& t = tm;
                    if (rank == 0)
                        asm volatile("{.reg .pred p; elect.sync _|p, 0xffffffff; @p red.relaxed.gpu.global.max.u32 [%0+4],%1; @p red.relaxed.gpu.global.add.u32 [%0],1;}"
                                     ::"l"(hp), "r"(t) : "memory");
                    while (gtime32() - t < 150u) {}
                    do asm volatile("ld.relaxed.gpu.global.v2.u32 {%0,%1},[%2];" : "=r"(c), "=r"(t) : "l"(hp) : "memory"); while (__any_sync(~0u, c != H_));
                    while (gtime32() - t < (uint32_t)delay) {}
                    bar_arrive(NB_GO, 160);
                    t = clk();
                    while (clk() - t < (uint32_t)delay2) {}
                    bar_arrive(NB_PRO, 160);
                    while (clk() - t < 2 * (uint32_t)delay2) {}
                    bar_arrive(NB_LD, 160);
                    while (clk() - t < 3 * (uint32_t)delay2) {}
                    bar_arrive(NB_LD + 1, 160);
                }
            }
            float d0[4] = {0.f, 0.f, 0.f, 0.f}, d1[4] = {0.f, 0.f, 0.f, 0.f};
            uint32_t b[20][4];
            bar_sync(NB_MEM, 384);
            lds128(b[0], l16 + OFF_MEMB); lds128(b[1], l16 + OFF_MEMB + 512); lds128(b[2], l16 + OFF_MEMB + 1024);
            const uint32_t xb0 = mapa(bar + 8 * B_X1 + p8, 0), xb1 = mapa(bar + 8 * B_X1 + p8, 1);
            SFENCE();
            float is;
#pragma unroll
            for (int kp = 0; kp < 20; kp++) {
#pragma unroll
                for (int j = 0; j < 2; j++) {
                    const int ks = 2 * kp + j;
                    const uint32_t* f = ks < NS ? t[ks] : a[ks - NS];
                    mma16(j ? d1 : d0, f[0], f[1], f[2], f[3], b[kp][2 * j], b[kp][2 * j + 1]);
                }
                if (kp == 0 && warp == 4) PROFT(16);
                if (kp < 16 && (kp & 3) == 1) bar_sync(NB_MEM + 1 + (kp >> 2), 384);
                if (kp + 3 < 20) lds128(b[kp + 3], l16 + OFF_MEMB + (kp + 3) * 512);
                if (kp == 17) is = lds32f(sb + OFF_MX + 16);
                if (kp < 18) SFENCE();
            }
            const uint32_t p0 = pack2((d0[0] + d1[0]) * is, (d0[1] + d1[1]) * is), p1 = pack2((d0[2] + d1[2]) * is, (d0[3] + d1[3]) * is);
            stsm2t_if(dst, p0, p1, rank < 2);
            bar_arrive_if<NB_QK, 384>(rank < 2);
            if (rank == 2) {
                st_async1(mapa(dst, 0), p0, xb0); st_async1(mapa(dst, 1), p0, xb1);
                st_async1(mapa(dst + 128, 0), p1, xb0); st_async1(mapa(dst + 128, 1), p1, xb1);
                sts32(dst, p0); sts32(dst + 128, p1);
                bar_arrive(NB_QK, 384);
            }
            if (warp == 4) PROFT(17);
            dst += dstep; dstep = -dstep; p8 ^= 8;
        }
    } else if (warp < 12) {
        asm volatile("setmaxnreg.dec.sync.aligned.u32 96;");
        const uint32_t rank = cta_rank();
        const int w = warp - 8;
        uint32_t amax = 0;
#pragma unroll
        for (int it = 0; it < 5; it++) {
            const int kp = it * 4 + w;
            const bf16* p = mem0 + g * D_ + kp * 32 + 2 * q;
            uint32_t b0 = ldg32(p), b1 = ldg32(p + 8), b2 = ldg32(p + 16), b3 = ldg32(p + 24);
            sts128(sb + OFF_MEMB + kp * 512 + lane * 16, b0, b1, b2, b3);
            amax = absmax2(amax, absmax2(absmax2(b0, b1), absmax2(b2, b3)));
        }
        if (tid == 256) { sts32(sb + OFF_MX + 16, 0x3f800000u); sts128(sb + OFF_MX + 48, 0x3f803f80u, 0x3f803f80u, 0x3f803f80u, 0x3f803f80u); }
        bar_arrive(NB_MEM, 384); bar_arrive(NB_MEM + 1, 384); bar_arrive(NB_MEM + 2, 384); bar_arrive(NB_MEM + 3, 384); bar_arrive(NB_MEM + 4, 384);
        {
            const int t = tid & 127, nr = rank == 2 ? 4 : 3;
            for (int r = 0; r < nr; r++) {
                const bf16* src = Wo + (size_t)(h * E_) * D_ + (r < 3 ? 192 * r + 64 * rank : 576);
#pragma unroll
                for (int i = 0; i < 8; i++) {
                    const int e = i * 16 + (t >> 3);
                    cp16(sb + OFF_WO + r * 16384 + e * 128 + (((t & 7) ^ (e & 6)) << 4), src + e * D_ + (t & 7) * 8);
                }
            }
            cp_commit();
            pdl_wait();
            pdl_launch();
            cp_wait<0>();
            bar_sync(NB_ATT, 128);
            for (int r = 0; r < nr; r++) {
                uint32_t u[8][4];
                const uint32_t p = sb + OFF_WO + r * 16384 + 2 * q * 128 + (((2 * w + (g & 1)) ^ (2 * q)) << 4) + (g >> 1) * 4;
#pragma unroll
                for (int ks = 0; ks < 8; ks++)
#pragma unroll
                    for (int j = 0; j < 4; j++) u[ks][j] = lds32(p + (16 * ks + (j & 1) * 8 + (j >> 1)) * 128);
                bar_sync(NB_ATT, 128);
#pragma unroll
                for (int ks = 0; ks < 8; ks++)
                    sts128(sb + OFF_WO + (r * 4 + w) * 4096 + ks * 512 + lane * 16, prmt(u[ks][0], u[ks][2], 0x5410), prmt(u[ks][0], u[ks][2], 0x7632),
                           prmt(u[ks][1], u[ks][3], 0x5410), prmt(u[ks][1], u[ks][3], 0x7632));
            }
        }
        float cw;
        {
            const float4 a = ((const float4*)g_nrm)[lane], c = ((const float4*)g_nrm)[32 + lane];
            float sm = sqrtf((a.x + a.y) + (a.z + a.w)) * sqrtf((c.x + c.y) + (c.z + c.w)), mxv = sm;
#pragma unroll
            for (int o = 16; o; o >>= 1) { sm += __shfl_xor_sync(~0u, sm, o); mxv = fmaxf(mxv, __shfl_xor_sync(~0u, mxv, o)); }
            cw = 26.5f * fmaxf(sm, 8.f * mxv);
        }
        if (w == 0) {
            mbar_expect_elect(bar + 8 * B_X1, rank < 2 ? 3328 : 1280);
            mbar_expect_elect(bar + 8 * B_VX, rank < 2 ? 8192 : 4096);
        }
        {
            const int kind = rank;
            const uint32_t l16 = opaque(sb + lane * 16), lw = opaque(sb + lane * 16 + w * 512);
            const uint32_t pa = opaque(sb + OFF_PS + rank * 512 + lane * 4 + w * 128);
            uint32_t lq = opaque(sb + OFF_Q + (lane & 7) * 16 + ((lane >> 3) & 1) * 256 + (lane >> 4) * 128);
            const uint32_t lv = opaque(sb + OFF_VX + w * 2048 + (lane & 7) * 16 + ((lane >> 3) & 1) * 512 + (lane >> 4) * 128);
            const uint32_t lo = opaque(sb + OFF_WO + w * 4096 + lane * 16);
            uint32_t& sfd = lq;
            const char* rp = (const char*)(g_acc + layer * ACC_LAYER) + (4 * rank + w) * 4096 + opaque((q >> 1) * 1024 + ((q & 1) * 8 + g) * 8);
            const char* lp = (const char*)(g_acc + layer * ACC_LAYER) + opaque(w * 8192 + (2 * (g & 1) + (g >> 2)) * 1024 + (((g >> 1) & 1) * 8 + 2 * q) * 8);
            float isig = 1.f;
            uint32_t kf[8];
            bar_sync_if<NB_KX, 256>(kind < 2);
            ldsm4(kf, l16 + OFF_K + (1 + w) * 1024); ldsm4(kf + 4, l16 + OFF_K + (1 + w) * 1024 + 512);
            for (int s = 0; s < NSEG - 1; s++) {
                const uint32_t pb = s & 1, ph = (s >> 1) & 1, x1 = bar + 8 * (B_X1 + pb);
                sts32(sb + OFF_MX + w * 4, __reduce_max_sync(~0u, max(amax & 0x7fff0000u, (amax << 16) & 0x7fff0000u)));
                const bool vok = mbar_try(bar + 8 * (B_VX + pb), ph, 1);
                const uint32_t va = lv + pb * 8192, vma = lw + OFF_VM + pb * 2048;
                uint32_t wf[8][4], vf[2][2][4], vm[4], one[4];
                auto scores = [&](auto MM) {
                    constexpr int mm = MM.value;
                    uint32_t qf[8], mf[8];
                    const uint32_t qa = lq + pb * 5120, ka = l16 + OFF_K + pb * 5120;
                    const uint32_t pa0 = mapa(pa, rank ^ 1), pa1 = mapa(pa, 2), pa2 = mapa(pa, rank);
                    const uint32_t xb0 = mapa(x1, rank ^ 1), xb1 = mapa(x1, 2), xb2 = mapa(x1, rank);
                    const uint32_t pm = 640 - rank * 384;
                    SFENCE();
                    bar_sync(NB_QK, 384);
                    ldsm4(qf, qa); ldsm4(qf + 4, qa + 512);
                    if (mm) { ldsm4(mf, ka); ldsm4(mf + 4, ka + 512); }
                    SFENCE();
                    float c[8][4];
#pragma unroll
                    for (int i = 0; i < (mm ? 8 : 4); i++) {
                        const uint32_t* f = (i < 4 ? kf : mf) + 2 * (i & 3);
                        c[i][0] = c[i][1] = c[i][2] = c[i][3] = 0.f;
                        mma16(c[i], qf[i & 2 ? 4 : 0], qf[i & 2 ? 5 : 1], qf[i & 2 ? 6 : 2], qf[i & 2 ? 7 : 3], f[0], f[1]);
                    }
                    SFENCE();
                    bar_arrive(NB_W1, 384);
                    const uint32_t y = pack2((c[0][0] + c[1][2]) + (c[2][0] + c[3][2]), (c[0][1] + c[1][3]) + (c[2][1] + c[3][3]));
                    st_async1(pa0, y, xb0); st_async1(pa1, y, xb1);
                    if (mm) {
                        const uint32_t z = pack2((c[4][0] + c[5][2]) + (c[6][0] + c[7][2]), (c[4][1] + c[5][3]) + (c[6][1] + c[7][3]));
                        st_async1(pa0 + pm, z, xb0); st_async1(pa1 + pm, z, xb1); st_async1(pa2 + pm, z, xb2);
                    }
                    st_async1(pa2, y, xb2);
                };
                if (kind == 2) bar_sync(NB_QK, 384);
                else if (w == 3) scores(IC<1>{});
                else scores(IC<0>{});
                if (!vok) mbar_wait(bar + 8 * (B_VX + pb), ph);
#pragma unroll
                for (int t = 0; t < 2; t++)
#pragma unroll
                    for (int j = 0; j < 2; j++) ldsm4(vf[t][j], va + t * 1024 + j * 256);
                float m4[4];
                lds128f(m4, sb + OFF_MX);
                bar_arrive_if<NB_W1, 352>(kind == 2);
                lds128(one, sb + OFF_MX + 48);
                mbar_wait(x1, ph);
                if (w == 0) PROFT(6);
                float sc[10];
                {
                    uint32_t u[4], v[4], m[2];
                    ldsm4(u, l16 + OFF_PS); ldsm4(v, l16 + OFF_PS + 512); ldsm2(m, l16 + OFF_PS + 1024);
                    ldsm4(vm, vma);
                    SFENCE();
                    m4[0] = fmaxf(fmaxf(m4[0], m4[1]), fmaxf(m4[2], m4[3])) * isig;
                    SFENCE();
#pragma unroll
                    for (int i = 0; i < 4; i++) { sc[2 * i] = bf_lo(u[i]) + bf_lo(v[i]); sc[2 * i + 1] = bf_hi(u[i]) + bf_hi(v[i]); }
                    sc[8] = bf_lo(m[0]) + bf_lo(m[1]); sc[9] = bf_hi(m[0]) + bf_hi(m[1]);
                }
                float mx = fmaxf(fmaxf(fmaxf(fmaxf(sc[0], sc[1]), fmaxf(sc[2], sc[3])), fmaxf(fmaxf(sc[4], sc[5]), fmaxf(sc[6], sc[7]))), fmaxf(sc[8], sc[9]));
                auto fetch = [&](int i) { lds128(wf[i], lo + i * 512); };
                {
                    float m1 = __shfl_xor_sync(~0u, mx, 1), m2 = __shfl_xor_sync(~0u, mx, 2), m3 = __shfl_xor_sync(~0u, mx, 3);
                    SFENCE();
#pragma unroll
                    for (int i = 0; i < 4; i++) fetch(i);
                    SFENCE();
                    mx = fmaxf(fmaxf(mx, m1), fmaxf(m2, m3)) * SM_SCALE;
                }
#pragma unroll
                for (int i = 0; i < 10; i++) sc[i] = fmaf(sc[i], SM_SCALE, -mx);
                float o0[4] = {0.f, 0.f, 0.f, 0.f}, o1[4] = {0.f, 0.f, 0.f, 0.f}, rs[4] = {0.f, 0.f, 0.f, 0.f};
                sc[8] = ex2(sc[8]); sc[9] = ex2(sc[9]);
                SFENCE();
                sc[0] = ex2(sc[0]); fetch(4); sc[1] = ex2(sc[1]); fetch(5); sc[2] = ex2(sc[2]); fetch(6);
                SFENCE();
                {
                    const uint32_t p = pack2(sc[8], sc[9]);
                    sc[3] = ex2(sc[3]); fetch(7);
                    mma8(o0, vm[0], vm[1], p);
                    mma8(o1, vm[2], vm[3], p);
                    sc[4] = ex2(sc[4]);
                    mma8(rs, one[0], one[1], p);
                    sc[5] = ex2(sc[5]);
                }
                SFENCE();
                {
                    const uint32_t p0 = pack2(sc[0], sc[1]), p1 = pack2(sc[2], sc[3]);
                    sc[6] = ex2(sc[6]);
                    mma16(o0, vf[0][0][0], vf[0][0][1], vf[0][0][2], vf[0][0][3], p0, p1);
                    SFENCE();
                    sc[7] = ex2(sc[7]);
                    mma16(o1, vf[1][0][0], vf[1][0][1], vf[1][0][2], vf[1][0][3], p0, p1);
                    SFENCE();
                    mma16(rs, one[0], one[1], one[2], one[3], p0, p1);
                    SFENCE();
                }
                {
                    const uint32_t p0 = pack2(sc[4], sc[5]), p1 = pack2(sc[6], sc[7]);
                    mma16(o0, vf[0][1][0], vf[0][1][1], vf[0][1][2], vf[0][1][3], p0, p1);
                    mma16(o1, vf[1][1][0], vf[1][1][1], vf[1][1][2], vf[1][1][3], p0, p1);
                    SFENCE();
                    mma16(rs, one[0], one[1], one[2], one[3], p0, p1);
                }
                const uint32_t e = max((__float_as_uint(cw * fmaxf(m4[0], 1.f)) >> 23) & 255u, 31u);
                SFENCE();
                stsm4t(lw + OFF_OB, pack2(o0[0], o0[1]), pack2(o0[2], o0[3]), pack2(o1[0], o1[1]), pack2(o1[2], o1[3]));
                bar_sync(NB_ATT, 128);
                uint32_t ob[16];
#pragma unroll
                for (int j = 0; j < 4; j++) ldsm4(ob + 4 * j, l16 + OFF_OB + j * 512);
                SFENCE();
                const float sig = __uint_as_float((278u - e) << 23);
                isig = __uint_as_float((e - 30u) << 23);
                const float sg0 = rcp(rs[0]) * sig, sg1 = rcp(rs[1]) * sig;
                SFENCE();
                auto tile = [&](uint32_t next, const char* p, auto LAST) {
                    float c[4][4];
#pragma unroll
                    for (int i = 0; i < 4; i++) c[i][0] = c[i][1] = c[i][2] = c[i][3] = 0.f;
#pragma unroll
                    for (int ks = 0; ks < 8; ks++) {
                        mma16(c[ks & 3], wf[ks][0], wf[ks][1], wf[ks][2], wf[ks][3], ob[2 * ks], ob[2 * ks + 1]);
                        if ((ks & 3) == 3 && !LAST.value) {
                            SFENCE();
#pragma unroll
                            for (int i = ks - 3; i <= ks; i++) lds128(wf[i], next + i * 512);
                        }
                    }
                    SFENCE();
                    if (LAST.value) bar_arrive(NB_WIN, 256);
                    uint32_t v[4];
#pragma unroll
                    for (int i = 0; i < 4; i++)
                        v[i] = (__float_as_uint(fmaf((c[0][i] + c[1][i]) + (c[2][i] + c[3][i]), i & 1 ? sg1 : sg0, 12582912.f)) << 6) + (i < 2);
                    red_add64((u64*)p, v[0], v[2]);
                    red_add64((u64*)(p + 2048), v[1], v[3]);
                };
                tile(lo + 16384, rp, IC<0>{});
                if (w == 0) PROFT(7);
                if (w == 0) GPROF(4, 0);
                tile(lo + 32768, rp + 49152, IC<0>{});
                if (kind == 2) tile(lo + 49152, rp + 98304, IC<0>{});
                tile(0, rp + (kind == 2 ? 28 * 4096 : 98304), IC<1>{});
                if (w == 0) PROFT(8);
                sts32(sb + OFF_MX + 16, __float_as_uint(isig));
                if (w == 0) {
                    if (kind < 2 || s < NSEG - 2) mbar_expect_elect(bar + 8 * (B_VX + (pb ^ 1)), kind < 2 ? 8192 : 4096);
                    mbar_expect_elect(bar + 8 * (B_X1 + (pb ^ 1)), (kind < 2 ? 2048 : 0) + (s < NSEG - 2 ? 1280 : 0));
                }
                u64 y[20];
                const uint32_t kn = lw + OFF_K + 1024 + w * 512 + (pb ^ 1) * 5120;
#pragma unroll
                for (int i = 0; i < 10; i++) {
                    if (i == 0 || i == 2 || i == 4 || i == 7) bar_sync(i == 0 ? NB_GO : i == 2 ? NB_PRO : i == 4 ? NB_LD : NB_LD + 1, 160);
                    ld_acc0(y[2 * i], y[2 * i + 1], lp + (i >> 1) * 32768 + (i & 1) * 4096);
                }
                if (w == 0) PROFT(9);
                uint32_t nretry = 0, b[20];
                bool done[5] = {false, false, false, false, false};
                auto publish = [&](auto FIRST) {
                    uint32_t ok = 32u, late = 32u;
                    static_for<5>([&](auto IT) {
                        constexpr int it = IT.value;
                        if (it == 2) late = and3((uint32_t)y[8], (uint32_t)y[10], (uint32_t)y[12]);
                        else if (it == 3) late &= and3((uint32_t)y[14], (uint32_t)y[16], (uint32_t)y[18]);
                        else ok = and3(ok, (uint32_t)y[4 * it], it == 4 ? late : (uint32_t)y[4 * it + 2]);
                        if (FIRST.value && it < 4) SFENCE();
                        if (it == 2 || it == 3) ok = and3(ok, (uint32_t)y[4 * it], (uint32_t)y[4 * it + 2]);
                        ok = and3(ok, (uint32_t)y[4 * it + 1], (uint32_t)y[4 * it + 3]);
                        const bool all = __all_sync(~0u, ok);
#pragma unroll
                        for (int j = 0; j < 4; j++) {
                            const u64 z = y[4 * it + j];
                            b[4 * it + j] = pack2((float)(int)(uint32_t)z, (float)(int)(uint32_t)(z >> 32));
                        }
                        sts128(lw + OFF_MEMB + it * 2048, b[4 * it], b[4 * it + 1], b[4 * it + 2], b[4 * it + 3]);
                        bar_arrive_if<NB_MEM + it, 384>(all && (FIRST.value || !done[it]));
                        done[it] = all;
                        if (FIRST.value) SFENCE();
                        if (FIRST.value && it == 0) {
                            if (w == 0) PROFT(10);
                            bar_sync_if<NB_KX, 256>(kind < 2);
                            ldsm4(kf, kn); ldsm4(kf + 4, kn + 512);
                            SFENCE();
                        }
                    });
                };
                publish(IC<1>{});
                while (!done[4]) {
                    if (++nretry > SPIN_LIMIT) die();
#pragma unroll
                    for (int i = 0; i < 10; i++) ld_acc(y[2 * i], y[2 * i + 1], lp + (i >> 1) * 32768 + (i & 1) * 4096);
                    publish(IC<0>{});
                }
                if (w == 0) PROFT(11);
                GPROF(w, nretry);
                amax = b[0];
#pragma unroll
                for (int i = 1; i < 19; i += 2) amax = absmax2(amax, absmax2(b[i], b[i + 1]));
                amax = absmax2(amax, b[19]);
                const int adv = (s & 7) == 7 ? 163840 - 896 : 128;
                rp += adv; lp += adv;
            }
        }
        bar_sync(NB_QK, 384);
        if (rank < 2) { bar_arrive(NB_W1, 384); bar_arrive(NB_WIN, 256); } else bar_arrive(NB_W1, 352);
    } else {
        asm volatile("setmaxnreg.dec.sync.aligned.u32 %0;" ::"n"(48));
        const uint32_t rank = cta_rank();
        const int w = warp - 12;
        pdl_wait();
        pdl_launch();
        uint32_t* sy = g_sync + layer * SYNC_LAYER;
        if (w == 1) {
            mbar_expect_elect(bar + 8 * B_XT, 40960);
            bulk_g2s_elect(sb + OFF_X, g_xn, 40960, bar + 8 * B_XT);
            bar_sync(NB_PRO, 288);
            if (rank == 2) mbar_wait(bar + 8 * B_ST, 0);
            else mbar_arrive_remote_elect(mapa(bar + 8 * B_ST, 2));
            mbar_wait(bar + 8 * B_XT, 0);
            bar_arrive(NB_LD, 288);
            mbar_expect_elect(bar + 8 * (B_XT + 1), rank < 2 ? 45056 : 40960);
            bulk_g2s_elect(sb + OFF_X + 40960, g_xn + 40960, 40960, bar + 8 * (B_XT + 1));
            flag_wait<true, true>(sy + wk::SY_P + h, 3);
            if (rank < 2) bulk_g2s_elect(sb + OFF_Q + 1024, g_p + h * 12288 + rank * 4096, 4096, bar + 8 * (B_XT + 1));
            bulk_g2s_elect(sb + OFF_VX, g_p + h * 12288 + 8192, 4096, bar + 8 * B_VX);
        }
        if (rank == 2 && w == 3) {
            for (uint32_t s = 0, n = 0; s < NSEG; s++) {
                uint32_t c[2];
                for (;;) {
                    asm volatile("ld.acquire.cluster.shared::cta.v2.u32 {%0,%1},[%2];" : "=r"(c[0]), "=r"(c[1]) : "r"(sb + OFF_MX + 32) : "memory");
                    if (__all_sync(~0u, min(c[0], c[1]) > s)) break;
                    if (++n > (SPIN_LIMIT << 3)) die();
                    __nanosleep(s < NSEG - 2 ? 400 : 50);
                }
                if (h == 0) TLI(940 + s, 0, gtime());
                if (lane == 0) flag_add(sy + wk::SY_O + s);
                __syncwarp();
            }
        } else if (rank == 2) {
            const char* pf = (const char*)(g_acc + layer * ACC_LAYER) + (5 * h + lane % 5) * 1024;
            if (w == 2 && lane < 20) prefetch_l2(pf + lane / 5 * 128);
            if (w == 2 && lane < 4 && h == 0) prefetch_l2(sy + 1024 + lane * 32);
            for (int s = 0; s < NSEG; s++) {
                const int pb = s & 1, ph = (s >> 1) & 1;
                if (w == 0) {
                    mbar_wait(bar + 8 * (B_KX + pb), ph);
                    const uint32_t va = sb + OFF_VX + pb * 8192 + 4096;
                    bulk_s2s_elect(mapa(va, 0), va, 4096, mapa(bar + 8 * (B_VX + pb), 0));
                    bulk_s2s_elect(mapa(va, 1), va, 4096, mapa(bar + 8 * (B_VX + pb), 1));
                }
                if (w == 1) mbar_wait(bar + 8 * (B_XT + (pb ^ 1)), ((s + 1) >> 1) & 1);
                if (w == 2 && s >= 1) mbar_wait(bar + 8 * (B_XD + (pb ^ 1)), ((s - 1) >> 1) & 1);
                __syncwarp();
                bar_sync(NB_W1, 352);
                if (w == 2 && lane < 5 && s + 4 < NSEG) prefetch_l2(pf + ((s + 4) >> 3) * 163840 + ((s + 4) & 7) * 128);
                if (w == 2 && lane == 5 && h == 0 && s + 4 < NSEG) prefetch_l2(sy + 1024 + (s + 4) * 32);
            }
        } else {
            if (w < 2) sts32(sb + OFF_PT + w * 768 + 640 + lane * 4, 0u);
            const uint32_t px = opaque(sb + OFF_PX + (w & 1) * 1280 + lane * 8);
            const uint32_t pt = opaque(sb + OFF_PT + (w & 1) * 768 + lane * 4);
            uint32_t os = opaque(sb + OFF_OST + (lane >> 4) * 1024 + w * 256 + (lane & 15) * 16);
            uint32_t& sfd = os;
            const int lim = opaque(8 * w + g + 8 - 2 * q);
            for (int s = 0; s < NSEG; s++) {
                const uint32_t pb = s & 1, ph = (s >> 1) & 1;
                if ((w >> 1) != rank) { if (s >= 1) mbar_wait(bar + 8 * B_PXE, pb ^ 1); }
                else if (w & 1) mbar_wait(bar + 8 * (B_XT + (pb ^ 1)), ((s + 1) >> 1) & 1);
                else mbar_expect_elect(bar + 8 * B_PXF, rank ? 2560 : 1536);
                const u64 dq = mkdesc(sb + OFF_Q + pb * 5120 + 1024, 128, 512), dk = mkdesc(sb + OFF_K + pb * 5120, 128, 1024);
                SFENCE();
                bar_sync(NB_W1, 384);
                float c[20];
                wg_fence();
                wgmma_n40_ss<0>(c, dq, dk);
#pragma unroll
                for (int ks = 1; ks < 4; ks++) wgmma_n40_ss<1>(c, dq + ks * 16, dk + ks * 16);
                wg_commit();
                bar_arrive(NB_X, 320);
                wg_wait<0>();
                if ((w >> 1) != rank) {
                    const uint32_t pa = mapa(px, rank ^ 1), pf = mapa(bar + 8 * B_PXF, rank ^ 1);
#pragma unroll
                    for (int nt = 0; nt < 5; nt++)
                        if (nt < 3 || rank == 0) st_async2(pa + nt * 256, __float_as_uint(c[4 * nt]), __float_as_uint(c[4 * nt + 1]), pf);
                    mbar_wait(bar + 8 * (w & 1 ? B_X1 : B_VX) + 8 * pb, ph);
                } else {
                    mbar_wait(bar + 8 * B_PXF, pb);
                    float u[10];
#pragma unroll
                    for (int nt = 0; nt < 5; nt++) lds64f(u[2 * nt], u[2 * nt + 1], px + nt * 256);
#pragma unroll
                    for (int i = 0; i < 10; i++) u[i] = 8 * (i >> 1) + (i & 1) <= lim ? u[i] + c[4 * (i >> 1) + (i & 1)] : -INFINITY;
                    float mx = fmaxf(fmaxf(fmaxf(fmaxf(u[0], u[1]), fmaxf(u[2], u[3])), fmaxf(fmaxf(u[4], u[5]), fmaxf(u[6], u[7]))), fmaxf(u[8], u[9]));
                    const float m1 = __shfl_xor_sync(~0u, mx, 1), m2 = __shfl_xor_sync(~0u, mx, 2), m3 = __shfl_xor_sync(~0u, mx, 3);
                    mx = fmaxf(fmaxf(mx, m1), fmaxf(m2, m3)) * SM_SCALE;
#pragma unroll
                    for (int i = 0; i < 10; i++) u[i] = ex2(fmaf(u[i], SM_SCALE, -mx));
                    float sum = (((u[0] + u[1]) + (u[2] + u[3])) + ((u[4] + u[5]) + (u[6] + u[7]))) + (u[8] + u[9]);
                    const float s1 = __shfl_xor_sync(~0u, sum, 1), s2 = __shfl_xor_sync(~0u, sum, 2), s3 = __shfl_xor_sync(~0u, sum, 3);
                    sum = rcp((sum + s1) + (s2 + s3));
#pragma unroll
                    for (int nt = 0; nt < 5; nt++) sts32(pt + (nt ? nt - 1 : 4) * 128, pack2(u[2 * nt] * sum, u[2 * nt + 1] * sum));
                }
                float acc[2][8];
                const u64 dv = mkdesc(sb + OFF_VX + pb * 8192, 128, 512), dp = mkdesc(sb + OFF_PT, 128, 768);
                const u64 dm = mkdesc(sb + OFF_VM + pb * 2048, 0, 128);
                fence_async();
                bar_sync(NB_WIN, 256);
                wg_fence();
#pragma unroll
                for (int m = 0; m < 2; m++) {
                    wgmma_n16_ss<0>(acc[m], dv + m * 256, dp);
                    wgmma_n16_ss<1>(acc[m], dv + m * 256 + 16, dp + 16);
                    wgmma_n16_ss<1>(acc[m], dm + m * 64, dp + 32);
                }
                wg_commit();
                bar_arrive_if<NB_W2, 256>(s < NSEG - 1);
                wg_wait<0>();
#pragma unroll
                for (int m = 0; m < 2; m++)
                    stsm4t(os + pb * 4096 + m * 2048, pack2(acc[m][0], acc[m][1]), pack2(acc[m][2], acc[m][3]), pack2(acc[m][4], acc[m][5]), pack2(acc[m][6], acc[m][7]));
                fence_async();
                mbar_arrive_remote_elect(mapa(bar + 8 * (B_XD + pb), 2));
                if ((w >> 1) == rank) mbar_arrive_remote_elect(mapa(bar + 8 * B_PXE, rank ^ 1));
            }
            bar_sync(NB_W2, 160);
        }
    }
    __syncwarp();
    if (lane < 3) mbar_arrive_remote(mapa(bar + 8 * B_FIN, lane));
    mbar_wait(bar + 8 * B_FIN, 0);
    TLE(2 + 5 * layer);
}

int g_delay = 1000700, g_layers = 2;

void make_map(CUtensorMap* m, CUtensorMapDataType dt, const void* p, const cuuint64_t* dim, const cuuint64_t* str, const cuuint32_t* box, CUtensorMapSwizzle sw) {
    typedef CUresult (*Fn)(CUtensorMap*, CUtensorMapDataType, cuuint32_t, void*, const cuuint64_t*, const cuuint64_t*, const cuuint32_t*,
                           const cuuint32_t*, CUtensorMapInterleave, CUtensorMapSwizzle, CUtensorMapL2promotion, CUtensorMapFloatOOBfill);
    static Fn fn = nullptr;
    if (!fn) {
        cudaDriverEntryPointQueryResult qr;
        cudaGetDriverEntryPoint("cuTensorMapEncodeTiled", (void**)&fn, cudaEnableDefault, &qr);
    }
    const cuuint32_t es[3] = {1, 1, 1};
    fn(m, dt, 3, (void*)p, dim, str, box, es, CU_TENSOR_MAP_INTERLEAVE_NONE, sw, CU_TENSOR_MAP_L2_PROMOTION_L2_128B, CU_TENSOR_MAP_FLOAT_OOB_FILL_NONE);
}
void map_weight(CUtensorMap* m, const bf16* p, int rows, int cols, int ng, int br = 64) {
    const cuuint64_t dim[3] = {64, (cuuint64_t)rows, (cuuint64_t)cols / 64}, str[2] = {(cuuint64_t)cols * 2, 128};
    const cuuint32_t box[3] = {64, (cuuint32_t)br, (cuuint32_t)ng};
    make_map(m, CU_TENSOR_MAP_DATA_TYPE_BFLOAT16, p, dim, str, box, CU_TENSOR_MAP_SWIZZLE_128B);
}
void map_pieces(CUtensorMap* m, const void* p, int np, int ns) {
    const cuuint64_t dim[3] = {256, (cuuint64_t)np * 2, NSEG}, str[2] = {2048, (cuuint64_t)np * 4096};
    const cuuint32_t box[3] = {256, 2, (cuuint32_t)ns};
    make_map(m, CU_TENSOR_MAP_DATA_TYPE_UINT64, p, dim, str, box, CU_TENSOR_MAP_SWIZZLE_NONE);
}

template <class... P, class... A> void launch(void (*k)(P...), int grid, int block, int smem, int cluster, bool pdl, A... args) {
    cudaLaunchConfig_t c = {};
    c.gridDim = dim3(grid); c.blockDim = dim3(block); c.dynamicSmemBytes = smem; c.stream = cudaStreamPerThread;
    cudaLaunchAttribute at[2];
    int n = 0;
    if (cluster > 1) { at[n].id = cudaLaunchAttributeClusterDimension; at[n].val.clusterDim.x = cluster; at[n].val.clusterDim.y = 1; at[n].val.clusterDim.z = 1; n++; }
    if (pdl) { at[n].id = cudaLaunchAttributeProgrammaticStreamSerialization; at[n].val.programmaticStreamSerializationAllowed = 1; n++; }
    c.attrs = at; c.numAttrs = n;
    cudaLaunchKernelEx(&c, k, args...);
}

int max_clusters() {
    cudaLaunchConfig_t c = {};
    c.gridDim = dim3(3 * H_); c.blockDim = dim3(512); c.dynamicSmemBytes = rec::SMEM;
    cudaLaunchAttribute at[1];
    at[0].id = cudaLaunchAttributeClusterDimension; at[0].val.clusterDim.x = 3; at[0].val.clusterDim.y = 1; at[0].val.clusterDim.z = 1;
    c.attrs = at; c.numAttrs = 1;
    int n = 0;
    cudaOccupancyMaxActiveClusters(&n, rec_kernel, &c);
    return n;
}

}

extern "C" void kernel_launch(void* const* d_in, const int* in_sizes, int n_in, void* d_out, int out_size) {
    const bf16* x = (const bf16*)d_in[0];
    const bf16* mem0 = (const bf16*)d_in[1];
    const bf16* Wq = (const bf16*)d_in[2];
    const bf16* Wk = (const bf16*)d_in[3];
    const bf16* Wv = (const bf16*)d_in[4];
    const bf16* Wo = (const bf16*)d_in[5];
    const bf16* wr = (const bf16*)d_in[8];
    const bf16* wi = (const bf16*)d_in[9];
    cudaFuncSetAttribute(rec_kernel, cudaFuncAttributeMaxDynamicSharedMemorySize, rec::SMEM);
    cudaFuncSetAttribute(side_kernel, cudaFuncAttributeMaxDynamicSharedMemorySize, wk::SMEM);
    cudaFuncSetAttribute(colfft_kernel, cudaFuncAttributeMaxDynamicSharedMemorySize, CF_SMEM);
    Maps maps;
    void *pxn, *po;
    cudaGetSymbolAddress(&pxn, g_xn);
    cudaGetSymbolAddress(&po, g_o);
    map_weight(&maps.wq2, Wq, D_, 4096, 2); map_weight(&maps.wv1, Wv, D_, 4096, 1);
    map_weight(&maps.wo2, Wo, 4096, D_, 2); map_weight(&maps.wo1, Wo, 4096, D_, 1, 192);
    map_pieces(&maps.x6, pxn, 10, 6); map_pieces(&maps.x2, pxn, 10, 2);
    map_pieces(&maps.o6, po, 64, 6); map_pieces(&maps.o2, po, 64, 2);
    bf16 *x1, *x2;
    cudaGetSymbolAddress((void**)&x1, g_x1);
    cudaGetSymbolAddress((void**)&x2, g_x2);
    constexpr int ONE_PER_SM = 120 * 1024;
    cudaFuncSetAttribute(rowfft_kernel, cudaFuncAttributeMaxDynamicSharedMemorySize, ONE_PER_SM);
    cudaFuncSetAttribute(rowifft_kernel, cudaFuncAttributeMaxDynamicSharedMemorySize, ONE_PER_SM);
    static int ncl = 0, nsm = 0;
    if (!ncl) { ncl = max_clusters(); cudaDeviceGetAttribute(&nsm, cudaDevAttrMultiProcessorCount, 0); }
    maps.wr = wr; maps.wi = wi;
    launch(prep_kernel, 128, 512, 0, 1, false, x, Wq, Wk, Wv, Wo);
    for (int layer = 0; layer < g_layers; layer++) {
        const bf16* xin = layer ? x2 : x;
        launch(rec_kernel, 3 * ncl, 512, rec::SMEM, 3, true, maps, xin, x1, mem0, Wq, Wk, Wv, Wo, layer, g_delay % 10000, g_delay / 10000);
        launch(side_kernel, nsm - 3 * (ncl - H_), 512, wk::SMEM, 1, true, maps, xin, x1, layer);
        launch(rowfft_kernel, 128, 256, ONE_PER_SM, 1, true, xin, x1, Wq, Wk, Wv, layer);
        launch(colfft_kernel, 107, 384, CF_SMEM, 1, true, layer);
        launch(rowifft_kernel, 128, 256, ONE_PER_SM, 1, true, (const bf16*)x1, layer ? (bf16*)d_out : x2, layer);
    }
}
```

```cpp
#include <cuda_runtime.h>
#include <cuda_bf16.h>
#include <cuda.h>
#include <stdint.h>

#define DEV __device__ __forceinline__
typedef unsigned long long u64;
typedef __nv_bfloat16 bf16;

namespace {

constexpr int S_ = 2048, D_ = 640, H_ = 32, E_ = 128, NSEG = 64;

__device__ __align__(1024) unsigned char g_xn[S_ * D_ * 2];
__device__ __align__(1024) unsigned char g_o[S_ * H_ * E_ * 2];
constexpr int ACC_LAYER = 32 * 5120;
__device__ __align__(4096) u64 g_acc[2 * ACC_LAYER];
__device__ __align__(16) float g_nrm[256];
__device__ __align__(1024) unsigned char g_p[NSEG * H_ * 3 * 4096];
constexpr int SYNC_LAYER = 1024 + 64 * 32;
__device__ __align__(128) uint32_t g_sync[2 * SYNC_LAYER];
__device__ __align__(1024) bf16 g_x1[S_ * D_];
__device__ __align__(1024) bf16 g_x2[S_ * D_];
constexpr int YT_ROWS = 128;
__device__ __align__(1024) float g_yt[2 * YT_ROWS * D_];
constexpr int NCOL = 321;
__device__ __align__(1024) unsigned char g_z[NCOL * 8192];
__device__ __align__(1024) unsigned char g_wt[NCOL * 8192];
__device__ __align__(1024) uint4 g_f128[2 * 8 * 256];
__device__ __align__(1024) uint4 g_f64[2 * 4 * 128];
__device__ __align__(1024) bf16 g_g32[2 * 4096];
#define TLI(id, k, v)
#define TLS(i)
#define TLE(i)

DEV uint32_t s2u(const void* p) { return (uint32_t)__cvta_generic_to_shared(p); }
DEV uint32_t clk() { uint32_t c; asm volatile("mov.u32 %0,%%clock;" : "=r"(c)::"memory"); return c; }
DEV uint32_t gtime32() { uint32_t t; asm volatile("mov.u32 %0,%%globaltimer_lo;" : "=r"(t)::"memory"); return t; }
DEV uint32_t cta_rank() { uint32_t r; asm volatile("mov.u32 %0,%%cluster_ctarank;" : "=r"(r)); return __shfl_sync(~0u, r, 0); }
DEV uint32_t mapa(uint32_t a, uint32_t r) { uint32_t o; asm("mapa.shared::cluster.u32 %0,%1,%2;" : "=r"(o) : "r"(a), "r"(r)); return o; }
DEV void mbar_init(uint32_t b, uint32_t n) { asm volatile("mbarrier.init.shared::cta.b64 [%0],%1;" ::"r"(b), "r"(n) : "memory"); }
DEV bool mbar_try(uint32_t b, uint32_t par, int) {
    uint32_t ok;
    asm volatile("{.reg .pred p; mbarrier.test_wait.parity.shared::cta.b64 p,[%1],%2; selp.u32 %0,1,0,p;}" : "=r"(ok) : "r"(b), "r"(par) : "memory");
    return ok;
}
DEV bool mbar_try(uint32_t b, uint32_t par) {
    uint32_t ok;
    asm volatile("{.reg .pred p; mbarrier.try_wait.parity.shared::cta.b64 p,[%1],%2; selp.u32 %0,1,0,p;}" : "=r"(ok) : "r"(b), "r"(par) : "memory");
    return ok;
}
constexpr uint32_t SPIN_LIMIT = 1u << 18;
DEV void die() { __trap(); }
DEV void mbar_wait(uint32_t b, uint32_t par) {
    uint32_t n = 0;
    while (!mbar_try(b, par)) if (++n > SPIN_LIMIT) die();
}
DEV uint32_t opaque(uint32_t x) { return __shfl_xor_sync(~0u, x, 0); }
#define SFENCE() asm volatile("{.reg .pred p; setp.ne.u32 p,%1,0; @p mov.u32 %0,%%clock;}" : "+r"(sfd) : "r"((uint32_t)never) : "memory")
DEV void mbar_arrive(uint32_t b) { asm volatile("mbarrier.arrive.shared::cta.b64 _,[%0];" ::"r"(b) : "memory"); }
DEV void mbar_arrive_elect(uint32_t b) { asm volatile("{.reg .pred p; elect.sync _|p, 0xffffffff; @p mbarrier.arrive.shared::cta.b64 _,[%0];}" ::"r"(b) : "memory"); }
DEV void mbar_expect_elect(uint32_t b, uint32_t tx) {
    asm volatile("{.reg .pred p; elect.sync _|p, 0xffffffff; @p mbarrier.arrive.expect_tx.shared::cta.b64 _,[%0],%1;}" ::"r"(b), "r"(tx) : "memory");
}
DEV void mbar_arrive_remote_elect(uint32_t b) { asm volatile("{.reg .pred p; elect.sync _|p, 0xffffffff; @p mbarrier.arrive.shared::cluster.b64 _,[%0];}" ::"r"(b) : "memory"); }
DEV bool elect() { uint32_t r; asm volatile("{.reg .pred p; elect.sync _|p, 0xffffffff; selp.u32 %0,1,0,p;}" : "=r"(r)); return r; }
DEV void mbar_arrive_remote(uint32_t b) { asm volatile("mbarrier.arrive.shared::cluster.b64 _,[%0];" ::"r"(b) : "memory"); }
DEV void mbar_expect(uint32_t b, uint32_t tx) { asm volatile("mbarrier.arrive.expect_tx.shared::cta.b64 _,[%0],%1;" ::"r"(b), "r"(tx) : "memory"); }
DEV void bar_sync(int id, int n) { asm volatile("bar.sync %0,%1;" ::"r"(id), "r"(n) : "memory"); }
DEV void bar_arrive(int id, int n) { asm volatile("bar.arrive %0,%1;" ::"r"(id), "r"(n) : "memory"); }
template <int ID, int N> DEV void bar_arrive_if(bool p) {
    asm volatile("{.reg .pred p; setp.ne.u32 p,%0,0; @p bar.arrive %1,%2;}" ::"r"((uint32_t)p), "n"(ID), "n"(N) : "memory");
}
DEV void prefetch_bulk(const void* p, uint32_t bytes) { asm volatile("cp.async.bulk.prefetch.L2.global [%0],%1;" ::"l"(p), "r"(bytes) : "memory"); }
DEV void prefetch_l2(const void* p) { asm volatile("prefetch.global.L2 [%0];" ::"l"(p) : "memory"); }
template <int ID, int N> DEV void bar_sync_if(bool p) {
    asm volatile("{.reg .pred p; setp.ne.u32 p,%0,0; @p bar.sync %1,%2;}" ::"r"((uint32_t)p), "n"(ID), "n"(N) : "memory");
}
DEV void st_remote(uint32_t a, uint32_t x) { asm volatile("st.relaxed.cluster.shared::cluster.u32 [%0],%1;" ::"r"(a), "r"(x) : "memory"); }
DEV void st_async1(uint32_t a, uint32_t x, uint32_t b) {
    asm volatile("st.async.shared::cluster.mbarrier::complete_tx::bytes.u32 [%0],%1,[%2];" ::"r"(a), "r"(x), "r"(b) : "memory");
}
DEV void st_async2(uint32_t a, uint32_t x, uint32_t y, uint32_t b) {
    asm volatile("st.async.shared::cluster.mbarrier::complete_tx::bytes.v2.u32 [%0],{%1,%2},[%3];" ::"r"(a), "r"(x), "r"(y), "r"(b) : "memory");
}
DEV void st_async4(uint32_t a, uint32_t x, uint32_t y, uint32_t z, uint32_t w, uint32_t b) {
    asm volatile("st.async.shared::cluster.mbarrier::complete_tx::bytes.v4.u32 [%0],{%1,%2,%3,%4},[%5];" ::"r"(a), "r"(x), "r"(y), "r"(z), "r"(w), "r"(b) : "memory");
}
DEV void bulk_g2s(uint32_t dst, const void* src, uint32_t bytes, uint32_t b) {
    asm volatile("cp.async.bulk.shared::cluster.global.mbarrier::complete_tx::bytes [%0],[%1],%2,[%3];" ::"r"(dst), "l"(src), "r"(bytes), "r"(b) : "memory");
}
DEV void bulk_g2s_elect(uint32_t dst, const void* src, uint32_t bytes, uint32_t b) {
    asm volatile("{.reg .pred p; elect.sync _|p, 0xffffffff; @p cp.async.bulk.shared::cluster.global.mbarrier::complete_tx::bytes [%0],[%1],%2,[%3];}"
                 ::"r"(dst), "l"(src), "r"(bytes), "r"(b) : "memory");
}
DEV void bulk_g2s_all3_elect(uint32_t dst, const void* src, uint32_t bytes, uint32_t b) {
    asm volatile("{.reg .pred p; elect.sync _|p, 0xffffffff; @p cp.async.bulk.shared::cluster.global.mbarrier::complete_tx::bytes.multicast::cluster [%0],[%1],%2,[%3],%4;}"
                 ::"r"(dst), "l"(src), "r"(bytes), "r"(b), "h"((unsigned short)7) : "memory");
}
DEV void bulk_s2s_elect(uint32_t dst, uint32_t src, uint32_t bytes, uint32_t b) {
    asm volatile("{.reg .pred p; elect.sync _|p, 0xffffffff; @p cp.async.bulk.shared::cluster.shared::cta.mbarrier::complete_tx::bytes [%0],[%1],%2,[%3];}"
                 ::"r"(dst), "r"(src), "r"(bytes), "r"(b) : "memory");
}
DEV void bulk_s2g_elect(void* dst, uint32_t src, uint32_t bytes) {
    asm volatile("{.reg .pred p; elect.sync _|p, 0xffffffff; @p cp.async.bulk.global.shared::cta.bulk_group [%0],[%1],%2;}" ::"l"(dst), "r"(src), "r"(bytes) : "memory");
}
DEV void bulk_s2s(uint32_t dst, uint32_t src, uint32_t bytes, uint32_t b) {
    asm volatile("cp.async.bulk.shared::cluster.shared::cta.mbarrier::complete_tx::bytes [%0],[%1],%2,[%3];" ::"r"(dst), "r"(src), "r"(bytes), "r"(b) : "memory");
}
DEV void bulk_s2g(void* dst, uint32_t src, uint32_t bytes) {
    asm volatile("cp.async.bulk.global.shared::cta.bulk_group [%0],[%1],%2;" ::"l"(dst), "r"(src), "r"(bytes) : "memory");
}
DEV void tma3d(uint32_t dst, const CUtensorMap* m, int c0, int c1, int c2, uint32_t b) {
    asm volatile("cp.async.bulk.tensor.3d.shared::cluster.global.mbarrier::complete_tx::bytes [%0],[%1,{%3,%4,%5}],[%2];"
                 ::"r"(dst), "l"(m), "r"(b), "r"(c0), "r"(c1), "r"(c2) : "memory");
}
DEV void bulk_commit() { asm volatile("cp.async.bulk.commit_group;" ::: "memory"); }
template <int N> DEV void bulk_wait() { asm volatile("cp.async.bulk.wait_group %0;" ::"n"(N) : "memory"); }
template <int N> DEV void bulk_wait_read() { asm volatile("cp.async.bulk.wait_group.read %0;" ::"n"(N) : "memory"); }
DEV void fence_async_all() { asm volatile("fence.proxy.async;" ::: "memory"); }
DEV void flag_add(uint32_t* p) { fence_async_all(); asm volatile("red.release.gpu.global.add.u32 [%0],1;" ::"l"(p) : "memory"); }
template <bool BOUNDED = true, bool UNIFORM = false> DEV void flag_wait(const uint32_t* p, uint32_t n) {
    uint32_t v, it = 0;
    for (;;) {
        asm volatile("ld.acquire.gpu.global.u32 %0,[%1];" : "=r"(v) : "l"(p) : "memory");
        if (UNIFORM ? __all_sync(~0u, v >= n) : v >= n) break;
        if (BOUNDED && ++it > (SPIN_LIMIT << 3)) die();
        __nanosleep(100);
    }
    fence_async_all();
}
DEV void cp16(uint32_t dst, const void* src) { asm volatile("cp.async.cg.shared.global [%0],[%1],16;" ::"r"(dst), "l"(src) : "memory"); }
DEV void cp_commit() { asm volatile("cp.async.commit_group;" ::: "memory"); }
template <int N> DEV void cp_wait() { asm volatile("cp.async.wait_group %0;" ::"n"(N) : "memory"); }
DEV uint32_t lds32(uint32_t a) { uint32_t x; asm volatile("ld.shared.u32 %0,[%1];" : "=r"(x) : "r"(a) : "memory"); return x; }
DEV void fence_async() { asm volatile("fence.proxy.async.shared::cta;" ::: "memory"); }
DEV uint32_t pack2(float lo, float hi) { uint32_t r; asm("cvt.rn.bf16x2.f32 %0,%1,%2;" : "=r"(r) : "f"(hi), "f"(lo)); return r; }
DEV uint32_t prmt(uint32_t a, uint32_t b, uint32_t s) { uint32_t r; asm("prmt.b32 %0,%1,%2,%3;" : "=r"(r) : "r"(a), "r"(b), "r"(s)); return r; }
DEV float ex2(float x) { float r; asm("ex2.approx.ftz.f32 %0,%1;" : "=f"(r) : "f"(x)); return r; }
DEV float rcp(float x) { float r; asm("rcp.approx.ftz.f32 %0,%1;" : "=f"(r) : "f"(x)); return r; }
DEV void lds128(uint32_t* r, uint32_t a) { asm volatile("ld.shared.v4.u32 {%0,%1,%2,%3},[%4];" : "=r"(r[0]), "=r"(r[1]), "=r"(r[2]), "=r"(r[3]) : "r"(a) : "memory"); }
DEV void lds64(uint32_t* r, uint32_t a) { asm volatile("ld.shared.v2.u32 {%0,%1},[%2];" : "=r"(r[0]), "=r"(r[1]) : "r"(a) : "memory"); }
DEV void lds64f(float& x, float& y, uint32_t a) { asm volatile("ld.shared.v2.f32 {%0,%1},[%2];" : "=f"(x), "=f"(y) : "r"(a) : "memory"); }
DEV void lds128f(float* r, uint32_t a) { asm volatile("ld.shared.v4.f32 {%0,%1,%2,%3},[%4];" : "=f"(r[0]), "=f"(r[1]), "=f"(r[2]), "=f"(r[3]) : "r"(a) : "memory"); }
DEV void sts128(uint32_t a, uint32_t x, uint32_t y, uint32_t z, uint32_t w) { asm volatile("st.shared.v4.u32 [%0],{%1,%2,%3,%4};" ::"r"(a), "r"(x), "r"(y), "r"(z), "r"(w) : "memory"); }
DEV void sts64(uint32_t a, uint32_t x, uint32_t y) { asm volatile("st.shared.v2.u32 [%0],{%1,%2};" ::"r"(a), "r"(x), "r"(y) : "memory"); }
DEV void sts32(uint32_t a, uint32_t x) { asm volatile("st.shared.u32 [%0],%1;" ::"r"(a), "r"(x) : "memory"); }
DEV void ldsm4(uint32_t* r, uint32_t a) { asm volatile("ldmatrix.sync.aligned.m8n8.x4.shared.b16 {%0,%1,%2,%3},[%4];" : "=r"(r[0]), "=r"(r[1]), "=r"(r[2]), "=r"(r[3]) : "r"(a) : "memory"); }
DEV void ldsm4t(uint32_t* r, uint32_t a) { asm volatile("ldmatrix.sync.aligned.m8n8.x4.trans.shared.b16 {%0,%1,%2,%3},[%4];" : "=r"(r[0]), "=r"(r[1]), "=r"(r[2]), "=r"(r[3]) : "r"(a) : "memory"); }
DEV void ldsm2(uint32_t* r, uint32_t a) { asm volatile("ldmatrix.sync.aligned.m8n8.x2.shared.b16 {%0,%1},[%2];" : "=r"(r[0]), "=r"(r[1]) : "r"(a) : "memory"); }
DEV void stsm4t(uint32_t a, uint32_t x, uint32_t y, uint32_t z, uint32_t w) { asm volatile("stmatrix.sync.aligned.m8n8.x4.trans.shared.b16 [%0],{%1,%2,%3,%4};" ::"r"(a), "r"(x), "r"(y), "r"(z), "r"(w) : "memory"); }
DEV void stsm4(uint32_t a, uint32_t x, uint32_t y, uint32_t z, uint32_t w) { asm volatile("stmatrix.sync.aligned.m8n8.x4.shared.b16 [%0],{%1,%2,%3,%4};" ::"r"(a), "r"(x), "r"(y), "r"(z), "r"(w) : "memory"); }
DEV void stsm2(uint32_t a, uint32_t x, uint32_t y) { asm volatile("stmatrix.sync.aligned.m8n8.x2.shared.b16 [%0],{%1,%2};" ::"r"(a), "r"(x), "r"(y) : "memory"); }
DEV void sts128f_if(uint32_t a, const float* v, bool p) {
    asm volatile("{.reg .pred p; setp.ne.u32 p,%5,0; @p st.shared.v4.f32 [%0],{%1,%2,%3,%4};}" ::"r"(a), "f"(v[0]), "f"(v[1]), "f"(v[2]), "f"(v[3]), "r"((uint32_t)p) : "memory");
}
DEV void stsm2t_if(uint32_t a, uint32_t x, uint32_t y, bool p) {
    asm volatile("{.reg .pred p; setp.ne.u32 p,%3,0; @p stmatrix.sync.aligned.m8n8.x2.trans.shared.b16 [%0],{%1,%2};}" ::"r"(a), "r"(x), "r"(y), "r"((uint32_t)p) : "memory");
}
DEV void stsm2t(uint32_t a, uint32_t x, uint32_t y) { asm volatile("stmatrix.sync.aligned.m8n8.x2.trans.shared.b16 [%0],{%1,%2};" ::"r"(a), "r"(x), "r"(y) : "memory"); }
DEV void mma16(float* d, uint32_t a0, uint32_t a1, uint32_t a2, uint32_t a3, uint32_t b0, uint32_t b1) {
    asm volatile("mma.sync.aligned.m16n8k16.row.col.f32.bf16.bf16.f32 {%0,%1,%2,%3},{%4,%5,%6,%7},{%8,%9},{%0,%1,%2,%3};"
                 : "+f"(d[0]), "+f"(d[1]), "+f"(d[2]), "+f"(d[3]) : "r"(a0), "r"(a1), "r"(a2), "r"(a3), "r"(b0), "r"(b1));
}
DEV void mma8(float* d, uint32_t a0, uint32_t a1, uint32_t b0) {
    asm volatile("mma.sync.aligned.m16n8k8.row.col.f32.bf16.bf16.f32 {%0,%1,%2,%3},{%4,%5},{%6},{%0,%1,%2,%3};"
                 : "+f"(d[0]), "+f"(d[1]), "+f"(d[2]), "+f"(d[3]) : "r"(a0), "r"(a1), "r"(b0));
}
DEV u64 mkdesc(uint32_t a, uint32_t lbo, uint32_t sbo) { return (u64)((a & 0x3ffff) >> 4) | ((u64)(lbo >> 4) << 16) | ((u64)(sbo >> 4) << 32); }
constexpr u64 SW128 = 1ull << 62;
DEV void wg_fence() { asm volatile("wgmma.fence.sync.aligned;" ::: "memory"); }
DEV void wg_commit() { asm volatile("wgmma.commit_group.sync.aligned;" ::: "memory"); }
template <int N> DEV void wg_wait() { asm volatile("wgmma.wait_group.sync.aligned %0;" ::"n"(N) : "memory"); }
template <int ACC> DEV void wgmma_n32_rs(float* d, const uint32_t* a, u64 desc) {
    asm volatile("wgmma.mma_async.sync.aligned.m64n32k16.f32.bf16.bf16 {%0,%1,%2,%3,%4,%5,%6,%7,%8,%9,%10,%11,%12,%13,%14,%15},{%16,%17,%18,%19},%20,%21,1,1,0;"
                 : "+f"(d[0]), "+f"(d[1]), "+f"(d[2]), "+f"(d[3]), "+f"(d[4]), "+f"(d[5]), "+f"(d[6]), "+f"(d[7]),
                   "+f"(d[8]), "+f"(d[9]), "+f"(d[10]), "+f"(d[11]), "+f"(d[12]), "+f"(d[13]), "+f"(d[14]), "+f"(d[15])
                 : "r"(a[0]), "r"(a[1]), "r"(a[2]), "r"(a[3]), "l"(desc), "n"(ACC));
}
template <int ACC> DEV void wgmma_n32_ss(float* d, u64 da, u64 desc) {
    asm volatile("wgmma.mma_async.sync.aligned.m64n32k16.f32.bf16.bf16 {%0,%1,%2,%3,%4,%5,%6,%7,%8,%9,%10,%11,%12,%13,%14,%15},%16,%17,%18,1,1,0,0;"
                 : "+f"(d[0]), "+f"(d[1]), "+f"(d[2]), "+f"(d[3]), "+f"(d[4]), "+f"(d[5]), "+f"(d[6]), "+f"(d[7]),
                   "+f"(d[8]), "+f"(d[9]), "+f"(d[10]), "+f"(d[11]), "+f"(d[12]), "+f"(d[13]), "+f"(d[14]), "+f"(d[15])
                 : "l"(da), "l"(desc), "n"(ACC));
}
template <int ACC> DEV void wgmma_n16_ss(float* d, u64 da, u64 desc) {
    asm volatile("wgmma.mma_async.sync.aligned.m64n16k16.f32.bf16.bf16 {%0,%1,%2,%3,%4,%5,%6,%7},%8,%9,%10,1,1,0,0;"
                 : "+f"(d[0]), "+f"(d[1]), "+f"(d[2]), "+f"(d[3]), "+f"(d[4]), "+f"(d[5]), "+f"(d[6]), "+f"(d[7])
                 : "l"(da), "l"(desc), "n"(ACC));
}
#define ACC8(o) "+f"(d[o]), "+f"(d[o + 1]), "+f"(d[o + 2]), "+f"(d[o + 3]), "+f"(d[o + 4]), "+f"(d[o + 5]), "+f"(d[o + 6]), "+f"(d[o + 7])
template <int ACC, int TB> DEV void wgmma_n64_rs(float* d, const uint32_t* a, u64 desc) {
    asm volatile("wgmma.mma_async.sync.aligned.m64n64k16.f32.bf16.bf16 {%0,%1,%2,%3,%4,%5,%6,%7,%8,%9,%10,%11,%12,%13,%14,%15,"
                 "%16,%17,%18,%19,%20,%21,%22,%23,%24,%25,%26,%27,%28,%29,%30,%31},{%32,%33,%34,%35},%36,%37,1,1,%38;"
                 : ACC8(0), ACC8(8), ACC8(16), ACC8(24) : "r"(a[0]), "r"(a[1]), "r"(a[2]), "r"(a[3]), "l"(desc), "n"(ACC), "n"(TB));
}
template <int ACC, int TB> DEV void wgmma_n80_rs(float* d, const uint32_t* a, u64 desc) {
    asm volatile("wgmma.mma_async.sync.aligned.m64n80k16.f32.bf16.bf16 {%0,%1,%2,%3,%4,%5,%6,%7,%8,%9,%10,%11,%12,%13,%14,%15,"
                 "%16,%17,%18,%19,%20,%21,%22,%23,%24,%25,%26,%27,%28,%29,%30,%31,%32,%33,%34,%35,%36,%37,%38,%39},{%40,%41,%42,%43},%44,%45,1,1,%46;"
                 : ACC8(0), ACC8(8), ACC8(16), ACC8(24), ACC8(32) : "r"(a[0]), "r"(a[1]), "r"(a[2]), "r"(a[3]), "l"(desc), "n"(ACC), "n"(TB));
}
template <int TA, int TB> DEV void wgmma_n64_ss(float* d, u64 da, u64 db, int acc) {
    asm volatile("{.reg .pred p; setp.ne.b32 p,%34,0; wgmma.mma_async.sync.aligned.m64n64k16.f32.bf16.bf16 {%0,%1,%2,%3,%4,%5,%6,%7,%8,%9,%10,%11,%12,%13,%14,%15,%16,%17,%18,%19,%20,%21,%22,%23,%24,%25,%26,%27,%28,%29,%30,%31},%32,%33,p,1,1,%35,%36;}"
                 : ACC8(0), ACC8(8), ACC8(16), ACC8(24) : "l"(da), "l"(db), "r"(acc), "n"(TA), "n"(TB));
}
template <int TA, int TB> DEV void wgmma_n128_ss(float* d, u64 da, u64 db, int acc) {
    asm volatile("{.reg .pred p; setp.ne.b32 p,%66,0; wgmma.mma_async.sync.aligned.m64n128k16.f32.bf16.bf16 {%0,%1,%2,%3,%4,%5,%6,%7,%8,%9,%10,%11,%12,%13,%14,%15,%16,%17,%18,%19,%20,%21,%22,%23,%24,%25,%26,%27,%28,%29,%30,%31,%32,%33,%34,%35,%36,%37,%38,%39,%40,%41,%42,%43,%44,%45,%46,%47,%48,%49,%50,%51,%52,%53,%54,%55,%56,%57,%58,%59,%60,%61,%62,%63},%64,%65,p,1,1,%67,%68;}"
                 : ACC8(0), ACC8(8), ACC8(16), ACC8(24), ACC8(32), ACC8(40), ACC8(48), ACC8(56) : "l"(da), "l"(db), "r"(acc), "n"(TA), "n"(TB));
}
template <int TA, int TB> DEV void wgmma_n192_ss(float* d, u64 da, u64 db, int acc) {
    asm volatile("{.reg .pred p; setp.ne.b32 p,%98,0; wgmma.mma_async.sync.aligned.m64n192k16.f32.bf16.bf16 {%0,%1,%2,%3,%4,%5,%6,%7,%8,%9,%10,%11,%12,%13,%14,%15,%16,%17,%18,%19,%20,%21,%22,%23,%24,%25,%26,%27,%28,%29,%30,%31,%32,%33,%34,%35,%36,%37,%38,%39,%40,%41,%42,%43,%44,%45,%46,%47,%48,%49,%50,%51,%52,%53,%54,%55,%56,%57,%58,%59,%60,%61,%62,%63,%64,%65,%66,%67,%68,%69,%70,%71,%72,%73,%74,%75,%76,%77,%78,%79,%80,%81,%82,%83,%84,%85,%86,%87,%88,%89,%90,%91,%92,%93,%94,%95},%96,%97,p,1,1,%99,%100;}"
                 : ACC8(0), ACC8(8), ACC8(16), ACC8(24), ACC8(32), ACC8(40), ACC8(48), ACC8(56), ACC8(64), ACC8(72), ACC8(80), ACC8(88) : "l"(da), "l"(db), "r"(acc), "n"(TA), "n"(TB));
}
template <int ACC> DEV void wgmma_n40_ss(float* d, u64 da, u64 desc) {
    asm volatile("wgmma.mma_async.sync.aligned.m64n40k16.f32.bf16.bf16 {%0,%1,%2,%3,%4,%5,%6,%7,%8,%9,%10,%11,%12,%13,%14,%15,%16,%17,%18,%19},%20,%21,%22,1,1,0,0;"
                 : ACC8(0), ACC8(8), "+f"(d[16]), "+f"(d[17]), "+f"(d[18]), "+f"(d[19]) : "l"(da), "l"(desc), "n"(ACC));
}
DEV void pdl_wait() { asm volatile("griddepcontrol.wait;" ::: "memory"); }
DEV void pdl_launch() { asm volatile("griddepcontrol.launch_dependents;" ::: "memory"); }
DEV uint32_t ldg32(const void* p) { uint32_t v; asm volatile("ld.global.nc.u32 %0,[%1];" : "=r"(v) : "l"(p)); return v; }
DEV void ld_acc(u64& a, u64& b, const void* p) {
    const uint32_t done = (uint32_t)a & (uint32_t)b & 32u;
    asm volatile("{.reg .pred p; setp.eq.u32 p,%3,0;\n"
                 "@p ld.relaxed.gpu.global.v2.u64 {%0,%1},[%2];}" : "+l"(a), "+l"(b) : "l"(p), "r"(done) : "memory");
}
DEV void ld_acc0(u64& a, u64& b, const void* p) {
    asm volatile("ld.relaxed.gpu.global.v2.u64 {%0,%1},[%2];" : "=l"(a), "=l"(b) : "l"(p) : "memory");
}
DEV uint32_t and3(uint32_t a, uint32_t b, uint32_t c) { uint32_t r; asm volatile("lop3.b32 %0,%1,%2,%3,0x80;" : "=r"(r) : "r"(a), "r"(b), "r"(c)); return r; }
DEV uint32_t absmax2(uint32_t a, uint32_t b) { uint32_t r; asm("max.xorsign.abs.bf16x2 %0,%1,%2;" : "=r"(r) : "r"(a), "r"(b)); return r; }
DEV float lds32f(uint32_t a) { float x; asm volatile("ld.shared.f32 %0,[%1];" : "=f"(x) : "r"(a) : "memory"); return x; }
DEV void red_add64(u64* p, uint32_t lo, uint32_t hi) {
    asm volatile("{.reg .b64 v; mov.b64 v,{%1,%2}; red.relaxed.gpu.global.add.u64 [%0],v;}" ::"l"(p), "r"(lo), "r"(hi) : "memory");
}
DEV float bf_round(float x) { return __bfloat162float(__float2bfloat16_rn(x)); }
DEV float bf_lo(uint32_t u) { return __uint_as_float(u << 16); }
DEV float bf_hi(uint32_t u) { return __uint_as_float(u & 0xffff0000u); }

#define GPROF(i, n)
#define PROFT(i)
#define STAMP(i)

DEV void unpack8(float* v, uint4 u) {
    v[0] = bf_lo(u.x); v[1] = bf_hi(u.x); v[2] = bf_lo(u.y); v[3] = bf_hi(u.y);
    v[4] = bf_lo(u.z); v[5] = bf_hi(u.z); v[6] = bf_lo(u.w); v[7] = bf_hi(u.w);
}
DEV int xn_off(int row, int chunk) { return (row >> 5) * 40960 + (chunk >> 3) * 4096 + (row & 31) * 128 + (((chunk ^ row) & 7) << 4); }

DEV void ln_row(float (&v)[3][8], int lane) {
    float s = 0.f;
#pragma unroll
    for (int c = 0; c < 3; c++)
#pragma unroll
        for (int j = 0; j < 8; j++) s += v[c][j];
#pragma unroll
    for (int o = 16; o; o >>= 1) s += __shfl_xor_sync(~0u, s, o);
    float mean = s * (1.f / D_), q = 0.f;
#pragma unroll
    for (int c = 0; c < 3; c++)
        if (c < 2 || lane < 16)
#pragma unroll
            for (int j = 0; j < 8; j++) { float d = v[c][j] - mean; q += d * d; }
#pragma unroll
    for (int o = 16; o; o >>= 1) q += __shfl_xor_sync(~0u, q, o);
    float mb = bf_round(mean);
    float inv = 1.f / bf_round(sqrtf(bf_round(bf_round(q * (1.f / D_)) + 1e-5f)));
#pragma unroll
    for (int c = 0; c < 3; c++)
#pragma unroll
        for (int j = 0; j < 8; j++) v[c][j] = bf_round(v[c][j] - mb) * inv;
}

__host__ __device__ constexpr int col_freq(int c) {
    return c == 320 ? 320 : c < 192 ? (c >> 6) * 128 + (c & 63) : c == 192 ? 192 : c < 256 ? 448 - c : c == 256 ? 64 : 384 - c;
}
DEV float rdft(int n, int k, int sn, int N) {
    float s, c;
    sincospif((float)((n * k) & (N - 1)) * (2.f / N), &s, &c);
    return !sn ? c : k ? s : (n & 1 ? -1.f : 1.f);
}

__global__ void __launch_bounds__(512) prep_kernel(const bf16* __restrict__ x, const bf16* __restrict__ Wq, const bf16* __restrict__ Wk,
                                                   const bf16* __restrict__ Wv, const bf16* __restrict__ Wo) {
    __shared__ float red[32], col[4][640];
    const int tid = threadIdx.x, lane = tid & 31, warp = tid >> 5, b = blockIdx.x, row = b * 16 + warp;
    TLS(0);
    pdl_launch();
    uint4 ux[3], uv[5], uo[8];
#pragma unroll
    for (int c = 0; c < 3; c++) ux[c] = c < 2 || lane < 16 ? *(const uint4*)(x + row * D_ + (c * 32 + lane) * 8) : make_uint4(0, 0, 0, 0);
#pragma unroll
    for (int i = 0; i < 5; i++) uv[i] = *(const uint4*)(Wv + (size_t)((b & 3) * 160 + i * 32 + (tid >> 4)) * 4096 + (b >> 2) * E_ + (tid & 15) * 8);
    if (tid < 320) {
#pragma unroll
        for (int r = 0; r < 8; r++) uo[r] = *(const uint4*)(Wo + (size_t)(b * 32 + tid / 80 * 8 + r) * D_ + tid % 80 * 8);
    }
    if (tid >= 504) prefetch_bulk((const char*)(tid & 4 ? Wk : Wq) + (b * 4 + (tid & 3)) * 10240, 10240);
    if (b < 3) ((uint4*)g_sync)[b * 512 + tid] = make_uint4(0, 0, 0, 0);
    for (int i = b * 512 + tid; i < ACC_LAYER; i += 128 * 512) ((uint4*)g_acc)[i] = make_uint4(0, 0, 0, 0);
    if (tid < 2 * YT_ROWS * D_ / 4 / 128) ((uint4*)g_yt)[b * (2 * YT_ROWS * D_ / 4 / 128) + tid] = make_uint4(0, 0, 0, 0);
    const int gid = tid < 104 ? b * 104 + tid : 1 << 20;
    if (gid < 4096) {
        const int inv = gid >> 11, ks = (gid >> 8) & 7, t = gid & 255, g = (t & 31) >> 2, q = t & 3, tile = t >> 5;
        uint32_t v[4];
#pragma unroll
        for (int j = 0; j < 4; j++) {
            float x[2];
#pragma unroll
            for (int u = 0; u < 2; u++) {
                const int m = inv ? 16 * tile + 2 * g + (j & 1) : 16 * ks + 8 * (j >> 1) + 2 * q + u;
                const int k2 = inv ? 8 * ks + 2 * q + u : 8 * tile + g, sn = inv ? j >> 1 : j & 1;
                x[u] = rdft(m, k2, sn, 128);
                if (sn && k2) x[u] = -x[u];
            }
            v[j] = pack2(x[0], x[1]);
        }
        g_f128[gid] = make_uint4(v[0], v[1], v[2], v[3]);
    } else if (gid < 5120) {
        const int id = gid - 4096, inv = id >> 9, ks = (id >> 7) & 3, t = id & 127, g = (t & 31) >> 2, q = t & 3, tile = t >> 5;
        uint32_t v[4];
#pragma unroll
        for (int j = 0; j < 4; j++) {
            float x[2];
#pragma unroll
            for (int u = 0; u < 2; u++) {
                const int a = inv ? 16 * tile + g + 8 * (j & 1) : 16 * ks + 8 * (j >> 1) + 2 * q + u;
                const int ka = inv ? 8 * ks + 2 * q + u : 8 * tile + g, sn = inv ? j >> 1 : j & 1;
                x[u] = rdft(a, ka, sn, 64);
            }
            v[j] = pack2(x[0], x[1]);
        }
        g_f64[id] = make_uint4(v[0], v[1], v[2], v[3]);
    } else if (gid < 5120 + 8192) {
        const int id = gid - 5120, inv = id >> 12, n = ((id >> 9) & 7) * 8 + ((id >> 3) & 7), k = ((id >> 6) & 7) * 8 + (id & 7);
        float s, c;
        sincospif((float)(((n >> 1) * (k >> 1)) & 31) * (1.f / 16), &s, &c);
        if (inv) s = -s;
        g_g32[id] = __float2bfloat16_rn((n & 1) == (k & 1) ? c : (k & 1) ? s : -s);
    }
    {
        float v[3][8];
#pragma unroll
        for (int c = 0; c < 3; c++) unpack8(v[c], ux[c]);
        ln_row(v, lane);
#pragma unroll
        for (int c = 0; c < 3; c++)
            if (c < 2 || lane < 16)
                *(uint4*)(g_xn + xn_off(row, c * 32 + lane)) =
                    make_uint4(pack2(v[c][0], v[c][1]), pack2(v[c][2], v[c][3]), pack2(v[c][4], v[c][5]), pack2(v[c][6], v[c][7]));
    }
    float sv = 0.f;
#pragma unroll
    for (int i = 0; i < 5; i++) {
        float w[8];
        unpack8(w, uv[i]);
#pragma unroll
        for (int j = 0; j < 8; j++) sv += w[j] * w[j];
    }
    if (tid < 320) {
        float a[8] = {0.f, 0.f, 0.f, 0.f, 0.f, 0.f, 0.f, 0.f};
#pragma unroll
        for (int r = 0; r < 8; r++) {
            float w[8];
            unpack8(w, uo[r]);
#pragma unroll
            for (int j = 0; j < 8; j++) a[j] += w[j] * w[j];
        }
#pragma unroll
        for (int j = 0; j < 8; j++) col[tid / 80][tid % 80 * 8 + j] = a[j];
    }
    __syncthreads();
    float so = (col[0][tid] + col[1][tid]) + (col[2][tid] + col[3][tid]);
    if (tid < 128) so = fmaxf(so, (col[0][512 + tid] + col[1][512 + tid]) + (col[2][512 + tid] + col[3][512 + tid]));
#pragma unroll
    for (int o = 16; o; o >>= 1) { sv += __shfl_xor_sync(~0u, sv, o); so = fmaxf(so, __shfl_xor_sync(~0u, so, o)); }
    if (lane == 0) { red[warp] = sv; red[16 + warp] = so; }
    __syncthreads();
    if (tid == 0) {
        float a = 0.f, c = 0.f;
        for (int i = 0; i < 16; i++) { a += red[i]; c = fmaxf(c, red[16 + i]); }
        g_nrm[b] = a; g_nrm[128 + b] = c;
    }
    TLE(0);
}

DEV void filter_tile(const bf16* __restrict__ wr, const bf16* __restrict__ wi, int ka, int c) {
    const int kn = ka ? 2048 - ka : 32, kc = col_freq(c);
    const unsigned short* pr = (const unsigned short*)wr + kc;
    const unsigned short* pi = (const unsigned short*)wi + kc;
#pragma unroll 1
    for (int i = 0; i < 4; i += 2) {
        unsigned short a[32], b[32];
#pragma unroll
        for (int n = 0; n < 32; n++) {
            const int k = ((n & 1 ? kn : ka) + 64 * (4 * (2 * (i + (n >> 4)) + ((n >> 1) & 1)) + ((n >> 2) & 3))) & 2047;
            a[n] = __ldg(pr + k * NCOL); b[n] = __ldg(pi + k * NCOL);
        }
#pragma unroll
        for (int n = 0; n < 32; n += 4)
            *(uint4*)(g_wt + c * 8192 + (i + (n >> 4)) * 2048 + (ka * 4 + ((n >> 2) & 3)) * 16) =
                make_uint4(a[n] | ((uint32_t)b[n] << 16), a[n + 1] | ((uint32_t)b[n + 1] << 16), a[n + 2] | ((uint32_t)b[n + 2] << 16), a[n + 3] | ((uint32_t)b[n + 3] << 16));
    }
}

namespace wk {
constexpr int STAGE = 49152, NST = 4, OFF_OUT = 3 * STAGE, OFF_RED = 4 * STAGE, OFF_BAR = OFF_RED + 32768, SMEM = OFF_BAR + 128;
constexpr int NPB = 12;
DEV int pb_first(int n) { return n == 0 ? 0 : n == 2 ? 1 : n % 6 == 0 ? n / 6 + 1 : -1; }
__host__ __device__ constexpr int pb_start(int b) { return b == 0 ? 0 : b == 1 ? 2 : b < NPB ? 6 * b - 6 : 64; }
#define NOB 7
#define SPLIT_A 3
#define SPLIT_B 11
constexpr int N_P = NPB * H_, I_F = N_P, I_OB = I_F + 32, I_OT = I_OB + NOB * 5, I_SA = I_OT + (30 - 3 * NOB) * 10;
constexpr int I_SB = I_SA + 10 * SPLIT_A, N_ITEMS = I_SB + 10 * SPLIT_B;
DEV void ot_decode(int id, int& b, int& nt, int& k0, int& k1) {
    const int base = id < I_SA ? I_OT : id < I_SB ? I_SA : I_SB, j = (id - base) / 10;
    nt = (id - base) % 10;
    if (id < I_SA) { b = 3 * NOB + j; k0 = 0; k1 = 22; }
    else if (id < I_SB) { b = 30; k0 = 22 * j / SPLIT_A; k1 = 22 * (j + 1) / SPLIT_A; }
    else { b = 31; k0 = 22 * j / SPLIT_B; k1 = 22 * (j + 1) / SPLIT_B; }
}
enum { SY_TICKET = 0, SY_O = 32, SY_P = 128 };
}
struct Ring {
    int st; uint32_t ph;
    DEV uint32_t par() const { return (ph >> st) & 1; }
    DEV void next(int n) { ph ^= 1u << st; st = st + 1 >= n ? 0 : st + 1; }
};
struct Maps { CUtensorMap wq2, wv1, wo2, wo1, x6, x2, o6, o2; const bf16 *wr, *wi; };

template <int NSG> DEV void proj_tile(uint32_t sb, uint32_t bar, Ring& rg, int wg, int id) {
    using namespace wk;
    float acc[NSG * 16];
#pragma unroll
    for (int i = 0; i < NSG * 16; i++) acc[i] = 0.f;
    const int lane = threadIdx.x & 31, ww = (threadIdx.x >> 5) & 3;
    for (int kb = 0; kb < 10; kb++, rg.next(3)) {
        const int st = rg.st;
        if (kb) mbar_wait(bar + 8 * st, rg.par());
        const u64 da = mkdesc(sb + st * STAGE + wg * 8192, 0, 1024) | SW128, db = mkdesc(sb + st * STAGE + 24576, 0, 1024) | SW128;
        wg_fence();
#pragma unroll
        for (int ks = 0; ks < 4; ks++) {
            if (NSG == 2) wgmma_n64_ss<1, 0>(acc, da + ks * 128, db + ks * 2, 1);
            if (NSG == 4) wgmma_n128_ss<1, 0>(acc, da + ks * 128, db + ks * 2, 1);
            if (NSG == 6) wgmma_n192_ss<1, 0>(acc, da + ks * 128, db + ks * 2, 1);
        }
        wg_commit();
        wg_wait<0>();
        mbar_arrive_elect(bar + 8 * (NST + st));
    }
    const uint32_t out = sb + OFF_OUT + wg * 24576;
    bar_sync(5 + wg, 160);
    const uint32_t la = out + (wg < 2 ? (lane >> 4) * 1024 + ww * 256 + (lane & 15) * 16 : ww * 1024 + ((lane >> 3) & 1) * 512 + (lane >> 4) * 128 + (lane & 7) * 16);
#pragma unroll
    for (int j = 0; j < 2 * NSG; j++) {
        const float* c = acc + 8 * j;
        const uint32_t p0 = pack2(c[0], c[1]), p1 = pack2(c[2], c[3]), p2 = pack2(c[4], c[5]), p3 = pack2(c[6], c[7]);
        if (wg < 2) stsm4t(la + j * 2048, p0, p1, p2, p3);
        else stsm4(la + (j >> 1) * 4096 + (j & 1) * 256, p0, p1, p2, p3);
    }
    if ((threadIdx.x & 127) == 0) sts32(bar + 80 + 4 * wg, id);
    fence_async();
    bar_arrive(1 + wg, 160);
}

DEV uint32_t resid(uint32_t u, float a, float b) { return pack2(bf_lo(u) + bf_round(a), bf_hi(u) + bf_round(b)); }

DEV void worker(uint32_t sb, const Maps& maps, const bf16* __restrict__ x, bf16* __restrict__ x1, int layer) {
    using namespace wk;
    const uint32_t bar = sb + OFF_BAR, slot = bar + 64;
    const int tid = threadIdx.x, lane = tid & 31, warp = __shfl_sync(~0u, tid >> 5, 0);
    uint32_t* sy = g_sync + layer * SYNC_LAYER;
    if (tid == 0) {
        for (int i = 0; i < NST; i++) { mbar_init(bar + 8 * i, 1); mbar_init(bar + 8 * (NST + i), 12); }
        asm volatile("fence.mbarrier_init.release.cluster;" ::: "memory");
    }
    __syncthreads();
    if (warp > 12) {
        const int wg = warp - 13;
        bar_arrive(5 + wg, 160);
        for (;;) {
            bar_sync(1 + wg, 160);
            const int id = (int)lds32(bar + 80 + 4 * wg);
            if (id < 0) break;
            const int s0 = pb_start(id >> 5), ns = pb_start((id >> 5) + 1) - s0;
            if (lane == 0) {
                for (int j = 0; j < ns; j++)
                    bulk_s2g(g_p + (size_t)(((s0 + j) * H_ + (id & 31)) * 3 + wg) * 4096, sb + OFF_OUT + wg * 24576 + j * 4096, 4096);
                bulk_commit();
                bulk_wait<0>();
                flag_add(sy + SY_P + id);
            }
            __syncwarp();
            bar_arrive(5 + wg, 160);
        }
    } else if (warp == 12) {
        if (lane == 0) {
            Ring rg = {0, 7u};
            auto acquire = [&]() { mbar_wait(bar + 8 * (NST + rg.st), rg.par()); return sb + rg.st * STAGE; };
            for (;;) {
                int id = (int)atomicAdd(sy + SY_TICKET, 1u);
                if (layer && id >= I_F) id += I_OB - I_F;
                if (id >= N_ITEMS) id = -1;
                if (id >= 0) { TLI(id, 0, gtime()); TLI(id, 3, blockIdx.x + (gridDim.x % 3 == 0 && gridDim.x > 111 ? 0 : 1000)); }
                uint32_t d = acquire();
                sts32(slot + 4 * rg.st, id);
                if (id < 0) { mbar_arrive(bar + 8 * rg.st); break; }
                if (id < N_P) {
                    const int b = id >> 5, h = id & 31, s0 = pb_start(b), ns = pb_start(b + 1) - s0;
                    for (int kb = 0; kb < 10; kb++, rg.next(3)) {
                        if (kb) d = acquire();
                        const uint32_t fb = bar + 8 * rg.st;
                        mbar_expect(fb, 24576 + ns * 4096);
                        tma3d(d, &maps.wq2, 0, kb * 64, 2 * h, fb);
                        tma3d(d + 16384, &maps.wv1, 0, kb * 64, 2 * h, fb);
                        if (ns == 6) tma3d(d + 24576, &maps.x6, 0, 2 * kb, s0, fb);
                        else for (int j = 0; j < ns; j += 2) tma3d(d + 24576 + j * 4096, &maps.x2, 0, 2 * kb, s0 + j, fb);
                    }
                } else if (id < I_OB) {
                    mbar_arrive(bar + 8 * rg.st);
                    mbar_wait(bar + 8 * (NST + rg.st), rg.par() ^ 1);
                    rg.next(NST);
                } else if (id < I_OT) {
                    const int b = (id - I_OB) / 5, nt = (id - I_OB) % 5;
                    for (int j = 0; j < 6; j++) flag_wait(sy + SY_O + 6 * b + j, 32);
                    for (int kb = 0; kb < 64; kb++, rg.next(NST)) {
                        if (kb) d = acquire();
                        const uint32_t fb = bar + 8 * rg.st;
                        mbar_expect(fb, 40960);
                        tma3d(d, &maps.o6, 0, 2 * kb, 6 * b, fb);
                        tma3d(d + 24576, &maps.wo2, 0, kb * 64, 2 * nt, fb);
                    }
                } else {
                    int b, nt, k0, k1;
                    ot_decode(id, b, nt, k0, k1);
                    for (int kb = k0; kb < k1; kb++, rg.next(NST)) {
                        if (kb > k0) d = acquire();
                        const uint32_t fb = bar + 8 * rg.st;
                        mbar_expect(fb, 49152);
                        tma3d(d + 24576, &maps.wo1, 0, 3 * kb * 64, nt, fb);
                        if (kb == k0) for (int j = 0; j < 2; j++) flag_wait(sy + SY_O + 2 * b + j, 32);
                        for (int u = 0; u < 3; u++) tma3d(d + u * 8192, &maps.o2, 0, 2 * (3 * kb + u), 2 * b, fb);
                    }
                }
            }
        }
    } else {
        const int wg = warp >> 2, g = lane >> 2, q = lane & 3;
        Ring rg = {0, 0u};
        bool stores_done = false;
        for (;;) {
            mbar_wait(bar + 8 * rg.st, rg.par());
            const int id = (int)lds32(slot + 4 * rg.st);
            if ((id < 0 || id >= N_P) && !stores_done) {
                bar_sync(5 + wg, 160);
                if ((tid & 127) == 0) sts32(bar + 80 + 4 * wg, ~0u);
                bar_arrive(1 + wg, 160);
                stores_done = true;
                bar_sync(4, 384);
                mbar_arrive_elect(bar + 8 * (NST + 3));
            }
            if (id < 0) break;
            if (tid == 0) TLI(id, 1, gtime());
            if (id < N_P) {
                const int b = id >> 5;
                if (b == 0) proj_tile<2>(sb, bar, rg, wg, id);
                else if (b == 1 || b == NPB - 1) proj_tile<4>(sb, bar, rg, wg, id);
                else proj_tile<6>(sb, bar, rg, wg, id);
            } else if (id < I_OB) {
                if (tid < NCOL) filter_tile(maps.wr, maps.wi, id - I_F, tid);
                __syncwarp();
                mbar_arrive_elect(bar + 8 * (NST + rg.st));
                rg.next(NST);
            } else if (id < I_OT) {
                const int b = (id - I_OB) / 5, nt = (id - I_OB) % 5;
                const size_t o = (size_t)(192 * b + 16 * warp + g) * D_ + nt * 128 + 2 * q;
                float acc[64];
#pragma unroll
                for (int i = 0; i < 64; i++) acc[i] = 0.f;
                for (int kb = 0; kb < 64; kb++, rg.next(NST)) {
                    const int st = rg.st;
                    if (kb) mbar_wait(bar + 8 * st, rg.par());
                    const u64 da = mkdesc(sb + st * STAGE + wg * 8192, 128, 1024), db = mkdesc(sb + st * STAGE + 24576, 8192, 1024) | SW128;
                    wg_fence();
#pragma unroll
                    for (int ks = 0; ks < 4; ks++) wgmma_n128_ss<0, 1>(acc, da + ks * 16, db + ks * 128, 1);
                    wg_commit();
                    wg_wait<0>();
                    mbar_arrive_elect(bar + 8 * (NST + st));
                }
                uint32_t xr[32];
#pragma unroll
                for (int t = 0; t < 32; t++) xr[t] = ldg32(x + o + 8 * (t >> 1) + (t & 1) * 8 * D_);
#pragma unroll
                for (int t = 0; t < 32; t++) *(uint32_t*)(x1 + o + 8 * (t >> 1) + (t & 1) * 8 * D_) = resid(xr[t], acc[2 * t], acc[2 * t + 1]);
            } else {
                int b, nt, k0, k1;
                ot_decode(id, b, nt, k0, k1);
                const size_t o = (size_t)(64 * b + 16 * (warp & 3) + g) * D_ + nt * 64 + 2 * q;
                float acc[32];
                uint32_t xr[16];
#pragma unroll
                for (int t = 0; t < 16; t++) xr[t] = wg == 0 && id < I_SA ? ldg32(x + o + 8 * (t >> 1) + (t & 1) * 8 * D_) : 0;
#pragma unroll
                for (int i = 0; i < 32; i++) acc[i] = 0.f;
                for (int kb = k0; kb < k1; kb++, rg.next(NST)) {
                    const int st = rg.st;
                    if (kb > k0) mbar_wait(bar + 8 * st, rg.par());
                    const u64 da = mkdesc(sb + st * STAGE + wg * 8192, 128, 1024), db = mkdesc(sb + st * STAGE + 24576 + wg * 8192, 0, 1024) | SW128;
                    wg_fence();
#pragma unroll
                    for (int ks = 0; ks < 4; ks++) wgmma_n64_ss<0, 1>(acc, da + ks * 16, db + ks * 128, 1);
                    wg_commit();
                    wg_wait<0>();
                    mbar_arrive_elect(bar + 8 * (NST + st));
                }
                const uint32_t ra = sb + OFF_RED + (tid & 127) * 16;
                if (wg) {
#pragma unroll
                    for (int t = 0; t < 8; t++)
                        sts128(ra + (wg - 1) * 16384 + t * 2048, __float_as_uint(acc[4 * t]), __float_as_uint(acc[4 * t + 1]), __float_as_uint(acc[4 * t + 2]), __float_as_uint(acc[4 * t + 3]));
                }
                bar_sync(4, 384);
                if (wg == 0) {
#pragma unroll
                    for (int t = 0; t < 8; t++) {
                        float u[4], v[4];
                        lds128f(u, ra + t * 2048); lds128f(v, ra + 16384 + t * 2048);
#pragma unroll
                        for (int i = 0; i < 4; i++) acc[4 * t + i] += u[i] + v[i];
                    }
                }
                bar_sync(4, 384);
                if (wg == 0) {
                    if (id < I_SA) {
#pragma unroll
                        for (int t = 0; t < 16; t++) *(uint32_t*)(x1 + o + 8 * (t >> 1) + (t & 1) * 8 * D_) = resid(xr[t], acc[2 * t], acc[2 * t + 1]);
                    } else {
                        float* y = g_yt + (layer * YT_ROWS - (S_ - YT_ROWS)) * D_ + o;
#pragma unroll
                        for (int t = 0; t < 16; t++)
                            asm volatile("red.relaxed.gpu.global.add.v2.f32 [%0],{%1,%2};" ::"l"(y + 8 * (t >> 1) + (t & 1) * 8 * D_), "f"(acc[2 * t]), "f"(acc[2 * t + 1]) : "memory");
                    }
                }
            }
            if (tid == 0) TLI(id, 2, gtime());
        }
    }
}

__global__ void __launch_bounds__(512, 1) side_kernel(const __grid_constant__ Maps maps, const bf16* __restrict__ x, bf16* __restrict__ x1, int layer) {
    extern __shared__ __align__(1024) unsigned char smem[];
    pdl_launch();
    TLS(3 + 5 * layer);
    worker(s2u(smem), maps, x, x1, layer);
    __syncwarp();
    pdl_wait();
    TLE(3 + 5 * layer);
}

constexpr float C5A = 0.30901699437494742f, C5B = -0.80901699437494742f, S5A = 0.95105651629515357f, S5B = 0.58778525229247313f;
template <int SGN> DEV void dft5(const float (&tr)[5], const float (&ti)[5], float (&zr)[5], float (&zi)[5]) {
    const float ar = tr[1] + tr[4], ai = ti[1] + ti[4], br = tr[2] + tr[3], bi = ti[2] + ti[3];
    const float cr = tr[1] - tr[4], ci = ti[1] - ti[4], dr = tr[2] - tr[3], di = ti[2] - ti[3];
    zr[0] = tr[0] + ar + br; zi[0] = ti[0] + ai + bi;
    const float m1r = tr[0] + C5A * ar + C5B * br, m1i = ti[0] + C5A * ai + C5B * bi;
    const float m2r = tr[0] + C5B * ar + C5A * br, m2i = ti[0] + C5B * ai + C5A * bi;
    const float n1r = SGN * (S5A * cr + S5B * dr), n1i = SGN * (S5A * ci + S5B * di);
    const float n2r = SGN * (S5B * cr - S5A * dr), n2i = SGN * (S5B * ci - S5A * di);
    zr[1] = m1r + n1i; zi[1] = m1i - n1r; zr[4] = m1r - n1i; zi[4] = m1i + n1r;
    zr[2] = m2r + n2i; zi[2] = m2i - n2r; zr[3] = m2r - n2i; zi[3] = m2i + n2r;
}
DEV void ln40(float (&v)[40]) {
    float s = 0.f;
#pragma unroll
    for (int i = 0; i < 40; i++) s += v[i];
#pragma unroll
    for (int o = 8; o; o >>= 1) s += __shfl_xor_sync(~0u, s, o);
    const float mean = s * (1.f / D_);
    float q = 0.f;
#pragma unroll
    for (int i = 0; i < 40; i++) { const float d = v[i] - mean; q += d * d; }
#pragma unroll
    for (int o = 8; o; o >>= 1) q += __shfl_xor_sync(~0u, q, o);
    const float mb = bf_round(mean);
    const float inv = 1.f / bf_round(sqrtf(bf_round(bf_round(q * (1.f / D_)) + 1e-5f)));
#pragma unroll
    for (int i = 0; i < 40; i++) v[i] = bf_round(v[i] - mb) * inv;
}
__global__ void __launch_bounds__(256) rowfft_kernel(const bf16* __restrict__ x0, bf16* __restrict__ x, const bf16* __restrict__ Wq,
                                                     const bf16* __restrict__ Wk, const bf16* __restrict__ Wv, int layer) {
    extern __shared__ __align__(1024) unsigned char smem[];
    const uint32_t sb = s2u(smem), sx = sb + 23552, sy = sx + 20480, bar = sy + 40960;
    const int tid = threadIdx.x, lane = tid & 31, q = lane & 3, blk = blockIdx.x, k2 = tid >> 2;
    if (tid == 0) TLI(800 + blk, 0, gtime());
    float twr[5], twi[5];
#pragma unroll
    for (int r = 1; r < 5; r++) { sincospif((float)(r * k2) * (-1.f / 320), &twi[r], &twr[r]); }
    uint32_t f[8][4];
#pragma unroll
    for (int ks = 0; ks < 8; ks++) { const uint4 u = g_f128[ks * 256 + tid]; f[ks][0] = u.x; f[ks][1] = u.y; f[ks][2] = u.z; f[ks][3] = u.w; }
    const bool split = blk * 16 >= S_ - YT_ROWS;
    if (tid == 0) {
        mbar_init(bar, 1);
        asm volatile("fence.mbarrier_init.release.cluster;" ::: "memory");
        mbar_expect(bar, split ? 61440 : 20480);
        if (split) bulk_g2s(sx, x0 + (size_t)blk * 16 * D_, 20480, bar);
    }
    __syncthreads();
    pdl_wait();
    pdl_launch();
    TLS(4 + 5 * layer);
    if (tid == 0) TLI(800 + blk, 1, gtime());
    if (tid == 0) {
        if (split) bulk_g2s(sy, g_yt + (layer * YT_ROWS + blk * 16 - (S_ - YT_ROWS)) * D_, 40960, bar);
        else bulk_g2s(sx, x + (size_t)blk * 16 * D_, 20480, bar);
    }
    mbar_wait(bar, 0);
    {
        const int rho = tid >> 4, j = tid & 15;
        float v[40];
#pragma unroll
        for (int i = 0; i < 5; i++) {
            uint32_t u[4];
            lds128(u, sx + tid * 80 + i * 16);
            if (split) {
                float p[8];
                lds128f(p, sy + tid * 160 + i * 32); lds128f(p + 4, sy + tid * 160 + i * 32 + 16);
#pragma unroll
                for (int k = 0; k < 4; k++) u[k] = resid(u[k], p[2 * k], p[2 * k + 1]);
                sts128(sx + tid * 80 + i * 16, u[0], u[1], u[2], u[3]);
            }
            unpack8(v + 8 * i, make_uint4(u[0], u[1], u[2], u[3]));
        }
        if (layer == 0 && tid < 12) prefetch_bulk((const char*)(tid < 4 ? Wk : tid < 8 ? Wq : Wv) + (blk * 4 + (tid & 3)) * 10240, 10240);
        ln40(v);
        const uint32_t a = sb + ((rho >> 1) & 1) * 2304 + j * 144 + (2 * (rho >> 2) + (rho & 1)) * 16;
#pragma unroll
        for (int r = 0; r < 5; r++)
            sts128(a + r * 4608, pack2(v[r], v[5 + r]), pack2(v[10 + r], v[15 + r]), pack2(v[20 + r], v[25 + r]), pack2(v[30 + r], v[35 + r]));
    }
    fence_async();
    __syncthreads();
    if (tid == 0) TLI(800 + blk, 2, gtime());
    if (tid == 0 && split) { bulk_s2g(x + (size_t)blk * 16 * D_, sx, 20480); bulk_commit(); }
    float acc[40];
    const u64 db = mkdesc(sb, 144, 2304);
    wg_fence();
    wgmma_n80_rs<0, 0>(acc, f[0], db);
#pragma unroll
    for (int ks = 1; ks < 8; ks++) wgmma_n80_rs<1, 0>(acc, f[ks], db + ks * 18);
    wg_commit();
    wg_wait<0>();
    unsigned char* zp = g_z + (blk >> 1) * 128 + ((((blk & 1) * 4 + q) ^ ((blk >> 1) & 7)) << 4);
    uint32_t o[5][4];
#pragma unroll
    for (int u = 0; u < 4; u++) {
        float tr[5], ti[5], zr[5], zi[5];
#pragma unroll
        for (int r = 0; r < 5; r++) {
            const float yr = acc[8 * r + 4 * (u >> 1) + (u & 1)], yi = k2 ? acc[8 * r + 4 * (u >> 1) + 2 + (u & 1)] : 0.f;
            tr[r] = r ? yr * twr[r] - yi * twi[r] : yr;
            ti[r] = r ? yr * twi[r] + yi * twr[r] : yi;
        }
        dft5<1>(tr, ti, zr, zi);
#pragma unroll
        for (int j = 0; j < 5; j++) o[j][u] = pack2(zr[j], j < 3 ? zi[j] : -zi[j]);
    }
#pragma unroll
    for (int j = 0; j < 5; j++)
        if (j < 3 || k2) *(uint4*)(zp + (64 * j + k2) * 8192) = make_uint4(o[j][0], o[j][1], o[j][2], o[j][3]);
    if (k2 == 0) {
#pragma unroll
        for (int u = 0; u < 4; u++) {
            float tr[5], ti[5], zr[5], zi[5];
            const float cr[5] = {1.f, -C5B, C5A, -C5A, C5B}, ci[5] = {0.f, -S5B, -S5A, -S5A, -S5B};
#pragma unroll
            for (int r = 0; r < 5; r++) { const float y = acc[8 * r + 4 * (u >> 1) + 2 + (u & 1)]; tr[r] = y * cr[r]; ti[r] = y * ci[r]; }
            dft5<1>(tr, ti, zr, zi);
            o[0][u] = pack2(zr[0], zi[0]); o[1][u] = pack2(zr[1], zi[1]); o[2][u] = pack2(zr[2], 0.f);
        }
        *(uint4*)(zp + 256 * 8192) = make_uint4(o[0][0], o[0][1], o[0][2], o[0][3]);
        *(uint4*)(zp + 192 * 8192) = make_uint4(o[1][0], o[1][1], o[1][2], o[1][3]);
        *(uint4*)(zp + 320 * 8192) = make_uint4(o[2][0], o[2][1], o[2][2], o[2][3]);
    }
    if (tid == 0) bulk_wait<0>();
    TLE(4 + 5 * layer);
    if (tid == 0) TLI(800 + blk, 3, gtime());
}

constexpr int CF_SMEM = 16384 + 3 * 16384 + 64;
__global__ void __launch_bounds__(384) colfft_kernel(int layer) {
    extern __shared__ __align__(1024) unsigned char smem[];
    const uint32_t sb = s2u(smem), bar = sb + 65536;
    const int tid = threadIdx.x, lane = tid & 31, q = lane & 3, wg = __shfl_sync(~0u, tid >> 7, 0), t = tid & 127, ka = t >> 2;
    const int col = blockIdx.x * 3 + wg;
    const uint32_t d0 = sb + 16384 + wg * 16384, d1 = d0 + 8192;
    if (tid == 0) {
        for (int i = 0; i < 4; i++) mbar_init(bar + 8 * i, 1);
        asm volatile("fence.mbarrier_init.release.cluster;" ::: "memory");
    }
    float twr[8], twi[8];
#pragma unroll
    for (int i = 0; i < 8; i++) sincospif((float)((4 * i + q) * (ka ? ka : -32)) * (1.f / 1024), &twi[i], &twr[i]);
    __syncthreads();
    if (tid == 0) { mbar_expect(bar + 24, 16384); bulk_g2s(sb, g_g32, 16384, bar + 24); }
    uint32_t f[4][4], w[16];
#pragma unroll
    for (int ks = 0; ks < 4; ks++) { const uint4 u = g_f64[ks * 128 + t]; f[ks][0] = u.x; f[ks][1] = u.y; f[ks][2] = u.z; f[ks][3] = u.w; }
#pragma unroll
    for (int i = 0; i < 4; i++) { const uint4 u = *(const uint4*)(g_wt + col * 8192 + i * 2048 + t * 16); w[4 * i] = u.x; w[4 * i + 1] = u.y; w[4 * i + 2] = u.z; w[4 * i + 3] = u.w; }
    pdl_wait();
    pdl_launch();
    TLS(5 + 5 * layer);
    if (t == 0) {
        mbar_expect(bar + 8 * wg, 8192);
        bulk_g2s(d0, g_z + col * 8192, 8192, bar + 8 * wg);
    }
    float acc[32];
    uint32_t a[4][4];
    mbar_wait(bar + 8 * wg, 0);
    {
        const u64 db = mkdesc(d0, 0, 1024) | SW128;
        wg_fence();
        wgmma_n64_rs<0, 1>(acc, f[0], db);
#pragma unroll
        for (int ks = 1; ks < 4; ks++) wgmma_n64_rs<1, 1>(acc, f[ks], db + ks * 128);
        wg_commit();
        wg_wait<0>();
    }
#pragma unroll
    for (int ks = 0; ks < 4; ks++) { const uint4 u = g_f64[512 + ks * 128 + t]; f[ks][0] = u.x; f[ks][1] = u.y; f[ks][2] = u.z; f[ks][3] = u.w; }
#pragma unroll
    for (int i = 0; i < 8; i++) {
        const float c0 = acc[4 * i], c1 = acc[4 * i + 1], c2 = acc[4 * i + 2], c3 = acc[4 * i + 3];
        const float pr = c0 + c3, pi = c1 - c2, nr = ka ? c0 - c3 : c2, ni = ka ? c1 + c2 : c3;
        a[i >> 1][2 * (i & 1)] = ka ? pack2(pr * twr[i] + pi * twi[i], pi * twr[i] - pr * twi[i]) : pack2(c0, c1);
        a[i >> 1][2 * (i & 1) + 1] = pack2(nr * twr[i] - ni * twi[i], ni * twr[i] + nr * twi[i]);
    }
    mbar_wait(bar + 24, 0);
    {
        const u64 db = mkdesc(sb, 128, 1024);
        wg_fence();
        wgmma_n64_rs<0, 0>(acc, a[0], db);
#pragma unroll
        for (int ks = 1; ks < 4; ks++) wgmma_n64_rs<1, 0>(acc, a[ks], db + ks * 16);
        wg_commit();
        wg_wait<0>();
    }
    constexpr float NORM = 1.f / (2048.f * 640.f);
#pragma unroll
    for (int i = 0; i < 16; i++) {
        const float zr = acc[2 * i] * NORM, zi = acc[2 * i + 1] * NORM, wr = bf_lo(w[i]), wi = bf_hi(w[i]);
        a[i >> 2][i & 3] = pack2(zr * wr - zi * wi, zr * wi + zi * wr);
    }
    {
        const u64 db = mkdesc(sb + 8192, 128, 1024);
        wg_fence();
        wgmma_n64_rs<0, 0>(acc, a[0], db);
#pragma unroll
        for (int ks = 1; ks < 4; ks++) wgmma_n64_rs<1, 0>(acc, a[ks], db + ks * 16);
        wg_commit();
        wg_wait<0>();
    }
    const uint32_t row = (t >> 5) * 2048 + (lane & 15) * 128;
#pragma unroll
    for (int i = 0; i < 8; i++) {
        const float c0 = acc[4 * i], c1 = acc[4 * i + 1], c2 = acc[4 * i + 2], c3 = acc[4 * i + 3];
        const float pr = c0 * twr[i] - c1 * twi[i], pi = c1 * twr[i] + c0 * twi[i];
        const float nr = c2 * twr[i] + c3 * twi[i], ni = c3 * twr[i] - c2 * twi[i];
        a[i >> 1][2 * (i & 1)] = ka ? pack2(pr + nr, pi + ni) : pack2(c0, c1);
        a[i >> 1][2 * (i & 1) + 1] = ka ? pack2(ni - pi, pr - nr) : pack2(nr, ni);
    }
#pragma unroll
    for (int i = 0; i < 4; i++) stsm4(d1 + row + (((2 * i + (lane >> 4)) ^ (lane & 7)) << 4), a[i][0], a[i][1], a[i][2], a[i][3]);
    fence_async();
    bar_sync(1 + wg, 128);
    {
        const u64 db = mkdesc(d1, 0, 1024) | SW128;
        wg_fence();
        wgmma_n64_rs<0, 1>(acc, f[0], db);
#pragma unroll
        for (int ks = 1; ks < 4; ks++) wgmma_n64_rs<1, 1>(acc, f[ks], db + ks * 128);
        wg_commit();
        wg_wait<0>();
    }
#pragma unroll
    for (int i = 0; i < 4; i++)
        stsm4(d0 + row + (((2 * i + (lane >> 4)) ^ (lane & 7)) << 4), pack2(acc[8 * i], acc[8 * i + 1]), pack2(acc[8 * i + 2], acc[8 * i + 3]),
              pack2(acc[8 * i + 4], acc[8 * i + 5]), pack2(acc[8 * i + 6], acc[8 * i + 7]));
    fence_async();
    bar_sync(1 + wg, 128);
    if (t == 0) {
        bulk_s2g(g_z + col * 8192, d0, 8192);
        asm volatile("cp.async.bulk.commit_group;" ::: "memory");
        asm volatile("cp.async.bulk.wait_group 0;" ::: "memory");
    }
    TLE(5 + 5 * layer);
}

__global__ void __launch_bounds__(256) rowifft_kernel(const bf16* __restrict__ x, bf16* __restrict__ out, int last) {
    extern __shared__ __align__(1024) unsigned char smem[];
    const uint32_t sb = s2u(smem), sx = sb + 20480, sy = sx + 20480, bar = sy + 16 * 1296;
    const int tid = threadIdx.x, lane = tid & 31, q = lane & 3, blk = blockIdx.x, k2 = tid >> 2, warp = tid >> 5;
    float twr[5], twi[5];
#pragma unroll
    for (int r = 1; r < 5; r++) { sincospif((float)(r * k2) * (1.f / 320), &twi[r], &twr[r]); twr[r] *= 2.f; twi[r] *= 2.f; }
    uint32_t f[8][4];
#pragma unroll
    for (int ks = 0; ks < 8; ks++) { const uint4 u = g_f128[2048 + ks * 256 + tid]; f[ks][0] = u.x; f[ks][1] = u.y; f[ks][2] = u.z; f[ks][3] = u.w; }
    if (tid == 0) {
        mbar_init(bar, 1);
        asm volatile("fence.mbarrier_init.release.cluster;" ::: "memory");
        mbar_expect(bar, 20480);
        bulk_g2s(sx, x + (size_t)blk * 16 * D_, 20480, bar);
    }
    pdl_wait();
    pdl_launch();
    TLS(6 + 5 * last);
    const unsigned char* zp = g_z + (blk >> 1) * 128 + ((((blk & 1) * 4 + q) ^ ((blk >> 1) & 7)) << 4);
    uint4 z[6];
#pragma unroll
    for (int j = 0; j < 5; j++) z[j] = *(const uint4*)(zp + (64 * j + k2) * 8192);
    z[5] = k2 ? make_uint4(0, 0, 0, 0) : *(const uint4*)(zp + 320 * 8192);
    float acc[40];
#pragma unroll
    for (int u = 0; u < 4; u++) {
        float yr[6], yi[6], tr[5], ti[5], zr[5], zi[5];
#pragma unroll
        for (int j = 0; j < 6; j++) { const uint32_t v = u == 0 ? z[j].x : u == 1 ? z[j].y : u == 2 ? z[j].z : z[j].w; yr[j] = bf_lo(v); yi[j] = bf_hi(v); }
#pragma unroll
        for (int j = 0; j < 5; j++) { tr[j] = yr[j]; ti[j] = j < 3 ? yi[j] : -yi[j]; }
        dft5<-1>(tr, ti, zr, zi);
        const float c1[5] = {1.f, C5A, C5B, C5B, C5A}, s1[5] = {0.f, S5A, S5B, -S5B, -S5A};
        const float c2[5] = {1.f, C5B, C5A, C5A, C5B}, s2[5] = {0.f, S5B, -S5A, S5A, -S5B};
        const float c3[5] = {1.f, -C5B, C5A, -C5A, C5B}, s3[5] = {0.f, S5B, S5A, S5A, S5B};
        const float c4[5] = {1.f, -C5A, C5B, -C5B, C5A}, s4[5] = {0.f, S5A, -S5B, -S5B, S5A};
#pragma unroll
        for (int r = 0; r < 5; r++) {
            float er = r ? zr[r] * twr[r] - zi[r] * twi[r] : 2.f * zr[0], ei = r ? zr[r] * twi[r] + zi[r] * twr[r] : 2.f * zi[0];
            if (k2 == 0) {
                er = yr[0] + 2.f * (yr[1] * c1[r] - yi[1] * s1[r] + yr[2] * c2[r] - yi[2] * s2[r]);
                ei = (r & 1 ? -yr[5] : yr[5]) + 2.f * (yr[4] * c3[r] - yi[4] * s3[r] + yr[3] * c4[r] - yi[3] * s4[r]);
            }
            acc[8 * r + 4 * (u >> 1) + (u & 1)] = er;
            acc[8 * r + 4 * (u >> 1) + 2 + (u & 1)] = ei;
        }
    }
#pragma unroll
    for (int r = 0; r < 5; r++)
        stsm4(sb + (2 * warp + ((lane >> 3) & 1)) * 1280 + (2 * r + (lane >> 4)) * 128 + (lane & 7) * 16, pack2(acc[8 * r], acc[8 * r + 1]),
              pack2(acc[8 * r + 2], acc[8 * r + 3]), pack2(acc[8 * r + 4], acc[8 * r + 5]), pack2(acc[8 * r + 6], acc[8 * r + 7]));
    fence_async();
    __syncthreads();
    const u64 db = mkdesc(sb, 1280, 128);
    wg_fence();
    wgmma_n80_rs<0, 1>(acc, f[0], db);
#pragma unroll
    for (int ks = 1; ks < 8; ks++) wgmma_n80_rs<1, 1>(acc, f[ks], db + ks * 160);
    wg_commit();
    wg_wait<0>();
#pragma unroll
    for (int u = 0; u < 4; u++) {
        float e[10];
#pragma unroll
        for (int r = 0; r < 5; r++) { e[r] = acc[8 * r + 4 * (u >> 1) + (u & 1)]; e[5 + r] = acc[8 * r + 4 * (u >> 1) + 2 + (u & 1)]; }
#pragma unroll
        for (int i = 0; i < 5; i++) sts32(sy + (4 * q + u) * 1296 + k2 * 20 + i * 4, pack2(e[2 * i], e[2 * i + 1]));
    }
    __syncthreads();
    const int rho = tid >> 4, j = tid & 15;
    float v[40];
    mbar_wait(bar, 0);
#pragma unroll
    for (int i = 0; i < 5; i++) {
        uint32_t y[4], u[4];
        lds128(y, sy + rho * 1296 + j * 80 + i * 16);
        lds128(u, sx + tid * 80 + i * 16);
#pragma unroll
        for (int k = 0; k < 4; k++) u[k] = pack2(bf_lo(u[k]) + bf_lo(y[k]), bf_hi(u[k]) + bf_hi(y[k]));
        sts128(sx + tid * 80 + i * 16, u[0], u[1], u[2], u[3]);
        unpack8(v + 8 * i, make_uint4(u[0], u[1], u[2], u[3]));
    }
    if (!last) {
        ln40(v);
#pragma unroll
        for (int i = 0; i < 5; i++) {
            const int c = j * 5 + i;
            sts128(sb + (c >> 3) * 2048 + rho * 128 + (((c ^ rho) & 7) << 4), pack2(v[8 * i], v[8 * i + 1]), pack2(v[8 * i + 2], v[8 * i + 3]),
                   pack2(v[8 * i + 4], v[8 * i + 5]), pack2(v[8 * i + 6], v[8 * i + 7]));
        }
    }
    fence_async();
    __syncthreads();
    if (lane == 0) {
        if (warp == 7) bulk_s2g(out + (size_t)blk * 16 * D_, sx, 20480);
        else if (!last && warp < 5) {
            unsigned char* p = g_xn + (blk >> 1) * 40960 + warp * 8192 + (blk & 1) * 2048;
            bulk_s2g(p, sb + warp * 4096, 2048);
            bulk_s2g(p + 4096, sb + warp * 4096 + 2048, 2048);
        }
        bulk_commit();
        bulk_wait<0>();
    }
    TLE(6 + 5 * last);
}

namespace rec {
#define NS 0
constexpr int OFF_X = 0;
constexpr int OFF_WO = 81920;
constexpr int OFF_WS = OFF_WO + 65536;
constexpr int OFF_XCH = OFF_WS + NS * 4096;
constexpr int OFF_MEMB = OFF_XCH + 8192;
constexpr int OFF_VX = OFF_MEMB + 10240;
constexpr int OFF_VM = OFF_VX + 16384;
constexpr int OFF_Q = OFF_VM + 4096;
constexpr int OFF_K = OFF_Q + 10240;
constexpr int OFF_OST = OFF_WO + 49152;
constexpr int OFF_PX = OFF_OST + 8192;
constexpr int OFF_PT = OFF_PX + 2560;
constexpr int OFF_PS = OFF_K + 10240;
constexpr int OFF_OB = OFF_PS + 1280;
constexpr int OFF_MX = OFF_OB + 2048;
constexpr int OFF_BAR = OFF_MX + 64;
constexpr int OFF_PROF = OFF_BAR + 256;
constexpr int SMEM = OFF_PROF + 4096 > wk::SMEM ? OFF_PROF + 4096 : wk::SMEM;
enum { B_XT = 0, B_KX = 2, B_VX = 4, B_XD = 6, B_X1 = 8, B_GO = 10, B_PXF = 12, B_PXE = 13, B_FIN = 14, B_ST = 15 };
enum { NB_W2 = 0, NB_XCH = 1, NB_QK = 2, NB_WIN = 3, NB_ATT = 4, NB_X = 5, NB_PRO = 6, NB_W1 = 7, NB_MEM = 8  , NB_LD = 13, NB_KX = 15 };
#define NOX 0
#define NW1 4
#define NW1B 0
template <int N> struct IC { static constexpr int value = N; };
template <int N, int I = 0, class F> DEV void static_for(F&& f) { if constexpr (I < N) { f(IC<I>{}); static_for<N, I + 1>(f); } }
constexpr float SM_SCALE = 0.08838834764831845f * 1.4426950408889634f;
}

__global__ void __launch_bounds__(512, 1) rec_kernel(const __grid_constant__ Maps maps, const bf16* __restrict__ x, bf16* __restrict__ x1, const bf16* __restrict__ mem0, const bf16* __restrict__ Wq, const bf16* __restrict__ Wk,
                                                     const bf16* __restrict__ Wv, const bf16* __restrict__ Wo, int layer, int delay, int delay2) {
    using namespace rec;
    extern __shared__ __align__(1024) unsigned char smem[];
    const uint32_t sb = s2u(smem);
    if (blockIdx.x >= 3 * H_) {
        pdl_wait();
        pdl_launch();
        worker(sb, maps, x, x1, layer);
        return;
    }
    const int tid = threadIdx.x, lane = tid & 31, warp = __shfl_sync(~0u, tid >> 5, 0);
    const int g = lane >> 2, q = lane & 3;
    const int h = blockIdx.x / 3;
    const uint32_t bar = sb + OFF_BAR;
    STAMP(2 * layer);
    TLS(2 + 5 * layer);
    if (tid == 0) {
        for (int i = 0; i < 2; i++) {
            mbar_init(bar + 8 * (B_XT + i), 1); mbar_init(bar + 8 * (B_KX + i), 8); mbar_init(bar + 8 * (B_VX + i), 1);
            mbar_init(bar + 8 * (B_XD + i), 8); mbar_init(bar + 8 * (B_X1 + i), 1);
        }
        mbar_init(bar + 8 * B_PXF, 1); mbar_init(bar + 8 * B_PXE, 2); mbar_init(bar + 8 * B_ST, 2); mbar_init(bar + 8 * B_GO, 1);
        mbar_init(bar + 8 * B_FIN, 48);
        sts32(sb + OFF_MX + 32, 0); sts32(sb + OFF_MX + 36, 0);
        asm volatile("fence.mbarrier_init.release.cluster;" ::: "memory");
    }
    asm volatile("barrier.cluster.arrive.aligned; barrier.cluster.wait.aligned;" ::: "memory");
    const bool never = delay < 0;

    if (warp < 8) {
        asm volatile("setmaxnreg.inc.sync.aligned.u32 184;");
        const uint32_t rank = cta_rank();
        const int wg = warp >> 2;
        uint32_t fa[20 - NS][4], fb[20][4];
        const uint32_t l16 = opaque(sb + lane * 16);
        uint32_t dst = opaque(rank < 2 ? sb + OFF_Q + wg * 10240 + (warp & 3) * 256 + (lane & 15) * 16 + (lane >> 4) * 1024
                                       : sb + OFF_VM + warp * 256 + lane * 4);
        int dstep = rank < 2 ? 5120 : 2048;
        uint32_t& sfd = dst;
        const uint32_t ws = OFF_WS + warp * 512, xo = OFF_XCH + warp * 512, xi = OFF_XCH + (warp ^ 4) * 512, mb = OFF_MEMB + wg * 512;
        {
            const int t = tid & 127;
            const bf16* src = (rank == 2 ? Wv + wg * 64 : (wg ? Wk : Wq) + rank * 64) + h * E_ + (size_t)(t >> 3) * 4096 + (t & 7) * 8;
            constexpr int SA = OFF_X + 40960, SB = OFF_VX;
            const uint32_t sdst = sb + (wg ? SB : SA) + (t >> 3) * 128 + (((t & 7) ^ ((t >> 3) & 7)) << 4);
            const uint32_t ra = sb + wg * 4096 + ((lane >> 4) * 8 + (lane & 7)) * 128 + (((2 * (warp & 3) + ((lane >> 3) & 1)) ^ (lane & 7)) << 4);
            auto issue = [&](int rd) {
#pragma unroll
                for (int i = 0; i < 8; i++) cp16(sdst + (rd & 1) * 16384 + i * 2048, src + (size_t)(rd * 128 + i * 16) * 4096);
                cp_commit();
            };
            issue(0); issue(1);
#pragma unroll
            for (int rd = 0; rd < 5; rd++) {
                if (rd < 4) cp_wait<1>(); else cp_wait<0>();
                bar_sync(NB_XCH, 256);
#pragma unroll
                for (int i = 0; i < 4; i++) {
                    const int n = rd * 4 + i, o = (rd & 1) * 16384 + (i >> 1) * 8192 + (i & 1) * 2048;
                    if (n < NS) {
                        uint32_t f[4];
                        ldsm4t(f, ra + SA + o);
                        sts128(l16 + ws + n * 4096, f[0], f[1], f[2], f[3]);
                    } else ldsm4t(fa[n - NS], ra + SA + o);
                    ldsm4t(fb[n], ra + SB + o);
                }
                if (rd < 3) { bar_sync(NB_XCH, 256); issue(rd + 2); }
            }
            fence_async();
            bar_sync(NB_PRO, 288);
        }
        uint32_t xlo = (uint32_t)mkdesc(sb + OFF_X + wg * 64, 0, 0);
        const uint32_t xtog = xlo ^ (uint32_t)mkdesc(sb + OFF_X + 40960 + wg * 64, 0, 0);
        uint32_t p8 = 0;
        bar_sync(NB_LD, 288);
        for (int s = -1;; s++) {
            uint32_t t[NS ? NS : 1][4];
            {
                float acc[16];
                auto xproj = [&](auto I0, auto I1) {
                    const u64 desc = (u64)xlo | (64ull << 32) | SW128;
                    wg_fence();
#pragma unroll
                    for (int i = I0.value; i < I1.value; i++) {
                        const u64 db = desc + (i >> 1) * 256 + (i & 1) * 2;
                        if (i == 0) wgmma_n32_rs<0>(acc, fb[i], db);
                        else if (!NOX) wgmma_n32_rs<1>(acc, fb[i], db);
                    }
                    wg_commit();
                    wg_wait<0>();
                };
                if (s >= 0 && rank < 2) { fence_async(); bar_arrive(NB_W1, 512); bar_sync(NB_X, 384); }
                bar_sync_if<NB_W1, 480>(s >= 0 && rank == 2);
                if (s == NSEG - 1) break;
                xproj(IC<0>{}, IC<NW1>{});
                if (warp == 4 && s >= 0) PROFT(15);
                bar_sync_if<NB_W2, 384>(s >= 0 && rank < 2);
                if (NW1B > 0) xproj(IC<NW1>{}, IC<NW1 + NW1B>{});
                bar_sync_if<NB_WIN, 384>(s >= 0 && rank == 2);
                xproj(IC<NW1 + NW1B>{}, IC<20>{});
                if (warp == 4 && s >= 0) PROFT(12);
                sts128f_if(l16 + xo, acc + 8, !wg); sts128f_if(l16 + xo + 4096, acc + 12, !wg);
                sts128f_if(l16 + xo, acc, wg); sts128f_if(l16 + xo + 4096, acc + 4, wg);
                bar_sync(NB_XCH, 256);
                float u[8];
#pragma unroll
                for (int i = 0; i < 8; i++) acc[i] = wg ? acc[8 + i] : acc[i];
                lds128f(u, l16 + xi); lds128f(u + 4, l16 + xi + 4096);
#pragma unroll
                for (int i = 0; i < NS; i++) lds128(t[i], l16 + ws + i * 4096);
#pragma unroll
                for (int i = 0; i < 8; i++) u[i] += acc[i];
                if (rank < 2) {
                    stsm4t(dst + (wg ? 3072 : 11264), pack2(u[0], u[1]), pack2(u[2], u[3]), pack2(u[4], u[5]), pack2(u[6], u[7]));
                    bar_arrive(NB_KX, 384);
                } else {
                    stsm4(l16 + (l16 & 256) + OFF_VX + 4096 + (warp & 3) * 1024 + wg * 256 + p8 * 1024,
                          pack2(u[0], u[1]), pack2(u[4], u[5]), pack2(u[2], u[3]), pack2(u[6], u[7]));
                    fence_async();
                    mbar_arrive_elect(bar + 8 * B_KX + p8);
                }
                xlo ^= xtog;
                if (warp == 4 && s >= 0) PROFT(3);
            }
            float da[4] = {0.f, 0.f, 0.f, 0.f}, db[4] = {0.f, 0.f, 0.f, 0.f};
            uint32_t b[10][4];
            bar_sync(NB_MEM, 384);
            lds128(b[0], l16 + mb); lds128(b[1], l16 + mb + 1024);
            const uint32_t xb0 = mapa(bar + 8 * B_X1 + p8, 0), xb1 = mapa(bar + 8 * B_X1 + p8, 1);
            SFENCE();
            float is;
#pragma unroll
            for (int j = 0; j < 10; j++) {
#pragma unroll
                for (int x = 0; x < 2; x++) {
                    const int i = 2 * j + x;
                    const uint32_t* f = i < NS ? t[i] : fa[i - NS];
                    mma16(da, f[0], f[1], f[2], f[3], b[j][2 * x], b[j][2 * x + 1]);
                    mma16(db, fb[i][0], fb[i][1], fb[i][2], fb[i][3], b[j][2 * x], b[j][2 * x + 1]);
                }
                if (j == 0 && warp == 4) PROFT(16);
                if (j < 8) {
                    SFENCE();
                    if (!(j & 1)) bar_sync(NB_MEM + 1 + (j >> 1), 384);
                    lds128(b[j + 2], l16 + mb + (j + 2) * 1024);
                } else if (j == 8) is = lds32f(sb + OFF_MX + 16);
                if (j < 9) SFENCE();
            }
            sts128f_if(l16 + xo, db, !wg); sts128f_if(l16 + xo, da, wg);
            bar_sync(NB_XCH, 256);
            float u[4];
            lds128f(u, l16 + xi);
#pragma unroll
            for (int i = 0; i < 4; i++) da[i] = (wg ? db[i] : da[i]) * is;
            const uint32_t p0 = pack2(fmaf(u[0], is, da[0]), fmaf(u[1], is, da[1])), p1 = pack2(fmaf(u[2], is, da[2]), fmaf(u[3], is, da[3]));
            stsm2t_if(dst, p0, p1, rank < 2);
            bar_arrive_if<NB_QK, 384>(rank < 2);
            if (rank == 2) {
                st_async1(mapa(dst, 0), p0, xb0); st_async1(mapa(dst, 1), p0, xb1);
                st_async1(mapa(dst + 128, 0), p1, xb0); st_async1(mapa(dst + 128, 1), p1, xb1);
                sts32(dst, p0); sts32(dst + 128, p1);
                bar_arrive(NB_QK, 384);
            }
            if (warp == 4) PROFT(17);
            dst += dstep; dstep = -dstep; p8 ^= 8;
        }
    } else if (warp < 12) {
        asm volatile("setmaxnreg.dec.sync.aligned.u32 96;");
        const uint32_t rank = cta_rank();
        const int w = warp - 8;
        uint32_t amax = 0;
#pragma unroll
        for (int it = 0; it < 5; it++) {
            const int kp = it * 4 + w;
            const bf16* p = mem0 + g * D_ + kp * 32 + 2 * q;
            uint32_t b0 = ldg32(p), b1 = ldg32(p + 8), b2 = ldg32(p + 16), b3 = ldg32(p + 24);
            sts128(sb + OFF_MEMB + kp * 512 + lane * 16, b0, b1, b2, b3);
            amax = absmax2(amax, absmax2(absmax2(b0, b1), absmax2(b2, b3)));
        }
        if (tid == 256) { sts32(sb + OFF_MX + 16, 0x3f800000u); sts128(sb + OFF_MX + 48, 0x3f803f80u, 0x3f803f80u, 0x3f803f80u, 0x3f803f80u); }
        bar_arrive(NB_MEM, 384); bar_arrive(NB_MEM + 1, 384); bar_arrive(NB_MEM + 2, 384); bar_arrive(NB_MEM + 3, 384); bar_arrive(NB_MEM + 4, 384);
        {
            const int t = tid & 127, nr = rank == 2 ? 4 : 3;
            for (int r = 0; r < nr; r++) {
                const bf16* src = Wo + (size_t)(h * E_) * D_ + (r < 3 ? 192 * r + 64 * rank : 576);
#pragma unroll
                for (int i = 0; i < 8; i++) {
                    const int e = i * 16 + (t >> 3);
                    cp16(sb + OFF_WO + r * 16384 + e * 128 + (((t & 7) ^ (e & 6)) << 4), src + e * D_ + (t & 7) * 8);
                }
            }
            cp_commit();
            pdl_wait();
            pdl_launch();
            cp_wait<0>();
            bar_sync(NB_ATT, 128);
            for (int r = 0; r < nr; r++) {
                uint32_t u[8][4];
                const uint32_t p = sb + OFF_WO + r * 16384 + 2 * q * 128 + (((2 * w + (g & 1)) ^ (2 * q)) << 4) + (g >> 1) * 4;
#pragma unroll
                for (int ks = 0; ks < 8; ks++)
#pragma unroll
                    for (int j = 0; j < 4; j++) u[ks][j] = lds32(p + (16 * ks + (j & 1) * 8 + (j >> 1)) * 128);
                bar_sync(NB_ATT, 128);
#pragma unroll
                for (int ks = 0; ks < 8; ks++)
                    sts128(sb + OFF_WO + (r * 4 + w) * 4096 + ks * 512 + lane * 16, prmt(u[ks][0], u[ks][2], 0x5410), prmt(u[ks][0], u[ks][2], 0x7632),
                           prmt(u[ks][1], u[ks][3], 0x5410), prmt(u[ks][1], u[ks][3], 0x7632));
            }
        }
        float cw;
        {
            const float4 a = ((const float4*)g_nrm)[lane], c = ((const float4*)g_nrm)[32 + lane];
            float sm = sqrtf((a.x + a.y) + (a.z + a.w)) * sqrtf((c.x + c.y) + (c.z + c.w)), mxv = sm;
#pragma unroll
            for (int o = 16; o; o >>= 1) { sm += __shfl_xor_sync(~0u, sm, o); mxv = fmaxf(mxv, __shfl_xor_sync(~0u, mxv, o)); }
            cw = 26.5f * fmaxf(sm, 8.f * mxv);
        }
        if (w == 0) {
            mbar_expect_elect(bar + 8 * B_X1, rank < 2 ? 3328 : 1280);
            mbar_expect_elect(bar + 8 * B_VX, rank < 2 ? 8192 : 4096);
        }
        {
            const int kind = rank;
            const uint32_t l16 = opaque(sb + lane * 16), lw = opaque(sb + lane * 16 + w * 512);
            const uint32_t pa = opaque(sb + OFF_PS + rank * 512 + lane * 4 + w * 128);
            uint32_t lq = opaque(sb + OFF_Q + (lane & 7) * 16 + ((lane >> 3) & 1) * 256 + (lane >> 4) * 128);
            const uint32_t lv = opaque(sb + OFF_VX + w * 2048 + (lane & 7) * 16 + ((lane >> 3) & 1) * 512 + (lane >> 4) * 128);
            const uint32_t lo = opaque(sb + OFF_WO + w * 4096 + lane * 16);
            uint32_t& sfd = lq;
            const char* rp = (const char*)(g_acc + layer * ACC_LAYER) + (4 * rank + w) * 4096 + opaque((q >> 1) * 1024 + ((q & 1) * 8 + g) * 8);
            const char* lp = (const char*)(g_acc + layer * ACC_LAYER) + opaque(w * 8192 + (2 * (g & 1) + (g >> 2)) * 1024 + (((g >> 1) & 1) * 8 + 2 * q) * 8);
            float isig = 1.f;
            uint32_t kf[8];
            bar_sync_if<NB_KX, 384>(kind < 2);
            ldsm4(kf, l16 + OFF_K + (1 + w) * 1024); ldsm4(kf + 4, l16 + OFF_K + (1 + w) * 1024 + 512);
            for (int s = 0; s < NSEG - 1; s++) {
                const uint32_t pb = s & 1, ph = (s >> 1) & 1, x1 = bar + 8 * (B_X1 + pb);
                sts32(sb + OFF_MX + w * 4, __reduce_max_sync(~0u, max(amax & 0x7fff0000u, (amax << 16) & 0x7fff0000u)));
                const bool vok = mbar_try(bar + 8 * (B_VX + pb), ph, 1);
                const uint32_t va = lv + pb * 8192, vma = lw + OFF_VM + pb * 2048;
                uint32_t wf[8][4], vf[2][2][4], vm[4], one[4];
                auto scores = [&](auto MM) {
                    constexpr int mm = MM.value;
                    uint32_t qf[8], mf[8];
                    const uint32_t qa = lq + pb * 5120, ka = l16 + OFF_K + pb * 5120;
                    const uint32_t pa0 = mapa(pa, rank ^ 1), pa1 = mapa(pa, 2), pa2 = mapa(pa, rank);
                    const uint32_t xb0 = mapa(x1, rank ^ 1), xb1 = mapa(x1, 2), xb2 = mapa(x1, rank);
                    const uint32_t pm = 640 - rank * 384;
                    SFENCE();
                    bar_sync(NB_QK, 384);
                    ldsm4(qf, qa); ldsm4(qf + 4, qa + 512);
                    if (mm) { ldsm4(mf, ka); ldsm4(mf + 4, ka + 512); }
                    SFENCE();
                    float c[8][4];
#pragma unroll
                    for (int i = 0; i < (mm ? 8 : 4); i++) {
                        const uint32_t* f = (i < 4 ? kf : mf) + 2 * (i & 3);
                        c[i][0] = c[i][1] = c[i][2] = c[i][3] = 0.f;
                        mma16(c[i], qf[i & 2 ? 4 : 0], qf[i & 2 ? 5 : 1], qf[i & 2 ? 6 : 2], qf[i & 2 ? 7 : 3], f[0], f[1]);
                    }
                    SFENCE();
                    bar_arrive(NB_W1, 512);
                    const uint32_t y = pack2((c[0][0] + c[1][2]) + (c[2][0] + c[3][2]), (c[0][1] + c[1][3]) + (c[2][1] + c[3][3]));
                    st_async1(pa0, y, xb0); st_async1(pa1, y, xb1);
                    if (mm) {
                        const uint32_t z = pack2((c[4][0] + c[5][2]) + (c[6][0] + c[7][2]), (c[4][1] + c[5][3]) + (c[6][1] + c[7][3]));
                        st_async1(pa0 + pm, z, xb0); st_async1(pa1 + pm, z, xb1); st_async1(pa2 + pm, z, xb2);
                    }
                    st_async1(pa2, y, xb2);
                };
                if (kind == 2) bar_sync(NB_QK, 384);
                else if (w == 3) scores(IC<1>{});
                else scores(IC<0>{});
                if (!vok) mbar_wait(bar + 8 * (B_VX + pb), ph);
#pragma unroll
                for (int t = 0; t < 2; t++)
#pragma unroll
                    for (int j = 0; j < 2; j++) ldsm4(vf[t][j], va + t * 1024 + j * 256);
                float m4[4];
                lds128f(m4, sb + OFF_MX);
                bar_arrive_if<NB_W1, 480>(kind == 2);
                lds128(one, sb + OFF_MX + 48);
                mbar_wait(x1, ph);
                if (w == 0) PROFT(6);
                float sc[10];
                {
                    uint32_t u[4], v[4], m[2];
                    ldsm4(u, l16 + OFF_PS); ldsm4(v, l16 + OFF_PS + 512); ldsm2(m, l16 + OFF_PS + 1024);
                    ldsm4(vm, vma);
                    SFENCE();
                    m4[0] = fmaxf(fmaxf(m4[0], m4[1]), fmaxf(m4[2], m4[3])) * isig;
                    SFENCE();
#pragma unroll
                    for (int i = 0; i < 4; i++) { sc[2 * i] = bf_lo(u[i]) + bf_lo(v[i]); sc[2 * i + 1] = bf_hi(u[i]) + bf_hi(v[i]); }
                    sc[8] = bf_lo(m[0]) + bf_lo(m[1]); sc[9] = bf_hi(m[0]) + bf_hi(m[1]);
                }
                float mx = fmaxf(fmaxf(fmaxf(fmaxf(sc[0], sc[1]), fmaxf(sc[2], sc[3])), fmaxf(fmaxf(sc[4], sc[5]), fmaxf(sc[6], sc[7]))), fmaxf(sc[8], sc[9]));
                auto fetch = [&](int i) { lds128(wf[i], lo + i * 512); };
                {
                    float m1 = __shfl_xor_sync(~0u, mx, 1), m2 = __shfl_xor_sync(~0u, mx, 2), m3 = __shfl_xor_sync(~0u, mx, 3);
                    SFENCE();
#pragma unroll
                    for (int i = 0; i < 4; i++) fetch(i);
                    SFENCE();
                    mx = fmaxf(fmaxf(mx, m1), fmaxf(m2, m3)) * SM_SCALE;
                }
#pragma unroll
                for (int i = 0; i < 10; i++) sc[i] = fmaf(sc[i], SM_SCALE, -mx);
                float o0[4] = {0.f, 0.f, 0.f, 0.f}, o1[4] = {0.f, 0.f, 0.f, 0.f}, rs[4] = {0.f, 0.f, 0.f, 0.f};
                sc[8] = ex2(sc[8]); sc[9] = ex2(sc[9]);
                SFENCE();
                sc[0] = ex2(sc[0]); fetch(4); sc[1] = ex2(sc[1]); fetch(5); sc[2] = ex2(sc[2]); fetch(6);
                SFENCE();
                {
                    const uint32_t p = pack2(sc[8], sc[9]);
                    sc[3] = ex2(sc[3]); fetch(7);
                    mma8(o0, vm[0], vm[1], p);
                    mma8(o1, vm[2], vm[3], p);
                    sc[4] = ex2(sc[4]);
                    mma8(rs, one[0], one[1], p);
                    sc[5] = ex2(sc[5]);
                }
                SFENCE();
                {
                    const uint32_t p0 = pack2(sc[0], sc[1]), p1 = pack2(sc[2], sc[3]);
                    sc[6] = ex2(sc[6]);
                    mma16(o0, vf[0][0][0], vf[0][0][1], vf[0][0][2], vf[0][0][3], p0, p1);
                    SFENCE();
                    sc[7] = ex2(sc[7]);
                    mma16(o1, vf[1][0][0], vf[1][0][1], vf[1][0][2], vf[1][0][3], p0, p1);
                    SFENCE();
                    mma16(rs, one[0], one[1], one[2], one[3], p0, p1);
                    SFENCE();
                }
                {
                    const uint32_t p0 = pack2(sc[4], sc[5]), p1 = pack2(sc[6], sc[7]);
                    mma16(o0, vf[0][1][0], vf[0][1][1], vf[0][1][2], vf[0][1][3], p0, p1);
                    mma16(o1, vf[1][1][0], vf[1][1][1], vf[1][1][2], vf[1][1][3], p0, p1);
                    SFENCE();
                    mma16(rs, one[0], one[1], one[2], one[3], p0, p1);
                }
                const uint32_t e = max((__float_as_uint(cw * fmaxf(m4[0], 1.f)) >> 23) & 255u, 31u);
                SFENCE();
                stsm4t(lw + OFF_OB, pack2(o0[0], o0[1]), pack2(o0[2], o0[3]), pack2(o1[0], o1[1]), pack2(o1[2], o1[3]));
                bar_sync(NB_ATT, 128);
                uint32_t ob[16];
#pragma unroll
                for (int j = 0; j < 4; j++) ldsm4(ob + 4 * j, l16 + OFF_OB + j * 512);
                SFENCE();
                const float sig = __uint_as_float((278u - e) << 23);
                isig = __uint_as_float((e - 30u) << 23);
                const float sg0 = rcp(rs[0]) * sig, sg1 = rcp(rs[1]) * sig;
                SFENCE();
                auto tile = [&](uint32_t next, const char* p, auto LAST) {
                    float c[4][4];
#pragma unroll
                    for (int i = 0; i < 4; i++) c[i][0] = c[i][1] = c[i][2] = c[i][3] = 0.f;
#pragma unroll
                    for (int ks = 0; ks < 8; ks++) {
                        mma16(c[ks & 3], wf[ks][0], wf[ks][1], wf[ks][2], wf[ks][3], ob[2 * ks], ob[2 * ks + 1]);
                        if ((ks & 3) == 3 && !LAST.value) {
                            SFENCE();
#pragma unroll
                            for (int i = ks - 3; i <= ks; i++) lds128(wf[i], next + i * 512);
                        }
                    }
                    SFENCE();
                    if (LAST.value) { bar_arrive_if<NB_WIN, 256>(kind < 2); bar_arrive_if<NB_WIN, 384>(kind == 2); }
                    uint32_t v[4];
#pragma unroll
                    for (int i = 0; i < 4; i++)
                        v[i] = (__float_as_uint(fmaf((c[0][i] + c[1][i]) + (c[2][i] + c[3][i]), i & 1 ? sg1 : sg0, 12582912.f)) << 6) + (i < 2);
                    red_add64((u64*)p, v[0], v[2]);
                    red_add64((u64*)(p + 2048), v[1], v[3]);
                };
                tile(lo + 16384, rp, IC<0>{});
                if (w == 0) PROFT(7);
                if (w == 0) GPROF(4, 0);
                tile(lo + 32768, rp + 49152, IC<0>{});
                if (kind == 2) tile(lo + 49152, rp + 98304, IC<0>{});
                tile(0, rp + (kind == 2 ? 28 * 4096 : 98304), IC<1>{});
                if (w == 0) PROFT(8);
                sts32(sb + OFF_MX + 16, __float_as_uint(isig));
                if (w == 0) mbar_expect_elect(bar + 8 * (B_X1 + (pb ^ 1)), (kind < 2 ? 2048 : 0) + (s < NSEG - 2 ? 1280 : 0));
                if (w == 1) mbar_expect_elect(bar + 8 * (B_VX + (pb ^ 1)), kind < 2 ? 8192 : 4096);
                if (w == 2) mbar_expect_elect(bar + 8 * (B_XT + pb), (kind < 2 ? 4096 : 0) + (s < NSEG - 2 ? 40960 : 0));
                u64 y[20];
                const uint32_t kn = lw + OFF_K + 1024 + w * 512 + (pb ^ 1) * 5120;
                mbar_wait(bar + 8 * B_GO, pb);
#pragma unroll
                for (int i = 0; i < 10; i++) ld_acc0(y[2 * i], y[2 * i + 1], lp + (i >> 1) * 32768 + (i & 1) * 4096);
                if (w == 0) PROFT(9);
                uint32_t nretry = 0, b[20];
                bool done[5] = {false, false, false, false, false};
                auto publish = [&](auto FIRST) {
                    uint32_t ok = 32u, late = 32u;
                    static_for<5>([&](auto IT) {
                        constexpr int it = IT.value;
                        if (it == 2) late = and3((uint32_t)y[8], (uint32_t)y[10], (uint32_t)y[12]);
                        else if (it == 3) late &= and3((uint32_t)y[14], (uint32_t)y[16], (uint32_t)y[18]);
                        else ok = and3(ok, (uint32_t)y[4 * it], it == 4 ? late : (uint32_t)y[4 * it + 2]);
                        if (FIRST.value && it < 4) SFENCE();
                        if (it == 2 || it == 3) ok = and3(ok, (uint32_t)y[4 * it], (uint32_t)y[4 * it + 2]);
                        ok = and3(ok, (uint32_t)y[4 * it + 1], (uint32_t)y[4 * it + 3]);
                        const bool all = __all_sync(~0u, ok);
#pragma unroll
                        for (int j = 0; j < 4; j++) {
                            const u64 z = y[4 * it + j];
                            b[4 * it + j] = pack2((float)(int)(uint32_t)z, (float)(int)(uint32_t)(z >> 32));
                        }
                        sts128(lw + OFF_MEMB + it * 2048, b[4 * it], b[4 * it + 1], b[4 * it + 2], b[4 * it + 3]);
                        bar_arrive_if<NB_MEM + it, 384>(all && (FIRST.value || !done[it]));
                        done[it] = all;
                        if (FIRST.value) SFENCE();
                        if (FIRST.value && it == 0) {
                            if (w == 0) PROFT(10);
                            bar_sync_if<NB_KX, 384>(kind < 2);
                            ldsm4(kf, kn); ldsm4(kf + 4, kn + 512);
                            SFENCE();
                        }
                    });
                };
                publish(IC<1>{});
                while (!done[4]) {
                    if (++nretry > SPIN_LIMIT) die();
#pragma unroll
                    for (int i = 0; i < 10; i++) ld_acc(y[2 * i], y[2 * i + 1], lp + (i >> 1) * 32768 + (i & 1) * 4096);
                    publish(IC<0>{});
                }
                if (w == 0) PROFT(11);
                GPROF(w, nretry);
                amax = b[0];
#pragma unroll
                for (int i = 1; i < 19; i += 2) amax = absmax2(amax, absmax2(b[i], b[i + 1]));
                amax = absmax2(amax, b[19]);
                const int adv = (s & 7) == 7 ? 163840 - 896 : 128;
                rp += adv; lp += adv;
            }
        }
        bar_sync(NB_QK, 384);
        if (rank < 2) { bar_arrive(NB_W1, 512); bar_arrive(NB_WIN, 256); } else bar_arrive(NB_W1, 480);
    } else {
        asm volatile("setmaxnreg.dec.sync.aligned.u32 %0;" ::"n"(48));
        const uint32_t rank = cta_rank();
        const int w = warp - 12;
        pdl_wait();
        pdl_launch();
        uint32_t* sy = g_sync + layer * SYNC_LAYER;
        if (w == 1) {
            mbar_expect_elect(bar + 8 * B_XT, 40960);
            bulk_g2s_elect(sb + OFF_X, g_xn, 40960, bar + 8 * B_XT);
            bar_sync(NB_PRO, 288);
            if (rank == 2) mbar_wait(bar + 8 * B_ST, 0);
            else mbar_arrive_remote_elect(mapa(bar + 8 * B_ST, 2));
            mbar_wait(bar + 8 * B_XT, 0);
            bar_arrive(NB_LD, 288);
            mbar_expect_elect(bar + 8 * (B_XT + 1), rank < 2 ? 45056 : 40960);
        }
        if (rank == 2 && w == 3) {
            for (uint32_t s = 0, n = 0; s < NSEG; s++) {
                uint32_t c[2];
                for (;;) {
                    asm volatile("ld.acquire.cluster.shared::cta.v2.u32 {%0,%1},[%2];" : "=r"(c[0]), "=r"(c[1]) : "r"(sb + OFF_MX + 32) : "memory");
                    if (__all_sync(~0u, min(c[0], c[1]) > s)) break;
                    if (++n > (SPIN_LIMIT << 3)) die();
                    __nanosleep(s < NSEG - 2 ? 400 : 50);
                }
                if (h == 0) TLI(940 + s, 0, gtime());
                if (lane == 0) flag_add(sy + wk::SY_O + s);
                __syncwarp();
            }
        } else if (rank == 2) {
            const char* pf = (const char*)(g_acc + layer * ACC_LAYER) + (5 * h + lane % 5) * 1024;
            if (w == 2 && lane < 20) prefetch_l2(pf + lane / 5 * 128);
            if (w == 2 && lane < 4 && h == 0) prefetch_l2(sy + 1024 + lane * 32);
            for (int s = -1; s < NSEG - 1; s++) {
                const int pb = s & 1, n = s + 1;
                if (w == 0) {
                    mbar_wait(bar + 8 * (B_KX + (pb ^ 1)), (n >> 1) & 1);
                    const uint32_t va = sb + OFF_VX + (pb ^ 1) * 8192 + 4096, vb = bar + 8 * (B_VX + (pb ^ 1));
                    bulk_s2s_elect(mapa(va, 0), va, 4096, mapa(vb, 0));
                    bulk_s2s_elect(mapa(va, 1), va, 4096, mapa(vb, 1));
                    if (s >= 0) mbar_wait(bar + 8 * (B_XD + pb), (s >> 1) & 1);
                } else {
                    if (s >= 0) mbar_wait(bar + 8 * (B_X1 + pb), (s >> 1) & 1);
                    if (w == 1) {
                        const uint32_t xt = bar + 8 * (B_XT + pb), qa = sb + OFF_Q + (pb ^ 1) * 5120 + 1024;
                        const unsigned char* pn = g_p + (size_t)(n * H_ + h) * 12288;
                        if (n + 1 < NSEG) bulk_g2s_all3_elect(sb + OFF_X + pb * 40960, g_xn + (n + 1) * 40960, 40960, xt);
                        const int blk = wk::pb_first(n);
                        if (blk >= 0) flag_wait<true, true>(sy + wk::SY_P + blk * H_ + h, 3);
                        bulk_g2s_all3_elect(sb + OFF_VX + (pb ^ 1) * 8192, pn + 8192, 4096, bar + 8 * (B_VX + (pb ^ 1)));
                        bulk_g2s_elect(mapa(qa, 0), pn, 4096, mapa(xt, 0));
                        bulk_g2s_elect(mapa(qa, 1), pn + 4096, 4096, mapa(xt, 1));
                        mbar_wait(xt, ((n + 1) >> 1) & 1);
                    } else if (s >= 0) {
                        uint32_t* hp = sy + 1024 + s * 32;
                        uint32_t t = gtime32(), c, it = 0;
                        asm volatile("{.reg .pred p; elect.sync _|p, 0xffffffff; @p red.relaxed.gpu.global.max.u32 [%0+4],%1; @p red.relaxed.gpu.global.add.u32 [%0],1;}"
                                     ::"l"(hp), "r"(t) : "memory");
                        if (lane < 5 && s + 4 < NSEG) prefetch_l2(pf + ((s + 4) >> 3) * 163840 + ((s + 4) & 7) * 128);
                        if (lane == 5 && h == 0 && s + 4 < NSEG) prefetch_l2(hp + 4 * 32);
                        __syncwarp();
                        while (gtime32() - t < (uint32_t)delay2) {}
                        do {
                            asm volatile("ld.relaxed.gpu.global.v2.u32 {%0,%1},[%2];" : "=r"(c), "=r"(t) : "l"(hp) : "memory");
                            if (++it > (SPIN_LIMIT << 3)) die();
                        } while (__any_sync(~0u, c != H_));
                        while (gtime32() - t < (uint32_t)delay) {}
                        if (lane < 3) mbar_arrive_remote(mapa(bar + 8 * B_GO, lane));
                        __syncwarp();
                    }
                }
                bar_sync(NB_W1, 480);
            }
            if (w == 1) mbar_wait(bar + 8 * (B_VX + 1), 1);
        } else {
            if (w < 2) sts32(sb + OFF_PT + w * 768 + 640 + lane * 4, 0u);
            const uint32_t px = opaque(sb + OFF_PX + (w & 1) * 1280 + lane * 8);
            const uint32_t pt = opaque(sb + OFF_PT + (w & 1) * 768 + lane * 4);
            uint32_t os = opaque(sb + OFF_OST + (lane >> 4) * 1024 + w * 256 + (lane & 15) * 16);
            uint32_t& sfd = os;
            const int lim = opaque(8 * w + g + 8 - 2 * q);
            const uint32_t oc = mapa(sb + OFF_MX + 32 + 4 * rank, 2);
            auto store_o = [&](int n) {
                unsigned char* op = g_o + (size_t)(n * H_ + h) * 8192 + rank * 2048;
                bulk_s2g_elect(op, sb + OFF_OST + (n & 1) * 4096, 2048);
                bulk_s2g_elect(op + 4096, sb + OFF_OST + (n & 1) * 4096 + 2048, 2048);
                bulk_commit();
                bulk_wait<1>();
                __syncwarp();
                st_remote(oc, n);
            };
            for (int s = 0; s < NSEG; s++) {
                const uint32_t pb = s & 1, ph = (s >> 1) & 1;
                if ((w >> 1) != rank) { if (s >= 1) mbar_wait(bar + 8 * B_PXE, pb ^ 1); }
                else if (w & 1) mbar_wait(bar + 8 * (B_XT + (pb ^ 1)), ((s + 1) >> 1) & 1);
                else mbar_expect_elect(bar + 8 * B_PXF, rank ? 2560 : 1536);
                const u64 dq = mkdesc(sb + OFF_Q + pb * 5120 + 1024, 128, 512), dk = mkdesc(sb + OFF_K + pb * 5120, 128, 1024);
                SFENCE();
                bar_sync(NB_W1, 512);
                float c[20];
                wg_fence();
                wgmma_n40_ss<0>(c, dq, dk);
#pragma unroll
                for (int ks = 1; ks < 4; ks++) wgmma_n40_ss<1>(c, dq + ks * 16, dk + ks * 16);
                wg_commit();
                bar_arrive(NB_X, 384);
                wg_wait<0>();
                if ((w >> 1) != rank) {
                    const uint32_t pa = mapa(px, rank ^ 1), pf = mapa(bar + 8 * B_PXF, rank ^ 1);
#pragma unroll
                    for (int nt = 0; nt < 5; nt++)
                        if (nt < 3 || rank == 0) st_async2(pa + nt * 256, __float_as_uint(c[4 * nt]), __float_as_uint(c[4 * nt + 1]), pf);
                    if ((w & 1) && s) store_o(s - 1);
                    mbar_wait(bar + 8 * (w & 1 ? B_VX : B_X1) + 8 * pb, ph);
                } else {
                    mbar_wait(bar + 8 * B_PXF, pb);
                    float u[10];
#pragma unroll
                    for (int nt = 0; nt < 5; nt++) lds64f(u[2 * nt], u[2 * nt + 1], px + nt * 256);
#pragma unroll
                    for (int i = 0; i < 10; i++) u[i] = 8 * (i >> 1) + (i & 1) <= lim ? u[i] + c[4 * (i >> 1) + (i & 1)] : -INFINITY;
                    float mx = fmaxf(fmaxf(fmaxf(fmaxf(u[0], u[1]), fmaxf(u[2], u[3])), fmaxf(fmaxf(u[4], u[5]), fmaxf(u[6], u[7]))), fmaxf(u[8], u[9]));
                    const float m1 = __shfl_xor_sync(~0u, mx, 1), m2 = __shfl_xor_sync(~0u, mx, 2), m3 = __shfl_xor_sync(~0u, mx, 3);
                    mx = fmaxf(fmaxf(mx, m1), fmaxf(m2, m3)) * SM_SCALE;
#pragma unroll
                    for (int i = 0; i < 10; i++) u[i] = ex2(fmaf(u[i], SM_SCALE, -mx));
                    float sum = (((u[0] + u[1]) + (u[2] + u[3])) + ((u[4] + u[5]) + (u[6] + u[7]))) + (u[8] + u[9]);
                    const float s1 = __shfl_xor_sync(~0u, sum, 1), s2 = __shfl_xor_sync(~0u, sum, 2), s3 = __shfl_xor_sync(~0u, sum, 3);
                    sum = rcp((sum + s1) + (s2 + s3));
#pragma unroll
                    for (int nt = 0; nt < 5; nt++) sts32(pt + (nt ? nt - 1 : 4) * 128, pack2(u[2 * nt] * sum, u[2 * nt + 1] * sum));
                }
                float acc[2][8];
                const u64 dv = mkdesc(sb + OFF_VX + pb * 8192, 128, 512), dp = mkdesc(sb + OFF_PT, 128, 768);
                const u64 dm = mkdesc(sb + OFF_VM + pb * 2048, 0, 128);
                fence_async();
                bar_sync(NB_WIN, 256);
                wg_fence();
#pragma unroll
                for (int m = 0; m < 2; m++) {
                    wgmma_n16_ss<0>(acc[m], dv + m * 256, dp);
                    wgmma_n16_ss<1>(acc[m], dv + m * 256 + 16, dp + 16);
                    wgmma_n16_ss<1>(acc[m], dm + m * 64, dp + 32);
                }
                wg_commit();
                bar_arrive_if<NB_W2, 384>(s < NSEG - 1);
                wg_wait<0>();
#pragma unroll
                for (int m = 0; m < 2; m++)
                    stsm4t(os + pb * 4096 + m * 2048, pack2(acc[m][0], acc[m][1]), pack2(acc[m][2], acc[m][3]), pack2(acc[m][4], acc[m][5]), pack2(acc[m][6], acc[m][7]));
                fence_async();
                mbar_arrive_remote_elect(mapa(bar + 8 * (B_XD + pb), 2));
                if ((w >> 1) == rank) mbar_arrive_remote_elect(mapa(bar + 8 * B_PXE, rank ^ 1));
            }
            bar_sync(NB_W2, 128);
            if (w == 3 - 2 * rank) {
                store_o(NSEG - 1);
                bulk_wait<0>();
                __syncwarp();
                st_remote(oc, NSEG);
            }
        }
    }
    __syncwarp();
    if (lane < 3) mbar_arrive_remote(mapa(bar + 8 * B_FIN, lane));
    mbar_wait(bar + 8 * B_FIN, 0);
    TLE(2 + 5 * layer);
}

int g_delay = 1500650, g_layers = 2;

void make_map(CUtensorMap* m, CUtensorMapDataType dt, const void* p, const cuuint64_t* dim, const cuuint64_t* str, const cuuint32_t* box, CUtensorMapSwizzle sw) {
    typedef CUresult (*Fn)(CUtensorMap*, CUtensorMapDataType, cuuint32_t, void*, const cuuint64_t*, const cuuint64_t*, const cuuint32_t*,
                           const cuuint32_t*, CUtensorMapInterleave, CUtensorMapSwizzle, CUtensorMapL2promotion, CUtensorMapFloatOOBfill);
    static Fn fn = nullptr;
    if (!fn) {
        cudaDriverEntryPointQueryResult qr;
        cudaGetDriverEntryPoint("cuTensorMapEncodeTiled", (void**)&fn, cudaEnableDefault, &qr);
    }
    const cuuint32_t es[3] = {1, 1, 1};
    fn(m, dt, 3, (void*)p, dim, str, box, es, CU_TENSOR_MAP_INTERLEAVE_NONE, sw, CU_TENSOR_MAP_L2_PROMOTION_L2_128B, CU_TENSOR_MAP_FLOAT_OOB_FILL_NONE);
}
void map_weight(CUtensorMap* m, const bf16* p, int rows, int cols, int ng, int br = 64) {
    const cuuint64_t dim[3] = {64, (cuuint64_t)rows, (cuuint64_t)cols / 64}, str[2] = {(cuuint64_t)cols * 2, 128};
    const cuuint32_t box[3] = {64, (cuuint32_t)br, (cuuint32_t)ng};
    make_map(m, CU_TENSOR_MAP_DATA_TYPE_BFLOAT16, p, dim, str, box, CU_TENSOR_MAP_SWIZZLE_128B);
}
void map_pieces(CUtensorMap* m, const void* p, int np, int ns) {
    const cuuint64_t dim[3] = {256, (cuuint64_t)np * 2, NSEG}, str[2] = {2048, (cuuint64_t)np * 4096};
    const cuuint32_t box[3] = {256, 2, (cuuint32_t)ns};
    make_map(m, CU_TENSOR_MAP_DATA_TYPE_UINT64, p, dim, str, box, CU_TENSOR_MAP_SWIZZLE_NONE);
}

template <class... P, class... A> void launch(void (*k)(P...), int grid, int block, int smem, int cluster, bool pdl, A... args) {
    cudaLaunchConfig_t c = {};
    c.gridDim = dim3(grid); c.blockDim = dim3(block); c.dynamicSmemBytes = smem; c.stream = cudaStreamPerThread;
    cudaLaunchAttribute at[2];
    int n = 0;
    if (cluster > 1) { at[n].id = cudaLaunchAttributeClusterDimension; at[n].val.clusterDim.x = cluster; at[n].val.clusterDim.y = 1; at[n].val.clusterDim.z = 1; n++; }
    if (pdl) { at[n].id = cudaLaunchAttributeProgrammaticStreamSerialization; at[n].val.programmaticStreamSerializationAllowed = 1; n++; }
    c.attrs = at; c.numAttrs = n;
    cudaLaunchKernelEx(&c, k, args...);
}

int max_clusters() {
    cudaLaunchConfig_t c = {};
    c.gridDim = dim3(3 * H_); c.blockDim = dim3(512); c.dynamicSmemBytes = rec::SMEM;
    cudaLaunchAttribute at[1];
    at[0].id = cudaLaunchAttributeClusterDimension; at[0].val.clusterDim.x = 3; at[0].val.clusterDim.y = 1; at[0].val.clusterDim.z = 1;
    c.attrs = at; c.numAttrs = 1;
    int n = 0;
    cudaOccupancyMaxActiveClusters(&n, rec_kernel, &c);
    return n;
}

}

extern "C" void kernel_launch(void* const* d_in, const int* in_sizes, int n_in, void* d_out, int out_size) {
    const bf16* x = (const bf16*)d_in[0];
    const bf16* mem0 = (const bf16*)d_in[1];
    const bf16* Wq = (const bf16*)d_in[2];
    const bf16* Wk = (const bf16*)d_in[3];
    const bf16* Wv = (const bf16*)d_in[4];
    const bf16* Wo = (const bf16*)d_in[5];
    const bf16* wr = (const bf16*)d_in[8];
    const bf16* wi = (const bf16*)d_in[9];
    cudaFuncSetAttribute(rec_kernel, cudaFuncAttributeMaxDynamicSharedMemorySize, rec::SMEM);
    cudaFuncSetAttribute(side_kernel, cudaFuncAttributeMaxDynamicSharedMemorySize, wk::SMEM);
    cudaFuncSetAttribute(colfft_kernel, cudaFuncAttributeMaxDynamicSharedMemorySize, CF_SMEM);
    Maps maps;
    void *pxn, *po;
    cudaGetSymbolAddress(&pxn, g_xn);
    cudaGetSymbolAddress(&po, g_o);
    map_weight(&maps.wq2, Wq, D_, 4096, 2); map_weight(&maps.wv1, Wv, D_, 4096, 1);
    map_weight(&maps.wo2, Wo, 4096, D_, 2); map_weight(&maps.wo1, Wo, 4096, D_, 1, 192);
    map_pieces(&maps.x6, pxn, 10, 6); map_pieces(&maps.x2, pxn, 10, 2);
    map_pieces(&maps.o6, po, 64, 6); map_pieces(&maps.o2, po, 64, 2);
    bf16 *x1, *x2;
    cudaGetSymbolAddress((void**)&x1, g_x1);
    cudaGetSymbolAddress((void**)&x2, g_x2);
    constexpr int ONE_PER_SM = 120 * 1024;
    cudaFuncSetAttribute(rowfft_kernel, cudaFuncAttributeMaxDynamicSharedMemorySize, ONE_PER_SM);
    cudaFuncSetAttribute(rowifft_kernel, cudaFuncAttributeMaxDynamicSharedMemorySize, ONE_PER_SM);
    static int ncl = 0, nsm = 0;
    if (!ncl) { ncl = max_clusters(); cudaDeviceGetAttribute(&nsm, cudaDevAttrMultiProcessorCount, 0); }
    maps.wr = wr; maps.wi = wi;
    launch(prep_kernel, 128, 512, 0, 1, false, x, Wq, Wk, Wv, Wo);
    for (int layer = 0; layer < g_layers; layer++) {
        const bf16* xin = layer ? x2 : x;
        launch(rec_kernel, 3 * ncl, 512, rec::SMEM, 3, true, maps, xin, x1, mem0, Wq, Wk, Wv, Wo, layer, g_delay % 10000, g_delay / 10000);
        launch(side_kernel, nsm - 3 * (ncl - H_), 512, wk::SMEM, 1, true, maps, xin, x1, layer);
        launch(rowfft_kernel, 128, 256, ONE_PER_SM, 1, true, xin, x1, Wq, Wk, Wv, layer);
        launch(colfft_kernel, 107, 384, CF_SMEM, 1, true, layer);
        launch(rowifft_kernel, 128, 256, ONE_PER_SM, 1, true, (const bf16*)x1, layer ? (bf16*)d_out : x2, layer);
    }
}
```

```cpp
#include <cuda_runtime.h>
#include <cuda_bf16.h>
#include <cuda.h>
#include <stdint.h>

#define DEV __device__ __forceinline__
typedef unsigned long long u64;
typedef __nv_bfloat16 bf16;

namespace {

constexpr int S_ = 2048, D_ = 640, H_ = 32, E_ = 128, NSEG = 64;

__device__ __align__(1024) unsigned char g_xn[S_ * D_ * 2];
__device__ __align__(1024) unsigned char g_o[S_ * H_ * E_ * 2];
constexpr int ACC_LAYER = 32 * 5120;
__device__ __align__(4096) u64 g_acc[2 * ACC_LAYER];
__device__ __align__(16) float g_nrm[256];
__device__ __align__(1024) unsigned char g_p[NSEG * H_ * 3 * 4096];
constexpr int SYNC_LAYER = 1024 + 64 * 32;
__device__ __align__(128) uint32_t g_sync[2 * SYNC_LAYER];
__device__ __align__(1024) bf16 g_x1[S_ * D_];
__device__ __align__(1024) bf16 g_x2[S_ * D_];
constexpr int YT_ROWS = 128;
__device__ __align__(1024) float g_yt[2 * YT_ROWS * D_];
constexpr int NCOL = 321;
__device__ __align__(1024) unsigned char g_z[NCOL * 8192];
__device__ __align__(1024) unsigned char g_wt[NCOL * 8192];
__device__ __align__(1024) uint4 g_f128[2 * 8 * 256];
__device__ __align__(1024) uint4 g_f64[2 * 4 * 128];
__device__ __align__(1024) bf16 g_g32[2 * 4096];
#define TLI(id, k, v)
#define TLS(i)
#define TLE(i)

DEV uint32_t s2u(const void* p) { return (uint32_t)__cvta_generic_to_shared(p); }
DEV uint32_t clk() { uint32_t c; asm volatile("mov.u32 %0,%%clock;" : "=r"(c)::"memory"); return c; }
DEV uint32_t gtime32() { uint32_t t; asm volatile("mov.u32 %0,%%globaltimer_lo;" : "=r"(t)::"memory"); return t; }
DEV uint32_t cta_rank() { uint32_t r; asm volatile("mov.u32 %0,%%cluster_ctarank;" : "=r"(r)); return __shfl_sync(~0u, r, 0); }
DEV uint32_t mapa(uint32_t a, uint32_t r) { uint32_t o; asm("mapa.shared::cluster.u32 %0,%1,%2;" : "=r"(o) : "r"(a), "r"(r)); return o; }
DEV void mbar_init(uint32_t b, uint32_t n) { asm volatile("mbarrier.init.shared::cta.b64 [%0],%1;" ::"r"(b), "r"(n) : "memory"); }
DEV bool mbar_try(uint32_t b, uint32_t par, int) {
    uint32_t ok;
    asm volatile("{.reg .pred p; mbarrier.test_wait.parity.shared::cta.b64 p,[%1],%2; selp.u32 %0,1,0,p;}" : "=r"(ok) : "r"(b), "r"(par) : "memory");
    return ok;
}
DEV bool mbar_try(uint32_t b, uint32_t par) {
    uint32_t ok;
    asm volatile("{.reg .pred p; mbarrier.try_wait.parity.shared::cta.b64 p,[%1],%2; selp.u32 %0,1,0,p;}" : "=r"(ok) : "r"(b), "r"(par) : "memory");
    return ok;
}
constexpr uint32_t SPIN_LIMIT = 1u << 18;
DEV void die() { __trap(); }
DEV void mbar_wait(uint32_t b, uint32_t par) {
    uint32_t n = 0;
    while (!mbar_try(b, par)) if (++n > SPIN_LIMIT) die();
}
DEV uint32_t opaque(uint32_t x) { return __shfl_xor_sync(~0u, x, 0); }
#define SFENCE() asm volatile("{.reg .pred p; setp.ne.u32 p,%1,0; @p mov.u32 %0,%%clock;}" : "+r"(sfd) : "r"((uint32_t)never) : "memory")
DEV void mbar_arrive(uint32_t b) { asm volatile("mbarrier.arrive.shared::cta.b64 _,[%0];" ::"r"(b) : "memory"); }
DEV void mbar_arrive_elect(uint32_t b) { asm volatile("{.reg .pred p; elect.sync _|p, 0xffffffff; @p mbarrier.arrive.shared::cta.b64 _,[%0];}" ::"r"(b) : "memory"); }
DEV void mbar_arrive_elect_if(uint32_t b, bool c) {
    asm volatile("{.reg .pred p, q; setp.ne.u32 q,%1,0; elect.sync _|p, 0xffffffff; and.pred p,p,q; @p mbarrier.arrive.shared::cta.b64 _,[%0];}" ::"r"(b), "r"((uint32_t)c) : "memory");
}
DEV void mbar_expect_elect(uint32_t b, uint32_t tx) {
    asm volatile("{.reg .pred p; elect.sync _|p, 0xffffffff; @p mbarrier.arrive.expect_tx.shared::cta.b64 _,[%0],%1;}" ::"r"(b), "r"(tx) : "memory");
}
DEV void mbar_arrive_remote_elect(uint32_t b) { asm volatile("{.reg .pred p; elect.sync _|p, 0xffffffff; @p mbarrier.arrive.shared::cluster.b64 _,[%0];}" ::"r"(b) : "memory"); }
DEV bool elect() { uint32_t r; asm volatile("{.reg .pred p; elect.sync _|p, 0xffffffff; selp.u32 %0,1,0,p;}" : "=r"(r)); return r; }
DEV void mbar_arrive_remote(uint32_t b) { asm volatile("mbarrier.arrive.shared::cluster.b64 _,[%0];" ::"r"(b) : "memory"); }
DEV void mbar_expect(uint32_t b, uint32_t tx) { asm volatile("mbarrier.arrive.expect_tx.shared::cta.b64 _,[%0],%1;" ::"r"(b), "r"(tx) : "memory"); }
DEV void bar_sync(int id, int n) { asm volatile("bar.sync %0,%1;" ::"r"(id), "r"(n) : "memory"); }
DEV void bar_arrive(int id, int n) { asm volatile("bar.arrive %0,%1;" ::"r"(id), "r"(n) : "memory"); }
template <int ID, int N> DEV void bar_arrive_if(bool p) {
    asm volatile("{.reg .pred p; setp.ne.u32 p,%0,0; @p bar.arrive %1,%2;}" ::"r"((uint32_t)p), "n"(ID), "n"(N) : "memory");
}
DEV void prefetch_bulk(const void* p, uint32_t bytes) { asm volatile("cp.async.bulk.prefetch.L2.global [%0],%1;" ::"l"(p), "r"(bytes) : "memory"); }
DEV void prefetch_l2(const void* p) { asm volatile("prefetch.global.L2 [%0];" ::"l"(p) : "memory"); }
template <int ID, int N> DEV void bar_sync_if(bool p) {
    asm volatile("{.reg .pred p; setp.ne.u32 p,%0,0; @p bar.sync %1,%2;}" ::"r"((uint32_t)p), "n"(ID), "n"(N) : "memory");
}
DEV void st_remote(uint32_t a, uint32_t x) { asm volatile("st.relaxed.cluster.shared::cluster.u32 [%0],%1;" ::"r"(a), "r"(x) : "memory"); }
DEV void st_async1(uint32_t a, uint32_t x, uint32_t b) {
    asm volatile("st.async.shared::cluster.mbarrier::complete_tx::bytes.u32 [%0],%1,[%2];" ::"r"(a), "r"(x), "r"(b) : "memory");
}
DEV void st_async2(uint32_t a, uint32_t x, uint32_t y, uint32_t b) {
    asm volatile("st.async.shared::cluster.mbarrier::complete_tx::bytes.v2.u32 [%0],{%1,%2},[%3];" ::"r"(a), "r"(x), "r"(y), "r"(b) : "memory");
}
DEV void st_async4(uint32_t a, uint32_t x, uint32_t y, uint32_t z, uint32_t w, uint32_t b) {
    asm volatile("st.async.shared::cluster.mbarrier::complete_tx::bytes.v4.u32 [%0],{%1,%2,%3,%4},[%5];" ::"r"(a), "r"(x), "r"(y), "r"(z), "r"(w), "r"(b) : "memory");
}
DEV void bulk_g2s(uint32_t dst, const void* src, uint32_t bytes, uint32_t b) {
    asm volatile("cp.async.bulk.shared::cluster.global.mbarrier::complete_tx::bytes [%0],[%1],%2,[%3];" ::"r"(dst), "l"(src), "r"(bytes), "r"(b) : "memory");
}
DEV void bulk_g2s_elect(uint32_t dst, const void* src, uint32_t bytes, uint32_t b) {
    asm volatile("{.reg .pred p; elect.sync _|p, 0xffffffff; @p cp.async.bulk.shared::cluster.global.mbarrier::complete_tx::bytes [%0],[%1],%2,[%3];}"
                 ::"r"(dst), "l"(src), "r"(bytes), "r"(b) : "memory");
}
DEV void bulk_g2s_all3_elect(uint32_t dst, const void* src, uint32_t bytes, uint32_t b) {
    asm volatile("{.reg .pred p; elect.sync _|p, 0xffffffff; @p cp.async.bulk.shared::cluster.global.mbarrier::complete_tx::bytes.multicast::cluster [%0],[%1],%2,[%3],%4;}"
                 ::"r"(dst), "l"(src), "r"(bytes), "r"(b), "h"((unsigned short)7) : "memory");
}
DEV void bulk_s2s_elect(uint32_t dst, uint32_t src, uint32_t bytes, uint32_t b) {
    asm volatile("{.reg .pred p; elect.sync _|p, 0xffffffff; @p cp.async.bulk.shared::cluster.shared::cta.mbarrier::complete_tx::bytes [%0],[%1],%2,[%3];}"
                 ::"r"(dst), "r"(src), "r"(bytes), "r"(b) : "memory");
}
DEV void bulk_s2g_elect(void* dst, uint32_t src, uint32_t bytes) {
    asm volatile("{.reg .pred p; elect.sync _|p, 0xffffffff; @p cp.async.bulk.global.shared::cta.bulk_group [%0],[%1],%2;}" ::"l"(dst), "r"(src), "r"(bytes) : "memory");
}
DEV void bulk_s2s(uint32_t dst, uint32_t src, uint32_t bytes, uint32_t b) {
    asm volatile("cp.async.bulk.shared::cluster.shared::cta.mbarrier::complete_tx::bytes [%0],[%1],%2,[%3];" ::"r"(dst), "r"(src), "r"(bytes), "r"(b) : "memory");
}
DEV void bulk_s2g(void* dst, uint32_t src, uint32_t bytes) {
    asm volatile("cp.async.bulk.global.shared::cta.bulk_group [%0],[%1],%2;" ::"l"(dst), "r"(src), "r"(bytes) : "memory");
}
DEV void tma3d(uint32_t dst, const CUtensorMap* m, int c0, int c1, int c2, uint32_t b) {
    asm volatile("cp.async.bulk.tensor.3d.shared::cluster.global.mbarrier::complete_tx::bytes [%0],[%1,{%3,%4,%5}],[%2];"
                 ::"r"(dst), "l"(m), "r"(b), "r"(c0), "r"(c1), "r"(c2) : "memory");
}
DEV void bulk_commit() { asm volatile("cp.async.bulk.commit_group;" ::: "memory"); }
template <int N> DEV void bulk_wait() { asm volatile("cp.async.bulk.wait_group %0;" ::"n"(N) : "memory"); }
template <int N> DEV void bulk_wait_read() { asm volatile("cp.async.bulk.wait_group.read %0;" ::"n"(N) : "memory"); }
DEV void fence_async_all() { asm volatile("fence.proxy.async;" ::: "memory"); }
DEV void flag_add(uint32_t* p) { fence_async_all(); asm volatile("red.release.gpu.global.add.u32 [%0],1;" ::"l"(p) : "memory"); }
template <bool BOUNDED = true, bool UNIFORM = false> DEV void flag_wait(const uint32_t* p, uint32_t n) {
    uint32_t v, it = 0;
    for (;;) {
        asm volatile("ld.acquire.gpu.global.u32 %0,[%1];" : "=r"(v) : "l"(p) : "memory");
        if (UNIFORM ? __all_sync(~0u, v >= n) : v >= n) break;
        if (BOUNDED && ++it > (SPIN_LIMIT << 3)) die();
        __nanosleep(100);
    }
    fence_async_all();
}
DEV void cp16(uint32_t dst, const void* src) { asm volatile("cp.async.cg.shared.global [%0],[%1],16;" ::"r"(dst), "l"(src) : "memory"); }
DEV void cp_commit() { asm volatile("cp.async.commit_group;" ::: "memory"); }
template <int N> DEV void cp_wait() { asm volatile("cp.async.wait_group %0;" ::"n"(N) : "memory"); }
DEV uint32_t lds32(uint32_t a) { uint32_t x; asm volatile("ld.shared.u32 %0,[%1];" : "=r"(x) : "r"(a) : "memory"); return x; }
DEV void fence_async() { asm volatile("fence.proxy.async.shared::cta;" ::: "memory"); }
DEV uint32_t pack2(float lo, float hi) { uint32_t r; asm("cvt.rn.bf16x2.f32 %0,%1,%2;" : "=r"(r) : "f"(hi), "f"(lo)); return r; }
DEV uint32_t prmt(uint32_t a, uint32_t b, uint32_t s) { uint32_t r; asm("prmt.b32 %0,%1,%2,%3;" : "=r"(r) : "r"(a), "r"(b), "r"(s)); return r; }
DEV float ex2(float x) { float r; asm("ex2.approx.ftz.f32 %0,%1;" : "=f"(r) : "f"(x)); return r; }
DEV float rcp(float x) { float r; asm("rcp.approx.ftz.f32 %0,%1;" : "=f"(r) : "f"(x)); return r; }
DEV void lds128(uint32_t* r, uint32_t a) { asm volatile("ld.shared.v4.u32 {%0,%1,%2,%3},[%4];" : "=r"(r[0]), "=r"(r[1]), "=r"(r[2]), "=r"(r[3]) : "r"(a) : "memory"); }
DEV void lds64(uint32_t* r, uint32_t a) { asm volatile("ld.shared.v2.u32 {%0,%1},[%2];" : "=r"(r[0]), "=r"(r[1]) : "r"(a) : "memory"); }
DEV void lds64f(float& x, float& y, uint32_t a) { asm volatile("ld.shared.v2.f32 {%0,%1},[%2];" : "=f"(x), "=f"(y) : "r"(a) : "memory"); }
DEV void lds128f(float* r, uint32_t a) { asm volatile("ld.shared.v4.f32 {%0,%1,%2,%3},[%4];" : "=f"(r[0]), "=f"(r[1]), "=f"(r[2]), "=f"(r[3]) : "r"(a) : "memory"); }
DEV void sts128(uint32_t a, uint32_t x, uint32_t y, uint32_t z, uint32_t w) { asm volatile("st.shared.v4.u32 [%0],{%1,%2,%3,%4};" ::"r"(a), "r"(x), "r"(y), "r"(z), "r"(w) : "memory"); }
DEV void sts64(uint32_t a, uint32_t x, uint32_t y) { asm volatile("st.shared.v2.u32 [%0],{%1,%2};" ::"r"(a), "r"(x), "r"(y) : "memory"); }
DEV void sts32(uint32_t a, uint32_t x) { asm volatile("st.shared.u32 [%0],%1;" ::"r"(a), "r"(x) : "memory"); }
DEV void ldsm4(uint32_t* r, uint32_t a) { asm volatile("ldmatrix.sync.aligned.m8n8.x4.shared.b16 {%0,%1,%2,%3},[%4];" : "=r"(r[0]), "=r"(r[1]), "=r"(r[2]), "=r"(r[3]) : "r"(a) : "memory"); }
DEV void ldsm4t(uint32_t* r, uint32_t a) { asm volatile("ldmatrix.sync.aligned.m8n8.x4.trans.shared.b16 {%0,%1,%2,%3},[%4];" : "=r"(r[0]), "=r"(r[1]), "=r"(r[2]), "=r"(r[3]) : "r"(a) : "memory"); }
DEV void ldsm2(uint32_t* r, uint32_t a) { asm volatile("ldmatrix.sync.aligned.m8n8.x2.shared.b16 {%0,%1},[%2];" : "=r"(r[0]), "=r"(r[1]) : "r"(a) : "memory"); }
DEV void stsm4t(uint32_t a, uint32_t x, uint32_t y, uint32_t z, uint32_t w) { asm volatile("stmatrix.sync.aligned.m8n8.x4.trans.shared.b16 [%0],{%1,%2,%3,%4};" ::"r"(a), "r"(x), "r"(y), "r"(z), "r"(w) : "memory"); }
DEV void stsm4(uint32_t a, uint32_t x, uint32_t y, uint32_t z, uint32_t w) { asm volatile("stmatrix.sync.aligned.m8n8.x4.shared.b16 [%0],{%1,%2,%3,%4};" ::"r"(a), "r"(x), "r"(y), "r"(z), "r"(w) : "memory"); }
DEV void stsm2(uint32_t a, uint32_t x, uint32_t y) { asm volatile("stmatrix.sync.aligned.m8n8.x2.shared.b16 [%0],{%1,%2};" ::"r"(a), "r"(x), "r"(y) : "memory"); }
DEV void sts128f_if(uint32_t a, const float* v, bool p) {
    asm volatile("{.reg .pred p; setp.ne.u32 p,%5,0; @p st.shared.v4.f32 [%0],{%1,%2,%3,%4};}" ::"r"(a), "f"(v[0]), "f"(v[1]), "f"(v[2]), "f"(v[3]), "r"((uint32_t)p) : "memory");
}
DEV void stsm2t_if(uint32_t a, uint32_t x, uint32_t y, bool p) {
    asm volatile("{.reg .pred p; setp.ne.u32 p,%3,0; @p stmatrix.sync.aligned.m8n8.x2.trans.shared.b16 [%0],{%1,%2};}" ::"r"(a), "r"(x), "r"(y), "r"((uint32_t)p) : "memory");
}
DEV void stsm2t(uint32_t a, uint32_t x, uint32_t y) { asm volatile("stmatrix.sync.aligned.m8n8.x2.trans.shared.b16 [%0],{%1,%2};" ::"r"(a), "r"(x), "r"(y) : "memory"); }
DEV void mma16(float* d, uint32_t a0, uint32_t a1, uint32_t a2, uint32_t a3, uint32_t b0, uint32_t b1) {
    asm volatile("mma.sync.aligned.m16n8k16.row.col.f32.bf16.bf16.f32 {%0,%1,%2,%3},{%4,%5,%6,%7},{%8,%9},{%0,%1,%2,%3};"
                 : "+f"(d[0]), "+f"(d[1]), "+f"(d[2]), "+f"(d[3]) : "r"(a0), "r"(a1), "r"(a2), "r"(a3), "r"(b0), "r"(b1));
}
DEV void mma8(float* d, uint32_t a0, uint32_t a1, uint32_t b0) {
    asm volatile("mma.sync.aligned.m16n8k8.row.col.f32.bf16.bf16.f32 {%0,%1,%2,%3},{%4,%5},{%6},{%0,%1,%2,%3};"
                 : "+f"(d[0]), "+f"(d[1]), "+f"(d[2]), "+f"(d[3]) : "r"(a0), "r"(a1), "r"(b0));
}
DEV u64 mkdesc(uint32_t a, uint32_t lbo, uint32_t sbo) { return (u64)((a & 0x3ffff) >> 4) | ((u64)(lbo >> 4) << 16) | ((u64)(sbo >> 4) << 32); }
constexpr u64 SW128 = 1ull << 62;
DEV void wg_fence() { asm volatile("wgmma.fence.sync.aligned;" ::: "memory"); }
DEV void wg_commit() { asm volatile("wgmma.commit_group.sync.aligned;" ::: "memory"); }
template <int N> DEV void wg_wait() { asm volatile("wgmma.wait_group.sync.aligned %0;" ::"n"(N) : "memory"); }
template <int ACC> DEV void wgmma_n32_rs(float* d, const uint32_t* a, u64 desc) {
    asm volatile("wgmma.mma_async.sync.aligned.m64n32k16.f32.bf16.bf16 {%0,%1,%2,%3,%4,%5,%6,%7,%8,%9,%10,%11,%12,%13,%14,%15},{%16,%17,%18,%19},%20,%21,1,1,0;"
                 : "+f"(d[0]), "+f"(d[1]), "+f"(d[2]), "+f"(d[3]), "+f"(d[4]), "+f"(d[5]), "+f"(d[6]), "+f"(d[7]),
                   "+f"(d[8]), "+f"(d[9]), "+f"(d[10]), "+f"(d[11]), "+f"(d[12]), "+f"(d[13]), "+f"(d[14]), "+f"(d[15])
                 : "r"(a[0]), "r"(a[1]), "r"(a[2]), "r"(a[3]), "l"(desc), "n"(ACC));
}
template <int ACC> DEV void wgmma_n32_ss(float* d, u64 da, u64 desc) {
    asm volatile("wgmma.mma_async.sync.aligned.m64n32k16.f32.bf16.bf16 {%0,%1,%2,%3,%4,%5,%6,%7,%8,%9,%10,%11,%12,%13,%14,%15},%16,%17,%18,1,1,0,0;"
                 : "+f"(d[0]), "+f"(d[1]), "+f"(d[2]), "+f"(d[3]), "+f"(d[4]), "+f"(d[5]), "+f"(d[6]), "+f"(d[7]),
                   "+f"(d[8]), "+f"(d[9]), "+f"(d[10]), "+f"(d[11]), "+f"(d[12]), "+f"(d[13]), "+f"(d[14]), "+f"(d[15])
                 : "l"(da), "l"(desc), "n"(ACC));
}
template <int ACC> DEV void wgmma_n16_ss(float* d, u64 da, u64 desc) {
    asm volatile("wgmma.mma_async.sync.aligned.m64n16k16.f32.bf16.bf16 {%0,%1,%2,%3,%4,%5,%6,%7},%8,%9,%10,1,1,0,0;"
                 : "+f"(d[0]), "+f"(d[1]), "+f"(d[2]), "+f"(d[3]), "+f"(d[4]), "+f"(d[5]), "+f"(d[6]), "+f"(d[7])
                 : "l"(da), "l"(desc), "n"(ACC));
}
#define ACC8(o) "+f"(d[o]), "+f"(d[o + 1]), "+f"(d[o + 2]), "+f"(d[o + 3]), "+f"(d[o + 4]), "+f"(d[o + 5]), "+f"(d[o + 6]), "+f"(d[o + 7])
template <int ACC, int TB> DEV void wgmma_n64_rs(float* d, const uint32_t* a, u64 desc) {
    asm volatile("wgmma.mma_async.sync.aligned.m64n64k16.f32.bf16.bf16 {%0,%1,%2,%3,%4,%5,%6,%7,%8,%9,%10,%11,%12,%13,%14,%15,"
                 "%16,%17,%18,%19,%20,%21,%22,%23,%24,%25,%26,%27,%28,%29,%30,%31},{%32,%33,%34,%35},%36,%37,1,1,%38;"
                 : ACC8(0), ACC8(8), ACC8(16), ACC8(24) : "r"(a[0]), "r"(a[1]), "r"(a[2]), "r"(a[3]), "l"(desc), "n"(ACC), "n"(TB));
}
template <int ACC, int TB> DEV void wgmma_n80_rs(float* d, const uint32_t* a, u64 desc) {
    asm volatile("wgmma.mma_async.sync.aligned.m64n80k16.f32.bf16.bf16 {%0,%1,%2,%3,%4,%5,%6,%7,%8,%9,%10,%11,%12,%13,%14,%15,"
                 "%16,%17,%18,%19,%20,%21,%22,%23,%24,%25,%26,%27,%28,%29,%30,%31,%32,%33,%34,%35,%36,%37,%38,%39},{%40,%41,%42,%43},%44,%45,1,1,%46;"
                 : ACC8(0), ACC8(8), ACC8(16), ACC8(24), ACC8(32) : "r"(a[0]), "r"(a[1]), "r"(a[2]), "r"(a[3]), "l"(desc), "n"(ACC), "n"(TB));
}
template <int TA, int TB> DEV void wgmma_n64_ss(float* d, u64 da, u64 db, int acc) {
    asm volatile("{.reg .pred p; setp.ne.b32 p,%34,0; wgmma.mma_async.sync.aligned.m64n64k16.f32.bf16.bf16 {%0,%1,%2,%3,%4,%5,%6,%7,%8,%9,%10,%11,%12,%13,%14,%15,%16,%17,%18,%19,%20,%21,%22,%23,%24,%25,%26,%27,%28,%29,%30,%31},%32,%33,p,1,1,%35,%36;}"
                 : ACC8(0), ACC8(8), ACC8(16), ACC8(24) : "l"(da), "l"(db), "r"(acc), "n"(TA), "n"(TB));
}
template <int TA, int TB> DEV void wgmma_n128_ss(float* d, u64 da, u64 db, int acc) {
    asm volatile("{.reg .pred p; setp.ne.b32 p,%66,0; wgmma.mma_async.sync.aligned.m64n128k16.f32.bf16.bf16 {%0,%1,%2,%3,%4,%5,%6,%7,%8,%9,%10,%11,%12,%13,%14,%15,%16,%17,%18,%19,%20,%21,%22,%23,%24,%25,%26,%27,%28,%29,%30,%31,%32,%33,%34,%35,%36,%37,%38,%39,%40,%41,%42,%43,%44,%45,%46,%47,%48,%49,%50,%51,%52,%53,%54,%55,%56,%57,%58,%59,%60,%61,%62,%63},%64,%65,p,1,1,%67,%68;}"
                 : ACC8(0), ACC8(8), ACC8(16), ACC8(24), ACC8(32), ACC8(40), ACC8(48), ACC8(56) : "l"(da), "l"(db), "r"(acc), "n"(TA), "n"(TB));
}
template <int TA, int TB> DEV void wgmma_n192_ss(float* d, u64 da, u64 db, int acc) {
    asm volatile("{.reg .pred p; setp.ne.b32 p,%98,0; wgmma.mma_async.sync.aligned.m64n192k16.f32.bf16.bf16 {%0,%1,%2,%3,%4,%5,%6,%7,%8,%9,%10,%11,%12,%13,%14,%15,%16,%17,%18,%19,%20,%21,%22,%23,%24,%25,%26,%27,%28,%29,%30,%31,%32,%33,%34,%35,%36,%37,%38,%39,%40,%41,%42,%43,%44,%45,%46,%47,%48,%49,%50,%51,%52,%53,%54,%55,%56,%57,%58,%59,%60,%61,%62,%63,%64,%65,%66,%67,%68,%69,%70,%71,%72,%73,%74,%75,%76,%77,%78,%79,%80,%81,%82,%83,%84,%85,%86,%87,%88,%89,%90,%91,%92,%93,%94,%95},%96,%97,p,1,1,%99,%100;}"
                 : ACC8(0), ACC8(8), ACC8(16), ACC8(24), ACC8(32), ACC8(40), ACC8(48), ACC8(56), ACC8(64), ACC8(72), ACC8(80), ACC8(88) : "l"(da), "l"(db), "r"(acc), "n"(TA), "n"(TB));
}
template <int ACC> DEV void wgmma_n40_ss(float* d, u64 da, u64 desc) {
    asm volatile("wgmma.mma_async.sync.aligned.m64n40k16.f32.bf16.bf16 {%0,%1,%2,%3,%4,%5,%6,%7,%8,%9,%10,%11,%12,%13,%14,%15,%16,%17,%18,%19},%20,%21,%22,1,1,0,0;"
                 : ACC8(0), ACC8(8), "+f"(d[16]), "+f"(d[17]), "+f"(d[18]), "+f"(d[19]) : "l"(da), "l"(desc), "n"(ACC));
}
DEV void pdl_wait() { asm volatile("griddepcontrol.wait;" ::: "memory"); }
DEV void pdl_launch() { asm volatile("griddepcontrol.launch_dependents;" ::: "memory"); }
DEV uint32_t ldg32(const void* p) { uint32_t v; asm volatile("ld.global.nc.u32 %0,[%1];" : "=r"(v) : "l"(p)); return v; }
DEV void ld_acc(u64& a, u64& b, const void* p) {
    const uint32_t done = (uint32_t)a & (uint32_t)b & 32u;
    asm volatile("{.reg .pred p; setp.eq.u32 p,%3,0;\n"
                 "@p ld.relaxed.gpu.global.v2.u64 {%0,%1},[%2];}" : "+l"(a), "+l"(b) : "l"(p), "r"(done) : "memory");
}
DEV void ld_acc0(u64& a, u64& b, const void* p) {
    asm volatile("ld.relaxed.gpu.global.v2.u64 {%0,%1},[%2];" : "=l"(a), "=l"(b) : "l"(p) : "memory");
}
DEV uint32_t and3(uint32_t a, uint32_t b, uint32_t c) { uint32_t r; asm volatile("lop3.b32 %0,%1,%2,%3,0x80;" : "=r"(r) : "r"(a), "r"(b), "r"(c)); return r; }
DEV uint32_t absmax2(uint32_t a, uint32_t b) { uint32_t r; asm("max.xorsign.abs.bf16x2 %0,%1,%2;" : "=r"(r) : "r"(a), "r"(b)); return r; }
DEV float lds32f(uint32_t a) { float x; asm volatile("ld.shared.f32 %0,[%1];" : "=f"(x) : "r"(a) : "memory"); return x; }
DEV void red_add64(u64* p, uint32_t lo, uint32_t hi) {
    asm volatile("{.reg .b64 v; mov.b64 v,{%1,%2}; red.relaxed.gpu.global.add.u64 [%0],v;}" ::"l"(p), "r"(lo), "r"(hi) : "memory");
}
DEV float bf_round(float x) { return __bfloat162float(__float2bfloat16_rn(x)); }
DEV float bf_lo(uint32_t u) { return __uint_as_float(u << 16); }
DEV float bf_hi(uint32_t u) { return __uint_as_float(u & 0xffff0000u); }

#define GPROF(i, n)
#define PROFT(i)
#define STAMP(i)

DEV void unpack8(float* v, uint4 u) {
    v[0] = bf_lo(u.x); v[1] = bf_hi(u.x); v[2] = bf_lo(u.y); v[3] = bf_hi(u.y);
    v[4] = bf_lo(u.z); v[5] = bf_hi(u.z); v[6] = bf_lo(u.w); v[7] = bf_hi(u.w);
}
DEV int xn_off(int row, int chunk) { return (row >> 5) * 40960 + (chunk >> 3) * 4096 + (row & 31) * 128 + (((chunk ^ row) & 7) << 4); }

DEV void ln_row(float (&v)[3][8], int lane) {
    float s = 0.f;
#pragma unroll
    for (int c = 0; c < 3; c++)
#pragma unroll
        for (int j = 0; j < 8; j++) s += v[c][j];
#pragma unroll
    for (int o = 16; o; o >>= 1) s += __shfl_xor_sync(~0u, s, o);
    float mean = s * (1.f / D_), q = 0.f;
#pragma unroll
    for (int c = 0; c < 3; c++)
        if (c < 2 || lane < 16)
#pragma unroll
            for (int j = 0; j < 8; j++) { float d = v[c][j] - mean; q += d * d; }
#pragma unroll
    for (int o = 16; o; o >>= 1) q += __shfl_xor_sync(~0u, q, o);
    float mb = bf_round(mean);
    float inv = 1.f / bf_round(sqrtf(bf_round(bf_round(q * (1.f / D_)) + 1e-5f)));
#pragma unroll
    for (int c = 0; c < 3; c++)
#pragma unroll
        for (int j = 0; j < 8; j++) v[c][j] = bf_round(v[c][j] - mb) * inv;
}

__host__ __device__ constexpr int col_freq(int c) {
    return c == 320 ? 320 : c < 192 ? (c >> 6) * 128 + (c & 63) : c == 192 ? 192 : c < 256 ? 448 - c : c == 256 ? 64 : 384 - c;
}
DEV float rdft(int n, int k, int sn, int N) {
    float s, c;
    sincospif((float)((n * k) & (N - 1)) * (2.f / N), &s, &c);
    return !sn ? c : k ? s : (n & 1 ? -1.f : 1.f);
}

__global__ void __launch_bounds__(512) prep_kernel(const bf16* __restrict__ x, const bf16* __restrict__ Wq, const bf16* __restrict__ Wk,
                                                   const bf16* __restrict__ Wv, const bf16* __restrict__ Wo) {
    __shared__ float red[32], col[4][640];
    const int tid = threadIdx.x, lane = tid & 31, warp = tid >> 5, b = blockIdx.x, row = b * 16 + warp;
    TLS(0);
    pdl_launch();
    uint4 ux[3], uv[5], uo[8];
#pragma unroll
    for (int c = 0; c < 3; c++) ux[c] = c < 2 || lane < 16 ? *(const uint4*)(x + row * D_ + (c * 32 + lane) * 8) : make_uint4(0, 0, 0, 0);
#pragma unroll
    for (int i = 0; i < 5; i++) uv[i] = *(const uint4*)(Wv + (size_t)((b & 3) * 160 + i * 32 + (tid >> 4)) * 4096 + (b >> 2) * E_ + (tid & 15) * 8);
    if (tid < 320) {
#pragma unroll
        for (int r = 0; r < 8; r++) uo[r] = *(const uint4*)(Wo + (size_t)(b * 32 + tid / 80 * 8 + r) * D_ + tid % 80 * 8);
    }
    if (tid >= 504) prefetch_bulk((const char*)(tid & 4 ? Wk : Wq) + (b * 4 + (tid & 3)) * 10240, 10240);
    if (b < 3) ((uint4*)g_sync)[b * 512 + tid] = make_uint4(0, 0, 0, 0);
    for (int i = b * 512 + tid; i < ACC_LAYER; i += 128 * 512) ((uint4*)g_acc)[i] = make_uint4(0, 0, 0, 0);
    if (tid < 2 * YT_ROWS * D_ / 4 / 128) ((uint4*)g_yt)[b * (2 * YT_ROWS * D_ / 4 / 128) + tid] = make_uint4(0, 0, 0, 0);
    const int gid = tid < 104 ? b * 104 + tid : 1 << 20;
    if (gid < 4096) {
        const int inv = gid >> 11, ks = (gid >> 8) & 7, t = gid & 255, g = (t & 31) >> 2, q = t & 3, tile = t >> 5;
        uint32_t v[4];
#pragma unroll
        for (int j = 0; j < 4; j++) {
            float x[2];
#pragma unroll
            for (int u = 0; u < 2; u++) {
                const int m = inv ? 16 * tile + 2 * g + (j & 1) : 16 * ks + 8 * (j >> 1) + 2 * q + u;
                const int k2 = inv ? 8 * ks + 2 * q + u : 8 * tile + g, sn = inv ? j >> 1 : j & 1;
                x[u] = rdft(m, k2, sn, 128);
                if (sn && k2) x[u] = -x[u];
            }
            v[j] = pack2(x[0], x[1]);
        }
        g_f128[gid] = make_uint4(v[0], v[1], v[2], v[3]);
    } else if (gid < 5120) {
        const int id = gid - 4096, inv = id >> 9, ks = (id >> 7) & 3, t = id & 127, g = (t & 31) >> 2, q = t & 3, tile = t >> 5;
        uint32_t v[4];
#pragma unroll
        for (int j = 0; j < 4; j++) {
            float x[2];
#pragma unroll
            for (int u = 0; u < 2; u++) {
                const int a = inv ? 16 * tile + g + 8 * (j & 1) : 16 * ks + 8 * (j >> 1) + 2 * q + u;
                const int ka = inv ? 8 * ks + 2 * q + u : 8 * tile + g, sn = inv ? j >> 1 : j & 1;
                x[u] = rdft(a, ka, sn, 64);
            }
            v[j] = pack2(x[0], x[1]);
        }
        g_f64[id] = make_uint4(v[0], v[1], v[2], v[3]);
    } else if (gid < 5120 + 8192) {
        const int id = gid - 5120, inv = id >> 12, n = ((id >> 9) & 7) * 8 + ((id >> 3) & 7), k = ((id >> 6) & 7) * 8 + (id & 7);
        float s, c;
        sincospif((float)(((n >> 1) * (k >> 1)) & 31) * (1.f / 16), &s, &c);
        if (inv) s = -s;
        g_g32[id] = __float2bfloat16_rn((n & 1) == (k & 1) ? c : (k & 1) ? s : -s);
    }
    {
        float v[3][8];
#pragma unroll
        for (int c = 0; c < 3; c++) unpack8(v[c], ux[c]);
        ln_row(v, lane);
#pragma unroll
        for (int c = 0; c < 3; c++)
            if (c < 2 || lane < 16)
                *(uint4*)(g_xn + xn_off(row, c * 32 + lane)) =
                    make_uint4(pack2(v[c][0], v[c][1]), pack2(v[c][2], v[c][3]), pack2(v[c][4], v[c][5]), pack2(v[c][6], v[c][7]));
    }
    float sv = 0.f;
#pragma unroll
    for (int i = 0; i < 5; i++) {
        float w[8];
        unpack8(w, uv[i]);
#pragma unroll
        for (int j = 0; j < 8; j++) sv += w[j] * w[j];
    }
    if (tid < 320) {
        float a[8] = {0.f, 0.f, 0.f, 0.f, 0.f, 0.f, 0.f, 0.f};
#pragma unroll
        for (int r = 0; r < 8; r++) {
            float w[8];
            unpack8(w, uo[r]);
#pragma unroll
            for (int j = 0; j < 8; j++) a[j] += w[j] * w[j];
        }
#pragma unroll
        for (int j = 0; j < 8; j++) col[tid / 80][tid % 80 * 8 + j] = a[j];
    }
    __syncthreads();
    float so = (col[0][tid] + col[1][tid]) + (col[2][tid] + col[3][tid]);
    if (tid < 128) so = fmaxf(so, (col[0][512 + tid] + col[1][512 + tid]) + (col[2][512 + tid] + col[3][512 + tid]));
#pragma unroll
    for (int o = 16; o; o >>= 1) { sv += __shfl_xor_sync(~0u, sv, o); so = fmaxf(so, __shfl_xor_sync(~0u, so, o)); }
    if (lane == 0) { red[warp] = sv; red[16 + warp] = so; }
    __syncthreads();
    if (tid == 0) {
        float a = 0.f, c = 0.f;
        for (int i = 0; i < 16; i++) { a += red[i]; c = fmaxf(c, red[16 + i]); }
        g_nrm[b] = a; g_nrm[128 + b] = c;
    }
    TLE(0);
}

DEV void filter_tile(const bf16* __restrict__ wr, const bf16* __restrict__ wi, int ka, int c) {
    const int kn = ka ? 2048 - ka : 32, kc = col_freq(c);
    const unsigned short* pr = (const unsigned short*)wr + kc;
    const unsigned short* pi = (const unsigned short*)wi + kc;
#pragma unroll 1
    for (int i = 0; i < 4; i += 2) {
        unsigned short a[32], b[32];
#pragma unroll
        for (int n = 0; n < 32; n++) {
            const int k = ((n & 1 ? kn : ka) + 64 * (4 * (2 * (i + (n >> 4)) + ((n >> 1) & 1)) + ((n >> 2) & 3))) & 2047;
            a[n] = __ldg(pr + k * NCOL); b[n] = __ldg(pi + k * NCOL);
        }
#pragma unroll
        for (int n = 0; n < 32; n += 4)
            *(uint4*)(g_wt + c * 8192 + (i + (n >> 4)) * 2048 + (ka * 4 + ((n >> 2) & 3)) * 16) =
                make_uint4(a[n] | ((uint32_t)b[n] << 16), a[n + 1] | ((uint32_t)b[n + 1] << 16), a[n + 2] | ((uint32_t)b[n + 2] << 16), a[n + 3] | ((uint32_t)b[n + 3] << 16));
    }
}

namespace wk {
constexpr int STAGE = 49152, NST = 4, OFF_OUT = 3 * STAGE, OFF_RED = 4 * STAGE, OFF_BAR = OFF_RED + 32768, SMEM = OFF_BAR + 128;
constexpr int NPB = 12;
DEV int pb_first(int n) { return n == 0 ? 0 : n == 2 ? 1 : n % 6 == 0 ? n / 6 + 1 : -1; }
__host__ __device__ constexpr int pb_start(int b) { return b == 0 ? 0 : b == 1 ? 2 : b < NPB ? 6 * b - 6 : 64; }
#define NOB 7
#define SPLIT_A 3
#define SPLIT_B 11
constexpr int N_P = NPB * H_, I_F = N_P, I_OB = I_F + 32, I_OT = I_OB + NOB * 5, I_SA = I_OT + (30 - 3 * NOB) * 10;
constexpr int I_SB = I_SA + 10 * SPLIT_A, N_ITEMS = I_SB + 10 * SPLIT_B;
DEV void ot_decode(int id, int& b, int& nt, int& k0, int& k1) {
    const int base = id < I_SA ? I_OT : id < I_SB ? I_SA : I_SB, j = (id - base) / 10;
    nt = (id - base) % 10;
    if (id < I_SA) { b = 3 * NOB + j; k0 = 0; k1 = 22; }
    else if (id < I_SB) { b = 30; k0 = 22 * j / SPLIT_A; k1 = 22 * (j + 1) / SPLIT_A; }
    else { b = 31; k0 = 22 * j / SPLIT_B; k1 = 22 * (j + 1) / SPLIT_B; }
}
enum { SY_TICKET = 0, SY_O = 32, SY_P = 128 };
}
struct Ring {
    int st; uint32_t ph;
    DEV uint32_t par() const { return (ph >> st) & 1; }
    DEV void next(int n) { ph ^= 1u << st; st = st + 1 >= n ? 0 : st + 1; }
};
struct Maps { CUtensorMap wq2, wv1, wo2, wo1, x6, x2, o6, o2; const bf16 *wr, *wi; };

template <int NSG> DEV void proj_tile(uint32_t sb, uint32_t bar, Ring& rg, int wg, int id) {
    using namespace wk;
    float acc[NSG * 16];
#pragma unroll
    for (int i = 0; i < NSG * 16; i++) acc[i] = 0.f;
    const int lane = threadIdx.x & 31, ww = (threadIdx.x >> 5) & 3;
    for (int kb = 0; kb < 10; kb++, rg.next(3)) {
        const int st = rg.st;
        if (kb) mbar_wait(bar + 8 * st, rg.par());
        const u64 da = mkdesc(sb + st * STAGE + wg * 8192, 0, 1024) | SW128, db = mkdesc(sb + st * STAGE + 24576, 0, 1024) | SW128;
        wg_fence();
#pragma unroll
        for (int ks = 0; ks < 4; ks++) {
            if (NSG == 2) wgmma_n64_ss<1, 0>(acc, da + ks * 128, db + ks * 2, 1);
            if (NSG == 4) wgmma_n128_ss<1, 0>(acc, da + ks * 128, db + ks * 2, 1);
            if (NSG == 6) wgmma_n192_ss<1, 0>(acc, da + ks * 128, db + ks * 2, 1);
        }
        wg_commit();
        wg_wait<0>();
        mbar_arrive_elect(bar + 8 * (NST + st));
    }
    const uint32_t out = sb + OFF_OUT + wg * 24576;
    bar_sync(5 + wg, 160);
    const uint32_t la = out + (wg < 2 ? (lane >> 4) * 1024 + ww * 256 + (lane & 15) * 16 : ww * 1024 + ((lane >> 3) & 1) * 512 + (lane >> 4) * 128 + (lane & 7) * 16);
#pragma unroll
    for (int j = 0; j < 2 * NSG; j++) {
        const float* c = acc + 8 * j;
        const uint32_t p0 = pack2(c[0], c[1]), p1 = pack2(c[2], c[3]), p2 = pack2(c[4], c[5]), p3 = pack2(c[6], c[7]);
        if (wg < 2) stsm4t(la + j * 2048, p0, p1, p2, p3);
        else stsm4(la + (j >> 1) * 4096 + (j & 1) * 256, p0, p1, p2, p3);
    }
    if ((threadIdx.x & 127) == 0) sts32(bar + 80 + 4 * wg, id);
    fence_async();
    bar_arrive(1 + wg, 160);
}

DEV uint32_t resid(uint32_t u, float a, float b) { return pack2(bf_lo(u) + bf_round(a), bf_hi(u) + bf_round(b)); }

DEV void worker(uint32_t sb, const Maps& maps, const bf16* __restrict__ x, bf16* __restrict__ x1, int layer) {
    using namespace wk;
    const uint32_t bar = sb + OFF_BAR, slot = bar + 64;
    const int tid = threadIdx.x, lane = tid & 31, warp = __shfl_sync(~0u, tid >> 5, 0);
    uint32_t* sy = g_sync + layer * SYNC_LAYER;
    if (tid == 0) {
        for (int i = 0; i < NST; i++) { mbar_init(bar + 8 * i, 1); mbar_init(bar + 8 * (NST + i), 12); }
        asm volatile("fence.mbarrier_init.release.cluster;" ::: "memory");
    }
    __syncthreads();
    if (warp > 12) {
        const int wg = warp - 13;
        bar_arrive(5 + wg, 160);
        for (;;) {
            bar_sync(1 + wg, 160);
            const int id = (int)lds32(bar + 80 + 4 * wg);
            if (id < 0) break;
            const int s0 = pb_start(id >> 5), ns = pb_start((id >> 5) + 1) - s0;
            if (lane == 0) {
                for (int j = 0; j < ns; j++)
                    bulk_s2g(g_p + (size_t)(((s0 + j) * H_ + (id & 31)) * 3 + wg) * 4096, sb + OFF_OUT + wg * 24576 + j * 4096, 4096);
                bulk_commit();
                bulk_wait<0>();
                flag_add(sy + SY_P + id);
            }
            __syncwarp();
            bar_arrive(5 + wg, 160);
        }
    } else if (warp == 12) {
        if (lane == 0) {
            Ring rg = {0, 7u};
            auto acquire = [&]() { mbar_wait(bar + 8 * (NST + rg.st), rg.par()); return sb + rg.st * STAGE; };
            for (;;) {
                int id = (int)atomicAdd(sy + SY_TICKET, 1u);
                if (layer && id >= I_F) id += I_OB - I_F;
                if (id >= N_ITEMS) id = -1;
                if (id >= 0) { TLI(id, 0, gtime()); TLI(id, 3, blockIdx.x + (gridDim.x % 3 == 0 && gridDim.x > 111 ? 0 : 1000)); }
                uint32_t d = acquire();
                sts32(slot + 4 * rg.st, id);
                if (id < 0) { mbar_arrive(bar + 8 * rg.st); break; }
                if (id < N_P) {
                    const int b = id >> 5, h = id & 31, s0 = pb_start(b), ns = pb_start(b + 1) - s0;
                    for (int kb = 0; kb < 10; kb++, rg.next(3)) {
                        if (kb) d = acquire();
                        const uint32_t fb = bar + 8 * rg.st;
                        mbar_expect(fb, 24576 + ns * 4096);
                        tma3d(d, &maps.wq2, 0, kb * 64, 2 * h, fb);
                        tma3d(d + 16384, &maps.wv1, 0, kb * 64, 2 * h, fb);
                        if (ns == 6) tma3d(d + 24576, &maps.x6, 0, 2 * kb, s0, fb);
                        else for (int j = 0; j < ns; j += 2) tma3d(d + 24576 + j * 4096, &maps.x2, 0, 2 * kb, s0 + j, fb);
                    }
                } else if (id < I_OB) {
                    mbar_arrive(bar + 8 * rg.st);
                    mbar_wait(bar + 8 * (NST + rg.st), rg.par() ^ 1);
                    rg.next(NST);
                } else if (id < I_OT) {
                    const int b = (id - I_OB) / 5, nt = (id - I_OB) % 5;
                    for (int j = 0; j < 6; j++) flag_wait(sy + SY_O + 6 * b + j, 32);
                    for (int kb = 0; kb < 64; kb++, rg.next(NST)) {
                        if (kb) d = acquire();
                        const uint32_t fb = bar + 8 * rg.st;
                        mbar_expect(fb, 40960);
                        tma3d(d, &maps.o6, 0, 2 * kb, 6 * b, fb);
                        tma3d(d + 24576, &maps.wo2, 0, kb * 64, 2 * nt, fb);
                    }
                } else {
                    int b, nt, k0, k1;
                    ot_decode(id, b, nt, k0, k1);
                    for (int kb = k0; kb < k1; kb++, rg.next(NST)) {
                        if (kb > k0) d = acquire();
                        const uint32_t fb = bar + 8 * rg.st;
                        mbar_expect(fb, 49152);
                        tma3d(d + 24576, &maps.wo1, 0, 3 * kb * 64, nt, fb);
                        if (kb == k0) for (int j = 0; j < 2; j++) flag_wait(sy + SY_O + 2 * b + j, 32);
                        for (int u = 0; u < 3; u++) tma3d(d + u * 8192, &maps.o2, 0, 2 * (3 * kb + u), 2 * b, fb);
                    }
                }
            }
        }
    } else {
        const int wg = warp >> 2, g = lane >> 2, q = lane & 3;
        Ring rg = {0, 0u};
        bool stores_done = false;
        for (;;) {
            mbar_wait(bar + 8 * rg.st, rg.par());
            const int id = (int)lds32(slot + 4 * rg.st);
            if ((id < 0 || id >= N_P) && !stores_done) {
                bar_sync(5 + wg, 160);
                if ((tid & 127) == 0) sts32(bar + 80 + 4 * wg, ~0u);
                bar_arrive(1 + wg, 160);
                stores_done = true;
                bar_sync(4, 384);
                mbar_arrive_elect(bar + 8 * (NST + 3));
            }
            if (id < 0) break;
            if (tid == 0) TLI(id, 1, gtime());
            if (id < N_P) {
                const int b = id >> 5;
                if (b == 0) proj_tile<2>(sb, bar, rg, wg, id);
                else if (b == 1 || b == NPB - 1) proj_tile<4>(sb, bar, rg, wg, id);
                else proj_tile<6>(sb, bar, rg, wg, id);
            } else if (id < I_OB) {
                if (tid < NCOL) filter_tile(maps.wr, maps.wi, id - I_F, tid);
                __syncwarp();
                mbar_arrive_elect(bar + 8 * (NST + rg.st));
                rg.next(NST);
            } else if (id < I_OT) {
                const int b = (id - I_OB) / 5, nt = (id - I_OB) % 5;
                const size_t o = (size_t)(192 * b + 16 * warp + g) * D_ + nt * 128 + 2 * q;
                float acc[64];
#pragma unroll
                for (int i = 0; i < 64; i++) acc[i] = 0.f;
                for (int kb = 0; kb < 64; kb++, rg.next(NST)) {
                    const int st = rg.st;
                    if (kb) mbar_wait(bar + 8 * st, rg.par());
                    const u64 da = mkdesc(sb + st * STAGE + wg * 8192, 128, 1024), db = mkdesc(sb + st * STAGE + 24576, 8192, 1024) | SW128;
                    wg_fence();
#pragma unroll
                    for (int ks = 0; ks < 4; ks++) wgmma_n128_ss<0, 1>(acc, da + ks * 16, db + ks * 128, 1);
                    wg_commit();
                    wg_wait<0>();
                    mbar_arrive_elect(bar + 8 * (NST + st));
                }
                uint32_t xr[32];
#pragma unroll
                for (int t = 0; t < 32; t++) xr[t] = ldg32(x + o + 8 * (t >> 1) + (t & 1) * 8 * D_);
#pragma unroll
                for (int t = 0; t < 32; t++) *(uint32_t*)(x1 + o + 8 * (t >> 1) + (t & 1) * 8 * D_) = resid(xr[t], acc[2 * t], acc[2 * t + 1]);
            } else {
                int b, nt, k0, k1;
                ot_decode(id, b, nt, k0, k1);
                const size_t o = (size_t)(64 * b + 16 * (warp & 3) + g) * D_ + nt * 64 + 2 * q;
                float acc[32];
                uint32_t xr[16];
#pragma unroll
                for (int t = 0; t < 16; t++) xr[t] = wg == 0 && id < I_SA ? ldg32(x + o + 8 * (t >> 1) + (t & 1) * 8 * D_) : 0;
#pragma unroll
                for (int i = 0; i < 32; i++) acc[i] = 0.f;
                for (int kb = k0; kb < k1; kb++, rg.next(NST)) {
                    const int st = rg.st;
                    if (kb > k0) mbar_wait(bar + 8 * st, rg.par());
                    const u64 da = mkdesc(sb + st * STAGE + wg * 8192, 128, 1024), db = mkdesc(sb + st * STAGE + 24576 + wg * 8192, 0, 1024) | SW128;
                    wg_fence();
#pragma unroll
                    for (int ks = 0; ks < 4; ks++) wgmma_n64_ss<0, 1>(acc, da + ks * 16, db + ks * 128, 1);
                    wg_commit();
                    wg_wait<0>();
                    mbar_arrive_elect(bar + 8 * (NST + st));
                }
                const uint32_t ra = sb + OFF_RED + (tid & 127) * 16;
                if (wg) {
#pragma unroll
                    for (int t = 0; t < 8; t++)
                        sts128(ra + (wg - 1) * 16384 + t * 2048, __float_as_uint(acc[4 * t]), __float_as_uint(acc[4 * t + 1]), __float_as_uint(acc[4 * t + 2]), __float_as_uint(acc[4 * t + 3]));
                }
                bar_sync(4, 384);
                if (wg == 0) {
#pragma unroll
                    for (int t = 0; t < 8; t++) {
                        float u[4], v[4];
                        lds128f(u, ra + t * 2048); lds128f(v, ra + 16384 + t * 2048);
#pragma unroll
                        for (int i = 0; i < 4; i++) acc[4 * t + i] += u[i] + v[i];
                    }
                }
                bar_sync(4, 384);
                if (wg == 0) {
                    if (id < I_SA) {
#pragma unroll
                        for (int t = 0; t < 16; t++) *(uint32_t*)(x1 + o + 8 * (t >> 1) + (t & 1) * 8 * D_) = resid(xr[t], acc[2 * t], acc[2 * t + 1]);
                    } else {
                        float* y = g_yt + (layer * YT_ROWS - (S_ - YT_ROWS)) * D_ + o;
#pragma unroll
                        for (int t = 0; t < 16; t++)
                            asm volatile("red.relaxed.gpu.global.add.v2.f32 [%0],{%1,%2};" ::"l"(y + 8 * (t >> 1) + (t & 1) * 8 * D_), "f"(acc[2 * t]), "f"(acc[2 * t + 1]) : "memory");
                    }
                }
            }
            if (tid == 0) TLI(id, 2, gtime());
        }
    }
}

__global__ void __launch_bounds__(512, 1) side_kernel(const __grid_constant__ Maps maps, const bf16* __restrict__ x, bf16* __restrict__ x1, int layer) {
    extern __shared__ __align__(1024) unsigned char smem[];
    pdl_launch();
    TLS(3 + 5 * layer);
    worker(s2u(smem), maps, x, x1, layer);
    __syncwarp();
    pdl_wait();
    TLE(3 + 5 * layer);
}

constexpr float C5A = 0.30901699437494742f, C5B = -0.80901699437494742f, S5A = 0.95105651629515357f, S5B = 0.58778525229247313f;
template <int SGN> DEV void dft5(const float (&tr)[5], const float (&ti)[5], float (&zr)[5], float (&zi)[5]) {
    const float ar = tr[1] + tr[4], ai = ti[1] + ti[4], br = tr[2] + tr[3], bi = ti[2] + ti[3];
    const float cr = tr[1] - tr[4], ci = ti[1] - ti[4], dr = tr[2] - tr[3], di = ti[2] - ti[3];
    zr[0] = tr[0] + ar + br; zi[0] = ti[0] + ai + bi;
    const float m1r = tr[0] + C5A * ar + C5B * br, m1i = ti[0] + C5A * ai + C5B * bi;
    const float m2r = tr[0] + C5B * ar + C5A * br, m2i = ti[0] + C5B * ai + C5A * bi;
    const float n1r = SGN * (S5A * cr + S5B * dr), n1i = SGN * (S5A * ci + S5B * di);
    const float n2r = SGN * (S5B * cr - S5A * dr), n2i = SGN * (S5B * ci - S5A * di);
    zr[1] = m1r + n1i; zi[1] = m1i - n1r; zr[4] = m1r - n1i; zi[4] = m1i + n1r;
    zr[2] = m2r + n2i; zi[2] = m2i - n2r; zr[3] = m2r - n2i; zi[3] = m2i + n2r;
}
DEV void ln40(float (&v)[40]) {
    float s = 0.f;
#pragma unroll
    for (int i = 0; i < 40; i++) s += v[i];
#pragma unroll
    for (int o = 8; o; o >>= 1) s += __shfl_xor_sync(~0u, s, o);
    const float mean = s * (1.f / D_);
    float q = 0.f;
#pragma unroll
    for (int i = 0; i < 40; i++) { const float d = v[i] - mean; q += d * d; }
#pragma unroll
    for (int o = 8; o; o >>= 1) q += __shfl_xor_sync(~0u, q, o);
    const float mb = bf_round(mean);
    const float inv = 1.f / bf_round(sqrtf(bf_round(bf_round(q * (1.f / D_)) + 1e-5f)));
#pragma unroll
    for (int i = 0; i < 40; i++) v[i] = bf_round(v[i] - mb) * inv;
}
__global__ void __launch_bounds__(256) rowfft_kernel(const bf16* __restrict__ x0, bf16* __restrict__ x, const bf16* __restrict__ Wq,
                                                     const bf16* __restrict__ Wk, const bf16* __restrict__ Wv, int layer) {
    extern __shared__ __align__(1024) unsigned char smem[];
    const uint32_t sb = s2u(smem), sx = sb + 23552, sy = sx + 20480, bar = sy + 40960;
    const int tid = threadIdx.x, lane = tid & 31, q = lane & 3, blk = blockIdx.x, k2 = tid >> 2;
    if (tid == 0) TLI(800 + blk, 0, gtime());
    float twr[5], twi[5];
#pragma unroll
    for (int r = 1; r < 5; r++) { sincospif((float)(r * k2) * (-1.f / 320), &twi[r], &twr[r]); }
    uint32_t f[8][4];
#pragma unroll
    for (int ks = 0; ks < 8; ks++) { const uint4 u = g_f128[ks * 256 + tid]; f[ks][0] = u.x; f[ks][1] = u.y; f[ks][2] = u.z; f[ks][3] = u.w; }
    const bool split = blk * 16 >= S_ - YT_ROWS;
    if (tid == 0) {
        mbar_init(bar, 1);
        asm volatile("fence.mbarrier_init.release.cluster;" ::: "memory");
        mbar_expect(bar, split ? 61440 : 20480);
        if (split) bulk_g2s(sx, x0 + (size_t)blk * 16 * D_, 20480, bar);
    }
    __syncthreads();
    pdl_wait();
    pdl_launch();
    TLS(4 + 5 * layer);
    if (tid == 0) TLI(800 + blk, 1, gtime());
    if (tid == 0) {
        if (split) bulk_g2s(sy, g_yt + (layer * YT_ROWS + blk * 16 - (S_ - YT_ROWS)) * D_, 40960, bar);
        else bulk_g2s(sx, x + (size_t)blk * 16 * D_, 20480, bar);
    }
    mbar_wait(bar, 0);
    {
        const int rho = tid >> 4, j = tid & 15;
        float v[40];
#pragma unroll
        for (int i = 0; i < 5; i++) {
            uint32_t u[4];
            lds128(u, sx + tid * 80 + i * 16);
            if (split) {
                float p[8];
                lds128f(p, sy + tid * 160 + i * 32); lds128f(p + 4, sy + tid * 160 + i * 32 + 16);
#pragma unroll
                for (int k = 0; k < 4; k++) u[k] = resid(u[k], p[2 * k], p[2 * k + 1]);
                sts128(sx + tid * 80 + i * 16, u[0], u[1], u[2], u[3]);
            }
            unpack8(v + 8 * i, make_uint4(u[0], u[1], u[2], u[3]));
        }
        if (layer == 0 && tid < 12) prefetch_bulk((const char*)(tid < 4 ? Wk : tid < 8 ? Wq : Wv) + (blk * 4 + (tid & 3)) * 10240, 10240);
        ln40(v);
        const uint32_t a = sb + ((rho >> 1) & 1) * 2304 + j * 144 + (2 * (rho >> 2) + (rho & 1)) * 16;
#pragma unroll
        for (int r = 0; r < 5; r++)
            sts128(a + r * 4608, pack2(v[r], v[5 + r]), pack2(v[10 + r], v[15 + r]), pack2(v[20 + r], v[25 + r]), pack2(v[30 + r], v[35 + r]));
    }
    fence_async();
    __syncthreads();
    if (tid == 0) TLI(800 + blk, 2, gtime());
    if (tid == 0 && split) { bulk_s2g(x + (size_t)blk * 16 * D_, sx, 20480); bulk_commit(); }
    float acc[40];
    const u64 db = mkdesc(sb, 144, 2304);
    wg_fence();
    wgmma_n80_rs<0, 0>(acc, f[0], db);
#pragma unroll
    for (int ks = 1; ks < 8; ks++) wgmma_n80_rs<1, 0>(acc, f[ks], db + ks * 18);
    wg_commit();
    wg_wait<0>();
    unsigned char* zp = g_z + (blk >> 1) * 128 + ((((blk & 1) * 4 + q) ^ ((blk >> 1) & 7)) << 4);
    uint32_t o[5][4];
#pragma unroll
    for (int u = 0; u < 4; u++) {
        float tr[5], ti[5], zr[5], zi[5];
#pragma unroll
        for (int r = 0; r < 5; r++) {
            const float yr = acc[8 * r + 4 * (u >> 1) + (u & 1)], yi = k2 ? acc[8 * r + 4 * (u >> 1) + 2 + (u & 1)] : 0.f;
            tr[r] = r ? yr * twr[r] - yi * twi[r] : yr;
            ti[r] = r ? yr * twi[r] + yi * twr[r] : yi;
        }
        dft5<1>(tr, ti, zr, zi);
#pragma unroll
        for (int j = 0; j < 5; j++) o[j][u] = pack2(zr[j], j < 3 ? zi[j] : -zi[j]);
    }
#pragma unroll
    for (int j = 0; j < 5; j++)
        if (j < 3 || k2) *(uint4*)(zp + (64 * j + k2) * 8192) = make_uint4(o[j][0], o[j][1], o[j][2], o[j][3]);
    if (k2 == 0) {
#pragma unroll
        for (int u = 0; u < 4; u++) {
            float tr[5], ti[5], zr[5], zi[5];
            const float cr[5] = {1.f, -C5B, C5A, -C5A, C5B}, ci[5] = {0.f, -S5B, -S5A, -S5A, -S5B};
#pragma unroll
            for (int r = 0; r < 5; r++) { const float y = acc[8 * r + 4 * (u >> 1) + 2 + (u & 1)]; tr[r] = y * cr[r]; ti[r] = y * ci[r]; }
            dft5<1>(tr, ti, zr, zi);
            o[0][u] = pack2(zr[0], zi[0]); o[1][u] = pack2(zr[1], zi[1]); o[2][u] = pack2(zr[2], 0.f);
        }
        *(uint4*)(zp + 256 * 8192) = make_uint4(o[0][0], o[0][1], o[0][2], o[0][3]);
        *(uint4*)(zp + 192 * 8192) = make_uint4(o[1][0], o[1][1], o[1][2], o[1][3]);
        *(uint4*)(zp + 320 * 8192) = make_uint4(o[2][0], o[2][1], o[2][2], o[2][3]);
    }
    if (tid == 0) bulk_wait<0>();
    TLE(4 + 5 * layer);
    if (tid == 0) TLI(800 + blk, 3, gtime());
}

constexpr int CF_SMEM = 16384 + 3 * 16384 + 64;
__global__ void __launch_bounds__(384) colfft_kernel(int layer) {
    extern __shared__ __align__(1024) unsigned char smem[];
    const uint32_t sb = s2u(smem), bar = sb + 65536;
    const int tid = threadIdx.x, lane = tid & 31, q = lane & 3, wg = __shfl_sync(~0u, tid >> 7, 0), t = tid & 127, ka = t >> 2;
    const int col = blockIdx.x * 3 + wg;
    const uint32_t d0 = sb + 16384 + wg * 16384, d1 = d0 + 8192;
    if (tid == 0) {
        for (int i = 0; i < 4; i++) mbar_init(bar + 8 * i, 1);
        asm volatile("fence.mbarrier_init.release.cluster;" ::: "memory");
    }
    float twr[8], twi[8];
#pragma unroll
    for (int i = 0; i < 8; i++) sincospif((float)((4 * i + q) * (ka ? ka : -32)) * (1.f / 1024), &twi[i], &twr[i]);
    __syncthreads();
    if (tid == 0) { mbar_expect(bar + 24, 16384); bulk_g2s(sb, g_g32, 16384, bar + 24); }
    uint32_t f[4][4], w[16];
#pragma unroll
    for (int ks = 0; ks < 4; ks++) { const uint4 u = g_f64[ks * 128 + t]; f[ks][0] = u.x; f[ks][1] = u.y; f[ks][2] = u.z; f[ks][3] = u.w; }
#pragma unroll
    for (int i = 0; i < 4; i++) { const uint4 u = *(const uint4*)(g_wt + col * 8192 + i * 2048 + t * 16); w[4 * i] = u.x; w[4 * i + 1] = u.y; w[4 * i + 2] = u.z; w[4 * i + 3] = u.w; }
    pdl_wait();
    pdl_launch();
    TLS(5 + 5 * layer);
    if (t == 0) {
        mbar_expect(bar + 8 * wg, 8192);
        bulk_g2s(d0, g_z + col * 8192, 8192, bar + 8 * wg);
    }
    float acc[32];
    uint32_t a[4][4];
    mbar_wait(bar + 8 * wg, 0);
    {
        const u64 db = mkdesc(d0, 0, 1024) | SW128;
        wg_fence();
        wgmma_n64_rs<0, 1>(acc, f[0], db);
#pragma unroll
        for (int ks = 1; ks < 4; ks++) wgmma_n64_rs<1, 1>(acc, f[ks], db + ks * 128);
        wg_commit();
        wg_wait<0>();
    }
#pragma unroll
    for (int ks = 0; ks < 4; ks++) { const uint4 u = g_f64[512 + ks * 128 + t]; f[ks][0] = u.x; f[ks][1] = u.y; f[ks][2] = u.z; f[ks][3] = u.w; }
#pragma unroll
    for (int i = 0; i < 8; i++) {
        const float c0 = acc[4 * i], c1 = acc[4 * i + 1], c2 = acc[4 * i + 2], c3 = acc[4 * i + 3];
        const float pr = c0 + c3, pi = c1 - c2, nr = ka ? c0 - c3 : c2, ni = ka ? c1 + c2 : c3;
        a[i >> 1][2 * (i & 1)] = ka ? pack2(pr * twr[i] + pi * twi[i], pi * twr[i] - pr * twi[i]) : pack2(c0, c1);
        a[i >> 1][2 * (i & 1) + 1] = pack2(nr * twr[i] - ni * twi[i], ni * twr[i] + nr * twi[i]);
    }
    mbar_wait(bar + 24, 0);
    {
        const u64 db = mkdesc(sb, 128, 1024);
        wg_fence();
        wgmma_n64_rs<0, 0>(acc, a[0], db);
#pragma unroll
        for (int ks = 1; ks < 4; ks++) wgmma_n64_rs<1, 0>(acc, a[ks], db + ks * 16);
        wg_commit();
        wg_wait<0>();
    }
    constexpr float NORM = 1.f / (2048.f * 640.f);
#pragma unroll
    for (int i = 0; i < 16; i++) {
        const float zr = acc[2 * i] * NORM, zi = acc[2 * i + 1] * NORM, wr = bf_lo(w[i]), wi = bf_hi(w[i]);
        a[i >> 2][i & 3] = pack2(zr * wr - zi * wi, zr * wi + zi * wr);
    }
    {
        const u64 db = mkdesc(sb + 8192, 128, 1024);
        wg_fence();
        wgmma_n64_rs<0, 0>(acc, a[0], db);
#pragma unroll
        for (int ks = 1; ks < 4; ks++) wgmma_n64_rs<1, 0>(acc, a[ks], db + ks * 16);
        wg_commit();
        wg_wait<0>();
    }
    const uint32_t row = (t >> 5) * 2048 + (lane & 15) * 128;
#pragma unroll
    for (int i = 0; i < 8; i++) {
        const float c0 = acc[4 * i], c1 = acc[4 * i + 1], c2 = acc[4 * i + 2], c3 = acc[4 * i + 3];
        const float pr = c0 * twr[i] - c1 * twi[i], pi = c1 * twr[i] + c0 * twi[i];
        const float nr = c2 * twr[i] + c3 * twi[i], ni = c3 * twr[i] - c2 * twi[i];
        a[i >> 1][2 * (i & 1)] = ka ? pack2(pr + nr, pi + ni) : pack2(c0, c1);
        a[i >> 1][2 * (i & 1) + 1] = ka ? pack2(ni - pi, pr - nr) : pack2(nr, ni);
    }
#pragma unroll
    for (int i = 0; i < 4; i++) stsm4(d1 + row + (((2 * i + (lane >> 4)) ^ (lane & 7)) << 4), a[i][0], a[i][1], a[i][2], a[i][3]);
    fence_async();
    bar_sync(1 + wg, 128);
    {
        const u64 db = mkdesc(d1, 0, 1024) | SW128;
        wg_fence();
        wgmma_n64_rs<0, 1>(acc, f[0], db);
#pragma unroll
        for (int ks = 1; ks < 4; ks++) wgmma_n64_rs<1, 1>(acc, f[ks], db + ks * 128);
        wg_commit();
        wg_wait<0>();
    }
#pragma unroll
    for (int i = 0; i < 4; i++)
        stsm4(d0 + row + (((2 * i + (lane >> 4)) ^ (lane & 7)) << 4), pack2(acc[8 * i], acc[8 * i + 1]), pack2(acc[8 * i + 2], acc[8 * i + 3]),
              pack2(acc[8 * i + 4], acc[8 * i + 5]), pack2(acc[8 * i + 6], acc[8 * i + 7]));
    fence_async();
    bar_sync(1 + wg, 128);
    if (t == 0) {
        bulk_s2g(g_z + col * 8192, d0, 8192);
        asm volatile("cp.async.bulk.commit_group;" ::: "memory");
        asm volatile("cp.async.bulk.wait_group 0;" ::: "memory");
    }
    TLE(5 + 5 * layer);
}

__global__ void __launch_bounds__(256) rowifft_kernel(const bf16* __restrict__ x, bf16* __restrict__ out, int last) {
    extern __shared__ __align__(1024) unsigned char smem[];
    const uint32_t sb = s2u(smem), sx = sb + 20480, sy = sx + 20480, bar = sy + 16 * 1296;
    const int tid = threadIdx.x, lane = tid & 31, q = lane & 3, blk = blockIdx.x, k2 = tid >> 2, warp = tid >> 5;
    float twr[5], twi[5];
#pragma unroll
    for (int r = 1; r < 5; r++) { sincospif((float)(r * k2) * (1.f / 320), &twi[r], &twr[r]); twr[r] *= 2.f; twi[r] *= 2.f; }
    uint32_t f[8][4];
#pragma unroll
    for (int ks = 0; ks < 8; ks++) { const uint4 u = g_f128[2048 + ks * 256 + tid]; f[ks][0] = u.x; f[ks][1] = u.y; f[ks][2] = u.z; f[ks][3] = u.w; }
    if (tid == 0) {
        mbar_init(bar, 1);
        asm volatile("fence.mbarrier_init.release.cluster;" ::: "memory");
        mbar_expect(bar, 20480);
        bulk_g2s(sx, x + (size_t)blk * 16 * D_, 20480, bar);
    }
    pdl_wait();
    pdl_launch();
    TLS(6 + 5 * last);
    const unsigned char* zp = g_z + (blk >> 1) * 128 + ((((blk & 1) * 4 + q) ^ ((blk >> 1) & 7)) << 4);
    uint4 z[6];
#pragma unroll
    for (int j = 0; j < 5; j++) z[j] = *(const uint4*)(zp + (64 * j + k2) * 8192);
    z[5] = k2 ? make_uint4(0, 0, 0, 0) : *(const uint4*)(zp + 320 * 8192);
    float acc[40];
#pragma unroll
    for (int u = 0; u < 4; u++) {
        float yr[6], yi[6], tr[5], ti[5], zr[5], zi[5];
#pragma unroll
        for (int j = 0; j < 6; j++) { const uint32_t v = u == 0 ? z[j].x : u == 1 ? z[j].y : u == 2 ? z[j].z : z[j].w; yr[j] = bf_lo(v); yi[j] = bf_hi(v); }
#pragma unroll
        for (int j = 0; j < 5; j++) { tr[j] = yr[j]; ti[j] = j < 3 ? yi[j] : -yi[j]; }
        dft5<-1>(tr, ti, zr, zi);
        const float c1[5] = {1.f, C5A, C5B, C5B, C5A}, s1[5] = {0.f, S5A, S5B, -S5B, -S5A};
        const float c2[5] = {1.f, C5B, C5A, C5A, C5B}, s2[5] = {0.f, S5B, -S5A, S5A, -S5B};
        const float c3[5] = {1.f, -C5B, C5A, -C5A, C5B}, s3[5] = {0.f, S5B, S5A, S5A, S5B};
        const float c4[5] = {1.f, -C5A, C5B, -C5B, C5A}, s4[5] = {0.f, S5A, -S5B, -S5B, S5A};
#pragma unroll
        for (int r = 0; r < 5; r++) {
            float er = r ? zr[r] * twr[r] - zi[r] * twi[r] : 2.f * zr[0], ei = r ? zr[r] * twi[r] + zi[r] * twr[r] : 2.f * zi[0];
            if (k2 == 0) {
                er = yr[0] + 2.f * (yr[1] * c1[r] - yi[1] * s1[r] + yr[2] * c2[r] - yi[2] * s2[r]);
                ei = (r & 1 ? -yr[5] : yr[5]) + 2.f * (yr[4] * c3[r] - yi[4] * s3[r] + yr[3] * c4[r] - yi[3] * s4[r]);
            }
            acc[8 * r + 4 * (u >> 1) + (u & 1)] = er;
            acc[8 * r + 4 * (u >> 1) + 2 + (u & 1)] = ei;
        }
    }
#pragma unroll
    for (int r = 0; r < 5; r++)
        stsm4(sb + (2 * warp + ((lane >> 3) & 1)) * 1280 + (2 * r + (lane >> 4)) * 128 + (lane & 7) * 16, pack2(acc[8 * r], acc[8 * r + 1]),
              pack2(acc[8 * r + 2], acc[8 * r + 3]), pack2(acc[8 * r + 4], acc[8 * r + 5]), pack2(acc[8 * r + 6], acc[8 * r + 7]));
    fence_async();
    __syncthreads();
    const u64 db = mkdesc(sb, 1280, 128);
    wg_fence();
    wgmma_n80_rs<0, 1>(acc, f[0], db);
#pragma unroll
    for (int ks = 1; ks < 8; ks++) wgmma_n80_rs<1, 1>(acc, f[ks], db + ks * 160);
    wg_commit();
    wg_wait<0>();
#pragma unroll
    for (int u = 0; u < 4; u++) {
        float e[10];
#pragma unroll
        for (int r = 0; r < 5; r++) { e[r] = acc[8 * r + 4 * (u >> 1) + (u & 1)]; e[5 + r] = acc[8 * r + 4 * (u >> 1) + 2 + (u & 1)]; }
#pragma unroll
        for (int i = 0; i < 5; i++) sts32(sy + (4 * q + u) * 1296 + k2 * 20 + i * 4, pack2(e[2 * i], e[2 * i + 1]));
    }
    __syncthreads();
    const int rho = tid >> 4, j = tid & 15;
    float v[40];
    mbar_wait(bar, 0);
#pragma unroll
    for (int i = 0; i < 5; i++) {
        uint32_t y[4], u[4];
        lds128(y, sy + rho * 1296 + j * 80 + i * 16);
        lds128(u, sx + tid * 80 + i * 16);
#pragma unroll
        for (int k = 0; k < 4; k++) u[k] = pack2(bf_lo(u[k]) + bf_lo(y[k]), bf_hi(u[k]) + bf_hi(y[k]));
        sts128(sx + tid * 80 + i * 16, u[0], u[1], u[2], u[3]);
        unpack8(v + 8 * i, make_uint4(u[0], u[1], u[2], u[3]));
    }
    if (!last) {
        ln40(v);
#pragma unroll
        for (int i = 0; i < 5; i++) {
            const int c = j * 5 + i;
            sts128(sb + (c >> 3) * 2048 + rho * 128 + (((c ^ rho) & 7) << 4), pack2(v[8 * i], v[8 * i + 1]), pack2(v[8 * i + 2], v[8 * i + 3]),
                   pack2(v[8 * i + 4], v[8 * i + 5]), pack2(v[8 * i + 6], v[8 * i + 7]));
        }
    }
    fence_async();
    __syncthreads();
    if (lane == 0) {
        if (warp == 7) bulk_s2g(out + (size_t)blk * 16 * D_, sx, 20480);
        else if (!last && warp < 5) {
            unsigned char* p = g_xn + (blk >> 1) * 40960 + warp * 8192 + (blk & 1) * 2048;
            bulk_s2g(p, sb + warp * 4096, 2048);
            bulk_s2g(p + 4096, sb + warp * 4096 + 2048, 2048);
        }
        bulk_commit();
        bulk_wait<0>();
    }
    TLE(6 + 5 * last);
}

namespace rec {
#define NS 1
constexpr int OFF_X = 0;
constexpr int OFF_WO = 81920;
constexpr int OFF_WS = OFF_WO + 65536;
constexpr int OFF_XCH = OFF_WS + NS * 4096;
constexpr int OFF_MEMB = OFF_XCH + 12288;
constexpr int OFF_VX = OFF_MEMB + 10240;
constexpr int OFF_VM = OFF_VX + 16384;
constexpr int OFF_Q = OFF_VM + 4096;
constexpr int OFF_K = OFF_Q + 10240;
constexpr int OFF_OST = OFF_WO + 49152;
constexpr int OFF_PX = OFF_OST + 8192;
constexpr int OFF_PT = OFF_PX + 2560;
constexpr int OFF_PS = OFF_K + 10240;
constexpr int OFF_OB = OFF_PS + 1280;
constexpr int OFF_MX = OFF_OB + 2048;
constexpr int OFF_BAR = OFF_MX + 64;
constexpr int OFF_PROF = OFF_BAR + 256;
constexpr int SMEM = OFF_PROF + 4096 > wk::SMEM ? OFF_PROF + 4096 : wk::SMEM;
enum { B_XT = 0, B_VX = 4, B_XD = 6, B_X1 = 8, B_GO = 10, B_PXF = 12, B_PXE = 13, B_FIN = 14, B_ST = 15, B_MEM = 16   };
enum { NB_W2 = 0, NB_XCH = 1, NB_QK = 2, NB_WIN = 3, NB_ATT = 4, NB_X = 5, NB_PRO = 6, NB_W1 = 7, NB_LD = 13, NB_KX = 15 };
#define STAG 3
#define NOX 0
#define NW1 4
#define NW1B 0
template <int N> struct IC { static constexpr int value = N; };
template <int N, int I = 0, class F> DEV void static_for(F&& f) { if constexpr (I < N) { f(IC<I>{}); static_for<N, I + 1>(f); } }
constexpr float SM_SCALE = 0.08838834764831845f * 1.4426950408889634f;
}

__global__ void __launch_bounds__(512, 1) rec_kernel(const __grid_constant__ Maps maps, const bf16* __restrict__ x, bf16* __restrict__ x1, const bf16* __restrict__ mem0, const bf16* __restrict__ Wq, const bf16* __restrict__ Wk,
                                                     const bf16* __restrict__ Wv, const bf16* __restrict__ Wo, int layer, int delay, int delay2) {
    using namespace rec;
    extern __shared__ __align__(1024) unsigned char smem[];
    const uint32_t sb = s2u(smem);
    if (blockIdx.x >= 3 * H_) {
        pdl_wait();
        pdl_launch();
        worker(sb, maps, x, x1, layer);
        return;
    }
    const int tid = threadIdx.x, lane = tid & 31, warp = __shfl_sync(~0u, tid >> 5, 0);
    const int g = lane >> 2, q = lane & 3;
    const int h = blockIdx.x / 3;
    const uint32_t bar = sb + OFF_BAR;
    STAMP(2 * layer);
    TLS(2 + 5 * layer);
    if (tid == 0) {
        for (int i = 0; i < 2; i++) {
            mbar_init(bar + 8 * (B_XT + i), 1); mbar_init(bar + 8 * (B_VX + i), 1);
            mbar_init(bar + 8 * (B_XD + i), 8); mbar_init(bar + 8 * (B_X1 + i), 1);
        }
        mbar_init(bar + 8 * B_PXF, 1); mbar_init(bar + 8 * B_PXE, 2); mbar_init(bar + 8 * B_ST, 2); mbar_init(bar + 8 * B_GO, 1);
        for (int i = 0; i < 5; i++) mbar_init(bar + 8 * (B_MEM + i), 4);
        mbar_init(bar + 8 * B_FIN, 48);
        sts32(sb + OFF_MX + 32, 0); sts32(sb + OFF_MX + 36, 0);
        asm volatile("fence.mbarrier_init.release.cluster;" ::: "memory");
    }
    asm volatile("barrier.cluster.arrive.aligned; barrier.cluster.wait.aligned;" ::: "memory");
    const bool never = delay < 0;

    if (warp < 8) {
        asm volatile("setmaxnreg.inc.sync.aligned.u32 184;");
        const uint32_t rank = cta_rank();
        const int wg = warp >> 2;
        uint32_t fa[20 - NS][4], fb[20][4];
        const uint32_t l16 = opaque(sb + lane * 16);
        uint32_t dst = opaque(rank < 2 ? sb + OFF_Q + wg * 10240 + (warp & 3) * 256 + (lane & 15) * 16 + (lane >> 4) * 1024
                                       : sb + OFF_VM + warp * 256 + lane * 4);
        int dstep = rank < 2 ? 5120 : 2048;
        uint32_t& sfd = dst;
        const uint32_t ws = OFF_WS + warp * 512, xo = OFF_XCH + warp * 512, xi = OFF_XCH + (warp ^ 4) * 512, mb = OFF_MEMB + wg * 512;
        {
            const int t = tid & 127;
            const bf16* src = (rank == 2 ? Wv + wg * 64 : (wg ? Wk : Wq) + rank * 64) + h * E_ + (size_t)(t >> 3) * 4096 + (t & 7) * 8;
            constexpr int SA = OFF_X + 40960, SB = OFF_VX;
            const uint32_t sdst = sb + (wg ? SB : SA) + (t >> 3) * 128 + (((t & 7) ^ ((t >> 3) & 7)) << 4);
            const uint32_t ra = sb + wg * 4096 + ((lane >> 4) * 8 + (lane & 7)) * 128 + (((2 * (warp & 3) + ((lane >> 3) & 1)) ^ (lane & 7)) << 4);
            auto issue = [&](int rd) {
#pragma unroll
                for (int i = 0; i < 8; i++) cp16(sdst + (rd & 1) * 16384 + i * 2048, src + (size_t)(rd * 128 + i * 16) * 4096);
                cp_commit();
            };
            issue(0); issue(1);
#pragma unroll
            for (int rd = 0; rd < 5; rd++) {
                if (rd < 4) cp_wait<1>(); else cp_wait<0>();
                bar_sync(NB_XCH, 256);
#pragma unroll
                for (int i = 0; i < 4; i++) {
                    const int n = rd * 4 + i, o = (rd & 1) * 16384 + (i >> 1) * 8192 + (i & 1) * 2048;
                    if (n < NS) {
                        uint32_t f[4];
                        ldsm4t(f, ra + SA + o);
                        sts128(l16 + ws + n * 4096, f[0], f[1], f[2], f[3]);
                    } else ldsm4t(fa[n - NS], ra + SA + o);
                    ldsm4t(fb[n], ra + SB + o);
                }
                if (rd < 3) { bar_sync(NB_XCH, 256); issue(rd + 2); }
            }
            fence_async();
            bar_sync(NB_PRO, 288);
        }
        uint32_t xlo = (uint32_t)mkdesc(sb + OFF_X + wg * 64, 0, 0);
        const uint32_t xtog = xlo ^ (uint32_t)mkdesc(sb + OFF_X + 40960 + wg * 64, 0, 0);
        uint32_t p8 = 0;
        bar_sync(NB_LD, 288);
        for (int s = -1;; s++) {
            uint32_t t[NS ? NS : 1][4];
            {
                float acc[16];
                auto xproj = [&](auto I0, auto I1) {
                    const u64 desc = (u64)xlo | (64ull << 32) | SW128;
                    wg_fence();
#pragma unroll
                    for (int i = I0.value; i < I1.value; i++) {
                        const u64 db = desc + (i >> 1) * 256 + (i & 1) * 2;
                        if (i == 0) wgmma_n32_rs<0>(acc, fb[i], db);
                        else if (!NOX) wgmma_n32_rs<1>(acc, fb[i], db);
                    }
                    wg_commit();
                    wg_wait<0>();
                };
                if (s >= 0 && rank < 2) { fence_async(); bar_arrive(NB_W1, 512); bar_sync(NB_X, 384); }
                bar_sync_if<NB_W1, 480>(s >= 0 && rank == 2);
                if (s == NSEG - 1) break;
                xproj(IC<0>{}, IC<NW1>{});
                if (warp == 4 && s >= 0) PROFT(15);
                bar_sync_if<NB_W2, 384>(s >= 0 && rank < 2);
                if (NW1B > 0) xproj(IC<NW1>{}, IC<NW1 + NW1B>{});
                bar_sync_if<NB_WIN, 384>(s >= 0 && rank == 2);
                xproj(IC<NW1 + NW1B>{}, IC<20>{});
                if (warp == 4 && s >= 0) PROFT(12);
                sts128f_if(l16 + xo, acc + 8, !wg); sts128f_if(l16 + xo + 4096, acc + 12, !wg);
                sts128f_if(l16 + xo, acc, wg); sts128f_if(l16 + xo + 4096, acc + 4, wg);
                bar_sync(NB_XCH, 256);
                float u[8];
#pragma unroll
                for (int i = 0; i < 8; i++) acc[i] = wg ? acc[8 + i] : acc[i];
                lds128f(u, l16 + xi); lds128f(u + 4, l16 + xi + 4096);
#pragma unroll
                for (int i = 0; i < NS; i++) lds128(t[i], l16 + ws + i * 4096);
#pragma unroll
                for (int i = 0; i < 8; i++) u[i] += acc[i];
                if (rank < 2) {
                    stsm4t(dst + (wg ? 3072 : 11264), pack2(u[0], u[1]), pack2(u[2], u[3]), pack2(u[4], u[5]), pack2(u[6], u[7]));
                    bar_arrive(NB_KX, 384);
                } else {
                    stsm4(l16 + (l16 & 256) + OFF_VX + 4096 + (warp & 3) * 1024 + wg * 256 + p8 * 1024,
                          pack2(u[0], u[1]), pack2(u[4], u[5]), pack2(u[2], u[3]), pack2(u[6], u[7]));
                    bar_arrive(NB_KX, 288);
                }
                xlo ^= xtog;
                if (warp == 4 && s >= 0) PROFT(3);
            }
            float da[4] = {0.f, 0.f, 0.f, 0.f}, db[4] = {0.f, 0.f, 0.f, 0.f};
            uint32_t b[10][4];
            const uint32_t mp = p8 >> 3;
            while (!mbar_try(bar + 8 * B_MEM, mp)) {}
            lds128(b[0], l16 + mb); lds128(b[1], l16 + mb + 1024);
            bool rdy = mbar_try(bar + 8 * (B_MEM + 1), mp, 1);
            const uint32_t xb0 = mapa(bar + 8 * B_X1 + p8, 0), xb1 = mapa(bar + 8 * B_X1 + p8, 1);
            SFENCE();
            float is;
#pragma unroll
            for (int j = 0; j < 10; j++) {
#pragma unroll
                for (int x = 0; x < 2; x++) {
                    const int i = 2 * j + x;
                    const uint32_t* f = i < NS ? t[i] : fa[i - NS];
                    mma16(da, f[0], f[1], f[2], f[3], b[j][2 * x], b[j][2 * x + 1]);
                    mma16(db, fb[i][0], fb[i][1], fb[i][2], fb[i][3], b[j][2 * x], b[j][2 * x + 1]);
                    SFENCE();
                    if (x == 0 && j < 8 && !(j & 1)) {
                        if (__builtin_expect(!rdy, 0)) while (!mbar_try(bar + 8 * (B_MEM + 1 + (j >> 1)), mp)) {}
                        lds128(b[j + 2], l16 + mb + (j + 2) * 1024);
                    }
                    if (x == 1 && j < 8 && !(j & 1)) lds128(b[j + 3], l16 + mb + (j + 3) * 1024);
                    if (x == 0 && j < 6 && (j & 1)) rdy = mbar_try(bar + 8 * (B_MEM + 2 + (j >> 1)), mp, 1);
                    if (x == 0 && j == 8) is = lds32f(sb + OFF_MX + 16);
                }
                if (j == 0 && warp == 4) PROFT(16);
            }
            sts128f_if(l16 + xo + 8192, db, !wg); sts128f_if(l16 + xo + 8192, da, wg);
            bar_sync(NB_XCH, 256);
            float u[4];
            lds128f(u, l16 + xi + 8192);
#pragma unroll
            for (int i = 0; i < 4; i++) da[i] = (wg ? db[i] : da[i]) * is;
            const uint32_t p0 = pack2(fmaf(u[0], is, da[0]), fmaf(u[1], is, da[1])), p1 = pack2(fmaf(u[2], is, da[2]), fmaf(u[3], is, da[3]));
            stsm2t_if(dst, p0, p1, rank < 2);
            bar_arrive_if<NB_QK, 384>(rank < 2);
            if (rank == 2) {
                st_async1(mapa(dst, 0), p0, xb0); st_async1(mapa(dst, 1), p0, xb1);
                st_async1(mapa(dst + 128, 0), p1, xb0); st_async1(mapa(dst + 128, 1), p1, xb1);
                sts32(dst, p0); sts32(dst + 128, p1);
                bar_arrive(NB_QK, 384);
            }
            if (warp == 4) PROFT(17);
            dst += dstep; dstep = -dstep; p8 ^= 8;
        }
    } else if (warp < 12) {
        asm volatile("setmaxnreg.dec.sync.aligned.u32 96;");
        const uint32_t rank = cta_rank();
        const int w = warp - 8;
        uint32_t amax = 0;
#pragma unroll
        for (int it = 0; it < 5; it++) {
            const int kp = it * 4 + w;
            const bf16* p = mem0 + g * D_ + kp * 32 + 2 * q;
            uint32_t b0 = ldg32(p), b1 = ldg32(p + 8), b2 = ldg32(p + 16), b3 = ldg32(p + 24);
            sts128(sb + OFF_MEMB + kp * 512 + lane * 16, b0, b1, b2, b3);
            amax = absmax2(amax, absmax2(absmax2(b0, b1), absmax2(b2, b3)));
        }
        if (tid == 256) { sts32(sb + OFF_MX + 16, 0x3f800000u); sts128(sb + OFF_MX + 48, 0x3f803f80u, 0x3f803f80u, 0x3f803f80u, 0x3f803f80u); }
        __syncwarp();
        if (lane < 5) mbar_arrive(bar + 8 * (B_MEM + lane));
        __syncwarp();
        {
            const int t = tid & 127, nr = rank == 2 ? 4 : 3;
            for (int r = 0; r < nr; r++) {
                const bf16* src = Wo + (size_t)(h * E_) * D_ + (r < 3 ? 192 * r + 64 * rank : 576);
#pragma unroll
                for (int i = 0; i < 8; i++) {
                    const int e = i * 16 + (t >> 3);
                    cp16(sb + OFF_WO + r * 16384 + e * 128 + (((t & 7) ^ (e & 6)) << 4), src + e * D_ + (t & 7) * 8);
                }
            }
            cp_commit();
            pdl_wait();
            pdl_launch();
            cp_wait<0>();
            bar_sync(NB_ATT, 128);
            for (int r = 0; r < nr; r++) {
                uint32_t u[8][4];
                const uint32_t p = sb + OFF_WO + r * 16384 + 2 * q * 128 + (((2 * w + (g & 1)) ^ (2 * q)) << 4) + (g >> 1) * 4;
#pragma unroll
                for (int ks = 0; ks < 8; ks++)
#pragma unroll
                    for (int j = 0; j < 4; j++) u[ks][j] = lds32(p + (16 * ks + (j & 1) * 8 + (j >> 1)) * 128);
                bar_sync(NB_ATT, 128);
#pragma unroll
                for (int ks = 0; ks < 8; ks++)
                    sts128(sb + OFF_WO + (r * 4 + w) * 4096 + ks * 512 + lane * 16, prmt(u[ks][0], u[ks][2], 0x5410), prmt(u[ks][0], u[ks][2], 0x7632),
                           prmt(u[ks][1], u[ks][3], 0x5410), prmt(u[ks][1], u[ks][3], 0x7632));
            }
        }
        float cw;
        {
            const float4 a = ((const float4*)g_nrm)[lane], c = ((const float4*)g_nrm)[32 + lane];
            float sm = sqrtf((a.x + a.y) + (a.z + a.w)) * sqrtf((c.x + c.y) + (c.z + c.w)), mxv = sm;
#pragma unroll
            for (int o = 16; o; o >>= 1) { sm += __shfl_xor_sync(~0u, sm, o); mxv = fmaxf(mxv, __shfl_xor_sync(~0u, mxv, o)); }
            cw = 26.5f * fmaxf(sm, 8.f * mxv);
        }
        if (w == 0) {
            mbar_expect_elect(bar + 8 * B_X1, rank < 2 ? 3328 : 1280);
            mbar_expect_elect(bar + 8 * B_VX, rank < 2 ? 8192 : 4096);
        }
        {
            const int kind = rank;
            const uint32_t l16 = opaque(sb + lane * 16), lw = opaque(sb + lane * 16 + w * 512);
            const uint32_t pa = opaque(sb + OFF_PS + rank * 512 + lane * 4 + w * 128);
            uint32_t lq = opaque(sb + OFF_Q + (lane & 7) * 16 + ((lane >> 3) & 1) * 256 + (lane >> 4) * 128);
            const uint32_t lv = opaque(sb + OFF_VX + w * 2048 + (lane & 7) * 16 + ((lane >> 3) & 1) * 512 + (lane >> 4) * 128);
            const uint32_t lo = opaque(sb + OFF_WO + w * 4096 + lane * 16);
            uint32_t& sfd = lq;
            const char* rp = (const char*)(g_acc + layer * ACC_LAYER) + (4 * rank + w) * 4096 + opaque((q >> 1) * 1024 + ((q & 1) * 8 + g) * 8);
            const char* lp = (const char*)(g_acc + layer * ACC_LAYER) + opaque(w * 8192 + (lane >> 3) * 1024 + (lane & 7) * 16);
            float isig = 1.f;
            for (int s = 0; s < NSEG - 1; s++) {
                const uint32_t pb = s & 1, ph = (s >> 1) & 1, x1 = bar + 8 * (B_X1 + pb);
                uint32_t kf[8];
                bar_sync_if<NB_KX, 384>(kind < 2);
                ldsm4(kf, lw + OFF_K + 1024 + w * 512 + pb * 5120); ldsm4(kf + 4, lw + OFF_K + 1536 + w * 512 + pb * 5120);
                sts32(sb + OFF_MX + w * 4, __reduce_max_sync(~0u, max(amax & 0x7fff0000u, (amax << 16) & 0x7fff0000u)));
                const bool vok = mbar_try(bar + 8 * (B_VX + pb), ph, 1);
                const uint32_t va = lv + pb * 8192, vma = lw + OFF_VM + pb * 2048;
                uint32_t wf[8][4], vf[2][2][4], vm[4], one[4];
                auto scores = [&](auto MM) {
                    constexpr int mm = MM.value;
                    uint32_t qf[8], mf[8];
                    const uint32_t qa = lq + pb * 5120, ka = l16 + OFF_K + pb * 5120;
                    const uint32_t pa0 = mapa(pa, rank ^ 1), pa1 = mapa(pa, 2), pa2 = mapa(pa, rank);
                    const uint32_t xb0 = mapa(x1, rank ^ 1), xb1 = mapa(x1, 2), xb2 = mapa(x1, rank);
                    const uint32_t pm = 640 - rank * 384;
                    SFENCE();
                    bar_sync(NB_QK, 384);
                    ldsm4(qf, qa); ldsm4(qf + 4, qa + 512);
                    if (mm) { ldsm4(mf, ka); ldsm4(mf + 4, ka + 512); }
                    SFENCE();
                    float c[8][4];
#pragma unroll
                    for (int i = 0; i < (mm ? 8 : 4); i++) {
                        const uint32_t* f = (i < 4 ? kf : mf) + 2 * (i & 3);
                        c[i][0] = c[i][1] = c[i][2] = c[i][3] = 0.f;
                        mma16(c[i], qf[i & 2 ? 4 : 0], qf[i & 2 ? 5 : 1], qf[i & 2 ? 6 : 2], qf[i & 2 ? 7 : 3], f[0], f[1]);
                    }
                    SFENCE();
                    bar_arrive(NB_W1, 512);
                    const uint32_t y = pack2((c[0][0] + c[1][2]) + (c[2][0] + c[3][2]), (c[0][1] + c[1][3]) + (c[2][1] + c[3][3]));
                    st_async1(pa0, y, xb0); st_async1(pa1, y, xb1);
                    if (mm) {
                        const uint32_t z = pack2((c[4][0] + c[5][2]) + (c[6][0] + c[7][2]), (c[4][1] + c[5][3]) + (c[6][1] + c[7][3]));
                        st_async1(pa0 + pm, z, xb0); st_async1(pa1 + pm, z, xb1); st_async1(pa2 + pm, z, xb2);
                    }
                    st_async1(pa2, y, xb2);
                };
                if (kind == 2) bar_sync(NB_QK, 384);
                else if (w == 3) scores(IC<1>{});
                else scores(IC<0>{});
                if (!vok) mbar_wait(bar + 8 * (B_VX + pb), ph);
#pragma unroll
                for (int t = 0; t < 2; t++)
#pragma unroll
                    for (int j = 0; j < 2; j++) ldsm4(vf[t][j], va + t * 1024 + j * 256);
                float m4[4];
                lds128f(m4, sb + OFF_MX);
                bar_arrive_if<NB_W1, 480>(kind == 2);
                lds128(one, sb + OFF_MX + 48);
                mbar_wait(x1, ph);
                if (w == 0) PROFT(6);
                float sc[10];
                {
                    uint32_t u[4], v[4], m[2];
                    ldsm4(u, l16 + OFF_PS); ldsm4(v, l16 + OFF_PS + 512); ldsm2(m, l16 + OFF_PS + 1024);
                    ldsm4(vm, vma);
                    SFENCE();
                    m4[0] = fmaxf(fmaxf(m4[0], m4[1]), fmaxf(m4[2], m4[3])) * isig;
                    SFENCE();
#pragma unroll
                    for (int i = 0; i < 4; i++) { sc[2 * i] = bf_lo(u[i]) + bf_lo(v[i]); sc[2 * i + 1] = bf_hi(u[i]) + bf_hi(v[i]); }
                    sc[8] = bf_lo(m[0]) + bf_lo(m[1]); sc[9] = bf_hi(m[0]) + bf_hi(m[1]);
                }
                float mx = fmaxf(fmaxf(fmaxf(fmaxf(sc[0], sc[1]), fmaxf(sc[2], sc[3])), fmaxf(fmaxf(sc[4], sc[5]), fmaxf(sc[6], sc[7]))), fmaxf(sc[8], sc[9]));
                auto fetch = [&](int i) { lds128(wf[i], lo + i * 512); };
                {
                    float m1 = __shfl_xor_sync(~0u, mx, 1), m2 = __shfl_xor_sync(~0u, mx, 2), m3 = __shfl_xor_sync(~0u, mx, 3);
                    SFENCE();
#pragma unroll
                    for (int i = 0; i < 4; i++) fetch(i);
                    SFENCE();
                    mx = fmaxf(fmaxf(mx, m1), fmaxf(m2, m3)) * SM_SCALE;
                }
#pragma unroll
                for (int i = 0; i < 10; i++) sc[i] = fmaf(sc[i], SM_SCALE, -mx);
                float o0[4] = {0.f, 0.f, 0.f, 0.f}, o1[4] = {0.f, 0.f, 0.f, 0.f}, rs[4] = {0.f, 0.f, 0.f, 0.f};
                sc[8] = ex2(sc[8]); sc[9] = ex2(sc[9]);
                SFENCE();
                sc[0] = ex2(sc[0]); fetch(4); sc[1] = ex2(sc[1]); fetch(5); sc[2] = ex2(sc[2]); fetch(6);
                SFENCE();
                {
                    const uint32_t p = pack2(sc[8], sc[9]);
                    sc[3] = ex2(sc[3]); fetch(7);
                    mma8(o0, vm[0], vm[1], p);
                    mma8(o1, vm[2], vm[3], p);
                    sc[4] = ex2(sc[4]);
                    mma8(rs, one[0], one[1], p);
                    sc[5] = ex2(sc[5]);
                }
                SFENCE();
                {
                    const uint32_t p0 = pack2(sc[0], sc[1]), p1 = pack2(sc[2], sc[3]);
                    sc[6] = ex2(sc[6]);
                    mma16(o0, vf[0][0][0], vf[0][0][1], vf[0][0][2], vf[0][0][3], p0, p1);
                    SFENCE();
                    sc[7] = ex2(sc[7]);
                    mma16(o1, vf[1][0][0], vf[1][0][1], vf[1][0][2], vf[1][0][3], p0, p1);
                    SFENCE();
                    mma16(rs, one[0], one[1], one[2], one[3], p0, p1);
                    SFENCE();
                }
                {
                    const uint32_t p0 = pack2(sc[4], sc[5]), p1 = pack2(sc[6], sc[7]);
                    mma16(o0, vf[0][1][0], vf[0][1][1], vf[0][1][2], vf[0][1][3], p0, p1);
                    mma16(o1, vf[1][1][0], vf[1][1][1], vf[1][1][2], vf[1][1][3], p0, p1);
                    SFENCE();
                    mma16(rs, one[0], one[1], one[2], one[3], p0, p1);
                }
                const uint32_t e = max((__float_as_uint(cw * fmaxf(m4[0], 1.f)) >> 23) & 255u, 31u);
                SFENCE();
                stsm4t(lw + OFF_OB, pack2(o0[0], o0[1]), pack2(o0[2], o0[3]), pack2(o1[0], o1[1]), pack2(o1[2], o1[3]));
                bar_sync(NB_ATT, 128);
                uint32_t ob[16];
#pragma unroll
                for (int j = 0; j < 4; j++) ldsm4(ob + 4 * j, l16 + OFF_OB + j * 512);
                SFENCE();
                const float sig = __uint_as_float((278u - e) << 23);
                isig = __uint_as_float((e - 30u) << 23);
                const float sg0 = rcp(rs[0]) * sig, sg1 = rcp(rs[1]) * sig;
                SFENCE();
                auto tile = [&](uint32_t next, const char* p, auto LAST) {
                    float c[4][4];
#pragma unroll
                    for (int i = 0; i < 4; i++) c[i][0] = c[i][1] = c[i][2] = c[i][3] = 0.f;
#pragma unroll
                    for (int ks = 0; ks < 8; ks++) {
                        mma16(c[ks & 3], wf[ks][0], wf[ks][1], wf[ks][2], wf[ks][3], ob[2 * ks], ob[2 * ks + 1]);
                        if ((ks & 3) == 3 && !LAST.value) {
                            SFENCE();
#pragma unroll
                            for (int i = ks - 3; i <= ks; i++) lds128(wf[i], next + i * 512);
                        }
                    }
                    SFENCE();
                    if (LAST.value) { bar_arrive_if<NB_WIN, 256>(kind < 2); bar_arrive_if<NB_WIN, 384>(kind == 2); }
                    uint32_t v[4];
#pragma unroll
                    for (int i = 0; i < 4; i++)
                        v[i] = (__float_as_uint(fmaf((c[0][i] + c[1][i]) + (c[2][i] + c[3][i]), i & 1 ? sg1 : sg0, 12582912.f)) << 6) + (i < 2);
                    red_add64((u64*)p, v[0], v[2]);
                    red_add64((u64*)(p + 2048), v[1], v[3]);
                };
                tile(lo + 16384, rp, IC<0>{});
                if (w == 0) PROFT(7);
                if (w == 0) GPROF(4, 0);
                tile(lo + 32768, rp + 49152, IC<0>{});
                if (kind == 2) tile(lo + 49152, rp + 98304, IC<0>{});
                tile(0, rp + (kind == 2 ? 28 * 4096 : 98304), IC<1>{});
                if (w == 0) PROFT(8);
                sts32(sb + OFF_MX + 16, __float_as_uint(isig));
                if (w == 0) mbar_expect_elect(bar + 8 * (B_X1 + (pb ^ 1)), (kind < 2 ? 2048 : 0) + (s < NSEG - 2 ? 1280 : 0));
                if (w == 1) mbar_expect_elect(bar + 8 * (B_VX + (pb ^ 1)), kind < 2 ? 8192 : 4096);
                if (w == 2) mbar_expect_elect(bar + 8 * (B_XT + pb), (kind < 2 ? 4096 : 0) + (s < NSEG - 2 ? 40960 : 0));
                u64 y[20];
                float z = isig;
                mbar_wait(bar + 8 * B_GO, pb);
#pragma unroll
                for (int i = 0; i < 10; i++) {
                    if (STAG && (i == 2 || i == 4 || i == 7)) {
#pragma unroll
                        for (int k = 0; k < STAG; k++) asm volatile("ex2.approx.ftz.f32 %0,%0;" : "+f"(z));
                        asm volatile("{.reg .pred p; setp.ne.u32 p,%1,0; @p mov.b32 %0,%2;}" : "+r"(sfd) : "r"((uint32_t)never), "f"(z));
                        SFENCE();
                    }
                    ld_acc0(y[2 * i], y[2 * i + 1], lp + (i >> 1) * 32768 + (i & 1) * 4096);
                    if (STAG && (i == 1 || i == 3 || i == 6)) SFENCE();
                }
                if (w == 0) PROFT(9);
                uint32_t nretry = 0, b[20];
                bool done[5] = {false, false, false, false, false};
                auto publish = [&](auto FIRST) {
                    uint32_t ok = 32u, late = 32u;
                    static_for<5>([&](auto IT) {
                        constexpr int it = IT.value;
                        if (it == 2) late = and3((uint32_t)y[8], (uint32_t)y[10], (uint32_t)y[12]);
                        else if (it == 3) late &= and3((uint32_t)y[14], (uint32_t)y[16], (uint32_t)y[18]);
                        else ok = and3(ok, (uint32_t)y[4 * it], it == 4 ? late : (uint32_t)y[4 * it + 2]);
                        if (FIRST.value && it < 4) SFENCE();
                        if (it == 2 || it == 3) ok = and3(ok, (uint32_t)y[4 * it], (uint32_t)y[4 * it + 2]);
                        ok = and3(ok, (uint32_t)y[4 * it + 1], (uint32_t)y[4 * it + 3]);
                        const bool all = __all_sync(~0u, ok);
#pragma unroll
                        for (int j = 0; j < 4; j++) {
                            const u64 z = y[4 * it + j];
                            b[4 * it + j] = pack2((float)(int)(uint32_t)z, (float)(int)(uint32_t)(z >> 32));
                        }
                        sts128(lw + OFF_MEMB + it * 2048, b[4 * it], b[4 * it + 1], b[4 * it + 2], b[4 * it + 3]);
                        mbar_arrive_elect_if(bar + 8 * (B_MEM + it), all && (FIRST.value || !done[it]));
                        done[it] = all;
                        if (FIRST.value) SFENCE();
                        if (FIRST.value && it == 0 && w == 0) PROFT(10);
                    });
                };
                publish(IC<1>{});
                while (!done[4]) {
                    if (++nretry > SPIN_LIMIT) die();
#pragma unroll
                    for (int i = 0; i < 10; i++) ld_acc(y[2 * i], y[2 * i + 1], lp + (i >> 1) * 32768 + (i & 1) * 4096);
                    publish(IC<0>{});
                }
                if (w == 0) PROFT(11);
                GPROF(w, nretry);
                amax = b[0];
#pragma unroll
                for (int i = 1; i < 19; i += 2) amax = absmax2(amax, absmax2(b[i], b[i + 1]));
                amax = absmax2(amax, b[19]);
                const int adv = (s & 7) == 7 ? 163840 - 896 : 128;
                rp += adv; lp += adv;
            }
        }
        bar_sync_if<NB_KX, 384>(rank < 2);
        bar_sync(NB_QK, 384);
        if (rank < 2) { bar_arrive(NB_W1, 512); bar_arrive(NB_WIN, 256); } else bar_arrive(NB_W1, 480);
    } else {
        asm volatile("setmaxnreg.dec.sync.aligned.u32 %0;" ::"n"(48));
        const uint32_t rank = cta_rank();
        const int w = warp - 12;
        pdl_wait();
        pdl_launch();
        uint32_t* sy = g_sync + layer * SYNC_LAYER;
        if (w == 1) {
            mbar_expect_elect(bar + 8 * B_XT, 40960);
            bulk_g2s_elect(sb + OFF_X, g_xn, 40960, bar + 8 * B_XT);
            bar_sync(NB_PRO, 288);
            if (rank == 2) mbar_wait(bar + 8 * B_ST, 0);
            else mbar_arrive_remote_elect(mapa(bar + 8 * B_ST, 2));
            mbar_wait(bar + 8 * B_XT, 0);
            bar_arrive(NB_LD, 288);
            mbar_expect_elect(bar + 8 * (B_XT + 1), rank < 2 ? 45056 : 40960);
        }
        if (rank == 2 && w == 3) {
            for (uint32_t s = 0, n = 0; s < NSEG; s++) {
                uint32_t c[2];
                for (;;) {
                    asm volatile("ld.acquire.cluster.shared::cta.v2.u32 {%0,%1},[%2];" : "=r"(c[0]), "=r"(c[1]) : "r"(sb + OFF_MX + 32) : "memory");
                    if (__all_sync(~0u, min(c[0], c[1]) > s)) break;
                    if (++n > (SPIN_LIMIT << 3)) die();
                    __nanosleep(s < NSEG - 2 ? 400 : 50);
                }
                if (h == 0) TLI(940 + s, 0, gtime());
                if (lane == 0) flag_add(sy + wk::SY_O + s);
                __syncwarp();
            }
        } else if (rank == 2) {
            const char* pf = (const char*)(g_acc + layer * ACC_LAYER) + (5 * h + lane % 5) * 1024;
            if (w == 2 && lane < 20) prefetch_l2(pf + lane / 5 * 128);
            if (w == 2 && lane < 4 && h == 0) prefetch_l2(sy + 1024 + lane * 32);
            for (int s = -1; s < NSEG - 1; s++) {
                const int pb = s & 1, n = s + 1;
                if (w == 0) {
                    bar_sync(NB_KX, 288);
                    fence_async();
                    const uint32_t va = sb + OFF_VX + (pb ^ 1) * 8192 + 4096, vb = bar + 8 * (B_VX + (pb ^ 1));
                    bulk_s2s_elect(mapa(va, 0), va, 4096, mapa(vb, 0));
                    bulk_s2s_elect(mapa(va, 1), va, 4096, mapa(vb, 1));
                    if (s >= 0) mbar_wait(bar + 8 * (B_XD + pb), (s >> 1) & 1);
                } else {
                    if (s >= 0) mbar_wait(bar + 8 * (B_X1 + pb), (s >> 1) & 1);
                    if (w == 1) {
                        const uint32_t xt = bar + 8 * (B_XT + pb), qa = sb + OFF_Q + (pb ^ 1) * 5120 + 1024;
                        const unsigned char* pn = g_p + (size_t)(n * H_ + h) * 12288;
                        if (n + 1 < NSEG) bulk_g2s_all3_elect(sb + OFF_X + pb * 40960, g_xn + (n + 1) * 40960, 40960, xt);
                        const int blk = wk::pb_first(n);
                        if (blk >= 0) flag_wait<true, true>(sy + wk::SY_P + blk * H_ + h, 3);
                        bulk_g2s_all3_elect(sb + OFF_VX + (pb ^ 1) * 8192, pn + 8192, 4096, bar + 8 * (B_VX + (pb ^ 1)));
                        bulk_g2s_elect(mapa(qa, 0), pn, 4096, mapa(xt, 0));
                        bulk_g2s_elect(mapa(qa, 1), pn + 4096, 4096, mapa(xt, 1));
                        mbar_wait(xt, ((n + 1) >> 1) & 1);
                    } else if (s >= 0) {
                        uint32_t* hp = sy + 1024 + s * 32;
                        uint32_t t = gtime32(), c, it = 0;
                        asm volatile("{.reg .pred p; elect.sync _|p, 0xffffffff; @p red.relaxed.gpu.global.max.u32 [%0+4],%1; @p red.relaxed.gpu.global.add.u32 [%0],1;}"
                                     ::"l"(hp), "r"(t) : "memory");
                        if (lane < 5 && s + 4 < NSEG) prefetch_l2(pf + ((s + 4) >> 3) * 163840 + ((s + 4) & 7) * 128);
                        if (lane == 5 && h == 0 && s + 4 < NSEG) prefetch_l2(hp + 4 * 32);
                        __syncwarp();
                        while (gtime32() - t < (uint32_t)delay2) {}
                        do {
                            asm volatile("ld.relaxed.gpu.global.v2.u32 {%0,%1},[%2];" : "=r"(c), "=r"(t) : "l"(hp) : "memory");
                            if (++it > (SPIN_LIMIT << 3)) die();
                        } while (__any_sync(~0u, c != H_));
                        while (gtime32() - t < (uint32_t)delay) {}
                        if (lane < 3) mbar_arrive_remote(mapa(bar + 8 * B_GO, lane));
                        __syncwarp();
                    }
                }
                bar_sync(NB_W1, 480);
            }
            if (w == 1) mbar_wait(bar + 8 * (B_VX + 1), 1);
        } else {
            if (w < 2) sts32(sb + OFF_PT + w * 768 + 640 + lane * 4, 0u);
            const uint32_t px = opaque(sb + OFF_PX + (w & 1) * 1280 + lane * 8);
            const uint32_t pt = opaque(sb + OFF_PT + (w & 1) * 768 + lane * 4);
            uint32_t os = opaque(sb + OFF_OST + (lane >> 4) * 1024 + w * 256 + (lane & 15) * 16);
            uint32_t& sfd = os;
            const int lim = opaque(8 * w + g + 8 - 2 * q);
            const uint32_t oc = mapa(sb + OFF_MX + 32 + 4 * rank, 2);
            auto store_o = [&](int n) {
                unsigned char* op = g_o + (size_t)(n * H_ + h) * 8192 + rank * 2048;
                bulk_s2g_elect(op, sb + OFF_OST + (n & 1) * 4096, 2048);
                bulk_s2g_elect(op + 4096, sb + OFF_OST + (n & 1) * 4096 + 2048, 2048);
                bulk_commit();
                bulk_wait<1>();
                __syncwarp();
                st_remote(oc, n);
            };
            for (int s = 0; s < NSEG; s++) {
                const uint32_t pb = s & 1, ph = (s >> 1) & 1;
                if ((w >> 1) != rank) { if (s >= 1) mbar_wait(bar + 8 * B_PXE, pb ^ 1); }
                else if (w & 1) mbar_wait(bar + 8 * (B_XT + (pb ^ 1)), ((s + 1) >> 1) & 1);
                else mbar_expect_elect(bar + 8 * B_PXF, rank ? 2560 : 1536);
                const u64 dq = mkdesc(sb + OFF_Q + pb * 5120 + 1024, 128, 512), dk = mkdesc(sb + OFF_K + pb * 5120, 128, 1024);
                SFENCE();
                bar_sync(NB_W1, 512);
                float c[20];
                wg_fence();
                wgmma_n40_ss<0>(c, dq, dk);
#pragma unroll
                for (int ks = 1; ks < 4; ks++) wgmma_n40_ss<1>(c, dq + ks * 16, dk + ks * 16);
                wg_commit();
                bar_arrive(NB_X, 384);
                wg_wait<0>();
                if ((w >> 1) != rank) {
                    const uint32_t pa = mapa(px, rank ^ 1), pf = mapa(bar + 8 * B_PXF, rank ^ 1);
#pragma unroll
                    for (int nt = 0; nt < 5; nt++)
                        if (nt < 3 || rank == 0) st_async2(pa + nt * 256, __float_as_uint(c[4 * nt]), __float_as_uint(c[4 * nt + 1]), pf);
                    if ((w & 1) && s) store_o(s - 1);
                    mbar_wait(bar + 8 * (w & 1 ? B_VX : B_X1) + 8 * pb, ph);
                } else {
                    mbar_wait(bar + 8 * B_PXF, pb);
                    float u[10];
#pragma unroll
                    for (int nt = 0; nt < 5; nt++) lds64f(u[2 * nt], u[2 * nt + 1], px + nt * 256);
#pragma unroll
                    for (int i = 0; i < 10; i++) u[i] = 8 * (i >> 1) + (i & 1) <= lim ? u[i] + c[4 * (i >> 1) + (i & 1)] : -INFINITY;
                    float mx = fmaxf(fmaxf(fmaxf(fmaxf(u[0], u[1]), fmaxf(u[2], u[3])), fmaxf(fmaxf(u[4], u[5]), fmaxf(u[6], u[7]))), fmaxf(u[8], u[9]));
                    const float m1 = __shfl_xor_sync(~0u, mx, 1), m2 = __shfl_xor_sync(~0u, mx, 2), m3 = __shfl_xor_sync(~0u, mx, 3);
                    mx = fmaxf(fmaxf(mx, m1), fmaxf(m2, m3)) * SM_SCALE;
#pragma unroll
                    for (int i = 0; i < 10; i++) u[i] = ex2(fmaf(u[i], SM_SCALE, -mx));
                    float sum = (((u[0] + u[1]) + (u[2] + u[3])) + ((u[4] + u[5]) + (u[6] + u[7]))) + (u[8] + u[9]);
                    const float s1 = __shfl_xor_sync(~0u, sum, 1), s2 = __shfl_xor_sync(~0u, sum, 2), s3 = __shfl_xor_sync(~0u, sum, 3);
                    sum = rcp((sum + s1) + (s2 + s3));
#pragma unroll
                    for (int nt = 0; nt < 5; nt++) sts32(pt + (nt ? nt - 1 : 4) * 128, pack2(u[2 * nt] * sum, u[2 * nt + 1] * sum));
                }
                float acc[2][8];
                const u64 dv = mkdesc(sb + OFF_VX + pb * 8192, 128, 512), dp = mkdesc(sb + OFF_PT, 128, 768);
                const u64 dm = mkdesc(sb + OFF_VM + pb * 2048, 0, 128);
                fence_async();
                bar_sync(NB_WIN, 256);
                wg_fence();
#pragma unroll
                for (int m = 0; m < 2; m++) {
                    wgmma_n16_ss<0>(acc[m], dv + m * 256, dp);
                    wgmma_n16_ss<1>(acc[m], dv + m * 256 + 16, dp + 16);
                    wgmma_n16_ss<1>(acc[m], dm + m * 64, dp + 32);
                }
                wg_commit();
                bar_arrive_if<NB_W2, 384>(s < NSEG - 1);
                wg_wait<0>();
#pragma unroll
                for (int m = 0; m < 2; m++)
                    stsm4t(os + pb * 4096 + m * 2048, pack2(acc[m][0], acc[m][1]), pack2(acc[m][2], acc[m][3]), pack2(acc[m][4], acc[m][5]), pack2(acc[m][6], acc[m][7]));
                fence_async();
                mbar_arrive_remote_elect(mapa(bar + 8 * (B_XD + pb), 2));
                if ((w >> 1) == rank) mbar_arrive_remote_elect(mapa(bar + 8 * B_PXE, rank ^ 1));
            }
            bar_sync(NB_W2, 128);
            if (w == 3 - 2 * rank) {
                store_o(NSEG - 1);
                bulk_wait<0>();
                __syncwarp();
                st_remote(oc, NSEG);
            }
        }
    }
    __syncwarp();
    if (lane < 3) mbar_arrive_remote(mapa(bar + 8 * B_FIN, lane));
    mbar_wait(bar + 8 * B_FIN, 0);
    TLE(2 + 5 * layer);
}

int g_delay = 1500575, g_layers = 2;

void make_map(CUtensorMap* m, CUtensorMapDataType dt, const void* p, const cuuint64_t* dim, const cuuint64_t* str, const cuuint32_t* box, CUtensorMapSwizzle sw) {
    typedef CUresult (*Fn)(CUtensorMap*, CUtensorMapDataType, cuuint32_t, void*, const cuuint64_t*, const cuuint64_t*, const cuuint32_t*,
                           const cuuint32_t*, CUtensorMapInterleave, CUtensorMapSwizzle, CUtensorMapL2promotion, CUtensorMapFloatOOBfill);
    static Fn fn = nullptr;
    if (!fn) {
        cudaDriverEntryPointQueryResult qr;
        cudaGetDriverEntryPoint("cuTensorMapEncodeTiled", (void**)&fn, cudaEnableDefault, &qr);
    }
    const cuuint32_t es[3] = {1, 1, 1};
    fn(m, dt, 3, (void*)p, dim, str, box, es, CU_TENSOR_MAP_INTERLEAVE_NONE, sw, CU_TENSOR_MAP_L2_PROMOTION_L2_128B, CU_TENSOR_MAP_FLOAT_OOB_FILL_NONE);
}
void map_weight(CUtensorMap* m, const bf16* p, int rows, int cols, int ng, int br = 64) {
    const cuuint64_t dim[3] = {64, (cuuint64_t)rows, (cuuint64_t)cols / 64}, str[2] = {(cuuint64_t)cols * 2, 128};
    const cuuint32_t box[3] = {64, (cuuint32_t)br, (cuuint32_t)ng};
    make_map(m, CU_TENSOR_MAP_DATA_TYPE_BFLOAT16, p, dim, str, box, CU_TENSOR_MAP_SWIZZLE_128B);
}
void map_pieces(CUtensorMap* m, const void* p, int np, int ns) {
    const cuuint64_t dim[3] = {256, (cuuint64_t)np * 2, NSEG}, str[2] = {2048, (cuuint64_t)np * 4096};
    const cuuint32_t box[3] = {256, 2, (cuuint32_t)ns};
    make_map(m, CU_TENSOR_MAP_DATA_TYPE_UINT64, p, dim, str, box, CU_TENSOR_MAP_SWIZZLE_NONE);
}

template <class... P, class... A> void launch(void (*k)(P...), int grid, int block, int smem, int cluster, bool pdl, A... args) {
    cudaLaunchConfig_t c = {};
    c.gridDim = dim3(grid); c.blockDim = dim3(block); c.dynamicSmemBytes = smem; c.stream = cudaStreamPerThread;
    cudaLaunchAttribute at[2];
    int n = 0;
    if (cluster > 1) { at[n].id = cudaLaunchAttributeClusterDimension; at[n].val.clusterDim.x = cluster; at[n].val.clusterDim.y = 1; at[n].val.clusterDim.z = 1; n++; }
    if (pdl) { at[n].id = cudaLaunchAttributeProgrammaticStreamSerialization; at[n].val.programmaticStreamSerializationAllowed = 1; n++; }
    c.attrs = at; c.numAttrs = n;
    cudaLaunchKernelEx(&c, k, args...);
}

int max_clusters() {
    cudaLaunchConfig_t c = {};
    c.gridDim = dim3(3 * H_); c.blockDim = dim3(512); c.dynamicSmemBytes = rec::SMEM;
    cudaLaunchAttribute at[1];
    at[0].id = cudaLaunchAttributeClusterDimension; at[0].val.clusterDim.x = 3; at[0].val.clusterDim.y = 1; at[0].val.clusterDim.z = 1;
    c.attrs = at; c.numAttrs = 1;
    int n = 0;
    cudaOccupancyMaxActiveClusters(&n, rec_kernel, &c);
    return n;
}

}

extern "C" void kernel_launch(void* const* d_in, const int* in_sizes, int n_in, void* d_out, int out_size) {
    const bf16* x = (const bf16*)d_in[0];
    const bf16* mem0 = (const bf16*)d_in[1];
    const bf16* Wq = (const bf16*)d_in[2];
    const bf16* Wk = (const bf16*)d_in[3];
    const bf16* Wv = (const bf16*)d_in[4];
    const bf16* Wo = (const bf16*)d_in[5];
    const bf16* wr = (const bf16*)d_in[8];
    const bf16* wi = (const bf16*)d_in[9];
    cudaFuncSetAttribute(rec_kernel, cudaFuncAttributeMaxDynamicSharedMemorySize, rec::SMEM);
    cudaFuncSetAttribute(side_kernel, cudaFuncAttributeMaxDynamicSharedMemorySize, wk::SMEM);
    cudaFuncSetAttribute(colfft_kernel, cudaFuncAttributeMaxDynamicSharedMemorySize, CF_SMEM);
    Maps maps;
    void *pxn, *po;
    cudaGetSymbolAddress(&pxn, g_xn);
    cudaGetSymbolAddress(&po, g_o);
    map_weight(&maps.wq2, Wq, D_, 4096, 2); map_weight(&maps.wv1, Wv, D_, 4096, 1);
    map_weight(&maps.wo2, Wo, 4096, D_, 2); map_weight(&maps.wo1, Wo, 4096, D_, 1, 192);
    map_pieces(&maps.x6, pxn, 10, 6); map_pieces(&maps.x2, pxn, 10, 2);
    map_pieces(&maps.o6, po, 64, 6); map_pieces(&maps.o2, po, 64, 2);
    bf16 *x1, *x2;
    cudaGetSymbolAddress((void**)&x1, g_x1);
    cudaGetSymbolAddress((void**)&x2, g_x2);
    constexpr int ONE_PER_SM = 120 * 1024;
    cudaFuncSetAttribute(rowfft_kernel, cudaFuncAttributeMaxDynamicSharedMemorySize, ONE_PER_SM);
    cudaFuncSetAttribute(rowifft_kernel, cudaFuncAttributeMaxDynamicSharedMemorySize, ONE_PER_SM);
    static int ncl = 0, nsm = 0;
    if (!ncl) { ncl = max_clusters(); cudaDeviceGetAttribute(&nsm, cudaDevAttrMultiProcessorCount, 0); }
    maps.wr = wr; maps.wi = wi;
    launch(prep_kernel, 128, 512, 0, 1, false, x, Wq, Wk, Wv, Wo);
    for (int layer = 0; layer < g_layers; layer++) {
        const bf16* xin = layer ? x2 : x;
        launch(rec_kernel, 3 * ncl, 512, rec::SMEM, 3, true, maps, xin, x1, mem0, Wq, Wk, Wv, Wo, layer, g_delay % 10000, g_delay / 10000);
        launch(side_kernel, nsm - 3 * (ncl - H_), 512, wk::SMEM, 1, true, maps, xin, x1, layer);
        launch(rowfft_kernel, 128, 256, ONE_PER_SM, 1, true, xin, x1, Wq, Wk, Wv, layer);
        launch(colfft_kernel, 107, 384, CF_SMEM, 1, true, layer);
        launch(rowifft_kernel, 128, 256, ONE_PER_SM, 1, true, (const bf16*)x1, layer ? (bf16*)d_out : x2, layer);
    }
}
```

```cpp
#include <cuda_runtime.h>
#include <cuda_bf16.h>
#include <cuda.h>
#include <stdint.h>

#define DEV __device__ __forceinline__
typedef unsigned long long u64;
typedef __nv_bfloat16 bf16;

namespace {

constexpr int S_ = 2048, D_ = 640, H_ = 32, E_ = 128, NSEG = 64;

__device__ __align__(1024) unsigned char g_xn[S_ * D_ * 2];
__device__ __align__(1024) unsigned char g_o[S_ * H_ * E_ * 2];
constexpr int ACC_LAYER = 32 * 5120;
__device__ __align__(4096) u64 g_acc[2 * ACC_LAYER];
__device__ __align__(16) float g_nrm[256];
__device__ __align__(1024) unsigned char g_p[NSEG * H_ * 3 * 4096];
constexpr int SYNC_LAYER = 1024 + 64 * 32;
__device__ __align__(128) uint32_t g_sync[2 * SYNC_LAYER];
__device__ __align__(1024) bf16 g_x1[S_ * D_];
__device__ __align__(1024) bf16 g_x2[S_ * D_];
constexpr int YT_ROWS = 128;
__device__ __align__(1024) float g_yt[2 * YT_ROWS * D_];
constexpr int NCOL = 321;
__device__ __align__(1024) unsigned char g_z[NCOL * 8192];
__device__ __align__(1024) unsigned char g_wt[NCOL * 8192];
__device__ __align__(1024) uint4 g_f128[2 * 8 * 256];
__device__ __align__(1024) uint4 g_f64[2 * 4 * 128];
__device__ __align__(1024) bf16 g_g32[2 * 4096];
#define TLI(id, k, v)
#define TLS(i)
#define TLE(i)

DEV uint32_t s2u(const void* p) { return (uint32_t)__cvta_generic_to_shared(p); }
DEV uint32_t clk() { uint32_t c; asm volatile("mov.u32 %0,%%clock;" : "=r"(c)::"memory"); return c; }
DEV uint32_t gtime32() { uint32_t t; asm volatile("mov.u32 %0,%%globaltimer_lo;" : "=r"(t)::"memory"); return t; }
DEV uint32_t cta_rank() { uint32_t r; asm volatile("mov.u32 %0,%%cluster_ctarank;" : "=r"(r)); return __shfl_sync(~0u, r, 0); }
DEV uint32_t mapa(uint32_t a, uint32_t r) { uint32_t o; asm("mapa.shared::cluster.u32 %0,%1,%2;" : "=r"(o) : "r"(a), "r"(r)); return o; }
DEV void mbar_init(uint32_t b, uint32_t n) { asm volatile("mbarrier.init.shared::cta.b64 [%0],%1;" ::"r"(b), "r"(n) : "memory"); }
DEV bool mbar_try(uint32_t b, uint32_t par, int) {
    uint32_t ok;
    asm volatile("{.reg .pred p; mbarrier.test_wait.parity.shared::cta.b64 p,[%1],%2; selp.u32 %0,1,0,p;}" : "=r"(ok) : "r"(b), "r"(par) : "memory");
    return ok;
}
DEV bool mbar_try(uint32_t b, uint32_t par) {
    uint32_t ok;
    asm volatile("{.reg .pred p; mbarrier.try_wait.parity.shared::cta.b64 p,[%1],%2; selp.u32 %0,1,0,p;}" : "=r"(ok) : "r"(b), "r"(par) : "memory");
    return ok;
}
constexpr uint32_t SPIN_LIMIT = 1u << 18;
DEV void die() { __trap(); }
DEV void mbar_wait(uint32_t b, uint32_t par) {
    uint32_t n = 0;
    while (!mbar_try(b, par)) if (++n > SPIN_LIMIT) die();
}
DEV void mbar_spin(uint32_t b, uint32_t par) { while (!mbar_try(b, par)) {} }
DEV uint32_t opaque(uint32_t x) { return __shfl_xor_sync(~0u, x, 0); }
#define SFENCE() asm volatile("{.reg .pred p; setp.ne.u32 p,%1,0; @p mov.u32 %0,%%clock;}" : "+r"(sfd) : "r"((uint32_t)never) : "memory")
DEV void mbar_arrive(uint32_t b) { asm volatile("mbarrier.arrive.shared::cta.b64 _,[%0];" ::"r"(b) : "memory"); }
DEV void mbar_arrive_elect(uint32_t b) { asm volatile("{.reg .pred p; elect.sync _|p, 0xffffffff; @p mbarrier.arrive.shared::cta.b64 _,[%0];}" ::"r"(b) : "memory"); }
DEV void mbar_arrive_elect_if(uint32_t b, bool c) {
    asm volatile("{.reg .pred p, q; setp.ne.u32 q,%1,0; elect.sync _|p, 0xffffffff; and.pred p,p,q; @p mbarrier.arrive.shared::cta.b64 _,[%0];}" ::"r"(b), "r"((uint32_t)c) : "memory");
}
DEV void mbar_expect_elect(uint32_t b, uint32_t tx) {
    asm volatile("{.reg .pred p; elect.sync _|p, 0xffffffff; @p mbarrier.arrive.expect_tx.shared::cta.b64 _,[%0],%1;}" ::"r"(b), "r"(tx) : "memory");
}
DEV void mbar_arrive_remote_elect(uint32_t b) { asm volatile("{.reg .pred p; elect.sync _|p, 0xffffffff; @p mbarrier.arrive.shared::cluster.b64 _,[%0];}" ::"r"(b) : "memory"); }
DEV bool elect() { uint32_t r; asm volatile("{.reg .pred p; elect.sync _|p, 0xffffffff; selp.u32 %0,1,0,p;}" : "=r"(r)); return r; }
DEV void mbar_arrive_remote(uint32_t b) { asm volatile("mbarrier.arrive.shared::cluster.b64 _,[%0];" ::"r"(b) : "memory"); }
DEV void mbar_expect(uint32_t b, uint32_t tx) { asm volatile("mbarrier.arrive.expect_tx.shared::cta.b64 _,[%0],%1;" ::"r"(b), "r"(tx) : "memory"); }
DEV void bar_sync(int id, int n) { asm volatile("bar.sync %0,%1;" ::"r"(id), "r"(n) : "memory"); }
DEV void bar_arrive(int id, int n) { asm volatile("bar.arrive %0,%1;" ::"r"(id), "r"(n) : "memory"); }
template <int ID, int N> DEV void bar_arrive_if(bool p) {
    asm volatile("{.reg .pred p; setp.ne.u32 p,%0,0; @p bar.arrive %1,%2;}" ::"r"((uint32_t)p), "n"(ID), "n"(N) : "memory");
}
DEV void prefetch_bulk(const void* p, uint32_t bytes) { asm volatile("cp.async.bulk.prefetch.L2.global [%0],%1;" ::"l"(p), "r"(bytes) : "memory"); }
DEV void prefetch_l2(const void* p) { asm volatile("prefetch.global.L2 [%0];" ::"l"(p) : "memory"); }
template <int ID, int N> DEV void bar_sync_if(bool p) {
    asm volatile("{.reg .pred p; setp.ne.u32 p,%0,0; @p bar.sync %1,%2;}" ::"r"((uint32_t)p), "n"(ID), "n"(N) : "memory");
}
DEV void st_remote(uint32_t a, uint32_t x) { asm volatile("st.relaxed.cluster.shared::cluster.u32 [%0],%1;" ::"r"(a), "r"(x) : "memory"); }
DEV void st_async1(uint32_t a, uint32_t x, uint32_t b) {
    asm volatile("st.async.shared::cluster.mbarrier::complete_tx::bytes.u32 [%0],%1,[%2];" ::"r"(a), "r"(x), "r"(b) : "memory");
}
DEV void st_async2(uint32_t a, uint32_t x, uint32_t y, uint32_t b) {
    asm volatile("st.async.shared::cluster.mbarrier::complete_tx::bytes.v2.u32 [%0],{%1,%2},[%3];" ::"r"(a), "r"(x), "r"(y), "r"(b) : "memory");
}
DEV void st_async4(uint32_t a, uint32_t x, uint32_t y, uint32_t z, uint32_t w, uint32_t b) {
    asm volatile("st.async.shared::cluster.mbarrier::complete_tx::bytes.v4.u32 [%0],{%1,%2,%3,%4},[%5];" ::"r"(a), "r"(x), "r"(y), "r"(z), "r"(w), "r"(b) : "memory");
}
DEV void bulk_g2s(uint32_t dst, const void* src, uint32_t bytes, uint32_t b) {
    asm volatile("cp.async.bulk.shared::cluster.global.mbarrier::complete_tx::bytes [%0],[%1],%2,[%3];" ::"r"(dst), "l"(src), "r"(bytes), "r"(b) : "memory");
}
DEV void bulk_g2s_elect(uint32_t dst, const void* src, uint32_t bytes, uint32_t b) {
    asm volatile("{.reg .pred p; elect.sync _|p, 0xffffffff; @p cp.async.bulk.shared::cluster.global.mbarrier::complete_tx::bytes [%0],[%1],%2,[%3];}"
                 ::"r"(dst), "l"(src), "r"(bytes), "r"(b) : "memory");
}
DEV void bulk_g2s_all3_elect(uint32_t dst, const void* src, uint32_t bytes, uint32_t b) {
    asm volatile("{.reg .pred p; elect.sync _|p, 0xffffffff; @p cp.async.bulk.shared::cluster.global.mbarrier::complete_tx::bytes.multicast::cluster [%0],[%1],%2,[%3],%4;}"
                 ::"r"(dst), "l"(src), "r"(bytes), "r"(b), "h"((unsigned short)7) : "memory");
}
DEV void bulk_s2s_elect(uint32_t dst, uint32_t src, uint32_t bytes, uint32_t b) {
    asm volatile("{.reg .pred p; elect.sync _|p, 0xffffffff; @p cp.async.bulk.shared::cluster.shared::cta.mbarrier::complete_tx::bytes [%0],[%1],%2,[%3];}"
                 ::"r"(dst), "r"(src), "r"(bytes), "r"(b) : "memory");
}
DEV void bulk_s2g_elect(void* dst, uint32_t src, uint32_t bytes) {
    asm volatile("{.reg .pred p; elect.sync _|p, 0xffffffff; @p cp.async.bulk.global.shared::cta.bulk_group [%0],[%1],%2;}" ::"l"(dst), "r"(src), "r"(bytes) : "memory");
}
DEV void bulk_s2s(uint32_t dst, uint32_t src, uint32_t bytes, uint32_t b) {
    asm volatile("cp.async.bulk.shared::cluster.shared::cta.mbarrier::complete_tx::bytes [%0],[%1],%2,[%3];" ::"r"(dst), "r"(src), "r"(bytes), "r"(b) : "memory");
}
DEV void bulk_s2g(void* dst, uint32_t src, uint32_t bytes) {
    asm volatile("cp.async.bulk.global.shared::cta.bulk_group [%0],[%1],%2;" ::"l"(dst), "r"(src), "r"(bytes) : "memory");
}
DEV void tma3d(uint32_t dst, const CUtensorMap* m, int c0, int c1, int c2, uint32_t b) {
    asm volatile("cp.async.bulk.tensor.3d.shared::cluster.global.mbarrier::complete_tx::bytes [%0],[%1,{%3,%4,%5}],[%2];"
                 ::"r"(dst), "l"(m), "r"(b), "r"(c0), "r"(c1), "r"(c2) : "memory");
}
DEV void bulk_commit() { asm volatile("cp.async.bulk.commit_group;" ::: "memory"); }
template <int N> DEV void bulk_wait() { asm volatile("cp.async.bulk.wait_group %0;" ::"n"(N) : "memory"); }
template <int N> DEV void bulk_wait_read() { asm volatile("cp.async.bulk.wait_group.read %0;" ::"n"(N) : "memory"); }
DEV void fence_async_all() { asm volatile("fence.proxy.async;" ::: "memory"); }
DEV void flag_add(uint32_t* p) { fence_async_all(); asm volatile("red.release.gpu.global.add.u32 [%0],1;" ::"l"(p) : "memory"); }
DEV uint32_t ld_acquire(const uint32_t* p) { uint32_t v; asm volatile("ld.acquire.gpu.global.u32 %0,[%1];" : "=r"(v) : "l"(p) : "memory"); return v; }
DEV void flag_wait(const uint32_t* p, uint32_t n) {
    for (uint32_t it = 0; ld_acquire(p) < n; __nanosleep(100)) if (++it > (SPIN_LIMIT << 3)) die();
    fence_async_all();
}
DEV void cp16(uint32_t dst, const void* src) { asm volatile("cp.async.cg.shared.global [%0],[%1],16;" ::"r"(dst), "l"(src) : "memory"); }
DEV void cp_commit() { asm volatile("cp.async.commit_group;" ::: "memory"); }
template <int N> DEV void cp_wait() { asm volatile("cp.async.wait_group %0;" ::"n"(N) : "memory"); }
DEV uint32_t lds32(uint32_t a) { uint32_t x; asm volatile("ld.shared.u32 %0,[%1];" : "=r"(x) : "r"(a) : "memory"); return x; }
DEV void fence_async() { asm volatile("fence.proxy.async.shared::cta;" ::: "memory"); }
DEV uint32_t pack2(float lo, float hi) { uint32_t r; asm("cvt.rn.bf16x2.f32 %0,%1,%2;" : "=r"(r) : "f"(hi), "f"(lo)); return r; }
DEV uint32_t prmt(uint32_t a, uint32_t b, uint32_t s) { uint32_t r; asm("prmt.b32 %0,%1,%2,%3;" : "=r"(r) : "r"(a), "r"(b), "r"(s)); return r; }
DEV float ex2(float x) { float r; asm("ex2.approx.ftz.f32 %0,%1;" : "=f"(r) : "f"(x)); return r; }
DEV float sqrt_approx(float x) { float r; asm("sqrt.approx.ftz.f32 %0,%1;" : "=f"(r) : "f"(x)); return r; }
DEV float rcp(float x) { float r; asm("rcp.approx.ftz.f32 %0,%1;" : "=f"(r) : "f"(x)); return r; }
DEV void lds128(uint32_t* r, uint32_t a) { asm volatile("ld.shared.v4.u32 {%0,%1,%2,%3},[%4];" : "=r"(r[0]), "=r"(r[1]), "=r"(r[2]), "=r"(r[3]) : "r"(a) : "memory"); }
DEV void lds64(uint32_t* r, uint32_t a) { asm volatile("ld.shared.v2.u32 {%0,%1},[%2];" : "=r"(r[0]), "=r"(r[1]) : "r"(a) : "memory"); }
DEV void lds64f(float& x, float& y, uint32_t a) { asm volatile("ld.shared.v2.f32 {%0,%1},[%2];" : "=f"(x), "=f"(y) : "r"(a) : "memory"); }
DEV void lds128f(float* r, uint32_t a) { asm volatile("ld.shared.v4.f32 {%0,%1,%2,%3},[%4];" : "=f"(r[0]), "=f"(r[1]), "=f"(r[2]), "=f"(r[3]) : "r"(a) : "memory"); }
DEV void sts128(uint32_t a, uint32_t x, uint32_t y, uint32_t z, uint32_t w) { asm volatile("st.shared.v4.u32 [%0],{%1,%2,%3,%4};" ::"r"(a), "r"(x), "r"(y), "r"(z), "r"(w) : "memory"); }
DEV void sts64(uint32_t a, uint32_t x, uint32_t y) { asm volatile("st.shared.v2.u32 [%0],{%1,%2};" ::"r"(a), "r"(x), "r"(y) : "memory"); }
DEV void sts32(uint32_t a, uint32_t x) { asm volatile("st.shared.u32 [%0],%1;" ::"r"(a), "r"(x) : "memory"); }
DEV void ldsm4(uint32_t* r, uint32_t a) { asm volatile("ldmatrix.sync.aligned.m8n8.x4.shared.b16 {%0,%1,%2,%3},[%4];" : "=r"(r[0]), "=r"(r[1]), "=r"(r[2]), "=r"(r[3]) : "r"(a) : "memory"); }
DEV void ldsm4t(uint32_t* r, uint32_t a) { asm volatile("ldmatrix.sync.aligned.m8n8.x4.trans.shared.b16 {%0,%1,%2,%3},[%4];" : "=r"(r[0]), "=r"(r[1]), "=r"(r[2]), "=r"(r[3]) : "r"(a) : "memory"); }
DEV void ldsm2(uint32_t* r, uint32_t a) { asm volatile("ldmatrix.sync.aligned.m8n8.x2.shared.b16 {%0,%1},[%2];" : "=r"(r[0]), "=r"(r[1]) : "r"(a) : "memory"); }
DEV void stsm4t(uint32_t a, uint32_t x, uint32_t y, uint32_t z, uint32_t w) { asm volatile("stmatrix.sync.aligned.m8n8.x4.trans.shared.b16 [%0],{%1,%2,%3,%4};" ::"r"(a), "r"(x), "r"(y), "r"(z), "r"(w) : "memory"); }
DEV void stsm4(uint32_t a, uint32_t x, uint32_t y, uint32_t z, uint32_t w) { asm volatile("stmatrix.sync.aligned.m8n8.x4.shared.b16 [%0],{%1,%2,%3,%4};" ::"r"(a), "r"(x), "r"(y), "r"(z), "r"(w) : "memory"); }
DEV void stsm2(uint32_t a, uint32_t x, uint32_t y) { asm volatile("stmatrix.sync.aligned.m8n8.x2.shared.b16 [%0],{%1,%2};" ::"r"(a), "r"(x), "r"(y) : "memory"); }
DEV void sts128f_if(uint32_t a, const float* v, bool p) {
    asm volatile("{.reg .pred p; setp.ne.u32 p,%5,0; @p st.shared.v4.f32 [%0],{%1,%2,%3,%4};}" ::"r"(a), "f"(v[0]), "f"(v[1]), "f"(v[2]), "f"(v[3]), "r"((uint32_t)p) : "memory");
}
DEV void stsm2t_if(uint32_t a, uint32_t x, uint32_t y, bool p) {
    asm volatile("{.reg .pred p; setp.ne.u32 p,%3,0; @p stmatrix.sync.aligned.m8n8.x2.trans.shared.b16 [%0],{%1,%2};}" ::"r"(a), "r"(x), "r"(y), "r"((uint32_t)p) : "memory");
}
DEV void stsm2t(uint32_t a, uint32_t x, uint32_t y) { asm volatile("stmatrix.sync.aligned.m8n8.x2.trans.shared.b16 [%0],{%1,%2};" ::"r"(a), "r"(x), "r"(y) : "memory"); }
DEV void mma16(float* d, uint32_t a0, uint32_t a1, uint32_t a2, uint32_t a3, uint32_t b0, uint32_t b1) {
    asm volatile("mma.sync.aligned.m16n8k16.row.col.f32.bf16.bf16.f32 {%0,%1,%2,%3},{%4,%5,%6,%7},{%8,%9},{%0,%1,%2,%3};"
                 : "+f"(d[0]), "+f"(d[1]), "+f"(d[2]), "+f"(d[3]) : "r"(a0), "r"(a1), "r"(a2), "r"(a3), "r"(b0), "r"(b1));
}
DEV void mma8(float* d, uint32_t a0, uint32_t a1, uint32_t b0) {
    asm volatile("mma.sync.aligned.m16n8k8.row.col.f32.bf16.bf16.f32 {%0,%1,%2,%3},{%4,%5},{%6},{%0,%1,%2,%3};"
                 : "+f"(d[0]), "+f"(d[1]), "+f"(d[2]), "+f"(d[3]) : "r"(a0), "r"(a1), "r"(b0));
}
DEV u64 mkdesc(uint32_t a, uint32_t lbo, uint32_t sbo) { return (u64)((a & 0x3ffff) >> 4) | ((u64)(lbo >> 4) << 16) | ((u64)(sbo >> 4) << 32); }
constexpr u64 SW128 = 1ull << 62;
DEV void wg_fence() { asm volatile("wgmma.fence.sync.aligned;" ::: "memory"); }
DEV void wg_commit() { asm volatile("wgmma.commit_group.sync.aligned;" ::: "memory"); }
template <int N> DEV void wg_wait() { asm volatile("wgmma.wait_group.sync.aligned %0;" ::"n"(N) : "memory"); }
template <int ACC> DEV void wgmma_n32_rs(float* d, const uint32_t* a, u64 desc) {
    asm volatile("wgmma.mma_async.sync.aligned.m64n32k16.f32.bf16.bf16 {%0,%1,%2,%3,%4,%5,%6,%7,%8,%9,%10,%11,%12,%13,%14,%15},{%16,%17,%18,%19},%20,%21,1,1,0;"
                 : "+f"(d[0]), "+f"(d[1]), "+f"(d[2]), "+f"(d[3]), "+f"(d[4]), "+f"(d[5]), "+f"(d[6]), "+f"(d[7]),
                   "+f"(d[8]), "+f"(d[9]), "+f"(d[10]), "+f"(d[11]), "+f"(d[12]), "+f"(d[13]), "+f"(d[14]), "+f"(d[15])
                 : "r"(a[0]), "r"(a[1]), "r"(a[2]), "r"(a[3]), "l"(desc), "n"(ACC));
}
template <int ACC> DEV void wgmma_n32_ss(float* d, u64 da, u64 desc) {
    asm volatile("wgmma.mma_async.sync.aligned.m64n32k16.f32.bf16.bf16 {%0,%1,%2,%3,%4,%5,%6,%7,%8,%9,%10,%11,%12,%13,%14,%15},%16,%17,%18,1,1,0,0;"
                 : "+f"(d[0]), "+f"(d[1]), "+f"(d[2]), "+f"(d[3]), "+f"(d[4]), "+f"(d[5]), "+f"(d[6]), "+f"(d[7]),
                   "+f"(d[8]), "+f"(d[9]), "+f"(d[10]), "+f"(d[11]), "+f"(d[12]), "+f"(d[13]), "+f"(d[14]), "+f"(d[15])
                 : "l"(da), "l"(desc), "n"(ACC));
}
template <int ACC> DEV void wgmma_n16_ss(float* d, u64 da, u64 desc) {
    asm volatile("wgmma.mma_async.sync.aligned.m64n16k16.f32.bf16.bf16 {%0,%1,%2,%3,%4,%5,%6,%7},%8,%9,%10,1,1,0,0;"
                 : "+f"(d[0]), "+f"(d[1]), "+f"(d[2]), "+f"(d[3]), "+f"(d[4]), "+f"(d[5]), "+f"(d[6]), "+f"(d[7])
                 : "l"(da), "l"(desc), "n"(ACC));
}
#define ACC8(o) "+f"(d[o]), "+f"(d[o + 1]), "+f"(d[o + 2]), "+f"(d[o + 3]), "+f"(d[o + 4]), "+f"(d[o + 5]), "+f"(d[o + 6]), "+f"(d[o + 7])
template <int ACC, int TB> DEV void wgmma_n64_rs(float* d, const uint32_t* a, u64 desc) {
    asm volatile("wgmma.mma_async.sync.aligned.m64n64k16.f32.bf16.bf16 {%0,%1,%2,%3,%4,%5,%6,%7,%8,%9,%10,%11,%12,%13,%14,%15,"
                 "%16,%17,%18,%19,%20,%21,%22,%23,%24,%25,%26,%27,%28,%29,%30,%31},{%32,%33,%34,%35},%36,%37,1,1,%38;"
                 : ACC8(0), ACC8(8), ACC8(16), ACC8(24) : "r"(a[0]), "r"(a[1]), "r"(a[2]), "r"(a[3]), "l"(desc), "n"(ACC), "n"(TB));
}
template <int ACC, int TB> DEV void wgmma_n80_rs(float* d, const uint32_t* a, u64 desc) {
    asm volatile("wgmma.mma_async.sync.aligned.m64n80k16.f32.bf16.bf16 {%0,%1,%2,%3,%4,%5,%6,%7,%8,%9,%10,%11,%12,%13,%14,%15,"
                 "%16,%17,%18,%19,%20,%21,%22,%23,%24,%25,%26,%27,%28,%29,%30,%31,%32,%33,%34,%35,%36,%37,%38,%39},{%40,%41,%42,%43},%44,%45,1,1,%46;"
                 : ACC8(0), ACC8(8), ACC8(16), ACC8(24), ACC8(32) : "r"(a[0]), "r"(a[1]), "r"(a[2]), "r"(a[3]), "l"(desc), "n"(ACC), "n"(TB));
}
template <int TA, int TB> DEV void wgmma_n64_ss(float* d, u64 da, u64 db, int acc) {
    asm volatile("{.reg .pred p; setp.ne.b32 p,%34,0; wgmma.mma_async.sync.aligned.m64n64k16.f32.bf16.bf16 {%0,%1,%2,%3,%4,%5,%6,%7,%8,%9,%10,%11,%12,%13,%14,%15,%16,%17,%18,%19,%20,%21,%22,%23,%24,%25,%26,%27,%28,%29,%30,%31},%32,%33,p,1,1,%35,%36;}"
                 : ACC8(0), ACC8(8), ACC8(16), ACC8(24) : "l"(da), "l"(db), "r"(acc), "n"(TA), "n"(TB));
}
template <int TA, int TB> DEV void wgmma_n128_ss(float* d, u64 da, u64 db, int acc) {
    asm volatile("{.reg .pred p; setp.ne.b32 p,%66,0; wgmma.mma_async.sync.aligned.m64n128k16.f32.bf16.bf16 {%0,%1,%2,%3,%4,%5,%6,%7,%8,%9,%10,%11,%12,%13,%14,%15,%16,%17,%18,%19,%20,%21,%22,%23,%24,%25,%26,%27,%28,%29,%30,%31,%32,%33,%34,%35,%36,%37,%38,%39,%40,%41,%42,%43,%44,%45,%46,%47,%48,%49,%50,%51,%52,%53,%54,%55,%56,%57,%58,%59,%60,%61,%62,%63},%64,%65,p,1,1,%67,%68;}"
                 : ACC8(0), ACC8(8), ACC8(16), ACC8(24), ACC8(32), ACC8(40), ACC8(48), ACC8(56) : "l"(da), "l"(db), "r"(acc), "n"(TA), "n"(TB));
}
template <int TA, int TB> DEV void wgmma_n192_ss(float* d, u64 da, u64 db, int acc) {
    asm volatile("{.reg .pred p; setp.ne.b32 p,%98,0; wgmma.mma_async.sync.aligned.m64n192k16.f32.bf16.bf16 {%0,%1,%2,%3,%4,%5,%6,%7,%8,%9,%10,%11,%12,%13,%14,%15,%16,%17,%18,%19,%20,%21,%22,%23,%24,%25,%26,%27,%28,%29,%30,%31,%32,%33,%34,%35,%36,%37,%38,%39,%40,%41,%42,%43,%44,%45,%46,%47,%48,%49,%50,%51,%52,%53,%54,%55,%56,%57,%58,%59,%60,%61,%62,%63,%64,%65,%66,%67,%68,%69,%70,%71,%72,%73,%74,%75,%76,%77,%78,%79,%80,%81,%82,%83,%84,%85,%86,%87,%88,%89,%90,%91,%92,%93,%94,%95},%96,%97,p,1,1,%99,%100;}"
                 : ACC8(0), ACC8(8), ACC8(16), ACC8(24), ACC8(32), ACC8(40), ACC8(48), ACC8(56), ACC8(64), ACC8(72), ACC8(80), ACC8(88) : "l"(da), "l"(db), "r"(acc), "n"(TA), "n"(TB));
}
template <int ACC> DEV void wgmma_n40_ss(float* d, u64 da, u64 desc) {
    asm volatile("wgmma.mma_async.sync.aligned.m64n40k16.f32.bf16.bf16 {%0,%1,%2,%3,%4,%5,%6,%7,%8,%9,%10,%11,%12,%13,%14,%15,%16,%17,%18,%19},%20,%21,%22,1,1,0,0;"
                 : ACC8(0), ACC8(8), "+f"(d[16]), "+f"(d[17]), "+f"(d[18]), "+f"(d[19]) : "l"(da), "l"(desc), "n"(ACC));
}
DEV void pdl_wait() { asm volatile("griddepcontrol.wait;" ::: "memory"); }
DEV void pdl_launch() { asm volatile("griddepcontrol.launch_dependents;" ::: "memory"); }
DEV uint32_t ldg32(const void* p) { uint32_t v; asm volatile("ld.global.nc.u32 %0,[%1];" : "=r"(v) : "l"(p)); return v; }
DEV void ld_acc(u64& a, u64& b, const void* p) {
    const uint32_t done = (uint32_t)a & (uint32_t)b & 32u;
    asm volatile("{.reg .pred p; setp.eq.u32 p,%3,0;\n"
                 "@p ld.relaxed.gpu.global.v2.u64 {%0,%1},[%2];}" : "+l"(a), "+l"(b) : "l"(p), "r"(done) : "memory");
}
DEV void ld_acc0(u64& a, u64& b, const void* p) {
    asm volatile("ld.relaxed.gpu.global.v2.u64 {%0,%1},[%2];" : "=l"(a), "=l"(b) : "l"(p) : "memory");
}
DEV uint32_t and3(uint32_t a, uint32_t b, uint32_t c) { uint32_t r; asm volatile("lop3.b32 %0,%1,%2,%3,0x80;" : "=r"(r) : "r"(a), "r"(b), "r"(c)); return r; }
DEV uint32_t absmax2(uint32_t a, uint32_t b) { uint32_t r; asm("max.xorsign.abs.bf16x2 %0,%1,%2;" : "=r"(r) : "r"(a), "r"(b)); return r; }
DEV float lds32f(uint32_t a) { float x; asm volatile("ld.shared.f32 %0,[%1];" : "=f"(x) : "r"(a) : "memory"); return x; }
DEV void red_add64(u64* p, uint32_t lo, uint32_t hi) {
    asm volatile("{.reg .b64 v; mov.b64 v,{%1,%2}; red.relaxed.gpu.global.add.u64 [%0],v;}" ::"l"(p), "r"(lo), "r"(hi) : "memory");
}
DEV float bf_round(float x) { return __bfloat162float(__float2bfloat16_rn(x)); }
DEV float bf_lo(uint32_t u) { return __uint_as_float(u << 16); }
DEV float bf_hi(uint32_t u) { return __uint_as_float(u & 0xffff0000u); }

#define GPROF(i, n)
#define PROFT(i)
#define STAMP(i)

DEV void unpack8(float* v, uint4 u) {
    v[0] = bf_lo(u.x); v[1] = bf_hi(u.x); v[2] = bf_lo(u.y); v[3] = bf_hi(u.y);
    v[4] = bf_lo(u.z); v[5] = bf_hi(u.z); v[6] = bf_lo(u.w); v[7] = bf_hi(u.w);
}
DEV int xn_off(int row, int chunk) { return (row >> 5) * 40960 + (chunk >> 3) * 4096 + (row & 31) * 128 + (((chunk ^ row) & 7) << 4); }

DEV void ln_row(float (&v)[3][8], int lane) {
    float s = 0.f;
#pragma unroll
    for (int c = 0; c < 3; c++)
#pragma unroll
        for (int j = 0; j < 8; j++) s += v[c][j];
#pragma unroll
    for (int o = 16; o; o >>= 1) s += __shfl_xor_sync(~0u, s, o);
    float mean = s * (1.f / D_), q = 0.f;
#pragma unroll
    for (int c = 0; c < 3; c++)
        if (c < 2 || lane < 16)
#pragma unroll
            for (int j = 0; j < 8; j++) { float d = v[c][j] - mean; q += d * d; }
#pragma unroll
    for (int o = 16; o; o >>= 1) q += __shfl_xor_sync(~0u, q, o);
    float mb = bf_round(mean);
    float inv = 1.f / bf_round(sqrtf(bf_round(bf_round(q * (1.f / D_)) + 1e-5f)));
#pragma unroll
    for (int c = 0; c < 3; c++)
#pragma unroll
        for (int j = 0; j < 8; j++) v[c][j] = bf_round(v[c][j] - mb) * inv;
}

__host__ __device__ constexpr int col_freq(int c) {
    return c == 320 ? 320 : c < 192 ? (c >> 6) * 128 + (c & 63) : c == 192 ? 192 : c < 256 ? 448 - c : c == 256 ? 64 : 384 - c;
}
DEV float rdft(int n, int k, int sn, int N) {
    float s, c;
    sincospif((float)((n * k) & (N - 1)) * (2.f / N), &s, &c);
    return !sn ? c : k ? s : (n & 1 ? -1.f : 1.f);
}

__global__ void __launch_bounds__(512) prep_kernel(const bf16* __restrict__ x, const bf16* __restrict__ Wq, const bf16* __restrict__ Wk,
                                                   const bf16* __restrict__ Wv, const bf16* __restrict__ Wo) {
    __shared__ float red[32], col[4][640];
    const int tid = threadIdx.x, lane = tid & 31, warp = tid >> 5, b = blockIdx.x, row = b * 16 + warp;
    TLS(0);
    pdl_launch();
    uint4 ux[3], uv[5], uo[8];
#pragma unroll
    for (int c = 0; c < 3; c++) ux[c] = c < 2 || lane < 16 ? *(const uint4*)(x + row * D_ + (c * 32 + lane) * 8) : make_uint4(0, 0, 0, 0);
#pragma unroll
    for (int i = 0; i < 5; i++) uv[i] = *(const uint4*)(Wv + (size_t)((b & 3) * 160 + i * 32 + (tid >> 4)) * 4096 + (b >> 2) * E_ + (tid & 15) * 8);
    if (tid < 320) {
#pragma unroll
        for (int r = 0; r < 8; r++) uo[r] = *(const uint4*)(Wo + (size_t)(b * 32 + tid / 80 * 8 + r) * D_ + tid % 80 * 8);
    }
    if (tid >= 504) prefetch_bulk((const char*)(tid & 4 ? Wk : Wq) + (b * 4 + (tid & 3)) * 10240, 10240);
    if (b < 3) ((uint4*)g_sync)[b * 512 + tid] = make_uint4(0, 0, 0, 0);
    for (int i = b * 512 + tid; i < ACC_LAYER; i += 128 * 512) ((uint4*)g_acc)[i] = make_uint4(0, 0, 0, 0);
    if (tid < 2 * YT_ROWS * D_ / 4 / 128) ((uint4*)g_yt)[b * (2 * YT_ROWS * D_ / 4 / 128) + tid] = make_uint4(0, 0, 0, 0);
    const int gid = tid < 104 ? b * 104 + tid : 1 << 20;
    if (gid < 4096) {
        const int inv = gid >> 11, ks = (gid >> 8) & 7, t = gid & 255, g = (t & 31) >> 2, q = t & 3, tile = t >> 5;
        uint32_t v[4];
#pragma unroll
        for (int j = 0; j < 4; j++) {
            float x[2];
#pragma unroll
            for (int u = 0; u < 2; u++) {
                const int m = inv ? 16 * tile + 2 * g + (j & 1) : 16 * ks + 8 * (j >> 1) + 2 * q + u;
                const int k2 = inv ? 8 * ks + 2 * q + u : 8 * tile + g, sn = inv ? j >> 1 : j & 1;
                x[u] = rdft(m, k2, sn, 128);
                if (sn && k2) x[u] = -x[u];
            }
            v[j] = pack2(x[0], x[1]);
        }
        g_f128[gid] = make_uint4(v[0], v[1], v[2], v[3]);
    } else if (gid < 5120) {
        const int id = gid - 4096, inv = id >> 9, ks = (id >> 7) & 3, t = id & 127, g = (t & 31) >> 2, q = t & 3, tile = t >> 5;
        uint32_t v[4];
#pragma unroll
        for (int j = 0; j < 4; j++) {
            float x[2];
#pragma unroll
            for (int u = 0; u < 2; u++) {
                const int a = inv ? 16 * tile + g + 8 * (j & 1) : 16 * ks + 8 * (j >> 1) + 2 * q + u;
                const int ka = inv ? 8 * ks + 2 * q + u : 8 * tile + g, sn = inv ? j >> 1 : j & 1;
                x[u] = rdft(a, ka, sn, 64);
            }
            v[j] = pack2(x[0], x[1]);
        }
        g_f64[id] = make_uint4(v[0], v[1], v[2], v[3]);
    } else if (gid < 5120 + 8192) {
        const int id = gid - 5120, inv = id >> 12, n = ((id >> 9) & 7) * 8 + ((id >> 3) & 7), k = ((id >> 6) & 7) * 8 + (id & 7);
        float s, c;
        sincospif((float)(((n >> 1) * (k >> 1)) & 31) * (1.f / 16), &s, &c);
        if (inv) s = -s;
        g_g32[id] = __float2bfloat16_rn((n & 1) == (k & 1) ? c : (k & 1) ? s : -s);
    }
    {
        float v[3][8];
#pragma unroll
        for (int c = 0; c < 3; c++) unpack8(v[c], ux[c]);
        ln_row(v, lane);
#pragma unroll
        for (int c = 0; c < 3; c++)
            if (c < 2 || lane < 16)
                *(uint4*)(g_xn + xn_off(row, c * 32 + lane)) =
                    make_uint4(pack2(v[c][0], v[c][1]), pack2(v[c][2], v[c][3]), pack2(v[c][4], v[c][5]), pack2(v[c][6], v[c][7]));
    }
    float sv = 0.f;
#pragma unroll
    for (int i = 0; i < 5; i++) {
        float w[8];
        unpack8(w, uv[i]);
#pragma unroll
        for (int j = 0; j < 8; j++) sv += w[j] * w[j];
    }
    if (tid < 320) {
        float a[8] = {0.f, 0.f, 0.f, 0.f, 0.f, 0.f, 0.f, 0.f};
#pragma unroll
        for (int r = 0; r < 8; r++) {
            float w[8];
            unpack8(w, uo[r]);
#pragma unroll
            for (int j = 0; j < 8; j++) a[j] += w[j] * w[j];
        }
#pragma unroll
        for (int j = 0; j < 8; j++) col[tid / 80][tid % 80 * 8 + j] = a[j];
    }
    __syncthreads();
    float so = (col[0][tid] + col[1][tid]) + (col[2][tid] + col[3][tid]);
    if (tid < 128) so = fmaxf(so, (col[0][512 + tid] + col[1][512 + tid]) + (col[2][512 + tid] + col[3][512 + tid]));
#pragma unroll
    for (int o = 16; o; o >>= 1) { sv += __shfl_xor_sync(~0u, sv, o); so = fmaxf(so, __shfl_xor_sync(~0u, so, o)); }
    if (lane == 0) { red[warp] = sv; red[16 + warp] = so; }
    __syncthreads();
    if (tid == 0) {
        float a = 0.f, c = 0.f;
        for (int i = 0; i < 16; i++) { a += red[i]; c = fmaxf(c, red[16 + i]); }
        g_nrm[b] = a; g_nrm[128 + b] = c;
    }
    TLE(0);
}

DEV void filter_tile(const bf16* __restrict__ wr, const bf16* __restrict__ wi, int ka, int c) {
    const int kn = ka ? 2048 - ka : 32, kc = col_freq(c);
    const unsigned short* pr = (const unsigned short*)wr + kc;
    const unsigned short* pi = (const unsigned short*)wi + kc;
#pragma unroll 1
    for (int i = 0; i < 4; i += 2) {
        unsigned short a[32], b[32];
#pragma unroll
        for (int n = 0; n < 32; n++) {
            const int k = ((n & 1 ? kn : ka) + 64 * (4 * (2 * (i + (n >> 4)) + ((n >> 1) & 1)) + ((n >> 2) & 3))) & 2047;
            a[n] = __ldg(pr + k * NCOL); b[n] = __ldg(pi + k * NCOL);
        }
#pragma unroll
        for (int n = 0; n < 32; n += 4)
            *(uint4*)(g_wt + c * 8192 + (i + (n >> 4)) * 2048 + (ka * 4 + ((n >> 2) & 3)) * 16) =
                make_uint4(a[n] | ((uint32_t)b[n] << 16), a[n + 1] | ((uint32_t)b[n + 1] << 16), a[n + 2] | ((uint32_t)b[n + 2] << 16), a[n + 3] | ((uint32_t)b[n + 3] << 16));
    }
}

namespace wk {
constexpr int STAGE = 49152, NST = 4, OFF_OUT = 3 * STAGE, OFF_RED = 4 * STAGE, OFF_BAR = OFF_RED + 32768, SMEM = OFF_BAR + 128;
constexpr int NPB = 12;
__host__ __device__ constexpr int pb_start(int b) { return b == 0 ? 0 : b == 1 ? 2 : b < NPB ? 6 * b - 6 : 64; }
#define NOB 7
#define SPLIT_A 3
#define SPLIT_B 11
constexpr int N_P = NPB * H_, I_F = N_P, I_OB = I_F + 32, I_OT = I_OB + NOB * 5, I_SA = I_OT + (30 - 3 * NOB) * 10;
constexpr int I_SB = I_SA + 10 * SPLIT_A, N_ITEMS = I_SB + 10 * SPLIT_B;
DEV void ot_decode(int id, int& b, int& nt, int& k0, int& k1) {
    const int base = id < I_SA ? I_OT : id < I_SB ? I_SA : I_SB, j = (id - base) / 10;
    nt = (id - base) % 10;
    if (id < I_SA) { b = 3 * NOB + j; k0 = 0; k1 = 22; }
    else if (id < I_SB) { b = 30; k0 = 22 * j / SPLIT_A; k1 = 22 * (j + 1) / SPLIT_A; }
    else { b = 31; k0 = 22 * j / SPLIT_B; k1 = 22 * (j + 1) / SPLIT_B; }
}
enum { SY_TICKET = 0, SY_O = 32, SY_P = 128 };
}
struct Ring {
    int st; uint32_t ph;
    DEV uint32_t par() const { return (ph >> st) & 1; }
    DEV void next(int n) { ph ^= 1u << st; st = st + 1 >= n ? 0 : st + 1; }
};
struct Maps { CUtensorMap wq2, wv1, wo2, wo1, x6, x2, o6, o2; const bf16 *wr, *wi; };

template <int NSG> DEV void proj_tile(uint32_t sb, uint32_t bar, Ring& rg, int wg, int id) {
    using namespace wk;
    float acc[NSG * 16];
#pragma unroll
    for (int i = 0; i < NSG * 16; i++) acc[i] = 0.f;
    const int lane = threadIdx.x & 31, ww = (threadIdx.x >> 5) & 3;
    for (int kb = 0; kb < 10; kb++, rg.next(3)) {
        const int st = rg.st;
        if (kb) mbar_wait(bar + 8 * st, rg.par());
        const u64 da = mkdesc(sb + st * STAGE + wg * 8192, 0, 1024) | SW128, db = mkdesc(sb + st * STAGE + 24576, 0, 1024) | SW128;
        wg_fence();
#pragma unroll
        for (int ks = 0; ks < 4; ks++) {
            if (NSG == 2) wgmma_n64_ss<1, 0>(acc, da + ks * 128, db + ks * 2, 1);
            if (NSG == 4) wgmma_n128_ss<1, 0>(acc, da + ks * 128, db + ks * 2, 1);
            if (NSG == 6) wgmma_n192_ss<1, 0>(acc, da + ks * 128, db + ks * 2, 1);
        }
        wg_commit();
        wg_wait<0>();
        mbar_arrive_elect(bar + 8 * (NST + st));
    }
    const uint32_t out = sb + OFF_OUT + wg * 24576;
    bar_sync(5 + wg, 160);
    const uint32_t la = out + (wg < 2 ? (lane >> 4) * 1024 + ww * 256 + (lane & 15) * 16 : ww * 1024 + ((lane >> 3) & 1) * 512 + (lane >> 4) * 128 + (lane & 7) * 16);
#pragma unroll
    for (int j = 0; j < 2 * NSG; j++) {
        const float* c = acc + 8 * j;
        const uint32_t p0 = pack2(c[0], c[1]), p1 = pack2(c[2], c[3]), p2 = pack2(c[4], c[5]), p3 = pack2(c[6], c[7]);
        if (wg < 2) stsm4t(la + j * 2048, p0, p1, p2, p3);
        else stsm4(la + (j >> 1) * 4096 + (j & 1) * 256, p0, p1, p2, p3);
    }
    if ((threadIdx.x & 127) == 0) sts32(bar + 80 + 4 * wg, id);
    fence_async();
    bar_arrive(1 + wg, 160);
}

DEV uint32_t resid(uint32_t u, float a, float b) { return pack2(bf_lo(u) + bf_round(a), bf_hi(u) + bf_round(b)); }

DEV void worker(uint32_t sb, const Maps& maps, const bf16* __restrict__ x, bf16* __restrict__ x1, int layer) {
    using namespace wk;
    const uint32_t bar = sb + OFF_BAR, slot = bar + 64;
    const int tid = threadIdx.x, lane = tid & 31, warp = __shfl_sync(~0u, tid >> 5, 0);
    uint32_t* sy = g_sync + layer * SYNC_LAYER;
    if (tid == 0) {
        for (int i = 0; i < NST; i++) { mbar_init(bar + 8 * i, 1); mbar_init(bar + 8 * (NST + i), 12); }
        asm volatile("fence.mbarrier_init.release.cluster;" ::: "memory");
    }
    __syncthreads();
    if (warp > 12) {
        const int wg = warp - 13;
        bar_arrive(5 + wg, 160);
        for (;;) {
            bar_sync(1 + wg, 160);
            const int id = (int)lds32(bar + 80 + 4 * wg);
            if (id < 0) break;
            const int s0 = pb_start(id >> 5), ns = pb_start((id >> 5) + 1) - s0;
            if (lane == 0) {
                for (int j = 0; j < ns; j++)
                    bulk_s2g(g_p + (size_t)(((s0 + j) * H_ + (id & 31)) * 3 + wg) * 4096, sb + OFF_OUT + wg * 24576 + j * 4096, 4096);
                bulk_commit();
                bulk_wait<0>();
                flag_add(sy + SY_P + id);
            }
            __syncwarp();
            bar_arrive(5 + wg, 160);
        }
    } else if (warp == 12) {
        if (lane == 0) {
            Ring rg = {0, 7u};
            auto acquire = [&]() { mbar_wait(bar + 8 * (NST + rg.st), rg.par()); return sb + rg.st * STAGE; };
            for (;;) {
                int id = (int)atomicAdd(sy + SY_TICKET, 1u);
                if (layer && id >= I_F) id += I_OB - I_F;
                if (id >= N_ITEMS) id = -1;
                if (id >= 0) { TLI(id, 0, gtime()); TLI(id, 3, blockIdx.x + (gridDim.x % 3 == 0 && gridDim.x > 111 ? 0 : 1000)); }
                uint32_t d = acquire();
                sts32(slot + 4 * rg.st, id);
                if (id < 0) { mbar_arrive(bar + 8 * rg.st); break; }
                if (id < N_P) {
                    const int b = id >> 5, h = id & 31, s0 = pb_start(b), ns = pb_start(b + 1) - s0;
                    for (int kb = 0; kb < 10; kb++, rg.next(3)) {
                        if (kb) d = acquire();
                        const uint32_t fb = bar + 8 * rg.st;
                        mbar_expect(fb, 24576 + ns * 4096);
                        tma3d(d, &maps.wq2, 0, kb * 64, 2 * h, fb);
                        tma3d(d + 16384, &maps.wv1, 0, kb * 64, 2 * h, fb);
                        if (ns == 6) tma3d(d + 24576, &maps.x6, 0, 2 * kb, s0, fb);
                        else for (int j = 0; j < ns; j += 2) tma3d(d + 24576 + j * 4096, &maps.x2, 0, 2 * kb, s0 + j, fb);
                    }
                } else if (id < I_OB) {
                    mbar_arrive(bar + 8 * rg.st);
                    mbar_wait(bar + 8 * (NST + rg.st), rg.par() ^ 1);
                    rg.next(NST);
                } else if (id < I_OT) {
                    const int b = (id - I_OB) / 5, nt = (id - I_OB) % 5;
                    for (int j = 0; j < 6; j++) flag_wait(sy + SY_O + 6 * b + j, 64);
                    for (int kb = 0; kb < 64; kb++, rg.next(NST)) {
                        if (kb) d = acquire();
                        const uint32_t fb = bar + 8 * rg.st;
                        mbar_expect(fb, 40960);
                        tma3d(d, &maps.o6, 0, 2 * kb, 6 * b, fb);
                        tma3d(d + 24576, &maps.wo2, 0, kb * 64, 2 * nt, fb);
                    }
                } else {
                    int b, nt, k0, k1;
                    ot_decode(id, b, nt, k0, k1);
                    for (int kb = k0; kb < k1; kb++, rg.next(NST)) {
                        if (kb > k0) d = acquire();
                        const uint32_t fb = bar + 8 * rg.st;
                        mbar_expect(fb, 49152);
                        tma3d(d + 24576, &maps.wo1, 0, 3 * kb * 64, nt, fb);
                        if (kb == k0) for (int j = 0; j < 2; j++) flag_wait(sy + SY_O + 2 * b + j, 64);
                        for (int u = 0; u < 3; u++) tma3d(d + u * 8192, &maps.o2, 0, 2 * (3 * kb + u), 2 * b, fb);
                    }
                }
            }
        }
    } else {
        const int wg = warp >> 2, g = lane >> 2, q = lane & 3;
        Ring rg = {0, 0u};
        bool stores_done = false;
        for (;;) {
            mbar_wait(bar + 8 * rg.st, rg.par());
            const int id = (int)lds32(slot + 4 * rg.st);
            if ((id < 0 || id >= N_P) && !stores_done) {
                bar_sync(5 + wg, 160);
                if ((tid & 127) == 0) sts32(bar + 80 + 4 * wg, ~0u);
                bar_arrive(1 + wg, 160);
                stores_done = true;
                bar_sync(4, 384);
                mbar_arrive_elect(bar + 8 * (NST + 3));
            }
            if (id < 0) break;
            if (tid == 0) TLI(id, 1, gtime());
            if (id < N_P) {
                const int b = id >> 5;
                if (b == 0) proj_tile<2>(sb, bar, rg, wg, id);
                else if (b == 1 || b == NPB - 1) proj_tile<4>(sb, bar, rg, wg, id);
                else proj_tile<6>(sb, bar, rg, wg, id);
            } else if (id < I_OB) {
                if (tid < NCOL) filter_tile(maps.wr, maps.wi, id - I_F, tid);
                __syncwarp();
                mbar_arrive_elect(bar + 8 * (NST + rg.st));
                rg.next(NST);
            } else if (id < I_OT) {
                const int b = (id - I_OB) / 5, nt = (id - I_OB) % 5;
                const size_t o = (size_t)(192 * b + 16 * warp + g) * D_ + nt * 128 + 2 * q;
                float acc[64];
#pragma unroll
                for (int i = 0; i < 64; i++) acc[i] = 0.f;
                for (int kb = 0; kb < 64; kb++, rg.next(NST)) {
                    const int st = rg.st;
                    if (kb) mbar_wait(bar + 8 * st, rg.par());
                    const u64 da = mkdesc(sb + st * STAGE + wg * 8192, 128, 1024), db = mkdesc(sb + st * STAGE + 24576, 8192, 1024) | SW128;
                    wg_fence();
#pragma unroll
                    for (int ks = 0; ks < 4; ks++) wgmma_n128_ss<0, 1>(acc, da + ks * 16, db + ks * 128, 1);
                    wg_commit();
                    wg_wait<0>();
                    mbar_arrive_elect(bar + 8 * (NST + st));
                }
                uint32_t xr[32];
#pragma unroll
                for (int t = 0; t < 32; t++) xr[t] = ldg32(x + o + 8 * (t >> 1) + (t & 1) * 8 * D_);
#pragma unroll
                for (int t = 0; t < 32; t++) *(uint32_t*)(x1 + o + 8 * (t >> 1) + (t & 1) * 8 * D_) = resid(xr[t], acc[2 * t], acc[2 * t + 1]);
            } else {
                int b, nt, k0, k1;
                ot_decode(id, b, nt, k0, k1);
                const size_t o = (size_t)(64 * b + 16 * (warp & 3) + g) * D_ + nt * 64 + 2 * q;
                float acc[32];
                uint32_t xr[16];
#pragma unroll
                for (int t = 0; t < 16; t++) xr[t] = wg == 0 && id < I_SA ? ldg32(x + o + 8 * (t >> 1) + (t & 1) * 8 * D_) : 0;
#pragma unroll
                for (int i = 0; i < 32; i++) acc[i] = 0.f;
                for (int kb = k0; kb < k1; kb++, rg.next(NST)) {
                    const int st = rg.st;
                    if (kb > k0) mbar_wait(bar + 8 * st, rg.par());
                    const u64 da = mkdesc(sb + st * STAGE + wg * 8192, 128, 1024), db = mkdesc(sb + st * STAGE + 24576 + wg * 8192, 0, 1024) | SW128;
                    wg_fence();
#pragma unroll
                    for (int ks = 0; ks < 4; ks++) wgmma_n64_ss<0, 1>(acc, da + ks * 16, db + ks * 128, 1);
                    wg_commit();
                    wg_wait<0>();
                    mbar_arrive_elect(bar + 8 * (NST + st));
                }
                const uint32_t ra = sb + OFF_RED + (tid & 127) * 16;
                if (wg) {
#pragma unroll
                    for (int t = 0; t < 8; t++)
                        sts128(ra + (wg - 1) * 16384 + t * 2048, __float_as_uint(acc[4 * t]), __float_as_uint(acc[4 * t + 1]), __float_as_uint(acc[4 * t + 2]), __float_as_uint(acc[4 * t + 3]));
                }
                bar_sync(4, 384);
                if (wg == 0) {
#pragma unroll
                    for (int t = 0; t < 8; t++) {
                        float u[4], v[4];
                        lds128f(u, ra + t * 2048); lds128f(v, ra + 16384 + t * 2048);
#pragma unroll
                        for (int i = 0; i < 4; i++) acc[4 * t + i] += u[i] + v[i];
                    }
                }
                bar_sync(4, 384);
                if (wg == 0) {
                    if (id < I_SA) {
#pragma unroll
                        for (int t = 0; t < 16; t++) *(uint32_t*)(x1 + o + 8 * (t >> 1) + (t & 1) * 8 * D_) = resid(xr[t], acc[2 * t], acc[2 * t + 1]);
                    } else {
                        float* y = g_yt + (layer * YT_ROWS - (S_ - YT_ROWS)) * D_ + o;
#pragma unroll
                        for (int t = 0; t < 16; t++)
                            asm volatile("red.relaxed.gpu.global.add.v2.f32 [%0],{%1,%2};" ::"l"(y + 8 * (t >> 1) + (t & 1) * 8 * D_), "f"(acc[2 * t]), "f"(acc[2 * t + 1]) : "memory");
                    }
                }
            }
            if (tid == 0) TLI(id, 2, gtime());
        }
    }
}

__global__ void __launch_bounds__(512, 1) side_kernel(const __grid_constant__ Maps maps, const bf16* __restrict__ x, bf16* __restrict__ x1, int layer) {
    extern __shared__ __align__(1024) unsigned char smem[];
    pdl_launch();
    TLS(3 + 5 * layer);
    worker(s2u(smem), maps, x, x1, layer);
    __syncwarp();
    pdl_wait();
    TLE(3 + 5 * layer);
}

constexpr float C5A = 0.30901699437494742f, C5B = -0.80901699437494742f, S5A = 0.95105651629515357f, S5B = 0.58778525229247313f;
template <int SGN> DEV void dft5(const float (&tr)[5], const float (&ti)[5], float (&zr)[5], float (&zi)[5]) {
    const float ar = tr[1] + tr[4], ai = ti[1] + ti[4], br = tr[2] + tr[3], bi = ti[2] + ti[3];
    const float cr = tr[1] - tr[4], ci = ti[1] - ti[4], dr = tr[2] - tr[3], di = ti[2] - ti[3];
    zr[0] = tr[0] + ar + br; zi[0] = ti[0] + ai + bi;
    const float m1r = tr[0] + C5A * ar + C5B * br, m1i = ti[0] + C5A * ai + C5B * bi;
    const float m2r = tr[0] + C5B * ar + C5A * br, m2i = ti[0] + C5B * ai + C5A * bi;
    const float n1r = SGN * (S5A * cr + S5B * dr), n1i = SGN * (S5A * ci + S5B * di);
    const float n2r = SGN * (S5B * cr - S5A * dr), n2i = SGN * (S5B * ci - S5A * di);
    zr[1] = m1r + n1i; zi[1] = m1i - n1r; zr[4] = m1r - n1i; zi[4] = m1i + n1r;
    zr[2] = m2r + n2i; zi[2] = m2i - n2r; zr[3] = m2r - n2i; zi[3] = m2i + n2r;
}
DEV void ln40(float (&v)[40]) {
    float s = 0.f;
#pragma unroll
    for (int i = 0; i < 40; i++) s += v[i];
#pragma unroll
    for (int o = 8; o; o >>= 1) s += __shfl_xor_sync(~0u, s, o);
    const float mean = s * (1.f / D_);
    float q = 0.f;
#pragma unroll
    for (int i = 0; i < 40; i++) { const float d = v[i] - mean; q += d * d; }
#pragma unroll
    for (int o = 8; o; o >>= 1) q += __shfl_xor_sync(~0u, q, o);
    const float mb = bf_round(mean);
    const float inv = 1.f / bf_round(sqrtf(bf_round(bf_round(q * (1.f / D_)) + 1e-5f)));
#pragma unroll
    for (int i = 0; i < 40; i++) v[i] = bf_round(v[i] - mb) * inv;
}
__global__ void __launch_bounds__(256) rowfft_kernel(const bf16* __restrict__ x0, bf16* __restrict__ x, const bf16* __restrict__ Wq,
                                                     const bf16* __restrict__ Wk, const bf16* __restrict__ Wv, int layer) {
    extern __shared__ __align__(1024) unsigned char smem[];
    const uint32_t sb = s2u(smem), sx = sb + 23552, sy = sx + 20480, bar = sy + 40960;
    const int tid = threadIdx.x, lane = tid & 31, q = lane & 3, blk = blockIdx.x, k2 = tid >> 2;
    if (tid == 0) TLI(800 + blk, 0, gtime());
    float twr[5], twi[5];
#pragma unroll
    for (int r = 1; r < 5; r++) { sincospif((float)(r * k2) * (-1.f / 320), &twi[r], &twr[r]); }
    uint32_t f[8][4];
#pragma unroll
    for (int ks = 0; ks < 8; ks++) { const uint4 u = g_f128[ks * 256 + tid]; f[ks][0] = u.x; f[ks][1] = u.y; f[ks][2] = u.z; f[ks][3] = u.w; }
    const bool split = blk * 16 >= S_ - YT_ROWS;
    if (tid == 0) {
        mbar_init(bar, 1);
        asm volatile("fence.mbarrier_init.release.cluster;" ::: "memory");
        mbar_expect(bar, split ? 61440 : 20480);
        if (split) bulk_g2s(sx, x0 + (size_t)blk * 16 * D_, 20480, bar);
    }
    __syncthreads();
    pdl_wait();
    pdl_launch();
    TLS(4 + 5 * layer);
    if (tid == 0) TLI(800 + blk, 1, gtime());
    if (tid == 0) {
        if (split) bulk_g2s(sy, g_yt + (layer * YT_ROWS + blk * 16 - (S_ - YT_ROWS)) * D_, 40960, bar);
        else bulk_g2s(sx, x + (size_t)blk * 16 * D_, 20480, bar);
    }
    mbar_wait(bar, 0);
    {
        const int rho = tid >> 4, j = tid & 15;
        float v[40];
#pragma unroll
        for (int i = 0; i < 5; i++) {
            uint32_t u[4];
            lds128(u, sx + tid * 80 + i * 16);
            if (split) {
                float p[8];
                lds128f(p, sy + tid * 160 + i * 32); lds128f(p + 4, sy + tid * 160 + i * 32 + 16);
#pragma unroll
                for (int k = 0; k < 4; k++) u[k] = resid(u[k], p[2 * k], p[2 * k + 1]);
                sts128(sx + tid * 80 + i * 16, u[0], u[1], u[2], u[3]);
            }
            unpack8(v + 8 * i, make_uint4(u[0], u[1], u[2], u[3]));
        }
        if (layer == 0 && tid < 12) prefetch_bulk((const char*)(tid < 4 ? Wk : tid < 8 ? Wq : Wv) + (blk * 4 + (tid & 3)) * 10240, 10240);
        ln40(v);
        const uint32_t a = sb + ((rho >> 1) & 1) * 2304 + j * 144 + (2 * (rho >> 2) + (rho & 1)) * 16;
#pragma unroll
        for (int r = 0; r < 5; r++)
            sts128(a + r * 4608, pack2(v[r], v[5 + r]), pack2(v[10 + r], v[15 + r]), pack2(v[20 + r], v[25 + r]), pack2(v[30 + r], v[35 + r]));
    }
    fence_async();
    __syncthreads();
    if (tid == 0) TLI(800 + blk, 2, gtime());
    if (tid == 0 && split) { bulk_s2g(x + (size_t)blk * 16 * D_, sx, 20480); bulk_commit(); }
    float acc[40];
    const u64 db = mkdesc(sb, 144, 2304);
    wg_fence();
    wgmma_n80_rs<0, 0>(acc, f[0], db);
#pragma unroll
    for (int ks = 1; ks < 8; ks++) wgmma_n80_rs<1, 0>(acc, f[ks], db + ks * 18);
    wg_commit();
    wg_wait<0>();
    unsigned char* zp = g_z + (blk >> 1) * 128 + ((((blk & 1) * 4 + q) ^ ((blk >> 1) & 7)) << 4);
    uint32_t o[5][4];
#pragma unroll
    for (int u = 0; u < 4; u++) {
        float tr[5], ti[5], zr[5], zi[5];
#pragma unroll
        for (int r = 0; r < 5; r++) {
            const float yr = acc[8 * r + 4 * (u >> 1) + (u & 1)], yi = k2 ? acc[8 * r + 4 * (u >> 1) + 2 + (u & 1)] : 0.f;
            tr[r] = r ? yr * twr[r] - yi * twi[r] : yr;
            ti[r] = r ? yr * twi[r] + yi * twr[r] : yi;
        }
        dft5<1>(tr, ti, zr, zi);
#pragma unroll
        for (int j = 0; j < 5; j++) o[j][u] = pack2(zr[j], j < 3 ? zi[j] : -zi[j]);
    }
#pragma unroll
    for (int j = 0; j < 5; j++)
        if (j < 3 || k2) *(uint4*)(zp + (64 * j + k2) * 8192) = make_uint4(o[j][0], o[j][1], o[j][2], o[j][3]);
    if (k2 == 0) {
#pragma unroll
        for (int u = 0; u < 4; u++) {
            float tr[5], ti[5], zr[5], zi[5];
            const float cr[5] = {1.f, -C5B, C5A, -C5A, C5B}, ci[5] = {0.f, -S5B, -S5A, -S5A, -S5B};
#pragma unroll
            for (int r = 0; r < 5; r++) { const float y = acc[8 * r + 4 * (u >> 1) + 2 + (u & 1)]; tr[r] = y * cr[r]; ti[r] = y * ci[r]; }
            dft5<1>(tr, ti, zr, zi);
            o[0][u] = pack2(zr[0], zi[0]); o[1][u] = pack2(zr[1], zi[1]); o[2][u] = pack2(zr[2], 0.f);
        }
        *(uint4*)(zp + 256 * 8192) = make_uint4(o[0][0], o[0][1], o[0][2], o[0][3]);
        *(uint4*)(zp + 192 * 8192) = make_uint4(o[1][0], o[1][1], o[1][2], o[1][3]);
        *(uint4*)(zp + 320 * 8192) = make_uint4(o[2][0], o[2][1], o[2][2], o[2][3]);
    }
    if (tid == 0) bulk_wait<0>();
    TLE(4 + 5 * layer);
    if (tid == 0) TLI(800 + blk, 3, gtime());
}

constexpr int CF_SMEM = 16384 + 3 * 16384 + 64;
__global__ void __launch_bounds__(384) colfft_kernel(int layer) {
    extern __shared__ __align__(1024) unsigned char smem[];
    const uint32_t sb = s2u(smem), bar = sb + 65536;
    const int tid = threadIdx.x, lane = tid & 31, q = lane & 3, wg = __shfl_sync(~0u, tid >> 7, 0), t = tid & 127, ka = t >> 2;
    const int col = blockIdx.x * 3 + wg;
    const uint32_t d0 = sb + 16384 + wg * 16384, d1 = d0 + 8192;
    if (tid == 0) {
        for (int i = 0; i < 4; i++) mbar_init(bar + 8 * i, 1);
        asm volatile("fence.mbarrier_init.release.cluster;" ::: "memory");
    }
    float twr[8], twi[8];
#pragma unroll
    for (int i = 0; i < 8; i++) sincospif((float)((4 * i + q) * (ka ? ka : -32)) * (1.f / 1024), &twi[i], &twr[i]);
    __syncthreads();
    if (tid == 0) { mbar_expect(bar + 24, 16384); bulk_g2s(sb, g_g32, 16384, bar + 24); }
    uint32_t f[4][4], w[16];
#pragma unroll
    for (int ks = 0; ks < 4; ks++) { const uint4 u = g_f64[ks * 128 + t]; f[ks][0] = u.x; f[ks][1] = u.y; f[ks][2] = u.z; f[ks][3] = u.w; }
#pragma unroll
    for (int i = 0; i < 4; i++) { const uint4 u = *(const uint4*)(g_wt + col * 8192 + i * 2048 + t * 16); w[4 * i] = u.x; w[4 * i + 1] = u.y; w[4 * i + 2] = u.z; w[4 * i + 3] = u.w; }
    pdl_wait();
    pdl_launch();
    TLS(5 + 5 * layer);
    if (t == 0) {
        mbar_expect(bar + 8 * wg, 8192);
        bulk_g2s(d0, g_z + col * 8192, 8192, bar + 8 * wg);
    }
    float acc[32];
    uint32_t a[4][4];
    mbar_wait(bar + 8 * wg, 0);
    {
        const u64 db = mkdesc(d0, 0, 1024) | SW128;
        wg_fence();
        wgmma_n64_rs<0, 1>(acc, f[0], db);
#pragma unroll
        for (int ks = 1; ks < 4; ks++) wgmma_n64_rs<1, 1>(acc, f[ks], db + ks * 128);
        wg_commit();
        wg_wait<0>();
    }
#pragma unroll
    for (int ks = 0; ks < 4; ks++) { const uint4 u = g_f64[512 + ks * 128 + t]; f[ks][0] = u.x; f[ks][1] = u.y; f[ks][2] = u.z; f[ks][3] = u.w; }
#pragma unroll
    for (int i = 0; i < 8; i++) {
        const float c0 = acc[4 * i], c1 = acc[4 * i + 1], c2 = acc[4 * i + 2], c3 = acc[4 * i + 3];
        const float pr = c0 + c3, pi = c1 - c2, nr = ka ? c0 - c3 : c2, ni = ka ? c1 + c2 : c3;
        a[i >> 1][2 * (i & 1)] = ka ? pack2(pr * twr[i] + pi * twi[i], pi * twr[i] - pr * twi[i]) : pack2(c0, c1);
        a[i >> 1][2 * (i & 1) + 1] = pack2(nr * twr[i] - ni * twi[i], ni * twr[i] + nr * twi[i]);
    }
    mbar_wait(bar + 24, 0);
    {
        const u64 db = mkdesc(sb, 128, 1024);
        wg_fence();
        wgmma_n64_rs<0, 0>(acc, a[0], db);
#pragma unroll
        for (int ks = 1; ks < 4; ks++) wgmma_n64_rs<1, 0>(acc, a[ks], db + ks * 16);
        wg_commit();
        wg_wait<0>();
    }
    constexpr float NORM = 1.f / (2048.f * 640.f);
#pragma unroll
    for (int i = 0; i < 16; i++) {
        const float zr = acc[2 * i] * NORM, zi = acc[2 * i + 1] * NORM, wr = bf_lo(w[i]), wi = bf_hi(w[i]);
        a[i >> 2][i & 3] = pack2(zr * wr - zi * wi, zr * wi + zi * wr);
    }
    {
        const u64 db = mkdesc(sb + 8192, 128, 1024);
        wg_fence();
        wgmma_n64_rs<0, 0>(acc, a[0], db);
#pragma unroll
        for (int ks = 1; ks < 4; ks++) wgmma_n64_rs<1, 0>(acc, a[ks], db + ks * 16);
        wg_commit();
        wg_wait<0>();
    }
    const uint32_t row = (t >> 5) * 2048 + (lane & 15) * 128;
#pragma unroll
    for (int i = 0; i < 8; i++) {
        const float c0 = acc[4 * i], c1 = acc[4 * i + 1], c2 = acc[4 * i + 2], c3 = acc[4 * i + 3];
        const float pr = c0 * twr[i] - c1 * twi[i], pi = c1 * twr[i] + c0 * twi[i];
        const float nr = c2 * twr[i] + c3 * twi[i], ni = c3 * twr[i] - c2 * twi[i];
        a[i >> 1][2 * (i & 1)] = ka ? pack2(pr + nr, pi + ni) : pack2(c0, c1);
        a[i >> 1][2 * (i & 1) + 1] = ka ? pack2(ni - pi, pr - nr) : pack2(nr, ni);
    }
#pragma unroll
    for (int i = 0; i < 4; i++) stsm4(d1 + row + (((2 * i + (lane >> 4)) ^ (lane & 7)) << 4), a[i][0], a[i][1], a[i][2], a[i][3]);
    fence_async();
    bar_sync(1 + wg, 128);
    {
        const u64 db = mkdesc(d1, 0, 1024) | SW128;
        wg_fence();
        wgmma_n64_rs<0, 1>(acc, f[0], db);
#pragma unroll
        for (int ks = 1; ks < 4; ks++) wgmma_n64_rs<1, 1>(acc, f[ks], db + ks * 128);
        wg_commit();
        wg_wait<0>();
    }
#pragma unroll
    for (int i = 0; i < 4; i++)
        stsm4(d0 + row + (((2 * i + (lane >> 4)) ^ (lane & 7)) << 4), pack2(acc[8 * i], acc[8 * i + 1]), pack2(acc[8 * i + 2], acc[8 * i + 3]),
              pack2(acc[8 * i + 4], acc[8 * i + 5]), pack2(acc[8 * i + 6], acc[8 * i + 7]));
    fence_async();
    bar_sync(1 + wg, 128);
    if (t == 0) {
        bulk_s2g(g_z + col * 8192, d0, 8192);
        asm volatile("cp.async.bulk.commit_group;" ::: "memory");
        asm volatile("cp.async.bulk.wait_group 0;" ::: "memory");
    }
    TLE(5 + 5 * layer);
}

__global__ void __launch_bounds__(256) rowifft_kernel(const bf16* __restrict__ x, bf16* __restrict__ out, int last) {
    extern __shared__ __align__(1024) unsigned char smem[];
    const uint32_t sb = s2u(smem), sx = sb + 20480, sy = sx + 20480, bar = sy + 16 * 1296;
    const int tid = threadIdx.x, lane = tid & 31, q = lane & 3, blk = blockIdx.x, k2 = tid >> 2, warp = tid >> 5;
    float twr[5], twi[5];
#pragma unroll
    for (int r = 1; r < 5; r++) { sincospif((float)(r * k2) * (1.f / 320), &twi[r], &twr[r]); twr[r] *= 2.f; twi[r] *= 2.f; }
    uint32_t f[8][4];
#pragma unroll
    for (int ks = 0; ks < 8; ks++) { const uint4 u = g_f128[2048 + ks * 256 + tid]; f[ks][0] = u.x; f[ks][1] = u.y; f[ks][2] = u.z; f[ks][3] = u.w; }
    if (tid == 0) {
        mbar_init(bar, 1);
        asm volatile("fence.mbarrier_init.release.cluster;" ::: "memory");
        mbar_expect(bar, 20480);
        bulk_g2s(sx, x + (size_t)blk * 16 * D_, 20480, bar);
    }
    pdl_wait();
    pdl_launch();
    TLS(6 + 5 * last);
    const unsigned char* zp = g_z + (blk >> 1) * 128 + ((((blk & 1) * 4 + q) ^ ((blk >> 1) & 7)) << 4);
    uint4 z[6];
#pragma unroll
    for (int j = 0; j < 5; j++) z[j] = *(const uint4*)(zp + (64 * j + k2) * 8192);
    z[5] = k2 ? make_uint4(0, 0, 0, 0) : *(const uint4*)(zp + 320 * 8192);
    float acc[40];
#pragma unroll
    for (int u = 0; u < 4; u++) {
        float yr[6], yi[6], tr[5], ti[5], zr[5], zi[5];
#pragma unroll
        for (int j = 0; j < 6; j++) { const uint32_t v = u == 0 ? z[j].x : u == 1 ? z[j].y : u == 2 ? z[j].z : z[j].w; yr[j] = bf_lo(v); yi[j] = bf_hi(v); }
#pragma unroll
        for (int j = 0; j < 5; j++) { tr[j] = yr[j]; ti[j] = j < 3 ? yi[j] : -yi[j]; }
        dft5<-1>(tr, ti, zr, zi);
        const float c1[5] = {1.f, C5A, C5B, C5B, C5A}, s1[5] = {0.f, S5A, S5B, -S5B, -S5A};
        const float c2[5] = {1.f, C5B, C5A, C5A, C5B}, s2[5] = {0.f, S5B, -S5A, S5A, -S5B};
        const float c3[5] = {1.f, -C5B, C5A, -C5A, C5B}, s3[5] = {0.f, S5B, S5A, S5A, S5B};
        const float c4[5] = {1.f, -C5A, C5B, -C5B, C5A}, s4[5] = {0.f, S5A, -S5B, -S5B, S5A};
#pragma unroll
        for (int r = 0; r < 5; r++) {
            float er = r ? zr[r] * twr[r] - zi[r] * twi[r] : 2.f * zr[0], ei = r ? zr[r] * twi[r] + zi[r] * twr[r] : 2.f * zi[0];
            if (k2 == 0) {
                er = yr[0] + 2.f * (yr[1] * c1[r] - yi[1] * s1[r] + yr[2] * c2[r] - yi[2] * s2[r]);
                ei = (r & 1 ? -yr[5] : yr[5]) + 2.f * (yr[4] * c3[r] - yi[4] * s3[r] + yr[3] * c4[r] - yi[3] * s4[r]);
            }
            acc[8 * r + 4 * (u >> 1) + (u & 1)] = er;
            acc[8 * r + 4 * (u >> 1) + 2 + (u & 1)] = ei;
        }
    }
#pragma unroll
    for (int r = 0; r < 5; r++)
        stsm4(sb + (2 * warp + ((lane >> 3) & 1)) * 1280 + (2 * r + (lane >> 4)) * 128 + (lane & 7) * 16, pack2(acc[8 * r], acc[8 * r + 1]),
              pack2(acc[8 * r + 2], acc[8 * r + 3]), pack2(acc[8 * r + 4], acc[8 * r + 5]), pack2(acc[8 * r + 6], acc[8 * r + 7]));
    fence_async();
    __syncthreads();
    const u64 db = mkdesc(sb, 1280, 128);
    wg_fence();
    wgmma_n80_rs<0, 1>(acc, f[0], db);
#pragma unroll
    for (int ks = 1; ks < 8; ks++) wgmma_n80_rs<1, 1>(acc, f[ks], db + ks * 160);
    wg_commit();
    wg_wait<0>();
#pragma unroll
    for (int u = 0; u < 4; u++) {
        float e[10];
#pragma unroll
        for (int r = 0; r < 5; r++) { e[r] = acc[8 * r + 4 * (u >> 1) + (u & 1)]; e[5 + r] = acc[8 * r + 4 * (u >> 1) + 2 + (u & 1)]; }
#pragma unroll
        for (int i = 0; i < 5; i++) sts32(sy + (4 * q + u) * 1296 + k2 * 20 + i * 4, pack2(e[2 * i], e[2 * i + 1]));
    }
    __syncthreads();
    const int rho = tid >> 4, j = tid & 15;
    float v[40];
    mbar_wait(bar, 0);
#pragma unroll
    for (int i = 0; i < 5; i++) {
        uint32_t y[4], u[4];
        lds128(y, sy + rho * 1296 + j * 80 + i * 16);
        lds128(u, sx + tid * 80 + i * 16);
#pragma unroll
        for (int k = 0; k < 4; k++) u[k] = pack2(bf_lo(u[k]) + bf_lo(y[k]), bf_hi(u[k]) + bf_hi(y[k]));
        sts128(sx + tid * 80 + i * 16, u[0], u[1], u[2], u[3]);
        unpack8(v + 8 * i, make_uint4(u[0], u[1], u[2], u[3]));
    }
    if (!last) {
        ln40(v);
#pragma unroll
        for (int i = 0; i < 5; i++) {
            const int c = j * 5 + i;
            sts128(sb + (c >> 3) * 2048 + rho * 128 + (((c ^ rho) & 7) << 4), pack2(v[8 * i], v[8 * i + 1]), pack2(v[8 * i + 2], v[8 * i + 3]),
                   pack2(v[8 * i + 4], v[8 * i + 5]), pack2(v[8 * i + 6], v[8 * i + 7]));
        }
    }
    fence_async();
    __syncthreads();
    if (lane == 0) {
        if (warp == 7) bulk_s2g(out + (size_t)blk * 16 * D_, sx, 20480);
        else if (!last && warp < 5) {
            unsigned char* p = g_xn + (blk >> 1) * 40960 + warp * 8192 + (blk & 1) * 2048;
            bulk_s2g(p, sb + warp * 4096, 2048);
            bulk_s2g(p + 4096, sb + warp * 4096 + 2048, 2048);
        }
        bulk_commit();
        bulk_wait<0>();
    }
    TLE(6 + 5 * last);
}

namespace rec {
#define NS 1
constexpr int OFF_X = 0;
constexpr int OFF_WO = 81920;
constexpr int OFF_WS = OFF_WO + 65536;
constexpr int OFF_XCH = OFF_WS + NS * 4096;
constexpr int OFF_MEMB = OFF_XCH + 12288;
constexpr int OFF_VX = OFF_MEMB + 10240;
constexpr int OFF_VM = OFF_VX + 16384;
constexpr int OFF_Q = OFF_VM + 4096;
constexpr int OFF_K = OFF_Q + 10240;
constexpr int OFF_OST = OFF_WO + 49152;
constexpr int OFF_PX = OFF_OST + 8192;
constexpr int OFF_PT = OFF_PX + 2560;
constexpr int OFF_PS = OFF_K + 10240;
constexpr int OFF_OB = OFF_PS + 1280;
constexpr int OFF_MX = OFF_OB + 2048;
constexpr int OFF_BAR = OFF_MX + 64;
constexpr int OFF_PROF = OFF_BAR + 256;
constexpr int SMEM = OFF_PROF + 4096 > wk::SMEM ? OFF_PROF + 4096 : wk::SMEM;
enum { B_XT = 0, B_VX = 4, B_XD = 6, B_X1 = 8, B_GO = 10, B_PXF = 12, B_PXE = 13, B_FIN = 14, B_ST = 15, B_MEM = 16   };
enum { NB_W2 = 0, NB_XCH = 1, NB_QK = 2, NB_WIN = 3, NB_ATT = 4, NB_X = 5, NB_PRO = 6, NB_W1 = 7, NB_LD = 13, NB_KX = 15 };
#define STAG 3
#define NOX 0
#define NW1 4
#define NW1B 0
template <int N> struct IC { static constexpr int value = N; };
template <int N, int I = 0, class F> DEV void static_for(F&& f) { if constexpr (I < N) { f(IC<I>{}); static_for<N, I + 1>(f); } }
constexpr float SM_SCALE = 0.08838834764831845f * 1.4426950408889634f;
}

__global__ void __launch_bounds__(512, 1) rec_kernel(const __grid_constant__ Maps maps, const bf16* __restrict__ x, bf16* __restrict__ x1, const bf16* __restrict__ mem0, const bf16* __restrict__ Wq, const bf16* __restrict__ Wk,
                                                     const bf16* __restrict__ Wv, const bf16* __restrict__ Wo, int layer, int delay, int delay2) {
    using namespace rec;
    extern __shared__ __align__(1024) unsigned char smem[];
    const uint32_t sb = s2u(smem);
    if (blockIdx.x >= 3 * H_) {
        pdl_wait();
        pdl_launch();
        worker(sb, maps, x, x1, layer);
        return;
    }
    const int tid = threadIdx.x, lane = tid & 31, warp = __shfl_sync(~0u, tid >> 5, 0);
    const int g = lane >> 2, q = lane & 3;
    const int h = blockIdx.x / 3;
    const uint32_t bar = sb + OFF_BAR;
    STAMP(2 * layer);
    TLS(2 + 5 * layer);
    if (tid == 0) {
        for (int i = 0; i < 2; i++) {
            mbar_init(bar + 8 * (B_XT + i), 1); mbar_init(bar + 8 * (B_VX + i), 1);
            mbar_init(bar + 8 * (B_XD + i), 8); mbar_init(bar + 8 * (B_X1 + i), 1);
        }
        mbar_init(bar + 8 * B_PXF, 1); mbar_init(bar + 8 * B_PXE, 2); mbar_init(bar + 8 * B_ST, 2); mbar_init(bar + 8 * B_GO, 1);
        for (int i = 0; i < 5; i++) mbar_init(bar + 8 * (B_MEM + i), 4);
        mbar_init(bar + 8 * B_FIN, 48);
        asm volatile("fence.mbarrier_init.release.cluster;" ::: "memory");
    }
    asm volatile("barrier.cluster.arrive.aligned; barrier.cluster.wait.aligned;" ::: "memory");
    const bool never = delay < 0;

    if (warp < 8) {
        asm volatile("setmaxnreg.inc.sync.aligned.u32 184;");
        const uint32_t rank = cta_rank();
        const int wg = warp >> 2;
        uint32_t fa[20 - NS][4], fb[20][4];
        const uint32_t l16 = opaque(sb + lane * 16);
        uint32_t dst = opaque(rank < 2 ? sb + OFF_Q + wg * 10240 + (warp & 3) * 256 + (lane & 15) * 16 + (lane >> 4) * 1024
                                       : sb + OFF_VM + warp * 256 + lane * 4);
        int dstep = rank < 2 ? 5120 : 2048;
        uint32_t& sfd = dst;
        const uint32_t ws = OFF_WS + warp * 512, xo = OFF_XCH + warp * 512, xi = OFF_XCH + (warp ^ 4) * 512, mb = OFF_MEMB + wg * 512;
        {
            const int t = tid & 127;
            const bf16* src = (rank == 2 ? Wv + wg * 64 : (wg ? Wk : Wq) + rank * 64) + h * E_ + (size_t)(t >> 3) * 4096 + (t & 7) * 8;
            constexpr int SA = OFF_X + 40960, SB = OFF_VX;
            const uint32_t sdst = sb + (wg ? SB : SA) + (t >> 3) * 128 + (((t & 7) ^ ((t >> 3) & 7)) << 4);
            const uint32_t ra = sb + wg * 4096 + ((lane >> 4) * 8 + (lane & 7)) * 128 + (((2 * (warp & 3) + ((lane >> 3) & 1)) ^ (lane & 7)) << 4);
            auto issue = [&](int rd) {
#pragma unroll 1
                for (int i = 0; i < 8; i++, src += 16 * 4096) cp16(sdst + (rd & 1) * 16384 + i * 2048, src);
                cp_commit();
            };
            issue(0); issue(1);
#pragma unroll
            for (int rd = 0; rd < 5; rd++) {
                if (rd < 4) cp_wait<1>(); else cp_wait<0>();
                bar_sync(NB_XCH, 256);
#pragma unroll
                for (int i = 0; i < 4; i++) {
                    const int n = rd * 4 + i, o = (rd & 1) * 16384 + (i >> 1) * 8192 + (i & 1) * 2048;
                    if (n < NS) {
                        uint32_t f[4];
                        ldsm4t(f, ra + SA + o);
                        sts128(l16 + ws + n * 4096, f[0], f[1], f[2], f[3]);
                    } else ldsm4t(fa[n - NS], ra + SA + o);
                    ldsm4t(fb[n], ra + SB + o);
                }
                if (rd < 3) { bar_sync(NB_XCH, 256); issue(rd + 2); }
            }
            fence_async();
            bar_sync(NB_PRO, 288);
        }
        uint32_t xlo = (uint32_t)mkdesc(sb + OFF_X + wg * 64, 0, 0);
        const uint32_t xtog = xlo ^ (uint32_t)mkdesc(sb + OFF_X + 40960 + wg * 64, 0, 0);
        uint32_t p8 = 0;
        bar_sync(NB_LD, 288);
        for (int s = -1;; s++) {
            uint32_t t[NS ? NS : 1][4];
            {
                float acc[16];
                auto xproj = [&](auto I0, auto I1) {
                    const u64 desc = (u64)xlo | (64ull << 32) | SW128;
                    wg_fence();
#pragma unroll
                    for (int i = I0.value; i < I1.value; i++) {
                        const u64 db = desc + (i >> 1) * 256 + (i & 1) * 2;
                        if (i == 0) wgmma_n32_rs<0>(acc, fb[i], db);
                        else if (!NOX) wgmma_n32_rs<1>(acc, fb[i], db);
                    }
                    wg_commit();
                    wg_wait<0>();
                };
                if (s >= 0 && rank < 2) { fence_async(); bar_arrive(NB_W1, 512); bar_sync(NB_X, 384); }
                bar_sync_if<NB_W1, 480>(s >= 0 && rank == 2);
                if (s == NSEG - 1) break;
                xproj(IC<0>{}, IC<NW1>{});
                if (warp == 4 && s >= 0) PROFT(15);
                bar_sync_if<NB_W2, 384>(s >= 0 && rank < 2);
                if (NW1B > 0) xproj(IC<NW1>{}, IC<NW1 + NW1B>{});
                bar_sync_if<NB_WIN, 384>(s >= 0 && rank == 2);
                xproj(IC<NW1 + NW1B>{}, IC<20>{});
                if (warp == 4 && s >= 0) PROFT(12);
                sts128f_if(l16 + xo, acc + 8, !wg); sts128f_if(l16 + xo + 4096, acc + 12, !wg);
                sts128f_if(l16 + xo, acc, wg); sts128f_if(l16 + xo + 4096, acc + 4, wg);
                bar_sync(NB_XCH, 256);
                float u[8];
#pragma unroll
                for (int i = 0; i < 8; i++) acc[i] = wg ? acc[8 + i] : acc[i];
                lds128f(u, l16 + xi); lds128f(u + 4, l16 + xi + 4096);
#pragma unroll
                for (int i = 0; i < NS; i++) lds128(t[i], l16 + ws + i * 4096);
#pragma unroll
                for (int i = 0; i < 8; i++) u[i] += acc[i];
                if (rank < 2) {
                    stsm4t(dst + (wg ? 3072 : 11264), pack2(u[0], u[1]), pack2(u[2], u[3]), pack2(u[4], u[5]), pack2(u[6], u[7]));
                    bar_arrive(NB_KX, 384);
                } else {
                    stsm4(l16 + (l16 & 256) + OFF_VX + 4096 + (warp & 3) * 1024 + wg * 256 + p8 * 1024,
                          pack2(u[0], u[1]), pack2(u[4], u[5]), pack2(u[2], u[3]), pack2(u[6], u[7]));
                    bar_arrive(NB_KX, 288);
                }
                xlo ^= xtog;
                if (warp == 4 && s >= 0) PROFT(3);
            }
            float da[4] = {0.f, 0.f, 0.f, 0.f}, db[4] = {0.f, 0.f, 0.f, 0.f};
            uint32_t b[10][4];
            const uint32_t mp = p8 >> 3;
            while (!mbar_try(bar + 8 * B_MEM, mp)) {}
            lds128(b[0], l16 + mb); lds128(b[1], l16 + mb + 1024);
            bool rdy = mbar_try(bar + 8 * (B_MEM + 1), mp, 1);
            const uint32_t xb0 = mapa(bar + 8 * B_X1 + p8, 0), xb1 = mapa(bar + 8 * B_X1 + p8, 1);
            SFENCE();
            float is;
#pragma unroll
            for (int j = 0; j < 10; j++) {
#pragma unroll
                for (int x = 0; x < 2; x++) {
                    const int i = 2 * j + x;
                    const uint32_t* f = i < NS ? t[i] : fa[i - NS];
                    mma16(da, f[0], f[1], f[2], f[3], b[j][2 * x], b[j][2 * x + 1]);
                    mma16(db, fb[i][0], fb[i][1], fb[i][2], fb[i][3], b[j][2 * x], b[j][2 * x + 1]);
                    SFENCE();
                    if (x == 0 && j < 8 && !(j & 1)) {
                        if (__builtin_expect(!rdy, 0)) while (!mbar_try(bar + 8 * (B_MEM + 1 + (j >> 1)), mp)) {}
                        lds128(b[j + 2], l16 + mb + (j + 2) * 1024);
                    }
                    if (x == 1 && j < 8 && !(j & 1)) lds128(b[j + 3], l16 + mb + (j + 3) * 1024);
                    if (x == 0 && j < 6 && (j & 1)) rdy = mbar_try(bar + 8 * (B_MEM + 2 + (j >> 1)), mp, 1);
                    if (x == 0 && j == 8) is = lds32f(sb + OFF_MX + 16);
                }
                if (j == 0 && warp == 4) PROFT(16);
            }
            sts128f_if(l16 + xo + 8192, db, !wg); sts128f_if(l16 + xo + 8192, da, wg);
            bar_sync(NB_XCH, 256);
            float u[4];
            lds128f(u, l16 + xi + 8192);
#pragma unroll
            for (int i = 0; i < 4; i++) da[i] = (wg ? db[i] : da[i]) * is;
            const uint32_t p0 = pack2(fmaf(u[0], is, da[0]), fmaf(u[1], is, da[1])), p1 = pack2(fmaf(u[2], is, da[2]), fmaf(u[3], is, da[3]));
            stsm2t_if(dst, p0, p1, rank < 2);
            bar_arrive_if<NB_QK, 384>(rank < 2);
            if (rank == 2) {
                st_async1(mapa(dst, 0), p0, xb0); st_async1(mapa(dst, 1), p0, xb1);
                st_async1(mapa(dst + 128, 0), p1, xb0); st_async1(mapa(dst + 128, 1), p1, xb1);
                sts32(dst, p0); sts32(dst + 128, p1);
                bar_arrive(NB_QK, 384);
            }
            if (warp == 4) PROFT(17);
            dst += dstep; dstep = -dstep; p8 ^= 8;
        }
    } else if (warp < 12) {
        asm volatile("setmaxnreg.dec.sync.aligned.u32 96;");
        const uint32_t rank = cta_rank();
        const int w = warp - 8;
        uint32_t amax = 0;
#pragma unroll 1
        for (int it = 0; it < 5; it++) {
            const int kp = it * 4 + w;
            const bf16* p = mem0 + g * D_ + kp * 32 + 2 * q;
            uint32_t b0 = ldg32(p), b1 = ldg32(p + 8), b2 = ldg32(p + 16), b3 = ldg32(p + 24);
            sts128(sb + OFF_MEMB + kp * 512 + lane * 16, b0, b1, b2, b3);
            amax = absmax2(amax, absmax2(absmax2(b0, b1), absmax2(b2, b3)));
        }
        if (tid == 256) { sts32(sb + OFF_MX + 16, 0x3f800000u); sts128(sb + OFF_MX + 48, 0x3f803f80u, 0x3f803f80u, 0x3f803f80u, 0x3f803f80u); }
        __syncwarp();
        if (lane < 5) mbar_arrive(bar + 8 * (B_MEM + lane));
        __syncwarp();
        {
            const int t = tid & 127, nr = rank == 2 ? 4 : 3;
            for (int r = 0; r < nr; r++) {
                const bf16* src = Wo + (size_t)(h * E_) * D_ + (r < 3 ? 192 * r + 64 * rank : 576);
#pragma unroll 1
                for (int i = 0; i < 8; i++) {
                    const int e = i * 16 + (t >> 3);
                    cp16(sb + OFF_WO + r * 16384 + e * 128 + (((t & 7) ^ (e & 6)) << 4), src + e * D_ + (t & 7) * 8);
                }
            }
            cp_commit();
            pdl_wait();
            pdl_launch();
            cp_wait<0>();
            bar_sync(NB_ATT, 128);
            for (int r = 0; r < nr; r++) {
                uint32_t u[8][4];
                const uint32_t p = sb + OFF_WO + r * 16384 + 2 * q * 128 + (((2 * w + (g & 1)) ^ (2 * q)) << 4) + (g >> 1) * 4;
#pragma unroll
                for (int ks = 0; ks < 8; ks++)
#pragma unroll
                    for (int j = 0; j < 4; j++) u[ks][j] = lds32(p + (16 * ks + (j & 1) * 8 + (j >> 1)) * 128);
                bar_sync(NB_ATT, 128);
#pragma unroll
                for (int ks = 0; ks < 8; ks++)
                    sts128(sb + OFF_WO + (r * 4 + w) * 4096 + ks * 512 + lane * 16, prmt(u[ks][0], u[ks][2], 0x5410), prmt(u[ks][0], u[ks][2], 0x7632),
                           prmt(u[ks][1], u[ks][3], 0x5410), prmt(u[ks][1], u[ks][3], 0x7632));
            }
        }
        float cw;
        {
            const float4 a = ((const float4*)g_nrm)[lane], c = ((const float4*)g_nrm)[32 + lane];
            float sm = sqrt_approx((a.x + a.y) + (a.z + a.w)) * sqrt_approx((c.x + c.y) + (c.z + c.w)), mxv = sm;
#pragma unroll 1
            for (int o = 16; o; o >>= 1) { sm += __shfl_xor_sync(~0u, sm, o); mxv = fmaxf(mxv, __shfl_xor_sync(~0u, mxv, o)); }
            cw = 26.5f * fmaxf(sm, 8.f * mxv);
        }
        if (w == 0) {
            mbar_expect_elect(bar + 8 * B_X1, rank < 2 ? 3328 : 1280);
            mbar_expect_elect(bar + 8 * B_VX, rank < 2 ? 8192 : 4096);
        }
        {
            const int kind = rank;
            const uint32_t l16 = opaque(sb + lane * 16), lw = opaque(sb + lane * 16 + w * 512);
            const uint32_t pa = opaque(sb + OFF_PS + rank * 512 + lane * 4 + w * 128);
            uint32_t lq = opaque(sb + OFF_Q + (lane & 7) * 16 + ((lane >> 3) & 1) * 256 + (lane >> 4) * 128);
            const uint32_t lv = opaque(sb + OFF_VX + w * 2048 + (lane & 7) * 16 + ((lane >> 3) & 1) * 512 + (lane >> 4) * 128);
            const uint32_t lo = opaque(sb + OFF_WO + w * 4096 + lane * 16);
            uint32_t& sfd = lq;
            const char* rp = (const char*)(g_acc + layer * ACC_LAYER) + (4 * rank + w) * 4096 + opaque((q >> 1) * 1024 + ((q & 1) * 8 + g) * 8);
            const char* lp = (const char*)(g_acc + layer * ACC_LAYER) + opaque(w * 8192 + (lane >> 3) * 1024 + (lane & 7) * 16);
            float isig = 1.f;
            for (int s = 0; s < NSEG - 1; s++) {
                const uint32_t pb = s & 1, ph = (s >> 1) & 1, x1 = bar + 8 * (B_X1 + pb);
                uint32_t kf[8];
                bar_sync_if<NB_KX, 384>(kind < 2);
                ldsm4(kf, lw + OFF_K + 1024 + w * 512 + pb * 5120); ldsm4(kf + 4, lw + OFF_K + 1536 + w * 512 + pb * 5120);
                sts32(sb + OFF_MX + w * 4, __reduce_max_sync(~0u, max(amax & 0x7fff0000u, (amax << 16) & 0x7fff0000u)));
                const bool vok = mbar_try(bar + 8 * (B_VX + pb), ph, 1);
                const uint32_t va = lv + pb * 8192, vma = lw + OFF_VM + pb * 2048;
                uint32_t wf[8][4], vf[2][2][4], vm[4], one[4];
                auto scores = [&](auto MM) {
                    constexpr int mm = MM.value;
                    uint32_t qf[8], mf[8];
                    const uint32_t qa = lq + pb * 5120, ka = l16 + OFF_K + pb * 5120;
                    const uint32_t pa0 = mapa(pa, rank ^ 1), pa1 = mapa(pa, 2), pa2 = mapa(pa, rank);
                    const uint32_t xb0 = mapa(x1, rank ^ 1), xb1 = mapa(x1, 2), xb2 = mapa(x1, rank);
                    const uint32_t pm = 640 - rank * 384;
                    SFENCE();
                    bar_sync(NB_QK, 384);
                    ldsm4(qf, qa); ldsm4(qf + 4, qa + 512);
                    if (mm) { ldsm4(mf, ka); ldsm4(mf + 4, ka + 512); }
                    SFENCE();
                    float c[8][4];
#pragma unroll
                    for (int i = 0; i < (mm ? 8 : 4); i++) {
                        const uint32_t* f = (i < 4 ? kf : mf) + 2 * (i & 3);
                        c[i][0] = c[i][1] = c[i][2] = c[i][3] = 0.f;
                        mma16(c[i], qf[i & 2 ? 4 : 0], qf[i & 2 ? 5 : 1], qf[i & 2 ? 6 : 2], qf[i & 2 ? 7 : 3], f[0], f[1]);
                    }
                    SFENCE();
                    bar_arrive(NB_W1, 512);
                    const uint32_t y = pack2((c[0][0] + c[1][2]) + (c[2][0] + c[3][2]), (c[0][1] + c[1][3]) + (c[2][1] + c[3][3]));
                    st_async1(pa0, y, xb0); st_async1(pa1, y, xb1);
                    if (mm) {
                        const uint32_t z = pack2((c[4][0] + c[5][2]) + (c[6][0] + c[7][2]), (c[4][1] + c[5][3]) + (c[6][1] + c[7][3]));
                        st_async1(pa0 + pm, z, xb0); st_async1(pa1 + pm, z, xb1); st_async1(pa2 + pm, z, xb2);
                    }
                    st_async1(pa2, y, xb2);
                };
                if (kind == 2) bar_sync(NB_QK, 384);
                else if (w == 3) scores(IC<1>{});
                else scores(IC<0>{});
                if (!vok) mbar_spin(bar + 8 * (B_VX + pb), ph);
#pragma unroll
                for (int t = 0; t < 2; t++)
#pragma unroll
                    for (int j = 0; j < 2; j++) ldsm4(vf[t][j], va + t * 1024 + j * 256);
                float m4[4];
                lds128f(m4, sb + OFF_MX);
                bar_arrive_if<NB_W1, 480>(kind == 2);
                lds128(one, sb + OFF_MX + 48);
                mbar_spin(x1, ph);
                if (w == 0) PROFT(6);
                float sc[10];
                {
                    uint32_t u[4], v[4], m[2];
                    ldsm4(u, l16 + OFF_PS); ldsm4(v, l16 + OFF_PS + 512); ldsm2(m, l16 + OFF_PS + 1024);
                    ldsm4(vm, vma);
                    SFENCE();
                    m4[0] = fmaxf(fmaxf(m4[0], m4[1]), fmaxf(m4[2], m4[3])) * isig;
                    SFENCE();
#pragma unroll
                    for (int i = 0; i < 4; i++) { sc[2 * i] = bf_lo(u[i]) + bf_lo(v[i]); sc[2 * i + 1] = bf_hi(u[i]) + bf_hi(v[i]); }
                    sc[8] = bf_lo(m[0]) + bf_lo(m[1]); sc[9] = bf_hi(m[0]) + bf_hi(m[1]);
                }
                float mx = fmaxf(fmaxf(fmaxf(fmaxf(sc[0], sc[1]), fmaxf(sc[2], sc[3])), fmaxf(fmaxf(sc[4], sc[5]), fmaxf(sc[6], sc[7]))), fmaxf(sc[8], sc[9]));
                auto fetch = [&](int i) { lds128(wf[i], lo + i * 512); };
                {
                    float m1 = __shfl_xor_sync(~0u, mx, 1), m2 = __shfl_xor_sync(~0u, mx, 2), m3 = __shfl_xor_sync(~0u, mx, 3);
                    SFENCE();
#pragma unroll
                    for (int i = 0; i < 4; i++) fetch(i);
                    SFENCE();
                    mx = fmaxf(fmaxf(mx, m1), fmaxf(m2, m3)) * SM_SCALE;
                }
#pragma unroll
                for (int i = 0; i < 10; i++) sc[i] = fmaf(sc[i], SM_SCALE, -mx);
                float o0[4] = {0.f, 0.f, 0.f, 0.f}, o1[4] = {0.f, 0.f, 0.f, 0.f}, rs[4] = {0.f, 0.f, 0.f, 0.f};
                sc[8] = ex2(sc[8]); sc[9] = ex2(sc[9]);
                SFENCE();
                sc[0] = ex2(sc[0]); fetch(4); sc[1] = ex2(sc[1]); fetch(5); sc[2] = ex2(sc[2]); fetch(6);
                SFENCE();
                {
                    const uint32_t p = pack2(sc[8], sc[9]);
                    sc[3] = ex2(sc[3]); fetch(7);
                    mma8(o0, vm[0], vm[1], p);
                    mma8(o1, vm[2], vm[3], p);
                    sc[4] = ex2(sc[4]);
                    mma8(rs, one[0], one[1], p);
                    sc[5] = ex2(sc[5]);
                }
                SFENCE();
                {
                    const uint32_t p0 = pack2(sc[0], sc[1]), p1 = pack2(sc[2], sc[3]);
                    sc[6] = ex2(sc[6]);
                    mma16(o0, vf[0][0][0], vf[0][0][1], vf[0][0][2], vf[0][0][3], p0, p1);
                    SFENCE();
                    sc[7] = ex2(sc[7]);
                    mma16(o1, vf[1][0][0], vf[1][0][1], vf[1][0][2], vf[1][0][3], p0, p1);
                    SFENCE();
                    mma16(rs, one[0], one[1], one[2], one[3], p0, p1);
                    SFENCE();
                }
                {
                    const uint32_t p0 = pack2(sc[4], sc[5]), p1 = pack2(sc[6], sc[7]);
                    mma16(o0, vf[0][1][0], vf[0][1][1], vf[0][1][2], vf[0][1][3], p0, p1);
                    mma16(o1, vf[1][1][0], vf[1][1][1], vf[1][1][2], vf[1][1][3], p0, p1);
                    SFENCE();
                    mma16(rs, one[0], one[1], one[2], one[3], p0, p1);
                }
                const uint32_t e = max((__float_as_uint(cw * fmaxf(m4[0], 1.f)) >> 23) & 255u, 31u);
                SFENCE();
                stsm4t(lw + OFF_OB, pack2(o0[0], o0[1]), pack2(o0[2], o0[3]), pack2(o1[0], o1[1]), pack2(o1[2], o1[3]));
                bar_sync(NB_ATT, 128);
                uint32_t ob[16];
#pragma unroll
                for (int j = 0; j < 4; j++) ldsm4(ob + 4 * j, l16 + OFF_OB + j * 512);
                SFENCE();
                const float sig = __uint_as_float((278u - e) << 23);
                isig = __uint_as_float((e - 30u) << 23);
                const float sg0 = rcp(rs[0]) * sig, sg1 = rcp(rs[1]) * sig;
                SFENCE();
                auto tile = [&](uint32_t next, const char* p, auto LAST) {
                    float c[4][4];
#pragma unroll
                    for (int i = 0; i < 4; i++) c[i][0] = c[i][1] = c[i][2] = c[i][3] = 0.f;
#pragma unroll
                    for (int ks = 0; ks < 8; ks++) {
                        mma16(c[ks & 3], wf[ks][0], wf[ks][1], wf[ks][2], wf[ks][3], ob[2 * ks], ob[2 * ks + 1]);
                        if ((ks & 3) == 3 && !LAST.value) {
                            SFENCE();
#pragma unroll
                            for (int i = ks - 3; i <= ks; i++) lds128(wf[i], next + i * 512);
                        }
                    }
                    SFENCE();
                    if (LAST.value) { bar_arrive_if<NB_WIN, 256>(kind < 2); bar_arrive_if<NB_WIN, 384>(kind == 2); }
                    uint32_t v[4];
#pragma unroll
                    for (int i = 0; i < 4; i++)
                        v[i] = (__float_as_uint(fmaf((c[0][i] + c[1][i]) + (c[2][i] + c[3][i]), i & 1 ? sg1 : sg0, 12582912.f)) << 6) + (i < 2);
                    red_add64((u64*)p, v[0], v[2]);
                    red_add64((u64*)(p + 2048), v[1], v[3]);
                };
                tile(lo + 16384, rp, IC<0>{});
                if (w == 0) PROFT(7);
                tile(lo + 32768, rp + 49152, IC<0>{});
                if (kind == 2) tile(lo + 49152, rp + 98304, IC<0>{});
                tile(0, rp + (kind == 2 ? 28 * 4096 : 98304), IC<1>{});
                if (w == 0) PROFT(8);
                sts32(sb + OFF_MX + 16, __float_as_uint(isig));
                if (w == 0) mbar_expect_elect(bar + 8 * (B_X1 + (pb ^ 1)), (kind < 2 ? 2048 : 0) + (s < NSEG - 2 ? 1280 : 0));
                if (w == 1) mbar_expect_elect(bar + 8 * (B_VX + (pb ^ 1)), kind < 2 ? 8192 : 4096);
                if (w == 2) mbar_expect_elect(bar + 8 * (B_XT + pb), (kind < 2 ? 4096 : 0) + (s < NSEG - 2 ? 40960 : 0));
                u64 y[20];
                uint32_t b[20];
                bool done[5] = {false, false, false, false, false};
                float z = isig;
                mbar_spin(bar + 8 * B_GO, pb);
                do {
#pragma unroll
                    for (int i = 0; i < 10; i++) {
                        if (STAG && (i == 2 || i == 4 || i == 7)) {
#pragma unroll
                            for (int k = 0; k < STAG; k++) asm volatile("ex2.approx.ftz.f32 %0,%0;" : "+f"(z));
                            asm volatile("{.reg .pred p; setp.ne.u32 p,%1,0; @p mov.b32 %0,%2;}" : "+r"(sfd) : "r"((uint32_t)never), "f"(z));
                            SFENCE();
                        }
                        ld_acc0(y[2 * i], y[2 * i + 1], lp + (i >> 1) * 32768 + (i & 1) * 4096);
                        if (STAG && (i == 1 || i == 3 || i == 6)) SFENCE();
                    }
                    if (w == 0 && !done[0]) PROFT(9);
                    uint32_t ok = 32u, late = 32u;
                    static_for<5>([&](auto IT) {
                        constexpr int it = IT.value;
                        if (it == 2) late = and3((uint32_t)y[8], (uint32_t)y[10], (uint32_t)y[12]);
                        else if (it == 3) late &= and3((uint32_t)y[14], (uint32_t)y[16], (uint32_t)y[18]);
                        else ok = and3(ok, (uint32_t)y[4 * it], it == 4 ? late : (uint32_t)y[4 * it + 2]);
                        if (it < 4) SFENCE();
                        if (it == 2 || it == 3) ok = and3(ok, (uint32_t)y[4 * it], (uint32_t)y[4 * it + 2]);
                        ok = and3(ok, (uint32_t)y[4 * it + 1], (uint32_t)y[4 * it + 3]);
                        const bool all = __all_sync(~0u, ok);
#pragma unroll
                        for (int j = 0; j < 4; j++) {
                            const u64 v = y[4 * it + j];
                            b[4 * it + j] = pack2((float)(int)(uint32_t)v, (float)(int)(uint32_t)(v >> 32));
                        }
                        sts128(lw + OFF_MEMB + it * 2048, b[4 * it], b[4 * it + 1], b[4 * it + 2], b[4 * it + 3]);
                        mbar_arrive_elect_if(bar + 8 * (B_MEM + it), all && !done[it]);
                        done[it] = all;
                        SFENCE();
                        if (it == 0 && w == 0) PROFT(10);
                    });
                } while (!done[4]);
                if (w == 0) PROFT(11);
                amax = b[0];
#pragma unroll
                for (int i = 1; i < 19; i += 2) amax = absmax2(amax, absmax2(b[i], b[i + 1]));
                amax = absmax2(amax, b[19]);
                const int adv = (s & 7) == 7 ? 163840 - 896 : 128;
                rp += adv; lp += adv;
            }
        }
        bar_sync_if<NB_KX, 384>(rank < 2);
        bar_sync(NB_QK, 384);
        if (rank < 2) { bar_arrive(NB_W1, 512); bar_arrive(NB_WIN, 256); } else bar_arrive(NB_W1, 480);
    } else {
        asm volatile("setmaxnreg.dec.sync.aligned.u32 %0;" ::"n"(48));
        const uint32_t rank = cta_rank();
        const int w = warp - 12;
        pdl_wait();
        pdl_launch();
        uint32_t* sy = g_sync + layer * SYNC_LAYER;
        if (w == 1) {
            mbar_expect_elect(bar + 8 * B_XT, 40960);
            bulk_g2s_elect(sb + OFF_X, g_xn, 40960, bar + 8 * B_XT);
            bar_sync(NB_PRO, 288);
            if (rank == 2) mbar_spin(bar + 8 * B_ST, 0);
            else mbar_arrive_remote_elect(mapa(bar + 8 * B_ST, 2));
            mbar_spin(bar + 8 * B_XT, 0);
            bar_arrive(NB_LD, 288);
            mbar_expect_elect(bar + 8 * (B_XT + 1), rank < 2 ? 45056 : 40960);
        }
        if (rank == 2) {
            if (w == 0) {
                for (int s = -1; s < NSEG - 1; s++) {
                    const uint32_t pb = s & 1, va = sb + OFF_VX + (pb ^ 1) * 8192 + 4096, vb = bar + 8 * (B_VX + (pb ^ 1));
                    bar_sync(NB_KX, 288);
                    fence_async();
                    bulk_s2s_elect(mapa(va, 0), va, 4096, mapa(vb, 0));
                    bulk_s2s_elect(mapa(va, 1), va, 4096, mapa(vb, 1));
                    if (s >= 0) mbar_spin(bar + 8 * (B_XD + pb), (s >> 1) & 1);
                    bar_sync(NB_W1, 480);
                }
            } else if (w == 1) {
                const unsigned char *pn = g_p + h * 12288, *px = g_xn + 40960;
                const uint32_t* pf = sy + wk::SY_P + h;
                for (int s = -1, nb = -1; s < NSEG - 1; s++, pn += H_ * 12288, px += 40960) {
                    const uint32_t pb = s & 1, xt = bar + 8 * (B_XT + pb), qa = sb + OFF_Q + (pb ^ 1) * 5120 + 1024;
                    if (s >= 0) mbar_spin(bar + 8 * (B_X1 + pb), (s >> 1) & 1);
                    if (s + 2 < NSEG) bulk_g2s_all3_elect(sb + OFF_X + pb * 40960, px, 40960, xt);
                    if (s == nb) {
                        while (__any_sync(~0u, ld_acquire(pf) < 3)) __nanosleep(100);
                        pf += H_;
                        nb += min(s + 3, 6);
                    }
                    bulk_g2s_all3_elect(sb + OFF_VX + (pb ^ 1) * 8192, pn + 8192, 4096, bar + 8 * (B_VX + (pb ^ 1)));
                    bulk_g2s_elect(mapa(qa, 0), pn, 4096, mapa(xt, 0));
                    bulk_g2s_elect(mapa(qa, 1), pn + 4096, 4096, mapa(xt, 1));
                    mbar_spin(xt, ((s + 2) >> 1) & 1);
                    bar_sync(NB_W1, 480);
                }
                mbar_spin(bar + 8 * (B_VX + 1), 1);
            } else if (w == 2) {
                uint32_t* hp = sy + 1024;
                const char* pf = lane < 5 ? (const char*)(g_acc + layer * ACC_LAYER) + (5 * h + lane) * 1024 : (const char*)hp;
                const int pfa = lane < 5 ? 163840 : 1024;
                const uint32_t go = mapa(bar + 8 * B_GO, min(lane, 2));
                if (lane < 6) for (int i = 0; i < 8; i++) prefetch_l2(pf + i * 128);
                __syncwarp();
                for (int s = 0; s < NSEG - 1; s++, hp += 32) {
                    bar_sync(NB_W1, 480);
                    mbar_spin(bar + 8 * (B_X1 + (s & 1)), (s >> 1) & 1);
                    uint32_t t = gtime32(), t0 = clk(), c, tm;
                    asm volatile("{.reg .pred p; elect.sync _|p, 0xffffffff; @p red.relaxed.gpu.global.max.u32 [%0+4],%1; @p red.relaxed.gpu.global.add.u32 [%0],1;}"
                                 ::"l"(hp), "r"(t) : "memory");
                    if (h == 0) TLI(940 + s, 0, t);
                    if (lane < 6 && s < NSEG - 8) prefetch_l2(pf + ((s >> 3) + 1) * pfa + (s & 7) * 128);
                    __syncwarp();
                    while (clk() - t0 < (uint32_t)delay2) {}
                    do asm volatile("ld.relaxed.gpu.global.v2.u32 {%0,%1},[%2];" : "=r"(c), "=r"(tm) : "l"(hp) : "memory"); while (__any_sync(~0u, c != H_));
                    const uint32_t wait = min(tm - t, 10000u) * 7 / 4 + delay;
                    while (clk() - t0 < wait) {}
                    if (lane < 3) mbar_arrive_remote(go);
                    __syncwarp();
                }
                bar_sync(NB_W1, 480);
            }
        } else {
            if (w < 2) sts32(sb + OFF_PT + w * 768 + 640 + lane * 4, 0u);
            const uint32_t px = opaque(sb + OFF_PX + (w & 1) * 1280 + lane * 8);
            const uint32_t pt = opaque(sb + OFF_PT + (w & 1) * 768 + lane * 4);
            uint32_t os = opaque(sb + OFF_OST + (lane >> 4) * 1024 + w * 256 + (lane & 15) * 16);
            uint32_t& sfd = os;
            const int lim = opaque(8 * w + g + 8 - 2 * q);
            unsigned char* op = g_o + h * 8192 + rank * 2048;
            uint32_t* oc = sy + wk::SY_O - 1;
            auto report = [&]() {
                __syncwarp();
                asm volatile("{.reg .pred p; elect.sync _|p, 0xffffffff; @p red.relaxed.gpu.global.add.u32 [%0],1;}" ::"l"(oc) : "memory");
                oc++;
            };
            auto store_o = [&](int n) {
                bulk_s2g_elect(op, sb + OFF_OST + (n & 1) * 4096, 2048);
                bulk_s2g_elect(op + 4096, sb + OFF_OST + (n & 1) * 4096 + 2048, 2048);
                bulk_commit();
                op += H_ * 8192;
                bulk_wait<1>();
                report();
            };
            for (int s = 0; s < NSEG; s++) {
                const uint32_t pb = s & 1, ph = (s >> 1) & 1;
                if ((w >> 1) != rank) { if (s >= 1) mbar_spin(bar + 8 * B_PXE, pb ^ 1); }
                else if (w & 1) mbar_spin(bar + 8 * (B_XT + (pb ^ 1)), ((s + 1) >> 1) & 1);
                else mbar_expect_elect(bar + 8 * B_PXF, rank ? 2560 : 1536);
                const u64 dq = mkdesc(sb + OFF_Q + pb * 5120 + 1024, 128, 512), dk = mkdesc(sb + OFF_K + pb * 5120, 128, 1024);
                SFENCE();
                bar_sync(NB_W1, 512);
                float c[20];
                wg_fence();
                wgmma_n40_ss<0>(c, dq, dk);
#pragma unroll
                for (int ks = 1; ks < 4; ks++) wgmma_n40_ss<1>(c, dq + ks * 16, dk + ks * 16);
                wg_commit();
                bar_arrive(NB_X, 384);
                wg_wait<0>();
                if ((w >> 1) != rank) {
                    const uint32_t pa = mapa(px, rank ^ 1), pf = mapa(bar + 8 * B_PXF, rank ^ 1);
#pragma unroll
                    for (int nt = 0; nt < 5; nt++)
                        if (nt < 3 || rank == 0) st_async2(pa + nt * 256, __float_as_uint(c[4 * nt]), __float_as_uint(c[4 * nt + 1]), pf);
                    if ((w & 1) && s) store_o(s - 1);
                    mbar_spin(bar + 8 * (w & 1 ? B_VX : B_X1) + 8 * pb, ph);
                } else {
                    mbar_spin(bar + 8 * B_PXF, pb);
                    float u[10];
#pragma unroll
                    for (int nt = 0; nt < 5; nt++) lds64f(u[2 * nt], u[2 * nt + 1], px + nt * 256);
#pragma unroll
                    for (int i = 0; i < 10; i++) u[i] = 8 * (i >> 1) + (i & 1) <= lim ? u[i] + c[4 * (i >> 1) + (i & 1)] : -INFINITY;
                    float mx = fmaxf(fmaxf(fmaxf(fmaxf(u[0], u[1]), fmaxf(u[2], u[3])), fmaxf(fmaxf(u[4], u[5]), fmaxf(u[6], u[7]))), fmaxf(u[8], u[9]));
                    const float m1 = __shfl_xor_sync(~0u, mx, 1), m2 = __shfl_xor_sync(~0u, mx, 2), m3 = __shfl_xor_sync(~0u, mx, 3);
                    mx = fmaxf(fmaxf(mx, m1), fmaxf(m2, m3)) * SM_SCALE;
#pragma unroll
                    for (int i = 0; i < 10; i++) u[i] = ex2(fmaf(u[i], SM_SCALE, -mx));
                    float sum = (((u[0] + u[1]) + (u[2] + u[3])) + ((u[4] + u[5]) + (u[6] + u[7]))) + (u[8] + u[9]);
                    const float s1 = __shfl_xor_sync(~0u, sum, 1), s2 = __shfl_xor_sync(~0u, sum, 2), s3 = __shfl_xor_sync(~0u, sum, 3);
                    sum = rcp((sum + s1) + (s2 + s3));
#pragma unroll
                    for (int nt = 0; nt < 5; nt++) sts32(pt + (nt ? nt - 1 : 4) * 128, pack2(u[2 * nt] * sum, u[2 * nt + 1] * sum));
                }
                float acc[2][8];
                const u64 dv = mkdesc(sb + OFF_VX + pb * 8192, 128, 512), dp = mkdesc(sb + OFF_PT, 128, 768);
                const u64 dm = mkdesc(sb + OFF_VM + pb * 2048, 0, 128);
                fence_async();
                bar_sync(NB_WIN, 256);
                wg_fence();
#pragma unroll
                for (int m = 0; m < 2; m++) {
                    wgmma_n16_ss<0>(acc[m], dv + m * 256, dp);
                    wgmma_n16_ss<1>(acc[m], dv + m * 256 + 16, dp + 16);
                    wgmma_n16_ss<1>(acc[m], dm + m * 64, dp + 32);
                }
                wg_commit();
                bar_arrive_if<NB_W2, 384>(s < NSEG - 1);
                wg_wait<0>();
#pragma unroll
                for (int m = 0; m < 2; m++)
                    stsm4t(os + pb * 4096 + m * 2048, pack2(acc[m][0], acc[m][1]), pack2(acc[m][2], acc[m][3]), pack2(acc[m][4], acc[m][5]), pack2(acc[m][6], acc[m][7]));
                fence_async();
                mbar_arrive_remote_elect(mapa(bar + 8 * (B_XD + pb), 2));
                if ((w >> 1) == rank) mbar_arrive_remote_elect(mapa(bar + 8 * B_PXE, rank ^ 1));
            }
            bar_sync(NB_W2, 128);
            if (w == 3 - 2 * rank) {
                store_o(NSEG - 1);
                bulk_wait<0>();
                report();
            }
        }
    }
    __syncwarp();
    if (lane < 3) mbar_arrive_remote(mapa(bar + 8 * B_FIN, lane));
    mbar_wait(bar + 8 * B_FIN, 0);
    TLE(2 + 5 * layer);
}

int g_delay = 2501000, g_layers = 2;

void make_map(CUtensorMap* m, CUtensorMapDataType dt, const void* p, const cuuint64_t* dim, const cuuint64_t* str, const cuuint32_t* box, CUtensorMapSwizzle sw) {
    typedef CUresult (*Fn)(CUtensorMap*, CUtensorMapDataType, cuuint32_t, void*, const cuuint64_t*, const cuuint64_t*, const cuuint32_t*,
                           const cuuint32_t*, CUtensorMapInterleave, CUtensorMapSwizzle, CUtensorMapL2promotion, CUtensorMapFloatOOBfill);
    static Fn fn = nullptr;
    if (!fn) {
        cudaDriverEntryPointQueryResult qr;
        cudaGetDriverEntryPoint("cuTensorMapEncodeTiled", (void**)&fn, cudaEnableDefault, &qr);
    }
    const cuuint32_t es[3] = {1, 1, 1};
    fn(m, dt, 3, (void*)p, dim, str, box, es, CU_TENSOR_MAP_INTERLEAVE_NONE, sw, CU_TENSOR_MAP_L2_PROMOTION_L2_128B, CU_TENSOR_MAP_FLOAT_OOB_FILL_NONE);
}
void map_weight(CUtensorMap* m, const bf16* p, int rows, int cols, int ng, int br = 64) {
    const cuuint64_t dim[3] = {64, (cuuint64_t)rows, (cuuint64_t)cols / 64}, str[2] = {(cuuint64_t)cols * 2, 128};
    const cuuint32_t box[3] = {64, (cuuint32_t)br, (cuuint32_t)ng};
    make_map(m, CU_TENSOR_MAP_DATA_TYPE_BFLOAT16, p, dim, str, box, CU_TENSOR_MAP_SWIZZLE_128B);
}
void map_pieces(CUtensorMap* m, const void* p, int np, int ns) {
    const cuuint64_t dim[3] = {256, (cuuint64_t)np * 2, NSEG}, str[2] = {2048, (cuuint64_t)np * 4096};
    const cuuint32_t box[3] = {256, 2, (cuuint32_t)ns};
    make_map(m, CU_TENSOR_MAP_DATA_TYPE_UINT64, p, dim, str, box, CU_TENSOR_MAP_SWIZZLE_NONE);
}

template <class... P, class... A> void launch(void (*k)(P...), int grid, int block, int smem, int cluster, bool pdl, A... args) {
    cudaLaunchConfig_t c = {};
    c.gridDim = dim3(grid); c.blockDim = dim3(block); c.dynamicSmemBytes = smem; c.stream = cudaStreamPerThread;
    cudaLaunchAttribute at[2];
    int n = 0;
    if (cluster > 1) { at[n].id = cudaLaunchAttributeClusterDimension; at[n].val.clusterDim.x = cluster; at[n].val.clusterDim.y = 1; at[n].val.clusterDim.z = 1; n++; }
    if (pdl) { at[n].id = cudaLaunchAttributeProgrammaticStreamSerialization; at[n].val.programmaticStreamSerializationAllowed = 1; n++; }
    c.attrs = at; c.numAttrs = n;
    cudaLaunchKernelEx(&c, k, args...);
}

int max_clusters() {
    cudaLaunchConfig_t c = {};
    c.gridDim = dim3(3 * H_); c.blockDim = dim3(512); c.dynamicSmemBytes = rec::SMEM;
    cudaLaunchAttribute at[1];
    at[0].id = cudaLaunchAttributeClusterDimension; at[0].val.clusterDim.x = 3; at[0].val.clusterDim.y = 1; at[0].val.clusterDim.z = 1;
    c.attrs = at; c.numAttrs = 1;
    int n = 0;
    cudaOccupancyMaxActiveClusters(&n, rec_kernel, &c);
    return n;
}

}

extern "C" void kernel_launch(void* const* d_in, const int* in_sizes, int n_in, void* d_out, int out_size) {
    const bf16* x = (const bf16*)d_in[0];
    const bf16* mem0 = (const bf16*)d_in[1];
    const bf16* Wq = (const bf16*)d_in[2];
    const bf16* Wk = (const bf16*)d_in[3];
    const bf16* Wv = (const bf16*)d_in[4];
    const bf16* Wo = (const bf16*)d_in[5];
    const bf16* wr = (const bf16*)d_in[8];
    const bf16* wi = (const bf16*)d_in[9];
    cudaFuncSetAttribute(rec_kernel, cudaFuncAttributeMaxDynamicSharedMemorySize, rec::SMEM);
    cudaFuncSetAttribute(side_kernel, cudaFuncAttributeMaxDynamicSharedMemorySize, wk::SMEM);
    cudaFuncSetAttribute(colfft_kernel, cudaFuncAttributeMaxDynamicSharedMemorySize, CF_SMEM);
    Maps maps;
    void *pxn, *po;
    cudaGetSymbolAddress(&pxn, g_xn);
    cudaGetSymbolAddress(&po, g_o);
    map_weight(&maps.wq2, Wq, D_, 4096, 2); map_weight(&maps.wv1, Wv, D_, 4096, 1);
    map_weight(&maps.wo2, Wo, 4096, D_, 2); map_weight(&maps.wo1, Wo, 4096, D_, 1, 192);
    map_pieces(&maps.x6, pxn, 10, 6); map_pieces(&maps.x2, pxn, 10, 2);
    map_pieces(&maps.o6, po, 64, 6); map_pieces(&maps.o2, po, 64, 2);
    bf16 *x1, *x2;
    cudaGetSymbolAddress((void**)&x1, g_x1);
    cudaGetSymbolAddress((void**)&x2, g_x2);
    constexpr int ONE_PER_SM = 120 * 1024;
    cudaFuncSetAttribute(rowfft_kernel, cudaFuncAttributeMaxDynamicSharedMemorySize, ONE_PER_SM);
    cudaFuncSetAttribute(rowifft_kernel, cudaFuncAttributeMaxDynamicSharedMemorySize, ONE_PER_SM);
    static int ncl = 0, nsm = 0;
    if (!ncl) { ncl = max_clusters(); cudaDeviceGetAttribute(&nsm, cudaDevAttrMultiProcessorCount, 0); }
    maps.wr = wr; maps.wi = wi;
    launch(prep_kernel, 128, 512, 0, 1, false, x, Wq, Wk, Wv, Wo);
    for (int layer = 0; layer < g_layers; layer++) {
        const bf16* xin = layer ? x2 : x;
        launch(rec_kernel, 3 * ncl, 512, rec::SMEM, 3, true, maps, xin, x1, mem0, Wq, Wk, Wv, Wo, layer, g_delay % 10000, g_delay / 10000);
        launch(side_kernel, nsm - 3 * (ncl - H_), 512, wk::SMEM, 1, true, maps, xin, x1, layer);
        launch(rowfft_kernel, 128, 256, ONE_PER_SM, 1, true, xin, x1, Wq, Wk, Wv, layer);
        launch(colfft_kernel, 107, 384, CF_SMEM, 1, true, layer);
        launch(rowifft_kernel, 128, 256, ONE_PER_SM, 1, true, (const bf16*)x1, layer ? (bf16*)d_out : x2, layer);
    }
}
```

```cpp
#include <cuda_runtime.h>
#include <cuda_bf16.h>
#include <cuda.h>
#include <stdint.h>

#define DEV __device__ __forceinline__
typedef unsigned long long u64;
typedef __nv_bfloat16 bf16;

namespace {

constexpr int S_ = 2048, D_ = 640, H_ = 32, E_ = 128, NSEG = 64;

__device__ __align__(1024) unsigned char g_xn[S_ * D_ * 2];
__device__ __align__(1024) unsigned char g_o[S_ * H_ * E_ * 2];
constexpr int ACC_LAYER = 32 * 5120;
__device__ __align__(4096) u64 g_acc[2 * ACC_LAYER];
__device__ __align__(16) float g_nrm[256];
__device__ __align__(1024) unsigned char g_p[NSEG * H_ * 3 * 4096];
constexpr int SYNC_LAYER = 1024 + 64 * 32;
__device__ __align__(128) uint32_t g_sync[2 * SYNC_LAYER];
__device__ __align__(1024) bf16 g_x1[S_ * D_];
__device__ __align__(1024) bf16 g_x2[S_ * D_];
constexpr int YT_ROWS = 128;
__device__ __align__(1024) float g_yt[2 * YT_ROWS * D_];
constexpr int NCOL = 321;
__device__ __align__(1024) unsigned char g_z[NCOL * 8192];
__device__ __align__(1024) unsigned char g_wt[NCOL * 8192];
__device__ __align__(1024) uint4 g_f128[2 * 8 * 256];
__device__ __align__(1024) uint4 g_f64[2 * 4 * 128];
__device__ __align__(1024) bf16 g_g32[2 * 4096];
#define TLI(id, k, v)
#define TLS(i)
#define TLE(i)

DEV uint32_t s2u(const void* p) { return (uint32_t)__cvta_generic_to_shared(p); }
DEV uint32_t clk() { uint32_t c; asm volatile("mov.u32 %0,%%clock;" : "=r"(c)::"memory"); return c; }
DEV uint32_t gtime32() { uint32_t t; asm volatile("mov.u32 %0,%%globaltimer_lo;" : "=r"(t)::"memory"); return t; }
DEV uint32_t cta_rank() { uint32_t r; asm volatile("mov.u32 %0,%%cluster_ctarank;" : "=r"(r)); return __shfl_sync(~0u, r, 0); }
DEV uint32_t mapa(uint32_t a, uint32_t r) { uint32_t o; asm("mapa.shared::cluster.u32 %0,%1,%2;" : "=r"(o) : "r"(a), "r"(r)); return o; }
DEV void mbar_init(uint32_t b, uint32_t n) { asm volatile("mbarrier.init.shared::cta.b64 [%0],%1;" ::"r"(b), "r"(n) : "memory"); }
DEV bool mbar_try(uint32_t b, uint32_t par, int) {
    uint32_t ok;
    asm volatile("{.reg .pred p; mbarrier.test_wait.parity.shared::cta.b64 p,[%1],%2; selp.u32 %0,1,0,p;}" : "=r"(ok) : "r"(b), "r"(par) : "memory");
    return ok;
}
DEV bool mbar_try(uint32_t b, uint32_t par) {
    uint32_t ok;
    asm volatile("{.reg .pred p; mbarrier.try_wait.parity.shared::cta.b64 p,[%1],%2; selp.u32 %0,1,0,p;}" : "=r"(ok) : "r"(b), "r"(par) : "memory");
    return ok;
}
constexpr uint32_t SPIN_LIMIT = 1u << 18;
DEV void die() { __trap(); }
DEV void mbar_wait(uint32_t b, uint32_t par) {
    uint32_t n = 0;
    while (!mbar_try(b, par)) if (++n > SPIN_LIMIT) die();
}
DEV void mbar_spin(uint32_t b, uint32_t par) { while (!mbar_try(b, par)) {} }
DEV uint32_t opaque(uint32_t x) { return __shfl_xor_sync(~0u, x, 0); }
#define SFENCE() asm volatile("{.reg .pred p; setp.ne.u32 p,%1,0; @p mov.u32 %0,%%clock;}" : "+r"(sfd) : "r"((uint32_t)never) : "memory")
DEV void mbar_arrive(uint32_t b) { asm volatile("mbarrier.arrive.shared::cta.b64 _,[%0];" ::"r"(b) : "memory"); }
DEV void mbar_arrive_elect(uint32_t b) { asm volatile("{.reg .pred p; elect.sync _|p, 0xffffffff; @p mbarrier.arrive.shared::cta.b64 _,[%0];}" ::"r"(b) : "memory"); }
DEV void mbar_arrive_elect_if(uint32_t b, bool c) {
    asm volatile("{.reg .pred p, q; setp.ne.u32 q,%1,0; elect.sync _|p, 0xffffffff; and.pred p,p,q; @p mbarrier.arrive.shared::cta.b64 _,[%0];}" ::"r"(b), "r"((uint32_t)c) : "memory");
}
DEV void mbar_expect_elect(uint32_t b, uint32_t tx) {
    asm volatile("{.reg .pred p; elect.sync _|p, 0xffffffff; @p mbarrier.arrive.expect_tx.shared::cta.b64 _,[%0],%1;}" ::"r"(b), "r"(tx) : "memory");
}
DEV void mbar_arrive_remote_elect(uint32_t b) { asm volatile("{.reg .pred p; elect.sync _|p, 0xffffffff; @p mbarrier.arrive.shared::cluster.b64 _,[%0];}" ::"r"(b) : "memory"); }
DEV bool elect() { uint32_t r; asm volatile("{.reg .pred p; elect.sync _|p, 0xffffffff; selp.u32 %0,1,0,p;}" : "=r"(r)); return r; }
DEV void mbar_arrive_remote(uint32_t b) { asm volatile("mbarrier.arrive.shared::cluster.b64 _,[%0];" ::"r"(b) : "memory"); }
DEV void mbar_expect(uint32_t b, uint32_t tx) { asm volatile("mbarrier.arrive.expect_tx.shared::cta.b64 _,[%0],%1;" ::"r"(b), "r"(tx) : "memory"); }
DEV void bar_sync(int id, int n) { asm volatile("bar.sync %0,%1;" ::"r"(id), "r"(n) : "memory"); }
DEV void bar_arrive(int id, int n) { asm volatile("bar.arrive %0,%1;" ::"r"(id), "r"(n) : "memory"); }
template <int ID, int N> DEV void bar_arrive_if(bool p) {
    asm volatile("{.reg .pred p; setp.ne.u32 p,%0,0; @p bar.arrive %1,%2;}" ::"r"((uint32_t)p), "n"(ID), "n"(N) : "memory");
}
DEV void prefetch_bulk(const void* p, uint32_t bytes) { asm volatile("cp.async.bulk.prefetch.L2.global [%0],%1;" ::"l"(p), "r"(bytes) : "memory"); }
DEV void prefetch_l2(const void* p) { asm volatile("prefetch.global.L2 [%0];" ::"l"(p) : "memory"); }
template <int ID, int N> DEV void bar_sync_if(bool p) {
    asm volatile("{.reg .pred p; setp.ne.u32 p,%0,0; @p bar.sync %1,%2;}" ::"r"((uint32_t)p), "n"(ID), "n"(N) : "memory");
}
DEV void st_remote(uint32_t a, uint32_t x) { asm volatile("st.relaxed.cluster.shared::cluster.u32 [%0],%1;" ::"r"(a), "r"(x) : "memory"); }
DEV void st_async1(uint32_t a, uint32_t x, uint32_t b) {
    asm volatile("st.async.shared::cluster.mbarrier::complete_tx::bytes.u32 [%0],%1,[%2];" ::"r"(a), "r"(x), "r"(b) : "memory");
}
DEV void st_async2(uint32_t a, uint32_t x, uint32_t y, uint32_t b) {
    asm volatile("st.async.shared::cluster.mbarrier::complete_tx::bytes.v2.u32 [%0],{%1,%2},[%3];" ::"r"(a), "r"(x), "r"(y), "r"(b) : "memory");
}
DEV void st_async4(uint32_t a, uint32_t x, uint32_t y, uint32_t z, uint32_t w, uint32_t b) {
    asm volatile("st.async.shared::cluster.mbarrier::complete_tx::bytes.v4.u32 [%0],{%1,%2,%3,%4},[%5];" ::"r"(a), "r"(x), "r"(y), "r"(z), "r"(w), "r"(b) : "memory");
}
DEV void bulk_g2s(uint32_t dst, const void* src, uint32_t bytes, uint32_t b) {
    asm volatile("cp.async.bulk.shared::cluster.global.mbarrier::complete_tx::bytes [%0],[%1],%2,[%3];" ::"r"(dst), "l"(src), "r"(bytes), "r"(b) : "memory");
}
DEV void bulk_g2s_elect(uint32_t dst, const void* src, uint32_t bytes, uint32_t b) {
    asm volatile("{.reg .pred p; elect.sync _|p, 0xffffffff; @p cp.async.bulk.shared::cluster.global.mbarrier::complete_tx::bytes [%0],[%1],%2,[%3];}"
                 ::"r"(dst), "l"(src), "r"(bytes), "r"(b) : "memory");
}
DEV void bulk_g2s_all3_elect(uint32_t dst, const void* src, uint32_t bytes, uint32_t b) {
    asm volatile("{.reg .pred p; elect.sync _|p, 0xffffffff; @p cp.async.bulk.shared::cluster.global.mbarrier::complete_tx::bytes.multicast::cluster [%0],[%1],%2,[%3],%4;}"
                 ::"r"(dst), "l"(src), "r"(bytes), "r"(b), "h"((unsigned short)7) : "memory");
}
DEV void bulk_s2s_elect(uint32_t dst, uint32_t src, uint32_t bytes, uint32_t b) {
    asm volatile("{.reg .pred p; elect.sync _|p, 0xffffffff; @p cp.async.bulk.shared::cluster.shared::cta.mbarrier::complete_tx::bytes [%0],[%1],%2,[%3];}"
                 ::"r"(dst), "r"(src), "r"(bytes), "r"(b) : "memory");
}
DEV void bulk_s2g_elect(void* dst, uint32_t src, uint32_t bytes) {
    asm volatile("{.reg .pred p; elect.sync _|p, 0xffffffff; @p cp.async.bulk.global.shared::cta.bulk_group [%0],[%1],%2;}" ::"l"(dst), "r"(src), "r"(bytes) : "memory");
}
DEV void bulk_s2s(uint32_t dst, uint32_t src, uint32_t bytes, uint32_t b) {
    asm volatile("cp.async.bulk.shared::cluster.shared::cta.mbarrier::complete_tx::bytes [%0],[%1],%2,[%3];" ::"r"(dst), "r"(src), "r"(bytes), "r"(b) : "memory");
}
DEV void bulk_s2g(void* dst, uint32_t src, uint32_t bytes) {
    asm volatile("cp.async.bulk.global.shared::cta.bulk_group [%0],[%1],%2;" ::"l"(dst), "r"(src), "r"(bytes) : "memory");
}
DEV void tma3d(uint32_t dst, const CUtensorMap* m, int c0, int c1, int c2, uint32_t b) {
    asm volatile("cp.async.bulk.tensor.3d.shared::cluster.global.mbarrier::complete_tx::bytes [%0],[%1,{%3,%4,%5}],[%2];"
                 ::"r"(dst), "l"(m), "r"(b), "r"(c0), "r"(c1), "r"(c2) : "memory");
}
DEV void bulk_commit() { asm volatile("cp.async.bulk.commit_group;" ::: "memory"); }
template <int N> DEV void bulk_wait() { asm volatile("cp.async.bulk.wait_group %0;" ::"n"(N) : "memory"); }
template <int N> DEV void bulk_wait_read() { asm volatile("cp.async.bulk.wait_group.read %0;" ::"n"(N) : "memory"); }
DEV void fence_async_all() { asm volatile("fence.proxy.async;" ::: "memory"); }
DEV void flag_add(uint32_t* p) { fence_async_all(); asm volatile("red.release.gpu.global.add.u32 [%0],1;" ::"l"(p) : "memory"); }
DEV uint32_t ld_acquire(const uint32_t* p) { uint32_t v; asm volatile("ld.acquire.gpu.global.u32 %0,[%1];" : "=r"(v) : "l"(p) : "memory"); return v; }
DEV void flag_wait(const uint32_t* p, uint32_t n) {
    for (uint32_t it = 0; ld_acquire(p) < n; __nanosleep(100)) if (++it > (SPIN_LIMIT << 3)) die();
    fence_async_all();
}
DEV void cp16(uint32_t dst, const void* src) { asm volatile("cp.async.cg.shared.global [%0],[%1],16;" ::"r"(dst), "l"(src) : "memory"); }
DEV void cp_commit() { asm volatile("cp.async.commit_group;" ::: "memory"); }
template <int N> DEV void cp_wait() { asm volatile("cp.async.wait_group %0;" ::"n"(N) : "memory"); }
DEV uint32_t lds32(uint32_t a) { uint32_t x; asm volatile("ld.shared.u32 %0,[%1];" : "=r"(x) : "r"(a) : "memory"); return x; }
DEV void fence_async() { asm volatile("fence.proxy.async.shared::cta;" ::: "memory"); }
DEV uint32_t pack2(float lo, float hi) { uint32_t r; asm("cvt.rn.bf16x2.f32 %0,%1,%2;" : "=r"(r) : "f"(hi), "f"(lo)); return r; }
DEV uint32_t prmt(uint32_t a, uint32_t b, uint32_t s) { uint32_t r; asm("prmt.b32 %0,%1,%2,%3;" : "=r"(r) : "r"(a), "r"(b), "r"(s)); return r; }
DEV float ex2(float x) { float r; asm("ex2.approx.ftz.f32 %0,%1;" : "=f"(r) : "f"(x)); return r; }
DEV float sqrt_approx(float x) { float r; asm("sqrt.approx.ftz.f32 %0,%1;" : "=f"(r) : "f"(x)); return r; }
DEV float rcp(float x) { float r; asm("rcp.approx.ftz.f32 %0,%1;" : "=f"(r) : "f"(x)); return r; }
DEV void lds128(uint32_t* r, uint32_t a) { asm volatile("ld.shared.v4.u32 {%0,%1,%2,%3},[%4];" : "=r"(r[0]), "=r"(r[1]), "=r"(r[2]), "=r"(r[3]) : "r"(a) : "memory"); }
DEV void lds64(uint32_t* r, uint32_t a) { asm volatile("ld.shared.v2.u32 {%0,%1},[%2];" : "=r"(r[0]), "=r"(r[1]) : "r"(a) : "memory"); }
DEV void lds64f(float& x, float& y, uint32_t a) { asm volatile("ld.shared.v2.f32 {%0,%1},[%2];" : "=f"(x), "=f"(y) : "r"(a) : "memory"); }
DEV void lds128f(float* r, uint32_t a) { asm volatile("ld.shared.v4.f32 {%0,%1,%2,%3},[%4];" : "=f"(r[0]), "=f"(r[1]), "=f"(r[2]), "=f"(r[3]) : "r"(a) : "memory"); }
DEV void sts128(uint32_t a, uint32_t x, uint32_t y, uint32_t z, uint32_t w) { asm volatile("st.shared.v4.u32 [%0],{%1,%2,%3,%4};" ::"r"(a), "r"(x), "r"(y), "r"(z), "r"(w) : "memory"); }
DEV void sts64(uint32_t a, uint32_t x, uint32_t y) { asm volatile("st.shared.v2.u32 [%0],{%1,%2};" ::"r"(a), "r"(x), "r"(y) : "memory"); }
DEV void sts32(uint32_t a, uint32_t x) { asm volatile("st.shared.u32 [%0],%1;" ::"r"(a), "r"(x) : "memory"); }
DEV void ldsm4(uint32_t* r, uint32_t a) { asm volatile("ldmatrix.sync.aligned.m8n8.x4.shared.b16 {%0,%1,%2,%3},[%4];" : "=r"(r[0]), "=r"(r[1]), "=r"(r[2]), "=r"(r[3]) : "r"(a) : "memory"); }
DEV void ldsm4t(uint32_t* r, uint32_t a) { asm volatile("ldmatrix.sync.aligned.m8n8.x4.trans.shared.b16 {%0,%1,%2,%3},[%4];" : "=r"(r[0]), "=r"(r[1]), "=r"(r[2]), "=r"(r[3]) : "r"(a) : "memory"); }
DEV void ldsm2(uint32_t* r, uint32_t a) { asm volatile("ldmatrix.sync.aligned.m8n8.x2.shared.b16 {%0,%1},[%2];" : "=r"(r[0]), "=r"(r[1]) : "r"(a) : "memory"); }
DEV void stsm4t(uint32_t a, uint32_t x, uint32_t y, uint32_t z, uint32_t w) { asm volatile("stmatrix.sync.aligned.m8n8.x4.trans.shared.b16 [%0],{%1,%2,%3,%4};" ::"r"(a), "r"(x), "r"(y), "r"(z), "r"(w) : "memory"); }
DEV void stsm4(uint32_t a, uint32_t x, uint32_t y, uint32_t z, uint32_t w) { asm volatile("stmatrix.sync.aligned.m8n8.x4.shared.b16 [%0],{%1,%2,%3,%4};" ::"r"(a), "r"(x), "r"(y), "r"(z), "r"(w) : "memory"); }
DEV void stsm2(uint32_t a, uint32_t x, uint32_t y) { asm volatile("stmatrix.sync.aligned.m8n8.x2.shared.b16 [%0],{%1,%2};" ::"r"(a), "r"(x), "r"(y) : "memory"); }
DEV void sts128f_if(uint32_t a, const float* v, bool p) {
    asm volatile("{.reg .pred p; setp.ne.u32 p,%5,0; @p st.shared.v4.f32 [%0],{%1,%2,%3,%4};}" ::"r"(a), "f"(v[0]), "f"(v[1]), "f"(v[2]), "f"(v[3]), "r"((uint32_t)p) : "memory");
}
DEV void stsm2t_if(uint32_t a, uint32_t x, uint32_t y, bool p) {
    asm volatile("{.reg .pred p; setp.ne.u32 p,%3,0; @p stmatrix.sync.aligned.m8n8.x2.trans.shared.b16 [%0],{%1,%2};}" ::"r"(a), "r"(x), "r"(y), "r"((uint32_t)p) : "memory");
}
DEV void stsm2t(uint32_t a, uint32_t x, uint32_t y) { asm volatile("stmatrix.sync.aligned.m8n8.x2.trans.shared.b16 [%0],{%1,%2};" ::"r"(a), "r"(x), "r"(y) : "memory"); }
DEV void mma16(float* d, uint32_t a0, uint32_t a1, uint32_t a2, uint32_t a3, uint32_t b0, uint32_t b1) {
    asm volatile("mma.sync.aligned.m16n8k16.row.col.f32.bf16.bf16.f32 {%0,%1,%2,%3},{%4,%5,%6,%7},{%8,%9},{%0,%1,%2,%3};"
                 : "+f"(d[0]), "+f"(d[1]), "+f"(d[2]), "+f"(d[3]) : "r"(a0), "r"(a1), "r"(a2), "r"(a3), "r"(b0), "r"(b1));
}
DEV void mma8(float* d, uint32_t a0, uint32_t a1, uint32_t b0) {
    asm volatile("mma.sync.aligned.m16n8k8.row.col.f32.bf16.bf16.f32 {%0,%1,%2,%3},{%4,%5},{%6},{%0,%1,%2,%3};"
                 : "+f"(d[0]), "+f"(d[1]), "+f"(d[2]), "+f"(d[3]) : "r"(a0), "r"(a1), "r"(b0));
}
DEV u64 mkdesc(uint32_t a, uint32_t lbo, uint32_t sbo) { return (u64)((a & 0x3ffff) >> 4) | ((u64)(lbo >> 4) << 16) | ((u64)(sbo >> 4) << 32); }
constexpr u64 SW128 = 1ull << 62;
DEV void wg_fence() { asm volatile("wgmma.fence.sync.aligned;" ::: "memory"); }
DEV void wg_commit() { asm volatile("wgmma.commit_group.sync.aligned;" ::: "memory"); }
template <int N> DEV void wg_wait() { asm volatile("wgmma.wait_group.sync.aligned %0;" ::"n"(N) : "memory"); }
template <int ACC> DEV void wgmma_n32_rs(float* d, const uint32_t* a, u64 desc) {
    asm volatile("wgmma.mma_async.sync.aligned.m64n32k16.f32.bf16.bf16 {%0,%1,%2,%3,%4,%5,%6,%7,%8,%9,%10,%11,%12,%13,%14,%15},{%16,%17,%18,%19},%20,%21,1,1,0;"
                 : "+f"(d[0]), "+f"(d[1]), "+f"(d[2]), "+f"(d[3]), "+f"(d[4]), "+f"(d[5]), "+f"(d[6]), "+f"(d[7]),
                   "+f"(d[8]), "+f"(d[9]), "+f"(d[10]), "+f"(d[11]), "+f"(d[12]), "+f"(d[13]), "+f"(d[14]), "+f"(d[15])
                 : "r"(a[0]), "r"(a[1]), "r"(a[2]), "r"(a[3]), "l"(desc), "n"(ACC));
}
template <int ACC> DEV void wgmma_n32_ss(float* d, u64 da, u64 desc) {
    asm volatile("wgmma.mma_async.sync.aligned.m64n32k16.f32.bf16.bf16 {%0,%1,%2,%3,%4,%5,%6,%7,%8,%9,%10,%11,%12,%13,%14,%15},%16,%17,%18,1,1,0,0;"
                 : "+f"(d[0]), "+f"(d[1]), "+f"(d[2]), "+f"(d[3]), "+f"(d[4]), "+f"(d[5]), "+f"(d[6]), "+f"(d[7]),
                   "+f"(d[8]), "+f"(d[9]), "+f"(d[10]), "+f"(d[11]), "+f"(d[12]), "+f"(d[13]), "+f"(d[14]), "+f"(d[15])
                 : "l"(da), "l"(desc), "n"(ACC));
}
template <int ACC> DEV void wgmma_n16_ss(float* d, u64 da, u64 desc) {
    asm volatile("wgmma.mma_async.sync.aligned.m64n16k16.f32.bf16.bf16 {%0,%1,%2,%3,%4,%5,%6,%7},%8,%9,%10,1,1,0,0;"
                 : "+f"(d[0]), "+f"(d[1]), "+f"(d[2]), "+f"(d[3]), "+f"(d[4]), "+f"(d[5]), "+f"(d[6]), "+f"(d[7])
                 : "l"(da), "l"(desc), "n"(ACC));
}
#define ACC8(o) "+f"(d[o]), "+f"(d[o + 1]), "+f"(d[o + 2]), "+f"(d[o + 3]), "+f"(d[o + 4]), "+f"(d[o + 5]), "+f"(d[o + 6]), "+f"(d[o + 7])
template <int ACC, int TB> DEV void wgmma_n64_rs(float* d, const uint32_t* a, u64 desc) {
    asm volatile("wgmma.mma_async.sync.aligned.m64n64k16.f32.bf16.bf16 {%0,%1,%2,%3,%4,%5,%6,%7,%8,%9,%10,%11,%12,%13,%14,%15,"
                 "%16,%17,%18,%19,%20,%21,%22,%23,%24,%25,%26,%27,%28,%29,%30,%31},{%32,%33,%34,%35},%36,%37,1,1,%38;"
                 : ACC8(0), ACC8(8), ACC8(16), ACC8(24) : "r"(a[0]), "r"(a[1]), "r"(a[2]), "r"(a[3]), "l"(desc), "n"(ACC), "n"(TB));
}
template <int ACC, int TB> DEV void wgmma_n80_rs(float* d, const uint32_t* a, u64 desc) {
    asm volatile("wgmma.mma_async.sync.aligned.m64n80k16.f32.bf16.bf16 {%0,%1,%2,%3,%4,%5,%6,%7,%8,%9,%10,%11,%12,%13,%14,%15,"
                 "%16,%17,%18,%19,%20,%21,%22,%23,%24,%25,%26,%27,%28,%29,%30,%31,%32,%33,%34,%35,%36,%37,%38,%39},{%40,%41,%42,%43},%44,%45,1,1,%46;"
                 : ACC8(0), ACC8(8), ACC8(16), ACC8(24), ACC8(32) : "r"(a[0]), "r"(a[1]), "r"(a[2]), "r"(a[3]), "l"(desc), "n"(ACC), "n"(TB));
}
template <int TA, int TB> DEV void wgmma_n64_ss(float* d, u64 da, u64 db, int acc) {
    asm volatile("{.reg .pred p; setp.ne.b32 p,%34,0; wgmma.mma_async.sync.aligned.m64n64k16.f32.bf16.bf16 {%0,%1,%2,%3,%4,%5,%6,%7,%8,%9,%10,%11,%12,%13,%14,%15,%16,%17,%18,%19,%20,%21,%22,%23,%24,%25,%26,%27,%28,%29,%30,%31},%32,%33,p,1,1,%35,%36;}"
                 : ACC8(0), ACC8(8), ACC8(16), ACC8(24) : "l"(da), "l"(db), "r"(acc), "n"(TA), "n"(TB));
}
template <int TA, int TB> DEV void wgmma_n128_ss(float* d, u64 da, u64 db, int acc) {
    asm volatile("{.reg .pred p; setp.ne.b32 p,%66,0; wgmma.mma_async.sync.aligned.m64n128k16.f32.bf16.bf16 {%0,%1,%2,%3,%4,%5,%6,%7,%8,%9,%10,%11,%12,%13,%14,%15,%16,%17,%18,%19,%20,%21,%22,%23,%24,%25,%26,%27,%28,%29,%30,%31,%32,%33,%34,%35,%36,%37,%38,%39,%40,%41,%42,%43,%44,%45,%46,%47,%48,%49,%50,%51,%52,%53,%54,%55,%56,%57,%58,%59,%60,%61,%62,%63},%64,%65,p,1,1,%67,%68;}"
                 : ACC8(0), ACC8(8), ACC8(16), ACC8(24), ACC8(32), ACC8(40), ACC8(48), ACC8(56) : "l"(da), "l"(db), "r"(acc), "n"(TA), "n"(TB));
}
template <int TA, int TB> DEV void wgmma_n192_ss(float* d, u64 da, u64 db, int acc) {
    asm volatile("{.reg .pred p; setp.ne.b32 p,%98,0; wgmma.mma_async.sync.aligned.m64n192k16.f32.bf16.bf16 {%0,%1,%2,%3,%4,%5,%6,%7,%8,%9,%10,%11,%12,%13,%14,%15,%16,%17,%18,%19,%20,%21,%22,%23,%24,%25,%26,%27,%28,%29,%30,%31,%32,%33,%34,%35,%36,%37,%38,%39,%40,%41,%42,%43,%44,%45,%46,%47,%48,%49,%50,%51,%52,%53,%54,%55,%56,%57,%58,%59,%60,%61,%62,%63,%64,%65,%66,%67,%68,%69,%70,%71,%72,%73,%74,%75,%76,%77,%78,%79,%80,%81,%82,%83,%84,%85,%86,%87,%88,%89,%90,%91,%92,%93,%94,%95},%96,%97,p,1,1,%99,%100;}"
                 : ACC8(0), ACC8(8), ACC8(16), ACC8(24), ACC8(32), ACC8(40), ACC8(48), ACC8(56), ACC8(64), ACC8(72), ACC8(80), ACC8(88) : "l"(da), "l"(db), "r"(acc), "n"(TA), "n"(TB));
}
template <int ACC> DEV void wgmma_n40_ss(float* d, u64 da, u64 desc) {
    asm volatile("wgmma.mma_async.sync.aligned.m64n40k16.f32.bf16.bf16 {%0,%1,%2,%3,%4,%5,%6,%7,%8,%9,%10,%11,%12,%13,%14,%15,%16,%17,%18,%19},%20,%21,%22,1,1,0,0;"
                 : ACC8(0), ACC8(8), "+f"(d[16]), "+f"(d[17]), "+f"(d[18]), "+f"(d[19]) : "l"(da), "l"(desc), "n"(ACC));
}
DEV void pdl_wait() { asm volatile("griddepcontrol.wait;" ::: "memory"); }
DEV void pdl_launch() { asm volatile("griddepcontrol.launch_dependents;" ::: "memory"); }
DEV uint32_t ldg32(const void* p) { uint32_t v; asm volatile("ld.global.nc.u32 %0,[%1];" : "=r"(v) : "l"(p)); return v; }
DEV void ld_acc(u64& a, u64& b, const void* p) {
    const uint32_t done = (uint32_t)a & (uint32_t)b & 32u;
    asm volatile("{.reg .pred p; setp.eq.u32 p,%3,0;\n"
                 "@p ld.relaxed.gpu.global.v2.u64 {%0,%1},[%2];}" : "+l"(a), "+l"(b) : "l"(p), "r"(done) : "memory");
}
DEV void ld_acc0(u64& a, u64& b, const void* p) {
    asm volatile("ld.relaxed.gpu.global.v2.u64 {%0,%1},[%2];" : "=l"(a), "=l"(b) : "l"(p) : "memory");
}
DEV uint32_t and3(uint32_t a, uint32_t b, uint32_t c) { uint32_t r; asm volatile("lop3.b32 %0,%1,%2,%3,0x80;" : "=r"(r) : "r"(a), "r"(b), "r"(c)); return r; }
DEV uint32_t absmax2(uint32_t a, uint32_t b) { uint32_t r; asm("max.xorsign.abs.bf16x2 %0,%1,%2;" : "=r"(r) : "r"(a), "r"(b)); return r; }
DEV float lds32f(uint32_t a) { float x; asm volatile("ld.shared.f32 %0,[%1];" : "=f"(x) : "r"(a) : "memory"); return x; }
DEV void red_add64(u64* p, uint32_t lo, uint32_t hi) {
    asm volatile("{.reg .b64 v; mov.b64 v,{%1,%2}; red.relaxed.gpu.global.add.u64 [%0],v;}" ::"l"(p), "r"(lo), "r"(hi) : "memory");
}
DEV float bf_round(float x) { return __bfloat162float(__float2bfloat16_rn(x)); }
DEV float bf_lo(uint32_t u) { return __uint_as_float(u << 16); }
DEV float bf_hi(uint32_t u) { return __uint_as_float(u & 0xffff0000u); }

#define GPROF(i, n)
#define PROFT(i)
#define STAMP(i)

DEV void unpack8(float* v, uint4 u) {
    v[0] = bf_lo(u.x); v[1] = bf_hi(u.x); v[2] = bf_lo(u.y); v[3] = bf_hi(u.y);
    v[4] = bf_lo(u.z); v[5] = bf_hi(u.z); v[6] = bf_lo(u.w); v[7] = bf_hi(u.w);
}
DEV int xn_off(int row, int chunk) { return (row >> 5) * 40960 + (chunk >> 3) * 4096 + (row & 31) * 128 + (((chunk ^ row) & 7) << 4); }

DEV void ln_row(float (&v)[3][8], int lane) {
    float s = 0.f;
#pragma unroll
    for (int c = 0; c < 3; c++)
#pragma unroll
        for (int j = 0; j < 8; j++) s += v[c][j];
#pragma unroll
    for (int o = 16; o; o >>= 1) s += __shfl_xor_sync(~0u, s, o);
    float mean = s * (1.f / D_), q = 0.f;
#pragma unroll
    for (int c = 0; c < 3; c++)
        if (c < 2 || lane < 16)
#pragma unroll
            for (int j = 0; j < 8; j++) { float d = v[c][j] - mean; q += d * d; }
#pragma unroll
    for (int o = 16; o; o >>= 1) q += __shfl_xor_sync(~0u, q, o);
    float mb = bf_round(mean);
    float inv = 1.f / bf_round(sqrtf(bf_round(bf_round(q * (1.f / D_)) + 1e-5f)));
#pragma unroll
    for (int c = 0; c < 3; c++)
#pragma unroll
        for (int j = 0; j < 8; j++) v[c][j] = bf_round(v[c][j] - mb) * inv;
}

__host__ __device__ constexpr int col_freq(int c) {
    return c == 320 ? 320 : c < 192 ? (c >> 6) * 128 + (c & 63) : c == 192 ? 192 : c < 256 ? 448 - c : c == 256 ? 64 : 384 - c;
}
DEV float rdft(int n, int k, int sn, int N) {
    float s, c;
    sincospif((float)((n * k) & (N - 1)) * (2.f / N), &s, &c);
    return !sn ? c : k ? s : (n & 1 ? -1.f : 1.f);
}

__global__ void __launch_bounds__(512) prep_kernel(const bf16* __restrict__ x, const bf16* __restrict__ Wq, const bf16* __restrict__ Wk,
                                                   const bf16* __restrict__ Wv, const bf16* __restrict__ Wo) {
    __shared__ float red[32], col[4][640];
    const int tid = threadIdx.x, lane = tid & 31, warp = tid >> 5, b = blockIdx.x, row = b * 16 + warp;
    TLS(0);
    pdl_launch();
    uint4 ux[3], uv[5], uo[8];
#pragma unroll
    for (int c = 0; c < 3; c++) ux[c] = c < 2 || lane < 16 ? *(const uint4*)(x + row * D_ + (c * 32 + lane) * 8) : make_uint4(0, 0, 0, 0);
#pragma unroll
    for (int i = 0; i < 5; i++) uv[i] = *(const uint4*)(Wv + (size_t)((b & 3) * 160 + i * 32 + (tid >> 4)) * 4096 + (b >> 2) * E_ + (tid & 15) * 8);
    if (tid < 320) {
#pragma unroll
        for (int r = 0; r < 8; r++) uo[r] = *(const uint4*)(Wo + (size_t)(b * 32 + tid / 80 * 8 + r) * D_ + tid % 80 * 8);
    }
    if (tid >= 504) prefetch_bulk((const char*)(tid & 4 ? Wk : Wq) + (b * 4 + (tid & 3)) * 10240, 10240);
    if (b < 3) ((uint4*)g_sync)[b * 512 + tid] = make_uint4(0, 0, 0, 0);
    for (int i = b * 512 + tid; i < ACC_LAYER; i += 128 * 512) ((uint4*)g_acc)[i] = make_uint4(0, 0, 0, 0);
    if (tid < 2 * YT_ROWS * D_ / 4 / 128) ((uint4*)g_yt)[b * (2 * YT_ROWS * D_ / 4 / 128) + tid] = make_uint4(0, 0, 0, 0);
    const int gid = tid < 104 ? b * 104 + tid : 1 << 20;
    if (gid < 4096) {
        const int inv = gid >> 11, ks = (gid >> 8) & 7, t = gid & 255, g = (t & 31) >> 2, q = t & 3, tile = t >> 5;
        uint32_t v[4];
#pragma unroll
        for (int j = 0; j < 4; j++) {
            float x[2];
#pragma unroll
            for (int u = 0; u < 2; u++) {
                const int m = inv ? 16 * tile + 2 * g + (j & 1) : 16 * ks + 8 * (j >> 1) + 2 * q + u;
                const int k2 = inv ? 8 * ks + 2 * q + u : 8 * tile + g, sn = inv ? j >> 1 : j & 1;
                x[u] = rdft(m, k2, sn, 128);
                if (sn && k2) x[u] = -x[u];
            }
            v[j] = pack2(x[0], x[1]);
        }
        g_f128[gid] = make_uint4(v[0], v[1], v[2], v[3]);
    } else if (gid < 5120) {
        const int id = gid - 4096, inv = id >> 9, ks = (id >> 7) & 3, t = id & 127, g = (t & 31) >> 2, q = t & 3, tile = t >> 5;
        uint32_t v[4];
#pragma unroll
        for (int j = 0; j < 4; j++) {
            float x[2];
#pragma unroll
            for (int u = 0; u < 2; u++) {
                const int a = inv ? 16 * tile + g + 8 * (j & 1) : 16 * ks + 8 * (j >> 1) + 2 * q + u;
                const int ka = inv ? 8 * ks + 2 * q + u : 8 * tile + g, sn = inv ? j >> 1 : j & 1;
                x[u] = rdft(a, ka, sn, 64);
            }
            v[j] = pack2(x[0], x[1]);
        }
        g_f64[id] = make_uint4(v[0], v[1], v[2], v[3]);
    } else if (gid < 5120 + 8192) {
        const int id = gid - 5120, inv = id >> 12, n = ((id >> 9) & 7) * 8 + ((id >> 3) & 7), k = ((id >> 6) & 7) * 8 + (id & 7);
        float s, c;
        sincospif((float)(((n >> 1) * (k >> 1)) & 31) * (1.f / 16), &s, &c);
        if (inv) s = -s;
        g_g32[id] = __float2bfloat16_rn((n & 1) == (k & 1) ? c : (k & 1) ? s : -s);
    }
    {
        float v[3][8];
#pragma unroll
        for (int c = 0; c < 3; c++) unpack8(v[c], ux[c]);
        ln_row(v, lane);
#pragma unroll
        for (int c = 0; c < 3; c++)
            if (c < 2 || lane < 16)
                *(uint4*)(g_xn + xn_off(row, c * 32 + lane)) =
                    make_uint4(pack2(v[c][0], v[c][1]), pack2(v[c][2], v[c][3]), pack2(v[c][4], v[c][5]), pack2(v[c][6], v[c][7]));
    }
    float sv = 0.f;
#pragma unroll
    for (int i = 0; i < 5; i++) {
        float w[8];
        unpack8(w, uv[i]);
#pragma unroll
        for (int j = 0; j < 8; j++) sv += w[j] * w[j];
    }
    if (tid < 320) {
        float a[8] = {0.f, 0.f, 0.f, 0.f, 0.f, 0.f, 0.f, 0.f};
#pragma unroll
        for (int r = 0; r < 8; r++) {
            float w[8];
            unpack8(w, uo[r]);
#pragma unroll
            for (int j = 0; j < 8; j++) a[j] += w[j] * w[j];
        }
#pragma unroll
        for (int j = 0; j < 8; j++) col[tid / 80][tid % 80 * 8 + j] = a[j];
    }
    __syncthreads();
    float so = (col[0][tid] + col[1][tid]) + (col[2][tid] + col[3][tid]);
    if (tid < 128) so = fmaxf(so, (col[0][512 + tid] + col[1][512 + tid]) + (col[2][512 + tid] + col[3][512 + tid]));
#pragma unroll
    for (int o = 16; o; o >>= 1) { sv += __shfl_xor_sync(~0u, sv, o); so = fmaxf(so, __shfl_xor_sync(~0u, so, o)); }
    if (lane == 0) { red[warp] = sv; red[16 + warp] = so; }
    __syncthreads();
    if (tid == 0) {
        float a = 0.f, c = 0.f;
        for (int i = 0; i < 16; i++) { a += red[i]; c = fmaxf(c, red[16 + i]); }
        g_nrm[b] = a; g_nrm[128 + b] = c;
    }
    TLE(0);
}

DEV void filter_tile(const bf16* __restrict__ wr, const bf16* __restrict__ wi, int ka, int c) {
    const int kn = ka ? 2048 - ka : 32, kc = col_freq(c);
    const unsigned short* pr = (const unsigned short*)wr + kc;
    const unsigned short* pi = (const unsigned short*)wi + kc;
#pragma unroll 1
    for (int i = 0; i < 4; i += 2) {
        unsigned short a[32], b[32];
#pragma unroll
        for (int n = 0; n < 32; n++) {
            const int k = ((n & 1 ? kn : ka) + 64 * (4 * (2 * (i + (n >> 4)) + ((n >> 1) & 1)) + ((n >> 2) & 3))) & 2047;
            a[n] = __ldg(pr + k * NCOL); b[n] = __ldg(pi + k * NCOL);
        }
#pragma unroll
        for (int n = 0; n < 32; n += 4)
            *(uint4*)(g_wt + c * 8192 + (i + (n >> 4)) * 2048 + (ka * 4 + ((n >> 2) & 3)) * 16) =
                make_uint4(a[n] | ((uint32_t)b[n] << 16), a[n + 1] | ((uint32_t)b[n + 1] << 16), a[n + 2] | ((uint32_t)b[n + 2] << 16), a[n + 3] | ((uint32_t)b[n + 3] << 16));
    }
}

namespace wk {
constexpr int STAGE = 49152, NST = 4, OFF_OUT = 3 * STAGE, OFF_RED = 4 * STAGE, OFF_BAR = OFF_RED + 32768, SMEM = OFF_BAR + 128;
constexpr int NPB = 12;
__host__ __device__ constexpr int pb_start(int b) { return b == 0 ? 0 : b == 1 ? 2 : b < NPB ? 6 * b - 6 : 64; }
#define NOB 7
#define SPLIT_A 3
#define SPLIT_B 11
constexpr int N_P = NPB * H_, I_F = N_P, I_OB = I_F + 32, I_OT = I_OB + NOB * 5, I_SA = I_OT + (30 - 3 * NOB) * 10;
constexpr int I_SB = I_SA + 10 * SPLIT_A, N_ITEMS = I_SB + 10 * SPLIT_B;
DEV void ot_decode(int id, int& b, int& nt, int& k0, int& k1) {
    const int base = id < I_SA ? I_OT : id < I_SB ? I_SA : I_SB, j = (id - base) / 10;
    nt = (id - base) % 10;
    if (id < I_SA) { b = 3 * NOB + j; k0 = 0; k1 = 22; }
    else if (id < I_SB) { b = 30; k0 = 22 * j / SPLIT_A; k1 = 22 * (j + 1) / SPLIT_A; }
    else { b = 31; k0 = 22 * j / SPLIT_B; k1 = 22 * (j + 1) / SPLIT_B; }
}
enum { SY_TICKET = 0, SY_O = 32, SY_P = 128 };
}
struct Ring {
    int st; uint32_t ph;
    DEV uint32_t par() const { return (ph >> st) & 1; }
    DEV void next(int n) { ph ^= 1u << st; st = st + 1 >= n ? 0 : st + 1; }
};
struct Maps { CUtensorMap wq2, wv1, wo2, wo1, x6, x2, o6, o2; const bf16 *wr, *wi; };

template <int NSG> DEV void proj_tile(uint32_t sb, uint32_t bar, Ring& rg, int wg, int id) {
    using namespace wk;
    float acc[NSG * 16];
#pragma unroll
    for (int i = 0; i < NSG * 16; i++) acc[i] = 0.f;
    const int lane = threadIdx.x & 31, ww = (threadIdx.x >> 5) & 3;
    for (int kb = 0; kb < 10; kb++, rg.next(3)) {
        const int st = rg.st;
        if (kb) mbar_wait(bar + 8 * st, rg.par());
        const u64 da = mkdesc(sb + st * STAGE + wg * 8192, 0, 1024) | SW128, db = mkdesc(sb + st * STAGE + 24576, 0, 1024) | SW128;
        wg_fence();
#pragma unroll
        for (int ks = 0; ks < 4; ks++) {
            if (NSG == 2) wgmma_n64_ss<1, 0>(acc, da + ks * 128, db + ks * 2, 1);
            if (NSG == 4) wgmma_n128_ss<1, 0>(acc, da + ks * 128, db + ks * 2, 1);
            if (NSG == 6) wgmma_n192_ss<1, 0>(acc, da + ks * 128, db + ks * 2, 1);
        }
        wg_commit();
        wg_wait<0>();
        mbar_arrive_elect(bar + 8 * (NST + st));
    }
    const uint32_t out = sb + OFF_OUT + wg * 24576;
    bar_sync(5 + wg, 160);
    const uint32_t la = out + (wg < 2 ? (lane >> 4) * 1024 + ww * 256 + (lane & 15) * 16 : ww * 1024 + ((lane >> 3) & 1) * 512 + (lane >> 4) * 128 + (lane & 7) * 16);
#pragma unroll
    for (int j = 0; j < 2 * NSG; j++) {
        const float* c = acc + 8 * j;
        const uint32_t p0 = pack2(c[0], c[1]), p1 = pack2(c[2], c[3]), p2 = pack2(c[4], c[5]), p3 = pack2(c[6], c[7]);
        if (wg < 2) stsm4t(la + j * 2048, p0, p1, p2, p3);
        else stsm4(la + (j >> 1) * 4096 + (j & 1) * 256, p0, p1, p2, p3);
    }
    if ((threadIdx.x & 127) == 0) sts32(bar + 80 + 4 * wg, id);
    fence_async();
    bar_arrive(1 + wg, 160);
}

DEV uint32_t resid(uint32_t u, float a, float b) { return pack2(bf_lo(u) + bf_round(a), bf_hi(u) + bf_round(b)); }

DEV void worker(uint32_t sb, const Maps& maps, const bf16* __restrict__ x, bf16* __restrict__ x1, int layer) {
    using namespace wk;
    const uint32_t bar = sb + OFF_BAR, slot = bar + 64;
    const int tid = threadIdx.x, lane = tid & 31, warp = __shfl_sync(~0u, tid >> 5, 0);
    uint32_t* sy = g_sync + layer * SYNC_LAYER;
    if (tid == 0) {
        for (int i = 0; i < NST; i++) { mbar_init(bar + 8 * i, 1); mbar_init(bar + 8 * (NST + i), 12); }
        asm volatile("fence.mbarrier_init.release.cluster;" ::: "memory");
    }
    __syncthreads();
    if (warp > 12) {
        const int wg = warp - 13;
        bar_arrive(5 + wg, 160);
        for (;;) {
            bar_sync(1 + wg, 160);
            const int id = (int)lds32(bar + 80 + 4 * wg);
            if (id < 0) break;
            const int s0 = pb_start(id >> 5), ns = pb_start((id >> 5) + 1) - s0;
            if (lane == 0) {
                for (int j = 0; j < ns; j++)
                    bulk_s2g(g_p + (size_t)(((s0 + j) * H_ + (id & 31)) * 3 + wg) * 4096, sb + OFF_OUT + wg * 24576 + j * 4096, 4096);
                bulk_commit();
                bulk_wait<0>();
                flag_add(sy + SY_P + id);
            }
            __syncwarp();
            bar_arrive(5 + wg, 160);
        }
    } else if (warp == 12) {
        if (lane == 0) {
            Ring rg = {0, 7u};
            auto acquire = [&]() { mbar_wait(bar + 8 * (NST + rg.st), rg.par()); return sb + rg.st * STAGE; };
            for (;;) {
                int id = (int)atomicAdd(sy + SY_TICKET, 1u);
                if (layer && id >= I_F) id += I_OB - I_F;
                if (id >= N_ITEMS) id = -1;
                if (id >= 0) { TLI(id, 0, gtime()); TLI(id, 3, blockIdx.x + (gridDim.x % 3 == 0 && gridDim.x > 111 ? 0 : 1000)); }
                uint32_t d = acquire();
                sts32(slot + 4 * rg.st, id);
                if (id < 0) { mbar_arrive(bar + 8 * rg.st); break; }
                if (id < N_P) {
                    const int b = id >> 5, h = id & 31, s0 = pb_start(b), ns = pb_start(b + 1) - s0;
                    for (int kb = 0; kb < 10; kb++, rg.next(3)) {
                        if (kb) d = acquire();
                        const uint32_t fb = bar + 8 * rg.st;
                        mbar_expect(fb, 24576 + ns * 4096);
                        tma3d(d, &maps.wq2, 0, kb * 64, 2 * h, fb);
                        tma3d(d + 16384, &maps.wv1, 0, kb * 64, 2 * h, fb);
                        if (ns == 6) tma3d(d + 24576, &maps.x6, 0, 2 * kb, s0, fb);
                        else for (int j = 0; j < ns; j += 2) tma3d(d + 24576 + j * 4096, &maps.x2, 0, 2 * kb, s0 + j, fb);
                    }
                } else if (id < I_OB) {
                    mbar_arrive(bar + 8 * rg.st);
                    mbar_wait(bar + 8 * (NST + rg.st), rg.par() ^ 1);
                    rg.next(NST);
                } else if (id < I_OT) {
                    const int b = (id - I_OB) / 5, nt = (id - I_OB) % 5;
                    for (int j = 0; j < 6; j++) flag_wait(sy + SY_O + 6 * b + j, 64);
                    for (int kb = 0; kb < 64; kb++, rg.next(NST)) {
                        if (kb) d = acquire();
                        const uint32_t fb = bar + 8 * rg.st;
                        mbar_expect(fb, 40960);
                        tma3d(d, &maps.o6, 0, 2 * kb, 6 * b, fb);
                        tma3d(d + 24576, &maps.wo2, 0, kb * 64, 2 * nt, fb);
                    }
                } else {
                    int b, nt, k0, k1;
                    ot_decode(id, b, nt, k0, k1);
                    for (int kb = k0; kb < k1; kb++, rg.next(NST)) {
                        if (kb > k0) d = acquire();
                        const uint32_t fb = bar + 8 * rg.st;
                        mbar_expect(fb, 49152);
                        tma3d(d + 24576, &maps.wo1, 0, 3 * kb * 64, nt, fb);
                        if (kb == k0) for (int j = 0; j < 2; j++) flag_wait(sy + SY_O + 2 * b + j, 64);
                        for (int u = 0; u < 3; u++) tma3d(d + u * 8192, &maps.o2, 0, 2 * (3 * kb + u), 2 * b, fb);
                    }
                }
            }
        }
    } else {
        const int wg = warp >> 2, g = lane >> 2, q = lane & 3;
        Ring rg = {0, 0u};
        bool stores_done = false;
        for (;;) {
            mbar_wait(bar + 8 * rg.st, rg.par());
            const int id = (int)lds32(slot + 4 * rg.st);
            if ((id < 0 || id >= N_P) && !stores_done) {
                bar_sync(5 + wg, 160);
                if ((tid & 127) == 0) sts32(bar + 80 + 4 * wg, ~0u);
                bar_arrive(1 + wg, 160);
                stores_done = true;
                bar_sync(4, 384);
                mbar_arrive_elect(bar + 8 * (NST + 3));
            }
            if (id < 0) break;
            if (tid == 0) TLI(id, 1, gtime());
            if (id < N_P) {
                const int b = id >> 5;
                if (b == 0) proj_tile<2>(sb, bar, rg, wg, id);
                else if (b == 1 || b == NPB - 1) proj_tile<4>(sb, bar, rg, wg, id);
                else proj_tile<6>(sb, bar, rg, wg, id);
            } else if (id < I_OB) {
                if (tid < NCOL) filter_tile(maps.wr, maps.wi, id - I_F, tid);
                __syncwarp();
                mbar_arrive_elect(bar + 8 * (NST + rg.st));
                rg.next(NST);
            } else if (id < I_OT) {
                const int b = (id - I_OB) / 5, nt = (id - I_OB) % 5;
                const size_t o = (size_t)(192 * b + 16 * warp + g) * D_ + nt * 128 + 2 * q;
                float acc[64];
#pragma unroll
                for (int i = 0; i < 64; i++) acc[i] = 0.f;
                for (int kb = 0; kb < 64; kb++, rg.next(NST)) {
                    const int st = rg.st;
                    if (kb) mbar_wait(bar + 8 * st, rg.par());
                    const u64 da = mkdesc(sb + st * STAGE + wg * 8192, 128, 1024), db = mkdesc(sb + st * STAGE + 24576, 8192, 1024) | SW128;
                    wg_fence();
#pragma unroll
                    for (int ks = 0; ks < 4; ks++) wgmma_n128_ss<0, 1>(acc, da + ks * 16, db + ks * 128, 1);
                    wg_commit();
                    wg_wait<0>();
                    mbar_arrive_elect(bar + 8 * (NST + st));
                }
                uint32_t xr[32];
#pragma unroll
                for (int t = 0; t < 32; t++) xr[t] = ldg32(x + o + 8 * (t >> 1) + (t & 1) * 8 * D_);
#pragma unroll
                for (int t = 0; t < 32; t++) *(uint32_t*)(x1 + o + 8 * (t >> 1) + (t & 1) * 8 * D_) = resid(xr[t], acc[2 * t], acc[2 * t + 1]);
            } else {
                int b, nt, k0, k1;
                ot_decode(id, b, nt, k0, k1);
                const size_t o = (size_t)(64 * b + 16 * (warp & 3) + g) * D_ + nt * 64 + 2 * q;
                float acc[32];
                uint32_t xr[16];
#pragma unroll
                for (int t = 0; t < 16; t++) xr[t] = wg == 0 && id < I_SA ? ldg32(x + o + 8 * (t >> 1) + (t & 1) * 8 * D_) : 0;
#pragma unroll
                for (int i = 0; i < 32; i++) acc[i] = 0.f;
                for (int kb = k0; kb < k1; kb++, rg.next(NST)) {
                    const int st = rg.st;
                    if (kb > k0) mbar_wait(bar + 8 * st, rg.par());
                    const u64 da = mkdesc(sb + st * STAGE + wg * 8192, 128, 1024), db = mkdesc(sb + st * STAGE + 24576 + wg * 8192, 0, 1024) | SW128;
                    wg_fence();
#pragma unroll
                    for (int ks = 0; ks < 4; ks++) wgmma_n64_ss<0, 1>(acc, da + ks * 16, db + ks * 128, 1);
                    wg_commit();
                    wg_wait<0>();
                    mbar_arrive_elect(bar + 8 * (NST + st));
                }
                const uint32_t ra = sb + OFF_RED + (tid & 127) * 16;
                if (wg) {
#pragma unroll
                    for (int t = 0; t < 8; t++)
                        sts128(ra + (wg - 1) * 16384 + t * 2048, __float_as_uint(acc[4 * t]), __float_as_uint(acc[4 * t + 1]), __float_as_uint(acc[4 * t + 2]), __float_as_uint(acc[4 * t + 3]));
                }
                bar_sync(4, 384);
                if (wg == 0) {
#pragma unroll
                    for (int t = 0; t < 8; t++) {
                        float u[4], v[4];
                        lds128f(u, ra + t * 2048); lds128f(v, ra + 16384 + t * 2048);
#pragma unroll
                        for (int i = 0; i < 4; i++) acc[4 * t + i] += u[i] + v[i];
                    }
                }
                bar_sync(4, 384);
                if (wg == 0) {
                    if (id < I_SA) {
#pragma unroll
                        for (int t = 0; t < 16; t++) *(uint32_t*)(x1 + o + 8 * (t >> 1) + (t & 1) * 8 * D_) = resid(xr[t], acc[2 * t], acc[2 * t + 1]);
                    } else {
                        float* y = g_yt + (layer * YT_ROWS - (S_ - YT_ROWS)) * D_ + o;
#pragma unroll
                        for (int t = 0; t < 16; t++)
                            asm volatile("red.relaxed.gpu.global.add.v2.f32 [%0],{%1,%2};" ::"l"(y + 8 * (t >> 1) + (t & 1) * 8 * D_), "f"(acc[2 * t]), "f"(acc[2 * t + 1]) : "memory");
                    }
                }
            }
            if (tid == 0) TLI(id, 2, gtime());
        }
    }
}

__global__ void __launch_bounds__(512, 1) side_kernel(const __grid_constant__ Maps maps, const bf16* __restrict__ x, bf16* __restrict__ x1, int layer) {
    extern __shared__ __align__(1024) unsigned char smem[];
    pdl_launch();
    TLS(3 + 5 * layer);
    worker(s2u(smem), maps, x, x1, layer);
    __syncwarp();
    pdl_wait();
    TLE(3 + 5 * layer);
}

constexpr float C5A = 0.30901699437494742f, C5B = -0.80901699437494742f, S5A = 0.95105651629515357f, S5B = 0.58778525229247313f;
template <int SGN> DEV void dft5(const float (&tr)[5], const float (&ti)[5], float (&zr)[5], float (&zi)[5]) {
    const float ar = tr[1] + tr[4], ai = ti[1] + ti[4], br = tr[2] + tr[3], bi = ti[2] + ti[3];
    const float cr = tr[1] - tr[4], ci = ti[1] - ti[4], dr = tr[2] - tr[3], di = ti[2] - ti[3];
    zr[0] = tr[0] + ar + br; zi[0] = ti[0] + ai + bi;
    const float m1r = tr[0] + C5A * ar + C5B * br, m1i = ti[0] + C5A * ai + C5B * bi;
    const float m2r = tr[0] + C5B * ar + C5A * br, m2i = ti[0] + C5B * ai + C5A * bi;
    const float n1r = SGN * (S5A * cr + S5B * dr), n1i = SGN * (S5A * ci + S5B * di);
    const float n2r = SGN * (S5B * cr - S5A * dr), n2i = SGN * (S5B * ci - S5A * di);
    zr[1] = m1r + n1i; zi[1] = m1i - n1r; zr[4] = m1r - n1i; zi[4] = m1i + n1r;
    zr[2] = m2r + n2i; zi[2] = m2i - n2r; zr[3] = m2r - n2i; zi[3] = m2i + n2r;
}
DEV void ln40(float (&v)[40]) {
    float s = 0.f;
#pragma unroll
    for (int i = 0; i < 40; i++) s += v[i];
#pragma unroll
    for (int o = 8; o; o >>= 1) s += __shfl_xor_sync(~0u, s, o);
    const float mean = s * (1.f / D_);
    float q = 0.f;
#pragma unroll
    for (int i = 0; i < 40; i++) { const float d = v[i] - mean; q += d * d; }
#pragma unroll
    for (int o = 8; o; o >>= 1) q += __shfl_xor_sync(~0u, q, o);
    const float mb = bf_round(mean);
    const float inv = 1.f / bf_round(sqrtf(bf_round(bf_round(q * (1.f / D_)) + 1e-5f)));
#pragma unroll
    for (int i = 0; i < 40; i++) v[i] = bf_round(v[i] - mb) * inv;
}
__global__ void __launch_bounds__(256) rowfft_kernel(const bf16* __restrict__ x0, bf16* __restrict__ x, const bf16* __restrict__ Wq,
                                                     const bf16* __restrict__ Wk, const bf16* __restrict__ Wv, int layer) {
    extern __shared__ __align__(1024) unsigned char smem[];
    const uint32_t sb = s2u(smem), sx = sb + 23552, sy = sx + 20480, bar = sy + 40960;
    const int tid = threadIdx.x, lane = tid & 31, q = lane & 3, blk = blockIdx.x, k2 = tid >> 2;
    if (tid == 0) TLI(800 + blk, 0, gtime());
    float twr[5], twi[5];
#pragma unroll
    for (int r = 1; r < 5; r++) { sincospif((float)(r * k2) * (-1.f / 320), &twi[r], &twr[r]); }
    uint32_t f[8][4];
#pragma unroll
    for (int ks = 0; ks < 8; ks++) { const uint4 u = g_f128[ks * 256 + tid]; f[ks][0] = u.x; f[ks][1] = u.y; f[ks][2] = u.z; f[ks][3] = u.w; }
    const bool split = blk * 16 >= S_ - YT_ROWS;
    if (tid == 0) {
        mbar_init(bar, 1);
        asm volatile("fence.mbarrier_init.release.cluster;" ::: "memory");
        mbar_expect(bar, split ? 61440 : 20480);
        if (split) bulk_g2s(sx, x0 + (size_t)blk * 16 * D_, 20480, bar);
    }
    __syncthreads();
    pdl_wait();
    pdl_launch();
    TLS(4 + 5 * layer);
    if (tid == 0) TLI(800 + blk, 1, gtime());
    if (tid == 0) {
        if (split) bulk_g2s(sy, g_yt + (layer * YT_ROWS + blk * 16 - (S_ - YT_ROWS)) * D_, 40960, bar);
        else bulk_g2s(sx, x + (size_t)blk * 16 * D_, 20480, bar);
    }
    mbar_wait(bar, 0);
    {
        const int rho = tid >> 4, j = tid & 15;
        float v[40];
#pragma unroll
        for (int i = 0; i < 5; i++) {
            uint32_t u[4];
            lds128(u, sx + tid * 80 + i * 16);
            if (split) {
                float p[8];
                lds128f(p, sy + tid * 160 + i * 32); lds128f(p + 4, sy + tid * 160 + i * 32 + 16);
#pragma unroll
                for (int k = 0; k < 4; k++) u[k] = resid(u[k], p[2 * k], p[2 * k + 1]);
                sts128(sx + tid * 80 + i * 16, u[0], u[1], u[2], u[3]);
            }
            unpack8(v + 8 * i, make_uint4(u[0], u[1], u[2], u[3]));
        }
        if (layer == 0 && tid < 12) prefetch_bulk((const char*)(tid < 4 ? Wk : tid < 8 ? Wq : Wv) + (blk * 4 + (tid & 3)) * 10240, 10240);
        ln40(v);
        const uint32_t a = sb + ((rho >> 1) & 1) * 2304 + j * 144 + (2 * (rho >> 2) + (rho & 1)) * 16;
#pragma unroll
        for (int r = 0; r < 5; r++)
            sts128(a + r * 4608, pack2(v[r], v[5 + r]), pack2(v[10 + r], v[15 + r]), pack2(v[20 + r], v[25 + r]), pack2(v[30 + r], v[35 + r]));
    }
    fence_async();
    __syncthreads();
    if (tid == 0) TLI(800 + blk, 2, gtime());
    if (tid == 0 && split) { bulk_s2g(x + (size_t)blk * 16 * D_, sx, 20480); bulk_commit(); }
    float acc[40];
    const u64 db = mkdesc(sb, 144, 2304);
    wg_fence();
    wgmma_n80_rs<0, 0>(acc, f[0], db);
#pragma unroll
    for (int ks = 1; ks < 8; ks++) wgmma_n80_rs<1, 0>(acc, f[ks], db + ks * 18);
    wg_commit();
    wg_wait<0>();
    unsigned char* zp = g_z + (blk >> 1) * 128 + ((((blk & 1) * 4 + q) ^ ((blk >> 1) & 7)) << 4);
    uint32_t o[5][4];
#pragma unroll
    for (int u = 0; u < 4; u++) {
        float tr[5], ti[5], zr[5], zi[5];
#pragma unroll
        for (int r = 0; r < 5; r++) {
            const float yr = acc[8 * r + 4 * (u >> 1) + (u & 1)], yi = k2 ? acc[8 * r + 4 * (u >> 1) + 2 + (u & 1)] : 0.f;
            tr[r] = r ? yr * twr[r] - yi * twi[r] : yr;
            ti[r] = r ? yr * twi[r] + yi * twr[r] : yi;
        }
        dft5<1>(tr, ti, zr, zi);
#pragma unroll
        for (int j = 0; j < 5; j++) o[j][u] = pack2(zr[j], j < 3 ? zi[j] : -zi[j]);
    }
#pragma unroll
    for (int j = 0; j < 5; j++)
        if (j < 3 || k2) *(uint4*)(zp + (64 * j + k2) * 8192) = make_uint4(o[j][0], o[j][1], o[j][2], o[j][3]);
    if (k2 == 0) {
#pragma unroll
        for (int u = 0; u < 4; u++) {
            float tr[5], ti[5], zr[5], zi[5];
            const float cr[5] = {1.f, -C5B, C5A, -C5A, C5B}, ci[5] = {0.f, -S5B, -S5A, -S5A, -S5B};
#pragma unroll
            for (int r = 0; r < 5; r++) { const float y = acc[8 * r + 4 * (u >> 1) + 2 + (u & 1)]; tr[r] = y * cr[r]; ti[r] = y * ci[r]; }
            dft5<1>(tr, ti, zr, zi);
            o[0][u] = pack2(zr[0], zi[0]); o[1][u] = pack2(zr[1], zi[1]); o[2][u] = pack2(zr[2], 0.f);
        }
        *(uint4*)(zp + 256 * 8192) = make_uint4(o[0][0], o[0][1], o[0][2], o[0][3]);
        *(uint4*)(zp + 192 * 8192) = make_uint4(o[1][0], o[1][1], o[1][2], o[1][3]);
        *(uint4*)(zp + 320 * 8192) = make_uint4(o[2][0], o[2][1], o[2][2], o[2][3]);
    }
    if (tid == 0) bulk_wait<0>();
    TLE(4 + 5 * layer);
    if (tid == 0) TLI(800 + blk, 3, gtime());
}

constexpr int CF_SMEM = 16384 + 3 * 16384 + 64;
__global__ void __launch_bounds__(384) colfft_kernel(int layer) {
    extern __shared__ __align__(1024) unsigned char smem[];
    const uint32_t sb = s2u(smem), bar = sb + 65536;
    const int tid = threadIdx.x, lane = tid & 31, q = lane & 3, wg = __shfl_sync(~0u, tid >> 7, 0), t = tid & 127, ka = t >> 2;
    const int col = blockIdx.x * 3 + wg;
    const uint32_t d0 = sb + 16384 + wg * 16384, d1 = d0 + 8192;
    if (tid == 0) {
        for (int i = 0; i < 4; i++) mbar_init(bar + 8 * i, 1);
        asm volatile("fence.mbarrier_init.release.cluster;" ::: "memory");
    }
    float twr[8], twi[8];
#pragma unroll
    for (int i = 0; i < 8; i++) sincospif((float)((4 * i + q) * (ka ? ka : -32)) * (1.f / 1024), &twi[i], &twr[i]);
    __syncthreads();
    if (tid == 0) { mbar_expect(bar + 24, 16384); bulk_g2s(sb, g_g32, 16384, bar + 24); }
    uint32_t f[4][4], w[16];
#pragma unroll
    for (int ks = 0; ks < 4; ks++) { const uint4 u = g_f64[ks * 128 + t]; f[ks][0] = u.x; f[ks][1] = u.y; f[ks][2] = u.z; f[ks][3] = u.w; }
#pragma unroll
    for (int i = 0; i < 4; i++) { const uint4 u = *(const uint4*)(g_wt + col * 8192 + i * 2048 + t * 16); w[4 * i] = u.x; w[4 * i + 1] = u.y; w[4 * i + 2] = u.z; w[4 * i + 3] = u.w; }
    pdl_wait();
    pdl_launch();
    TLS(5 + 5 * layer);
    if (t == 0) {
        mbar_expect(bar + 8 * wg, 8192);
        bulk_g2s(d0, g_z + col * 8192, 8192, bar + 8 * wg);
    }
    float acc[32];
    uint32_t a[4][4];
    mbar_wait(bar + 8 * wg, 0);
    {
        const u64 db = mkdesc(d0, 0, 1024) | SW128;
        wg_fence();
        wgmma_n64_rs<0, 1>(acc, f[0], db);
#pragma unroll
        for (int ks = 1; ks < 4; ks++) wgmma_n64_rs<1, 1>(acc, f[ks], db + ks * 128);
        wg_commit();
        wg_wait<0>();
    }
#pragma unroll
    for (int ks = 0; ks < 4; ks++) { const uint4 u = g_f64[512 + ks * 128 + t]; f[ks][0] = u.x; f[ks][1] = u.y; f[ks][2] = u.z; f[ks][3] = u.w; }
#pragma unroll
    for (int i = 0; i < 8; i++) {
        const float c0 = acc[4 * i], c1 = acc[4 * i + 1], c2 = acc[4 * i + 2], c3 = acc[4 * i + 3];
        const float pr = c0 + c3, pi = c1 - c2, nr = ka ? c0 - c3 : c2, ni = ka ? c1 + c2 : c3;
        a[i >> 1][2 * (i & 1)] = ka ? pack2(pr * twr[i] + pi * twi[i], pi * twr[i] - pr * twi[i]) : pack2(c0, c1);
        a[i >> 1][2 * (i & 1) + 1] = pack2(nr * twr[i] - ni * twi[i], ni * twr[i] + nr * twi[i]);
    }
    mbar_wait(bar + 24, 0);
    {
        const u64 db = mkdesc(sb, 128, 1024);
        wg_fence();
        wgmma_n64_rs<0, 0>(acc, a[0], db);
#pragma unroll
        for (int ks = 1; ks < 4; ks++) wgmma_n64_rs<1, 0>(acc, a[ks], db + ks * 16);
        wg_commit();
        wg_wait<0>();
    }
    constexpr float NORM = 1.f / (2048.f * 640.f);
#pragma unroll
    for (int i = 0; i < 16; i++) {
        const float zr = acc[2 * i] * NORM, zi = acc[2 * i + 1] * NORM, wr = bf_lo(w[i]), wi = bf_hi(w[i]);
        a[i >> 2][i & 3] = pack2(zr * wr - zi * wi, zr * wi + zi * wr);
    }
    {
        const u64 db = mkdesc(sb + 8192, 128, 1024);
        wg_fence();
        wgmma_n64_rs<0, 0>(acc, a[0], db);
#pragma unroll
        for (int ks = 1; ks < 4; ks++) wgmma_n64_rs<1, 0>(acc, a[ks], db + ks * 16);
        wg_commit();
        wg_wait<0>();
    }
    const uint32_t row = (t >> 5) * 2048 + (lane & 15) * 128;
#pragma unroll
    for (int i = 0; i < 8; i++) {
        const float c0 = acc[4 * i], c1 = acc[4 * i + 1], c2 = acc[4 * i + 2], c3 = acc[4 * i + 3];
        const float pr = c0 * twr[i] - c1 * twi[i], pi = c1 * twr[i] + c0 * twi[i];
        const float nr = c2 * twr[i] + c3 * twi[i], ni = c3 * twr[i] - c2 * twi[i];
        a[i >> 1][2 * (i & 1)] = ka ? pack2(pr + nr, pi + ni) : pack2(c0, c1);
        a[i >> 1][2 * (i & 1) + 1] = ka ? pack2(ni - pi, pr - nr) : pack2(nr, ni);
    }
#pragma unroll
    for (int i = 0; i < 4; i++) stsm4(d1 + row + (((2 * i + (lane >> 4)) ^ (lane & 7)) << 4), a[i][0], a[i][1], a[i][2], a[i][3]);
    fence_async();
    bar_sync(1 + wg, 128);
    {
        const u64 db = mkdesc(d1, 0, 1024) | SW128;
        wg_fence();
        wgmma_n64_rs<0, 1>(acc, f[0], db);
#pragma unroll
        for (int ks = 1; ks < 4; ks++) wgmma_n64_rs<1, 1>(acc, f[ks], db + ks * 128);
        wg_commit();
        wg_wait<0>();
    }
#pragma unroll
    for (int i = 0; i < 4; i++)
        stsm4(d0 + row + (((2 * i + (lane >> 4)) ^ (lane & 7)) << 4), pack2(acc[8 * i], acc[8 * i + 1]), pack2(acc[8 * i + 2], acc[8 * i + 3]),
              pack2(acc[8 * i + 4], acc[8 * i + 5]), pack2(acc[8 * i + 6], acc[8 * i + 7]));
    fence_async();
    bar_sync(1 + wg, 128);
    if (t == 0) {
        bulk_s2g(g_z + col * 8192, d0, 8192);
        asm volatile("cp.async.bulk.commit_group;" ::: "memory");
        asm volatile("cp.async.bulk.wait_group 0;" ::: "memory");
    }
    TLE(5 + 5 * layer);
}

__global__ void __launch_bounds__(256) rowifft_kernel(const bf16* __restrict__ x, bf16* __restrict__ out, int last) {
    extern __shared__ __align__(1024) unsigned char smem[];
    const uint32_t sb = s2u(smem), sx = sb + 20480, sy = sx + 20480, bar = sy + 16 * 1296;
    const int tid = threadIdx.x, lane = tid & 31, q = lane & 3, blk = blockIdx.x, k2 = tid >> 2, warp = tid >> 5;
    float twr[5], twi[5];
#pragma unroll
    for (int r = 1; r < 5; r++) { sincospif((float)(r * k2) * (1.f / 320), &twi[r], &twr[r]); twr[r] *= 2.f; twi[r] *= 2.f; }
    uint32_t f[8][4];
#pragma unroll
    for (int ks = 0; ks < 8; ks++) { const uint4 u = g_f128[2048 + ks * 256 + tid]; f[ks][0] = u.x; f[ks][1] = u.y; f[ks][2] = u.z; f[ks][3] = u.w; }
    if (tid == 0) {
        mbar_init(bar, 1);
        asm volatile("fence.mbarrier_init.release.cluster;" ::: "memory");
        mbar_expect(bar, 20480);
        bulk_g2s(sx, x + (size_t)blk * 16 * D_, 20480, bar);
    }
    pdl_wait();
    pdl_launch();
    TLS(6 + 5 * last);
    const unsigned char* zp = g_z + (blk >> 1) * 128 + ((((blk & 1) * 4 + q) ^ ((blk >> 1) & 7)) << 4);
    uint4 z[6];
#pragma unroll
    for (int j = 0; j < 5; j++) z[j] = *(const uint4*)(zp + (64 * j + k2) * 8192);
    z[5] = k2 ? make_uint4(0, 0, 0, 0) : *(const uint4*)(zp + 320 * 8192);
    float acc[40];
#pragma unroll
    for (int u = 0; u < 4; u++) {
        float yr[6], yi[6], tr[5], ti[5], zr[5], zi[5];
#pragma unroll
        for (int j = 0; j < 6; j++) { const uint32_t v = u == 0 ? z[j].x : u == 1 ? z[j].y : u == 2 ? z[j].z : z[j].w; yr[j] = bf_lo(v); yi[j] = bf_hi(v); }
#pragma unroll
        for (int j = 0; j < 5; j++) { tr[j] = yr[j]; ti[j] = j < 3 ? yi[j] : -yi[j]; }
        dft5<-1>(tr, ti, zr, zi);
        const float c1[5] = {1.f, C5A, C5B, C5B, C5A}, s1[5] = {0.f, S5A, S5B, -S5B, -S5A};
        const float c2[5] = {1.f, C5B, C5A, C5A, C5B}, s2[5] = {0.f, S5B, -S5A, S5A, -S5B};
        const float c3[5] = {1.f, -C5B, C5A, -C5A, C5B}, s3[5] = {0.f, S5B, S5A, S5A, S5B};
        const float c4[5] = {1.f, -C5A, C5B, -C5B, C5A}, s4[5] = {0.f, S5A, -S5B, -S5B, S5A};
#pragma unroll
        for (int r = 0; r < 5; r++) {
            float er = r ? zr[r] * twr[r] - zi[r] * twi[r] : 2.f * zr[0], ei = r ? zr[r] * twi[r] + zi[r] * twr[r] : 2.f * zi[0];
            if (k2 == 0) {
                er = yr[0] + 2.f * (yr[1] * c1[r] - yi[1] * s1[r] + yr[2] * c2[r] - yi[2] * s2[r]);
                ei = (r & 1 ? -yr[5] : yr[5]) + 2.f * (yr[4] * c3[r] - yi[4] * s3[r] + yr[3] * c4[r] - yi[3] * s4[r]);
            }
            acc[8 * r + 4 * (u >> 1) + (u & 1)] = er;
            acc[8 * r + 4 * (u >> 1) + 2 + (u & 1)] = ei;
        }
    }
#pragma unroll
    for (int r = 0; r < 5; r++)
        stsm4(sb + (2 * warp + ((lane >> 3) & 1)) * 1280 + (2 * r + (lane >> 4)) * 128 + (lane & 7) * 16, pack2(acc[8 * r], acc[8 * r + 1]),
              pack2(acc[8 * r + 2], acc[8 * r + 3]), pack2(acc[8 * r + 4], acc[8 * r + 5]), pack2(acc[8 * r + 6], acc[8 * r + 7]));
    fence_async();
    __syncthreads();
    const u64 db = mkdesc(sb, 1280, 128);
    wg_fence();
    wgmma_n80_rs<0, 1>(acc, f[0], db);
#pragma unroll
    for (int ks = 1; ks < 8; ks++) wgmma_n80_rs<1, 1>(acc, f[ks], db + ks * 160);
    wg_commit();
    wg_wait<0>();
#pragma unroll
    for (int u = 0; u < 4; u++) {
        float e[10];
#pragma unroll
        for (int r = 0; r < 5; r++) { e[r] = acc[8 * r + 4 * (u >> 1) + (u & 1)]; e[5 + r] = acc[8 * r + 4 * (u >> 1) + 2 + (u & 1)]; }
#pragma unroll
        for (int i = 0; i < 5; i++) sts32(sy + (4 * q + u) * 1296 + k2 * 20 + i * 4, pack2(e[2 * i], e[2 * i + 1]));
    }
    __syncthreads();
    const int rho = tid >> 4, j = tid & 15;
    float v[40];
    mbar_wait(bar, 0);
#pragma unroll
    for (int i = 0; i < 5; i++) {
        uint32_t y[4], u[4];
        lds128(y, sy + rho * 1296 + j * 80 + i * 16);
        lds128(u, sx + tid * 80 + i * 16);
#pragma unroll
        for (int k = 0; k < 4; k++) u[k] = pack2(bf_lo(u[k]) + bf_lo(y[k]), bf_hi(u[k]) + bf_hi(y[k]));
        sts128(sx + tid * 80 + i * 16, u[0], u[1], u[2], u[3]);
        unpack8(v + 8 * i, make_uint4(u[0], u[1], u[2], u[3]));
    }
    if (!last) {
        ln40(v);
#pragma unroll
        for (int i = 0; i < 5; i++) {
            const int c = j * 5 + i;
            sts128(sb + (c >> 3) * 2048 + rho * 128 + (((c ^ rho) & 7) << 4), pack2(v[8 * i], v[8 * i + 1]), pack2(v[8 * i + 2], v[8 * i + 3]),
                   pack2(v[8 * i + 4], v[8 * i + 5]), pack2(v[8 * i + 6], v[8 * i + 7]));
        }
    }
    fence_async();
    __syncthreads();
    if (lane == 0) {
        if (warp == 7) bulk_s2g(out + (size_t)blk * 16 * D_, sx, 20480);
        else if (!last && warp < 5) {
            unsigned char* p = g_xn + (blk >> 1) * 40960 + warp * 8192 + (blk & 1) * 2048;
            bulk_s2g(p, sb + warp * 4096, 2048);
            bulk_s2g(p + 4096, sb + warp * 4096 + 2048, 2048);
        }
        bulk_commit();
        bulk_wait<0>();
    }
    TLE(6 + 5 * last);
}

namespace rec {
#define NS 3
constexpr int OFF_X = 0;
constexpr int OFF_WO = 81920;
constexpr int OFF_WS = OFF_WO + 65536;
constexpr int OFF_XCH = OFF_WS + NS * 4096;
constexpr int OFF_MEMB = OFF_XCH + 12288;
constexpr int OFF_VX = OFF_MEMB + 10240;
constexpr int OFF_VM = OFF_VX + 16384;
constexpr int OFF_Q = OFF_VM + 4096;
constexpr int OFF_K = OFF_Q + 10240;
constexpr int OFF_OST = OFF_WO + 49152;
constexpr int OFF_PX = OFF_OST + 8192;
constexpr int OFF_PT = OFF_PX + 2560;
constexpr int OFF_PS = OFF_K + 10240;
constexpr int OFF_OB = OFF_PS + 1280;
constexpr int OFF_MX = OFF_OB + 2048;
constexpr int OFF_BAR = OFF_MX + 64;
constexpr int OFF_PROF = OFF_BAR + 256;
constexpr int SMEM = OFF_PROF + 4096 > wk::SMEM ? OFF_PROF + 4096 : wk::SMEM;
enum { B_XT = 0, B_VM = 2, B_VX = 4, B_XD = 6, B_X1 = 8, B_GO = 10, B_PXF = 12, B_PXE = 13, B_FIN = 14, B_ST = 15, B_MEM = 16   };
enum { NB_W2 = 0, NB_XCH = 1, NB_QK = 2, NB_WIN = 3, NB_ATT = 4, NB_X = 5, NB_PRO = 6, NB_W1 = 7, NB_PAIR = 8  , NB_KF = 12, NB_LD = 13, NB_KX = 15 };
#define STAG 3
#define NOX 0
#define NW1 4
#define NW1B 0
template <int N> struct IC { static constexpr int value = N; };
template <int N, int I = 0, class F> DEV void static_for(F&& f) { if constexpr (I < N) { f(IC<I>{}); static_for<N, I + 1>(f); } }
constexpr float SM_SCALE = 0.08838834764831845f * 1.4426950408889634f;
}

__global__ void __launch_bounds__(512, 1) rec_kernel(const __grid_constant__ Maps maps, const bf16* __restrict__ x, bf16* __restrict__ x1, const bf16* __restrict__ mem0, const bf16* __restrict__ Wq, const bf16* __restrict__ Wk,
                                                     const bf16* __restrict__ Wv, const bf16* __restrict__ Wo, int layer, int delay, int delay2) {
    using namespace rec;
    extern __shared__ __align__(1024) unsigned char smem[];
    const uint32_t sb = s2u(smem);
    if (blockIdx.x >= 3 * H_) {
        pdl_wait();
        pdl_launch();
        worker(sb, maps, x, x1, layer);
        return;
    }
    const int tid = threadIdx.x, lane = tid & 31, warp = __shfl_sync(~0u, tid >> 5, 0);
    const int g = lane >> 2, q = lane & 3;
    const int h = blockIdx.x / 3;
    const uint32_t bar = sb + OFF_BAR;
    STAMP(2 * layer);
    TLS(2 + 5 * layer);
    if (tid == 0) {
        for (int i = 0; i < 2; i++) {
            mbar_init(bar + 8 * (B_XT + i), 1); mbar_init(bar + 8 * (B_VX + i), 1);
            mbar_init(bar + 8 * (B_XD + i), 8); mbar_init(bar + 8 * (B_X1 + i), 1); mbar_init(bar + 8 * (B_VM + i), 1);
        }
        mbar_init(bar + 8 * B_PXF, 1); mbar_init(bar + 8 * B_PXE, 2); mbar_init(bar + 8 * B_ST, 2); mbar_init(bar + 8 * B_GO, 1);
        for (int i = 0; i < 5; i++) mbar_init(bar + 8 * (B_MEM + i), 4);
        mbar_init(bar + 8 * B_FIN, 48);
        asm volatile("fence.mbarrier_init.release.cluster;" ::: "memory");
    }
    asm volatile("barrier.cluster.arrive.aligned; barrier.cluster.wait.aligned;" ::: "memory");
    const bool never = delay < 0;

    if (warp < 8) {
        asm volatile("setmaxnreg.inc.sync.aligned.u32 184;");
        const uint32_t rank = cta_rank();
        const int wg = warp >> 2;
        uint32_t fa[20 - NS][4], fb[20][4];
        const uint32_t l16 = opaque(sb + lane * 16);
        uint32_t dst = opaque(rank < 2 ? sb + OFF_Q + wg * 10240 + (warp & 3) * 256 + (lane & 15) * 16 + (lane >> 4) * 1024
                                       : sb + OFF_VM + warp * 256 + lane * 4);
        int dstep = rank < 2 ? 5120 : 2048;
        uint32_t& sfd = dst;
        const uint32_t ws = OFF_WS + warp * 512, xo = OFF_XCH + warp * 512, xi = OFF_XCH + (warp ^ 4) * 512, mb = OFF_MEMB + wg * 512;
        {
            const int t = tid & 127;
            const bf16* src = (rank == 2 ? Wv + wg * 64 : (wg ? Wk : Wq) + rank * 64) + h * E_ + (size_t)(t >> 3) * 4096 + (t & 7) * 8;
            constexpr int SA = OFF_X + 40960, SB = OFF_VX;
            const uint32_t sdst = sb + (wg ? SB : SA) + (t >> 3) * 128 + (((t & 7) ^ ((t >> 3) & 7)) << 4);
            const uint32_t ra = sb + wg * 4096 + ((lane >> 4) * 8 + (lane & 7)) * 128 + (((2 * (warp & 3) + ((lane >> 3) & 1)) ^ (lane & 7)) << 4);
            auto issue = [&](int rd) {
#pragma unroll 1
                for (int i = 0; i < 8; i++, src += 16 * 4096) cp16(sdst + (rd & 1) * 16384 + i * 2048, src);
                cp_commit();
            };
            issue(0); issue(1);
#pragma unroll
            for (int rd = 0; rd < 5; rd++) {
                if (rd < 4) cp_wait<1>(); else cp_wait<0>();
                bar_sync(NB_XCH, 256);
#pragma unroll
                for (int i = 0; i < 4; i++) {
                    const int n = rd * 4 + i, o = (rd & 1) * 16384 + (i >> 1) * 8192 + (i & 1) * 2048;
                    if (n < NS) {
                        uint32_t f[4];
                        ldsm4t(f, ra + SA + o);
                        sts128(l16 + ws + n * 4096, f[0], f[1], f[2], f[3]);
                    } else ldsm4t(fa[n - NS], ra + SA + o);
                    ldsm4t(fb[n], ra + SB + o);
                }
                if (rd < 3) { bar_sync(NB_XCH, 256); issue(rd + 2); }
            }
            fence_async();
            bar_sync(NB_PRO, 288);
        }
        uint32_t xlo = (uint32_t)mkdesc(sb + OFF_X + wg * 64, 0, 0);
        const uint32_t xtog = xlo ^ (uint32_t)mkdesc(sb + OFF_X + 40960 + wg * 64, 0, 0);
        uint32_t p8 = 0;
        bar_sync(NB_LD, 288);
        for (int s = -1;; s++) {
            uint32_t t[NS ? NS : 1][4];
            {
                float acc[16];
                auto xproj = [&](auto I0, auto I1) {
                    const u64 desc = (u64)xlo | (64ull << 32) | SW128;
                    wg_fence();
#pragma unroll
                    for (int i = I0.value; i < I1.value; i++) {
                        const u64 db = desc + (i >> 1) * 256 + (i & 1) * 2;
                        if (i == 0) wgmma_n32_rs<0>(acc, fb[i], db);
                        else if (!NOX) wgmma_n32_rs<1>(acc, fb[i], db);
                    }
                    wg_commit();
                    wg_wait<0>();
                };
                if (s >= 0 && rank < 2) { fence_async(); bar_arrive(NB_W1, 512); bar_sync(NB_X, 384); }
                bar_sync_if<NB_W1, 480>(s >= 0 && rank == 2);
                if (s == NSEG - 1) break;
                xproj(IC<0>{}, IC<NW1>{});
                if (warp == 4 && s >= 0) PROFT(15);
                bar_sync_if<NB_W2, 384>(s >= 0 && rank < 2);
                if (NW1B > 0) xproj(IC<NW1>{}, IC<NW1 + NW1B>{});
                bar_sync_if<NB_WIN, 384>(s >= 0 && rank == 2);
                xproj(IC<NW1 + NW1B>{}, IC<20>{});
                if (warp == 4 && s >= 0) PROFT(12);
                sts128f_if(l16 + xo, acc + 8, !wg); sts128f_if(l16 + xo + 4096, acc + 12, !wg);
                sts128f_if(l16 + xo, acc, wg); sts128f_if(l16 + xo + 4096, acc + 4, wg);
                bar_sync(NB_PAIR + (warp & 3), 64);
                float u[8];
#pragma unroll
                for (int i = 0; i < 8; i++) acc[i] = wg ? acc[8 + i] : acc[i];
                lds128f(u, l16 + xi); lds128f(u + 4, l16 + xi + 4096);
#pragma unroll
                for (int i = 0; i < NS; i++) lds128(t[i], l16 + ws + i * 4096);
#pragma unroll
                for (int i = 0; i < 8; i++) u[i] += acc[i];
                if (rank < 2) {
                    stsm4t(dst + (wg ? 3072 : 11264), pack2(u[0], u[1]), pack2(u[2], u[3]), pack2(u[4], u[5]), pack2(u[6], u[7]));
                } else {
                    stsm4(l16 + (l16 & 256) + OFF_VX + 4096 + (warp & 3) * 1024 + wg * 256 + p8 * 1024,
                          pack2(u[0], u[1]), pack2(u[4], u[5]), pack2(u[2], u[3]), pack2(u[6], u[7]));
                    bar_arrive(NB_KF, 288);
                }
                bar_arrive(NB_KX, 384);
                xlo ^= xtog;
                if (warp == 4 && s >= 0) PROFT(3);
            }
            float da[4] = {0.f, 0.f, 0.f, 0.f}, db[4] = {0.f, 0.f, 0.f, 0.f}, ea[4] = {0.f, 0.f, 0.f, 0.f}, eb[4] = {0.f, 0.f, 0.f, 0.f};
            uint32_t b[10][4];
            const uint32_t mp = p8 >> 3;
            while (!mbar_try(bar + 8 * B_MEM, mp)) {}
            lds128(b[0], l16 + mb); lds128(b[1], l16 + mb + 1024);
            bool rdy = mbar_try(bar + 8 * (B_MEM + 1), mp, 1);
            const uint32_t xb0 = mapa(bar + 8 * B_VM + p8, 0), xb1 = mapa(bar + 8 * B_VM + p8, 1);
            SFENCE();
            float is;
#pragma unroll
            for (int j = 0; j < 10; j++) {
#pragma unroll
                for (int x = 0; x < 2; x++) {
                    const int i = 2 * j + x;
                    const uint32_t* f = i < NS ? t[i] : fa[i - NS];
                    mma16(NS > 2 && x && j ? ea : da, f[0], f[1], f[2], f[3], b[j][2 * x], b[j][2 * x + 1]);
                    mma16(NS > 2 && x && j ? eb : db, fb[i][0], fb[i][1], fb[i][2], fb[i][3], b[j][2 * x], b[j][2 * x + 1]);
                    SFENCE();
                    if (x == 0 && j < 8 && !(j & 1)) {
                        if (__builtin_expect(!rdy, 0)) while (!mbar_try(bar + 8 * (B_MEM + 1 + (j >> 1)), mp)) {}
                        lds128(b[j + 2], l16 + mb + (j + 2) * 1024);
                    }
                    if (x == 1 && j < 8 && !(j & 1)) lds128(b[j + 3], l16 + mb + (j + 3) * 1024);
                    if (x == 0 && j < 6 && (j & 1)) rdy = mbar_try(bar + 8 * (B_MEM + 2 + (j >> 1)), mp, 1);
                    if (x == 0 && j == 8) is = lds32f(sb + OFF_MX + 16);
                }
                if (j == 0 && warp == 4) PROFT(16);
            }
            if (warp == 4) PROFT(20);
            if (NS > 2) {
#pragma unroll
                for (int i = 0; i < 4; i++) { da[i] += ea[i]; db[i] += eb[i]; }
            }
            sts128f_if(l16 + xo + 8192, db, !wg); sts128f_if(l16 + xo + 8192, da, wg);
            bar_sync(NB_PAIR + (warp & 3), 64);
            float u[4];
            lds128f(u, l16 + xi + 8192);
#pragma unroll
            for (int i = 0; i < 4; i++) da[i] = (wg ? db[i] : da[i]) * is;
            const uint32_t p0 = pack2(fmaf(u[0], is, da[0]), fmaf(u[1], is, da[1])), p1 = pack2(fmaf(u[2], is, da[2]), fmaf(u[3], is, da[3]));
            stsm2t_if(dst, p0, p1, rank < 2);
            bar_arrive_if<NB_QK, 384>(rank < 2);
            if (rank == 2) {
                st_async1(mapa(dst, 0), p0, xb0); st_async1(mapa(dst, 1), p0, xb1);
                st_async1(mapa(dst + 128, 0), p1, xb0); st_async1(mapa(dst + 128, 1), p1, xb1);
                sts32(dst, p0); sts32(dst + 128, p1);
                bar_arrive(NB_QK, 384);
            }
            if (warp == 4) PROFT(17);
            dst += dstep; dstep = -dstep; p8 ^= 8;
        }
    } else if (warp < 12) {
        asm volatile("setmaxnreg.dec.sync.aligned.u32 96;");
        const uint32_t rank = cta_rank();
        const int w = warp - 8;
        uint32_t amax = 0;
#pragma unroll 1
        for (int it = 0; it < 5; it++) {
            const int kp = it * 4 + w;
            const bf16* p = mem0 + g * D_ + kp * 32 + 2 * q;
            uint32_t b0 = ldg32(p), b1 = ldg32(p + 8), b2 = ldg32(p + 16), b3 = ldg32(p + 24);
            sts128(sb + OFF_MEMB + kp * 512 + lane * 16, b0, b1, b2, b3);
            amax = absmax2(amax, absmax2(absmax2(b0, b1), absmax2(b2, b3)));
        }
        if (tid == 256) { sts32(sb + OFF_MX + 16, 0x3f800000u); sts128(sb + OFF_MX + 48, 0x3f803f80u, 0x3f803f80u, 0x3f803f80u, 0x3f803f80u); }
        __syncwarp();
        if (lane < 5) mbar_arrive(bar + 8 * (B_MEM + lane));
        __syncwarp();
        {
            const int t = tid & 127, nr = rank == 2 ? 4 : 3;
            for (int r = 0; r < nr; r++) {
                const bf16* src = Wo + (size_t)(h * E_) * D_ + (r < 3 ? 192 * r + 64 * rank : 576);
#pragma unroll 1
                for (int i = 0; i < 8; i++) {
                    const int e = i * 16 + (t >> 3);
                    cp16(sb + OFF_WO + r * 16384 + e * 128 + (((t & 7) ^ (e & 6)) << 4), src + e * D_ + (t & 7) * 8);
                }
            }
            cp_commit();
            pdl_wait();
            pdl_launch();
            cp_wait<0>();
            bar_sync(NB_ATT, 128);
            for (int r = 0; r < nr; r++) {
                uint32_t u[8][4];
                const uint32_t p = sb + OFF_WO + r * 16384 + 2 * q * 128 + (((2 * w + (g & 1)) ^ (2 * q)) << 4) + (g >> 1) * 4;
#pragma unroll
                for (int ks = 0; ks < 8; ks++)
#pragma unroll
                    for (int j = 0; j < 4; j++) u[ks][j] = lds32(p + (16 * ks + (j & 1) * 8 + (j >> 1)) * 128);
                bar_sync(NB_ATT, 128);
#pragma unroll
                for (int ks = 0; ks < 8; ks++)
                    sts128(sb + OFF_WO + (r * 4 + w) * 4096 + ks * 512 + lane * 16, prmt(u[ks][0], u[ks][2], 0x5410), prmt(u[ks][0], u[ks][2], 0x7632),
                           prmt(u[ks][1], u[ks][3], 0x5410), prmt(u[ks][1], u[ks][3], 0x7632));
            }
        }
        float cw;
        {
            const float4 a = ((const float4*)g_nrm)[lane], c = ((const float4*)g_nrm)[32 + lane];
            float sm = sqrt_approx((a.x + a.y) + (a.z + a.w)) * sqrt_approx((c.x + c.y) + (c.z + c.w)), mxv = sm;
#pragma unroll 1
            for (int o = 16; o; o >>= 1) { sm += __shfl_xor_sync(~0u, sm, o); mxv = fmaxf(mxv, __shfl_xor_sync(~0u, mxv, o)); }
            cw = 26.5f * fmaxf(sm, 8.f * mxv);
        }
        if (w == 0) {
            mbar_expect_elect(bar + 8 * B_X1, 1280);
            mbar_expect_elect(bar + 8 * B_VM, rank < 2 ? 2048 : 0);
            mbar_expect_elect(bar + 8 * B_VX, rank < 2 ? 8192 : 4096);
        }
        {
            const int kind = rank;
            const uint32_t l16 = opaque(sb + lane * 16), lw = opaque(sb + lane * 16 + w * 512);
            const uint32_t pa = opaque(sb + OFF_PS + rank * 512 + lane * 4 + w * 128);
            uint32_t lq = opaque(sb + OFF_Q + (lane & 7) * 16 + ((lane >> 3) & 1) * 256 + (lane >> 4) * 128);
            const uint32_t lv = opaque(sb + OFF_VX + w * 2048 + (lane & 7) * 16 + ((lane >> 3) & 1) * 512 + (lane >> 4) * 128);
            const uint32_t lo = opaque(sb + OFF_WO + w * 4096 + lane * 16);
            uint32_t& sfd = lq;
            const char* rp = (const char*)(g_acc + layer * ACC_LAYER) + (4 * rank + w) * 4096 + opaque((q >> 1) * 1024 + ((q & 1) * 8 + g) * 8);
            const char* lp = (const char*)(g_acc + layer * ACC_LAYER) + opaque(w * 8192 + (lane >> 3) * 1024 + (lane & 7) * 16);
            const uint32_t arm = bar + 8 * (w == 0 ? B_X1 + 1 : w == 1 ? B_VX + 1 : w == 2 ? B_XT : B_VM + 1);
            const uint32_t armb = w == 0 ? 1280 : (w == 1 ? 4096 : w == 2 ? 40960 : 0) + (rank == 2 ? 0 : w == 3 ? 2048 : 4096);
            float isig = 1.f;
            for (int s = 0; s < NSEG - 1; s++) {
                const uint32_t pb = s & 1, ph = (s >> 1) & 1, x1 = bar + 8 * (B_X1 + pb);
                uint32_t kf[8];
                bar_sync(NB_KX, 384);
                ldsm4(kf, lw + OFF_K + 1024 + w * 512 + pb * 5120); ldsm4(kf + 4, lw + OFF_K + 1536 + w * 512 + pb * 5120);
                sts32(sb + OFF_MX + w * 4, __reduce_max_sync(~0u, max(amax & 0x7fff0000u, (amax << 16) & 0x7fff0000u)));
                const uint32_t va = lv + pb * 8192, vma = lw + OFF_VM + pb * 2048;
                uint32_t wf[8][4], vf[2][2][4], vm[4], one[4];
                mbar_spin(bar + 8 * (B_VX + pb), ph);
#pragma unroll
                for (int t = 0; t < 2; t++)
#pragma unroll
                    for (int j = 0; j < 2; j++) ldsm4(vf[t][j], va + t * 1024 + j * 256);
                lds128(one, sb + OFF_MX + 48);
                auto scores = [&](auto MM) {
                    constexpr int mm = MM.value;
                    uint32_t qf[8], mf[8];
                    const uint32_t qa = lq + pb * 5120, ka = l16 + OFF_K + pb * 5120;
                    const uint32_t pa0 = mapa(pa, rank ^ 1), pa1 = mapa(pa, 2), pa2 = mapa(pa, rank);
                    const uint32_t xb0 = mapa(x1, rank ^ 1), xb1 = mapa(x1, 2), xb2 = mapa(x1, rank);
                    const uint32_t pm = 640 - rank * 384;
                    SFENCE();
                    if (w == 0) PROFT(2);
                    bar_sync(NB_QK, 384);
                    ldsm4(qf, qa); ldsm4(qf + 4, qa + 512);
                    if (mm) { ldsm4(mf, ka); ldsm4(mf + 4, ka + 512); }
                    SFENCE();
                    float c[4][4];
#pragma unroll
                    for (int i = 0; i < 4; i++) c[i][0] = c[i][1] = c[i][2] = c[i][3] = 0.f;
#pragma unroll
                    for (int i = 0; i < (mm ? 8 : 4); i++) {
                        const int hf = mm ? i >> 2 : i >> 1;
                        const uint32_t* f = (mm && (i & 2) ? mf : kf) + 4 * hf + 2 * (i & 1);
                        mma16(c[i & 3], qf[4 * hf], qf[4 * hf + 1], qf[4 * hf + 2], qf[4 * hf + 3], f[0], f[1]);
                    }
                    SFENCE();
                    bar_arrive(NB_W1, 512);
                    const uint32_t y = mm ? pack2(c[0][0] + c[1][2], c[0][1] + c[1][3])
                                          : pack2((c[0][0] + c[1][2]) + (c[2][0] + c[3][2]), (c[0][1] + c[1][3]) + (c[2][1] + c[3][3]));
                    st_async1(pa0, y, xb0); st_async1(pa1, y, xb1);
                    if (mm) {
                        const uint32_t z = pack2(c[2][0] + c[3][2], c[2][1] + c[3][3]);
                        st_async1(pa0 + pm, z, xb0); st_async1(pa1 + pm, z, xb1); st_async1(pa2 + pm, z, xb2);
                    }
                    st_async1(pa2, y, xb2);
                    if (w == 0) PROFT(5);
                };
                if (kind == 2) bar_sync(NB_QK, 384);
                else if (w == 3) scores(IC<1>{});
                else scores(IC<0>{});
                float m4[4];
                lds128f(m4, sb + OFF_MX);
                bar_arrive_if<NB_W1, 480>(kind == 2);
                mbar_spin(x1, ph);
                if (w == 0) PROFT(6);
                float sc[10];
                {
                    uint32_t u[4], v[4], m[2];
                    ldsm4(u, l16 + OFF_PS); ldsm4(v, l16 + OFF_PS + 512); ldsm2(m, l16 + OFF_PS + 1024);
                    SFENCE();
                    m4[0] = fmaxf(fmaxf(m4[0], m4[1]), fmaxf(m4[2], m4[3])) * isig;
                    SFENCE();
#pragma unroll
                    for (int i = 0; i < 4; i++) { sc[2 * i] = bf_lo(u[i]) + bf_lo(v[i]); sc[2 * i + 1] = bf_hi(u[i]) + bf_hi(v[i]); }
                    sc[8] = bf_lo(m[0]) + bf_lo(m[1]); sc[9] = bf_hi(m[0]) + bf_hi(m[1]);
                }
                float mx = fmaxf(fmaxf(fmaxf(fmaxf(sc[0], sc[1]), fmaxf(sc[2], sc[3])), fmaxf(fmaxf(sc[4], sc[5]), fmaxf(sc[6], sc[7]))), fmaxf(sc[8], sc[9]));
                auto fetch = [&](int i) { lds128(wf[i], lo + i * 512); };
                {
                    float m1 = __shfl_xor_sync(~0u, mx, 1), m2 = __shfl_xor_sync(~0u, mx, 2), m3 = __shfl_xor_sync(~0u, mx, 3);
                    mbar_spin(bar + 8 * (B_VM + pb), ph);
                    ldsm4(vm, vma);
                    mx = fmaxf(fmaxf(mx, m1), fmaxf(m2, m3)) * SM_SCALE;
                }
#pragma unroll
                for (int i = 0; i < 10; i++) sc[i] = fmaf(sc[i], SM_SCALE, -mx);
                float o0[4] = {0.f, 0.f, 0.f, 0.f}, o1[4] = {0.f, 0.f, 0.f, 0.f}, rs[4] = {0.f, 0.f, 0.f, 0.f};
                sc[8] = ex2(sc[8]); fetch(0); fetch(1); sc[9] = ex2(sc[9]);
                SFENCE();
                fetch(2); sc[0] = ex2(sc[0]); fetch(3); fetch(4); sc[1] = ex2(sc[1]); fetch(5); fetch(6); sc[2] = ex2(sc[2]);
                SFENCE();
                {
                    const uint32_t p = pack2(sc[8], sc[9]);
                    sc[3] = ex2(sc[3]); fetch(7);
                    mma8(o0, vm[0], vm[1], p);
                    mma8(o1, vm[2], vm[3], p);
                    sc[4] = ex2(sc[4]);
                    mma8(rs, one[0], one[1], p);
                    sc[5] = ex2(sc[5]);
                }
                SFENCE();
                {
                    const uint32_t p0 = pack2(sc[0], sc[1]), p1 = pack2(sc[2], sc[3]);
                    sc[6] = ex2(sc[6]);
                    mma16(o0, vf[0][0][0], vf[0][0][1], vf[0][0][2], vf[0][0][3], p0, p1);
                    SFENCE();
                    sc[7] = ex2(sc[7]);
                    mma16(o1, vf[1][0][0], vf[1][0][1], vf[1][0][2], vf[1][0][3], p0, p1);
                    SFENCE();
                    mma16(rs, one[0], one[1], one[2], one[3], p0, p1);
                    SFENCE();
                }
                {
                    const uint32_t p0 = pack2(sc[4], sc[5]), p1 = pack2(sc[6], sc[7]);
                    mma16(o0, vf[0][1][0], vf[0][1][1], vf[0][1][2], vf[0][1][3], p0, p1);
                    mma16(o1, vf[1][1][0], vf[1][1][1], vf[1][1][2], vf[1][1][3], p0, p1);
                    SFENCE();
                    mma16(rs, one[0], one[1], one[2], one[3], p0, p1);
                }
                const uint32_t e = max((__float_as_uint(cw * fmaxf(m4[0], 1.f)) >> 23) & 255u, 31u);
                SFENCE();
                stsm4t(lw + OFF_OB, pack2(o0[0], o0[1]), pack2(o0[2], o0[3]), pack2(o1[0], o1[1]), pack2(o1[2], o1[3]));
                if (w == 0) PROFT(13);
                bar_sync(NB_ATT, 128);
                uint32_t ob[16];
#pragma unroll
                for (int j = 0; j < 4; j++) ldsm4(ob + 4 * j, l16 + OFF_OB + j * 512);
                SFENCE();
                const float sig = __uint_as_float((278u - e) << 23);
                isig = __uint_as_float((e - 30u) << 23);
                const float sg0 = rcp(rs[0]) * sig, sg1 = rcp(rs[1]) * sig;
                SFENCE();
                auto tile = [&](uint32_t next, const char* p, auto LAST) {
                    float c[4][4];
#pragma unroll
                    for (int i = 0; i < 4; i++) c[i][0] = c[i][1] = c[i][2] = c[i][3] = 0.f;
#pragma unroll
                    for (int ks = 0; ks < 8; ks++) {
                        mma16(c[ks & 3], wf[ks][0], wf[ks][1], wf[ks][2], wf[ks][3], ob[2 * ks], ob[2 * ks + 1]);
                        if ((ks & 3) == 0) SFENCE();
                        if ((ks & 3) == 3 && !LAST.value) {
                            SFENCE();
#pragma unroll
                            for (int i = ks; i >= ks - 3; i--) { lds128(wf[i], next + i * 512); if (i == ks - 2) SFENCE(); }
                            if (ks == 3) SFENCE();
                        }
                    }
                    SFENCE();
                    if (LAST.value) { bar_arrive_if<NB_WIN, 256>(kind < 2); bar_arrive_if<NB_WIN, 384>(kind == 2); }
                    uint32_t v[4];
#pragma unroll
                    for (int i = 0; i < 4; i++)
                        v[i] = (__float_as_uint(fmaf((c[0][i] + c[1][i]) + (c[2][i] + c[3][i]), i & 1 ? sg1 : sg0, 12582912.f)) << 6) + (i < 2);
                    red_add64((u64*)p, v[0], v[2]);
                    red_add64((u64*)(p + 2048), v[1], v[3]);
                };
                tile(lo + 16384, rp, IC<0>{});
                if (w == 0) PROFT(7);
                tile(lo + 32768, rp + 49152, IC<0>{});
                if (kind == 2) tile(lo + 49152, rp + 98304, IC<0>{});
                tile(0, rp + (kind == 2 ? 28 * 4096 : 98304), IC<1>{});
                if (w == 0) PROFT(8);
                sts32(sb + OFF_MX + 16, __float_as_uint(isig));
                mbar_expect_elect(arm ^ (8 * pb), armb - (w == 2 && s == NSEG - 2 ? 40960 : 0));
                u64 y[20];
                uint32_t b[20];
                bool done[5] = {false, false, false, false, false};
                float z = isig;
                mbar_spin(bar + 8 * B_GO, pb);
                if (w == 0) PROFT(9);
                do {
#pragma unroll
                    for (int i = 0; i < 10; i++) {
                        if (STAG && (i == 2 || i == 4 || i == 7)) {
#pragma unroll
                            for (int k = 0; k < STAG; k++) asm volatile("ex2.approx.ftz.f32 %0,%0;" : "+f"(z));
                            asm volatile("{.reg .pred p; setp.ne.u32 p,%1,0; @p mov.b32 %0,%2;}" : "+r"(sfd) : "r"((uint32_t)never), "f"(z));
                            SFENCE();
                        }
                        ld_acc0(y[2 * i], y[2 * i + 1], lp + (i >> 1) * 32768 + (i & 1) * 4096);
                        if (STAG && (i == 1 || i == 3 || i == 6)) SFENCE();
                    }
                    uint32_t ok = 32u, late = 32u;
                    static_for<5>([&](auto IT) {
                        constexpr int it = IT.value;
                        if (it == 2) late = and3((uint32_t)y[8], (uint32_t)y[10], (uint32_t)y[12]);
                        else if (it == 3) late &= and3((uint32_t)y[14], (uint32_t)y[16], (uint32_t)y[18]);
                        else ok = and3(ok, (uint32_t)y[4 * it], it == 4 ? late : (uint32_t)y[4 * it + 2]);
                        if (it < 4) SFENCE();
                        if (it == 2 || it == 3) ok = and3(ok, (uint32_t)y[4 * it], (uint32_t)y[4 * it + 2]);
                        ok = and3(ok, (uint32_t)y[4 * it + 1], (uint32_t)y[4 * it + 3]);
                        const bool all = __all_sync(~0u, ok);
#pragma unroll
                        for (int j = 0; j < 4; j++) {
                            const u64 v = y[4 * it + j];
                            b[4 * it + j] = pack2((float)(int)(uint32_t)v, (float)(int)(uint32_t)(v >> 32));
                        }
                        sts128(lw + OFF_MEMB + it * 2048, b[4 * it], b[4 * it + 1], b[4 * it + 2], b[4 * it + 3]);
                        mbar_arrive_elect_if(bar + 8 * (B_MEM + it), all && !done[it]);
                        done[it] = all;
                        SFENCE();
                        if (it == 0 && w == 0) PROFT(10);
                    });
                } while (!done[4]);
                if (w == 0) PROFT(11);
                amax = b[0];
#pragma unroll
                for (int i = 1; i < 19; i += 2) amax = absmax2(amax, absmax2(b[i], b[i + 1]));
                amax = absmax2(amax, b[19]);
                const int adv = (s & 7) == 7 ? 163840 - 896 : 128;
                rp += adv; lp += adv;
            }
        }
        bar_sync(NB_KX, 384);
        bar_sync(NB_QK, 384);
        if (rank < 2) { bar_arrive(NB_W1, 512); bar_arrive(NB_WIN, 256); } else bar_arrive(NB_W1, 480);
    } else {
        asm volatile("setmaxnreg.dec.sync.aligned.u32 %0;" ::"n"(48));
        const uint32_t rank = cta_rank();
        const int w = warp - 12;
        pdl_wait();
        pdl_launch();
        uint32_t* sy = g_sync + layer * SYNC_LAYER;
        if (w == 1) {
            mbar_expect_elect(bar + 8 * B_XT, 40960);
            bulk_g2s_elect(sb + OFF_X, g_xn, 40960, bar + 8 * B_XT);
            bar_sync(NB_PRO, 288);
            if (rank == 2) mbar_spin(bar + 8 * B_ST, 0);
            else mbar_arrive_remote_elect(mapa(bar + 8 * B_ST, 2));
            mbar_spin(bar + 8 * B_XT, 0);
            bar_arrive(NB_LD, 288);
            mbar_expect_elect(bar + 8 * (B_XT + 1), rank < 2 ? 45056 : 40960);
        }
        if (rank == 2) {
            if (w == 0) {
                for (int s = -1; s < NSEG - 1; s++) {
                    const uint32_t pb = s & 1, va = sb + OFF_VX + (pb ^ 1) * 8192 + 4096, vb = bar + 8 * (B_VX + (pb ^ 1));
                    bar_sync(NB_KF, 288);
                    fence_async();
                    bulk_s2s_elect(mapa(va, 0), va, 4096, mapa(vb, 0));
                    bulk_s2s_elect(mapa(va, 1), va, 4096, mapa(vb, 1));
                    if (s >= 0) mbar_spin(bar + 8 * (B_XD + pb), (s >> 1) & 1);
                    bar_sync(NB_W1, 480);
                }
            } else if (w == 1) {
                const unsigned char *pn = g_p + h * 12288, *px = g_xn + 40960;
                const uint32_t* pf = sy + wk::SY_P + h;
                for (int s = -1, nb = -1; s < NSEG - 1; s++, pn += H_ * 12288, px += 40960) {
                    const uint32_t pb = s & 1, xt = bar + 8 * (B_XT + pb), qa = sb + OFF_Q + (pb ^ 1) * 5120 + 1024;
                    if (s >= 0) mbar_spin(bar + 8 * (B_X1 + pb), (s >> 1) & 1);
                    if (s + 2 < NSEG) bulk_g2s_all3_elect(sb + OFF_X + pb * 40960, px, 40960, xt);
                    if (s == nb) {
                        while (__any_sync(~0u, ld_acquire(pf) < 3)) __nanosleep(100);
                        pf += H_;
                        nb += min(s + 3, 6);
                    }
                    bulk_g2s_all3_elect(sb + OFF_VX + (pb ^ 1) * 8192, pn + 8192, 4096, bar + 8 * (B_VX + (pb ^ 1)));
                    bulk_g2s_elect(mapa(qa, 0), pn, 4096, mapa(xt, 0));
                    bulk_g2s_elect(mapa(qa, 1), pn + 4096, 4096, mapa(xt, 1));
                    mbar_spin(xt, ((s + 2) >> 1) & 1);
                    bar_sync(NB_W1, 480);
                }
                mbar_spin(bar + 8 * (B_VX + 1), 1);
            } else if (w == 2) {
                uint32_t* hp = sy + 1024;
                const char* pf = lane < 5 ? (const char*)(g_acc + layer * ACC_LAYER) + (5 * h + lane) * 1024 : (const char*)hp;
                const int pfa = lane < 5 ? 163840 : 1024;
                const uint32_t go = mapa(bar + 8 * B_GO, min(lane, 2));
                if (lane < 6) for (int i = 0; i < 8; i++) prefetch_l2(pf + i * 128);
                __syncwarp();
                for (int s = 0; s < NSEG - 1; s++, hp += 32) {
                    bar_sync(NB_W1, 480);
                    mbar_spin(bar + 8 * (B_X1 + (s & 1)), (s >> 1) & 1);
                    uint32_t t = gtime32(), t0 = clk(), c, tm;
                    asm volatile("{.reg .pred p; elect.sync _|p, 0xffffffff; @p red.relaxed.gpu.global.max.u32 [%0+4],%1; @p red.relaxed.gpu.global.add.u32 [%0],1;}"
                                 ::"l"(hp), "r"(t) : "memory");
                    if (h == 0) TLI(940 + s, 0, t);
                    if (lane < 6 && s < NSEG - 8) prefetch_l2(pf + ((s >> 3) + 1) * pfa + (s & 7) * 128);
                    __syncwarp();
                    while (clk() - t0 < (uint32_t)delay2) {}
                    do asm volatile("ld.relaxed.gpu.global.v2.u32 {%0,%1},[%2];" : "=r"(c), "=r"(tm) : "l"(hp) : "memory"); while (__any_sync(~0u, c != H_));
                    const uint32_t wait = min(tm - t, 10000u) * 7 / 4 + delay;
                    while (clk() - t0 < wait) {}
                    if (lane < 3) mbar_arrive_remote(go);
                    __syncwarp();
                }
                bar_sync(NB_W1, 480);
            }
        } else {
            if (w < 2) sts32(sb + OFF_PT + w * 768 + 640 + lane * 4, 0u);
            const uint32_t px = opaque(sb + OFF_PX + (w & 1) * 1280 + lane * 8);
            const uint32_t pt = opaque(sb + OFF_PT + (w & 1) * 768 + lane * 4);
            uint32_t os = opaque(sb + OFF_OST + (lane >> 4) * 1024 + w * 256 + (lane & 15) * 16);
            uint32_t& sfd = os;
            const int lim = opaque(8 * w + g + 8 - 2 * q);
            unsigned char* op = g_o + h * 8192 + rank * 2048;
            uint32_t* oc = sy + wk::SY_O - 1;
            auto report = [&]() {
                __syncwarp();
                asm volatile("{.reg .pred p; elect.sync _|p, 0xffffffff; @p red.relaxed.gpu.global.add.u32 [%0],1;}" ::"l"(oc) : "memory");
                oc++;
            };
            auto store_o = [&](int n) {
                bulk_s2g_elect(op, sb + OFF_OST + (n & 1) * 4096, 2048);
                bulk_s2g_elect(op + 4096, sb + OFF_OST + (n & 1) * 4096 + 2048, 2048);
                bulk_commit();
                op += H_ * 8192;
                bulk_wait<1>();
                report();
            };
            for (int s = 0; s < NSEG; s++) {
                const uint32_t pb = s & 1, ph = (s >> 1) & 1;
                if ((w >> 1) != rank) { if (s >= 1) mbar_spin(bar + 8 * B_PXE, pb ^ 1); }
                else if (w & 1) mbar_spin(bar + 8 * (B_XT + (pb ^ 1)), ((s + 1) >> 1) & 1);
                else mbar_expect_elect(bar + 8 * B_PXF, rank ? 2560 : 1536);
                const u64 dq = mkdesc(sb + OFF_Q + pb * 5120 + 1024, 128, 512), dk = mkdesc(sb + OFF_K + pb * 5120, 128, 1024);
                SFENCE();
                bar_sync(NB_W1, 512);
                float c[20];
                wg_fence();
                wgmma_n40_ss<0>(c, dq, dk);
#pragma unroll
                for (int ks = 1; ks < 4; ks++) wgmma_n40_ss<1>(c, dq + ks * 16, dk + ks * 16);
                wg_commit();
                bar_arrive(NB_X, 384);
                wg_wait<0>();
                if ((w >> 1) != rank) {
                    const uint32_t pa = mapa(px, rank ^ 1), pf = mapa(bar + 8 * B_PXF, rank ^ 1);
#pragma unroll
                    for (int nt = 0; nt < 5; nt++)
                        if (nt < 3 || rank == 0) st_async2(pa + nt * 256, __float_as_uint(c[4 * nt]), __float_as_uint(c[4 * nt + 1]), pf);
                    if ((w & 1) && s) store_o(s - 1);
                    mbar_spin(bar + 8 * (w & 1 ? B_VX : B_VM) + 8 * pb, ph);
                } else {
                    mbar_spin(bar + 8 * B_PXF, pb);
                    float u[10];
#pragma unroll
                    for (int nt = 0; nt < 5; nt++) lds64f(u[2 * nt], u[2 * nt + 1], px + nt * 256);
#pragma unroll
                    for (int i = 0; i < 10; i++) u[i] = 8 * (i >> 1) + (i & 1) <= lim ? u[i] + c[4 * (i >> 1) + (i & 1)] : -INFINITY;
                    float mx = fmaxf(fmaxf(fmaxf(fmaxf(u[0], u[1]), fmaxf(u[2], u[3])), fmaxf(fmaxf(u[4], u[5]), fmaxf(u[6], u[7]))), fmaxf(u[8], u[9]));
                    const float m1 = __shfl_xor_sync(~0u, mx, 1), m2 = __shfl_xor_sync(~0u, mx, 2), m3 = __shfl_xor_sync(~0u, mx, 3);
                    mx = fmaxf(fmaxf(mx, m1), fmaxf(m2, m3)) * SM_SCALE;
#pragma unroll
                    for (int i = 0; i < 10; i++) u[i] = ex2(fmaf(u[i], SM_SCALE, -mx));
                    float sum = (((u[0] + u[1]) + (u[2] + u[3])) + ((u[4] + u[5]) + (u[6] + u[7]))) + (u[8] + u[9]);
                    const float s1 = __shfl_xor_sync(~0u, sum, 1), s2 = __shfl_xor_sync(~0u, sum, 2), s3 = __shfl_xor_sync(~0u, sum, 3);
                    sum = rcp((sum + s1) + (s2 + s3));
#pragma unroll
                    for (int nt = 0; nt < 5; nt++) sts32(pt + (nt ? nt - 1 : 4) * 128, pack2(u[2 * nt] * sum, u[2 * nt + 1] * sum));
                }
                float acc[2][8];
                const u64 dv = mkdesc(sb + OFF_VX + pb * 8192, 128, 512), dp = mkdesc(sb + OFF_PT, 128, 768);
                const u64 dm = mkdesc(sb + OFF_VM + pb * 2048, 0, 128);
                fence_async();
                bar_sync(NB_WIN, 256);
                wg_fence();
#pragma unroll
                for (int m = 0; m < 2; m++) {
                    wgmma_n16_ss<0>(acc[m], dv + m * 256, dp);
                    wgmma_n16_ss<1>(acc[m], dv + m * 256 + 16, dp + 16);
                    wgmma_n16_ss<1>(acc[m], dm + m * 64, dp + 32);
                }
                wg_commit();
                bar_arrive_if<NB_W2, 384>(s < NSEG - 1);
                wg_wait<0>();
#pragma unroll
                for (int m = 0; m < 2; m++)
                    stsm4t(os + pb * 4096 + m * 2048, pack2(acc[m][0], acc[m][1]), pack2(acc[m][2], acc[m][3]), pack2(acc[m][4], acc[m][5]), pack2(acc[m][6], acc[m][7]));
                fence_async();
                mbar_arrive_remote_elect(mapa(bar + 8 * (B_XD + pb), 2));
                if ((w >> 1) == rank) mbar_arrive_remote_elect(mapa(bar + 8 * B_PXE, rank ^ 1));
            }
            bar_sync(NB_W2, 128);
            if (w == 3 - 2 * rank) {
                store_o(NSEG - 1);
                bulk_wait<0>();
                report();
            }
        }
    }
    __syncwarp();
    if (lane < 3) mbar_arrive_remote(mapa(bar + 8 * B_FIN, lane));
    mbar_wait(bar + 8 * B_FIN, 0);
    TLE(2 + 5 * layer);
}

int g_delay = 2501050, g_layers = 2;

void make_map(CUtensorMap* m, CUtensorMapDataType dt, const void* p, const cuuint64_t* dim, const cuuint64_t* str, const cuuint32_t* box, CUtensorMapSwizzle sw) {
    typedef CUresult (*Fn)(CUtensorMap*, CUtensorMapDataType, cuuint32_t, void*, const cuuint64_t*, const cuuint64_t*, const cuuint32_t*,
                           const cuuint32_t*, CUtensorMapInterleave, CUtensorMapSwizzle, CUtensorMapL2promotion, CUtensorMapFloatOOBfill);
    static Fn fn = nullptr;
    if (!fn) {
        cudaDriverEntryPointQueryResult qr;
        cudaGetDriverEntryPoint("cuTensorMapEncodeTiled", (void**)&fn, cudaEnableDefault, &qr);
    }
    const cuuint32_t es[3] = {1, 1, 1};
    fn(m, dt, 3, (void*)p, dim, str, box, es, CU_TENSOR_MAP_INTERLEAVE_NONE, sw, CU_TENSOR_MAP_L2_PROMOTION_L2_128B, CU_TENSOR_MAP_FLOAT_OOB_FILL_NONE);
}
void map_weight(CUtensorMap* m, const bf16* p, int rows, int cols, int ng, int br = 64) {
    const cuuint64_t dim[3] = {64, (cuuint64_t)rows, (cuuint64_t)cols / 64}, str[2] = {(cuuint64_t)cols * 2, 128};
    const cuuint32_t box[3] = {64, (cuuint32_t)br, (cuuint32_t)ng};
    make_map(m, CU_TENSOR_MAP_DATA_TYPE_BFLOAT16, p, dim, str, box, CU_TENSOR_MAP_SWIZZLE_128B);
}
void map_pieces(CUtensorMap* m, const void* p, int np, int ns) {
    const cuuint64_t dim[3] = {256, (cuuint64_t)np * 2, NSEG}, str[2] = {2048, (cuuint64_t)np * 4096};
    const cuuint32_t box[3] = {256, 2, (cuuint32_t)ns};
    make_map(m, CU_TENSOR_MAP_DATA_TYPE_UINT64, p, dim, str, box, CU_TENSOR_MAP_SWIZZLE_NONE);
}

template <class... P, class... A> void launch(void (*k)(P...), int grid, int block, int smem, int cluster, bool pdl, A... args) {
    cudaLaunchConfig_t c = {};
    c.gridDim = dim3(grid); c.blockDim = dim3(block); c.dynamicSmemBytes = smem; c.stream = cudaStreamPerThread;
    cudaLaunchAttribute at[2];
    int n = 0;
    if (cluster > 1) { at[n].id = cudaLaunchAttributeClusterDimension; at[n].val.clusterDim.x = cluster; at[n].val.clusterDim.y = 1; at[n].val.clusterDim.z = 1; n++; }
    if (pdl) { at[n].id = cudaLaunchAttributeProgrammaticStreamSerialization; at[n].val.programmaticStreamSerializationAllowed = 1; n++; }
    c.attrs = at; c.numAttrs = n;
    cudaLaunchKernelEx(&c, k, args...);
}

int max_clusters() {
    cudaLaunchConfig_t c = {};
    c.gridDim = dim3(3 * H_); c.blockDim = dim3(512); c.dynamicSmemBytes = rec::SMEM;
    cudaLaunchAttribute at[1];
    at[0].id = cudaLaunchAttributeClusterDimension; at[0].val.clusterDim.x = 3; at[0].val.clusterDim.y = 1; at[0].val.clusterDim.z = 1;
    c.attrs = at; c.numAttrs = 1;
    int n = 0;
    cudaOccupancyMaxActiveClusters(&n, rec_kernel, &c);
    return n;
}

}

extern "C" void kernel_launch(void* const* d_in, const int* in_sizes, int n_in, void* d_out, int out_size) {
    const bf16* x = (const bf16*)d_in[0];
    const bf16* mem0 = (const bf16*)d_in[1];
    const bf16* Wq = (const bf16*)d_in[2];
    const bf16* Wk = (const bf16*)d_in[3];
    const bf16* Wv = (const bf16*)d_in[4];
    const bf16* Wo = (const bf16*)d_in[5];
    const bf16* wr = (const bf16*)d_in[8];
    const bf16* wi = (const bf16*)d_in[9];
    cudaFuncSetAttribute(rec_kernel, cudaFuncAttributeMaxDynamicSharedMemorySize, rec::SMEM);
    cudaFuncSetAttribute(side_kernel, cudaFuncAttributeMaxDynamicSharedMemorySize, wk::SMEM);
    cudaFuncSetAttribute(colfft_kernel, cudaFuncAttributeMaxDynamicSharedMemorySize, CF_SMEM);
    Maps maps;
    void *pxn, *po;
    cudaGetSymbolAddress(&pxn, g_xn);
    cudaGetSymbolAddress(&po, g_o);
    map_weight(&maps.wq2, Wq, D_, 4096, 2); map_weight(&maps.wv1, Wv, D_, 4096, 1);
    map_weight(&maps.wo2, Wo, 4096, D_, 2); map_weight(&maps.wo1, Wo, 4096, D_, 1, 192);
    map_pieces(&maps.x6, pxn, 10, 6); map_pieces(&maps.x2, pxn, 10, 2);
    map_pieces(&maps.o6, po, 64, 6); map_pieces(&maps.o2, po, 64, 2);
    bf16 *x1, *x2;
    cudaGetSymbolAddress((void**)&x1, g_x1);
    cudaGetSymbolAddress((void**)&x2, g_x2);
    constexpr int ONE_PER_SM = 120 * 1024;
    cudaFuncSetAttribute(rowfft_kernel, cudaFuncAttributeMaxDynamicSharedMemorySize, ONE_PER_SM);
    cudaFuncSetAttribute(rowifft_kernel, cudaFuncAttributeMaxDynamicSharedMemorySize, ONE_PER_SM);
    static int ncl = 0, nsm = 0;
    if (!ncl) { ncl = max_clusters(); cudaDeviceGetAttribute(&nsm, cudaDevAttrMultiProcessorCount, 0); }
    maps.wr = wr; maps.wi = wi;
    launch(prep_kernel, 128, 512, 0, 1, false, x, Wq, Wk, Wv, Wo);
    for (int layer = 0; layer < g_layers; layer++) {
        const bf16* xin = layer ? x2 : x;
        launch(rec_kernel, 3 * ncl, 512, rec::SMEM, 3, true, maps, xin, x1, mem0, Wq, Wk, Wv, Wo, layer, g_delay % 10000, g_delay / 10000);
        launch(side_kernel, nsm - 3 * (ncl - H_), 512, wk::SMEM, 1, true, maps, xin, x1, layer);
        launch(rowfft_kernel, 128, 256, ONE_PER_SM, 1, true, xin, x1, Wq, Wk, Wv, layer);
        launch(colfft_kernel, 107, 384, CF_SMEM, 1, true, layer);
        launch(rowifft_kernel, 128, 256, ONE_PER_SM, 1, true, (const bf16*)x1, layer ? (bf16*)d_out : x2, layer);
    }
}
```

```cpp
#include <cuda_runtime.h>
#include <cuda_bf16.h>
#include <cuda.h>
#include <stdint.h>

#define DEV __device__ __forceinline__
typedef unsigned long long u64;
typedef __nv_bfloat16 bf16;

namespace {

constexpr int S_ = 2048, D_ = 640, H_ = 32, E_ = 128, NSEG = 64;

__device__ __align__(1024) unsigned char g_xn[S_ * D_ * 2];
__device__ __align__(1024) unsigned char g_o[S_ * H_ * E_ * 2];
constexpr int ACC_LAYER = 32 * 5120;
__device__ __align__(4096) u64 g_acc[2 * ACC_LAYER];
__device__ __align__(16) float g_nrm[256];
__device__ __align__(1024) unsigned char g_p[NSEG * H_ * 3 * 4096];
constexpr int SYNC_LAYER = 1024 + 64 * 32;
__device__ __align__(128) uint32_t g_sync[2 * SYNC_LAYER];
__device__ uint32_t g_started[2];
__device__ __align__(1024) bf16 g_x1[S_ * D_];
__device__ __align__(1024) bf16 g_x2[S_ * D_];
constexpr int YT_ROWS = 128;
__device__ __align__(1024) float g_yt[2 * YT_ROWS * D_];
constexpr int NCOL = 321;
__device__ __align__(1024) unsigned char g_z[NCOL * 8192];
__device__ __align__(1024) unsigned char g_wt[NCOL * 8192];
__device__ __align__(1024) uint4 g_f128[2 * 8 * 256];
__device__ __align__(1024) uint4 g_f64[2 * 4 * 128];
__device__ __align__(1024) bf16 g_g32[2 * 4096];
#define TLI(id, k, v)
#define TLS(i)
#define TLE(i)

DEV uint32_t s2u(const void* p) { return (uint32_t)__cvta_generic_to_shared(p); }
DEV uint32_t clk() { uint32_t c; asm volatile("mov.u32 %0,%%clock;" : "=r"(c)::"memory"); return c; }
DEV uint32_t gtime32() { uint32_t t; asm volatile("mov.u32 %0,%%globaltimer_lo;" : "=r"(t)::"memory"); return t; }
DEV uint32_t cta_rank() { uint32_t r; asm volatile("mov.u32 %0,%%cluster_ctarank;" : "=r"(r)); return __shfl_sync(~0u, r, 0); }
DEV uint32_t mapa(uint32_t a, uint32_t r) { uint32_t o; asm("mapa.shared::cluster.u32 %0,%1,%2;" : "=r"(o) : "r"(a), "r"(r)); return o; }
DEV void mbar_init(uint32_t b, uint32_t n) { asm volatile("mbarrier.init.shared::cta.b64 [%0],%1;" ::"r"(b), "r"(n) : "memory"); }
DEV bool mbar_try(uint32_t b, uint32_t par, int) {
    uint32_t ok;
    asm volatile("{.reg .pred p; mbarrier.test_wait.parity.shared::cta.b64 p,[%1],%2; selp.u32 %0,1,0,p;}" : "=r"(ok) : "r"(b), "r"(par) : "memory");
    return ok;
}
DEV bool mbar_try(uint32_t b, uint32_t par) {
    uint32_t ok;
    asm volatile("{.reg .pred p; mbarrier.try_wait.parity.shared::cta.b64 p,[%1],%2; selp.u32 %0,1,0,p;}" : "=r"(ok) : "r"(b), "r"(par) : "memory");
    return ok;
}
constexpr uint32_t SPIN_LIMIT = 1u << 18;
DEV void die() { __trap(); }
DEV void mbar_wait(uint32_t b, uint32_t par) {
    uint32_t n = 0;
    while (!mbar_try(b, par)) if (++n > SPIN_LIMIT) die();
}
DEV void mbar_spin(uint32_t b, uint32_t par) { while (!mbar_try(b, par)) {} }
DEV uint32_t opaque(uint32_t x) { return __shfl_xor_sync(~0u, x, 0); }
#define SFENCE() asm volatile("{.reg .pred p; setp.ne.u32 p,%1,0; @p mov.u32 %0,%%clock;}" : "+r"(sfd) : "r"((uint32_t)never) : "memory")
DEV void mbar_arrive(uint32_t b) { asm volatile("mbarrier.arrive.shared::cta.b64 _,[%0];" ::"r"(b) : "memory"); }
DEV void mbar_arrive_elect(uint32_t b) { asm volatile("{.reg .pred p; elect.sync _|p, 0xffffffff; @p mbarrier.arrive.shared::cta.b64 _,[%0];}" ::"r"(b) : "memory"); }
DEV void mbar_arrive_elect_if(uint32_t b, bool c) {
    asm volatile("{.reg .pred p, q; setp.ne.u32 q,%1,0; elect.sync _|p, 0xffffffff; and.pred p,p,q; @p mbarrier.arrive.shared::cta.b64 _,[%0];}" ::"r"(b), "r"((uint32_t)c) : "memory");
}
DEV void mbar_expect_elect(uint32_t b, uint32_t tx) {
    asm volatile("{.reg .pred p; elect.sync _|p, 0xffffffff; @p mbarrier.arrive.expect_tx.shared::cta.b64 _,[%0],%1;}" ::"r"(b), "r"(tx) : "memory");
}
DEV void mbar_arrive_remote_elect(uint32_t b) { asm volatile("{.reg .pred p; elect.sync _|p, 0xffffffff; @p mbarrier.arrive.shared::cluster.b64 _,[%0];}" ::"r"(b) : "memory"); }
DEV bool elect() { uint32_t r; asm volatile("{.reg .pred p; elect.sync _|p, 0xffffffff; selp.u32 %0,1,0,p;}" : "=r"(r)); return r; }
DEV void mbar_arrive_remote(uint32_t b) { asm volatile("mbarrier.arrive.shared::cluster.b64 _,[%0];" ::"r"(b) : "memory"); }
DEV void mbar_expect(uint32_t b, uint32_t tx) { asm volatile("mbarrier.arrive.expect_tx.shared::cta.b64 _,[%0],%1;" ::"r"(b), "r"(tx) : "memory"); }
DEV void bar_sync(int id, int n) { asm volatile("bar.sync %0,%1;" ::"r"(id), "r"(n) : "memory"); }
DEV void bar_arrive(int id, int n) { asm volatile("bar.arrive %0,%1;" ::"r"(id), "r"(n) : "memory"); }
template <int ID, int N> DEV void bar_arrive_if(bool p) {
    asm volatile("{.reg .pred p; setp.ne.u32 p,%0,0; @p bar.arrive %1,%2;}" ::"r"((uint32_t)p), "n"(ID), "n"(N) : "memory");
}
DEV void prefetch_bulk(const void* p, uint32_t bytes) { asm volatile("cp.async.bulk.prefetch.L2.global [%0],%1;" ::"l"(p), "r"(bytes) : "memory"); }
DEV void prefetch_l2(const void* p) { asm volatile("prefetch.global.L2 [%0];" ::"l"(p) : "memory"); }
template <int ID, int N> DEV void bar_sync_if(bool p) {
    asm volatile("{.reg .pred p; setp.ne.u32 p,%0,0; @p bar.sync %1,%2;}" ::"r"((uint32_t)p), "n"(ID), "n"(N) : "memory");
}
DEV void st_remote(uint32_t a, uint32_t x) { asm volatile("st.relaxed.cluster.shared::cluster.u32 [%0],%1;" ::"r"(a), "r"(x) : "memory"); }
DEV void st_async1(uint32_t a, uint32_t x, uint32_t b) {
    asm volatile("st.async.shared::cluster.mbarrier::complete_tx::bytes.u32 [%0],%1,[%2];" ::"r"(a), "r"(x), "r"(b) : "memory");
}
DEV void st_async2(uint32_t a, uint32_t x, uint32_t y, uint32_t b) {
    asm volatile("st.async.shared::cluster.mbarrier::complete_tx::bytes.v2.u32 [%0],{%1,%2},[%3];" ::"r"(a), "r"(x), "r"(y), "r"(b) : "memory");
}
DEV void st_async4(uint32_t a, uint32_t x, uint32_t y, uint32_t z, uint32_t w, uint32_t b) {
    asm volatile("st.async.shared::cluster.mbarrier::complete_tx::bytes.v4.u32 [%0],{%1,%2,%3,%4},[%5];" ::"r"(a), "r"(x), "r"(y), "r"(z), "r"(w), "r"(b) : "memory");
}
DEV void bulk_g2s(uint32_t dst, const void* src, uint32_t bytes, uint32_t b) {
    asm volatile("cp.async.bulk.shared::cluster.global.mbarrier::complete_tx::bytes [%0],[%1],%2,[%3];" ::"r"(dst), "l"(src), "r"(bytes), "r"(b) : "memory");
}
DEV void bulk_g2s_elect(uint32_t dst, const void* src, uint32_t bytes, uint32_t b) {
    asm volatile("{.reg .pred p; elect.sync _|p, 0xffffffff; @p cp.async.bulk.shared::cluster.global.mbarrier::complete_tx::bytes [%0],[%1],%2,[%3];}"
                 ::"r"(dst), "l"(src), "r"(bytes), "r"(b) : "memory");
}
DEV void bulk_g2s_all3_elect(uint32_t dst, const void* src, uint32_t bytes, uint32_t b) {
    asm volatile("{.reg .pred p; elect.sync _|p, 0xffffffff; @p cp.async.bulk.shared::cluster.global.mbarrier::complete_tx::bytes.multicast::cluster [%0],[%1],%2,[%3],%4;}"
                 ::"r"(dst), "l"(src), "r"(bytes), "r"(b), "h"((unsigned short)7) : "memory");
}
DEV void bulk_s2s_elect(uint32_t dst, uint32_t src, uint32_t bytes, uint32_t b) {
    asm volatile("{.reg .pred p; elect.sync _|p, 0xffffffff; @p cp.async.bulk.shared::cluster.shared::cta.mbarrier::complete_tx::bytes [%0],[%1],%2,[%3];}"
                 ::"r"(dst), "r"(src), "r"(bytes), "r"(b) : "memory");
}
DEV void bulk_s2g_elect(void* dst, uint32_t src, uint32_t bytes) {
    asm volatile("{.reg .pred p; elect.sync _|p, 0xffffffff; @p cp.async.bulk.global.shared::cta.bulk_group [%0],[%1],%2;}" ::"l"(dst), "r"(src), "r"(bytes) : "memory");
}
DEV void bulk_s2s(uint32_t dst, uint32_t src, uint32_t bytes, uint32_t b) {
    asm volatile("cp.async.bulk.shared::cluster.shared::cta.mbarrier::complete_tx::bytes [%0],[%1],%2,[%3];" ::"r"(dst), "r"(src), "r"(bytes), "r"(b) : "memory");
}
DEV void bulk_s2g(void* dst, uint32_t src, uint32_t bytes) {
    asm volatile("cp.async.bulk.global.shared::cta.bulk_group [%0],[%1],%2;" ::"l"(dst), "r"(src), "r"(bytes) : "memory");
}
DEV void tma3d(uint32_t dst, const CUtensorMap* m, int c0, int c1, int c2, uint32_t b) {
    asm volatile("cp.async.bulk.tensor.3d.shared::cluster.global.mbarrier::complete_tx::bytes [%0],[%1,{%3,%4,%5}],[%2];"
                 ::"r"(dst), "l"(m), "r"(b), "r"(c0), "r"(c1), "r"(c2) : "memory");
}
DEV void bulk_commit() { asm volatile("cp.async.bulk.commit_group;" ::: "memory"); }
template <int N> DEV void bulk_wait() { asm volatile("cp.async.bulk.wait_group %0;" ::"n"(N) : "memory"); }
template <int N> DEV void bulk_wait_read() { asm volatile("cp.async.bulk.wait_group.read %0;" ::"n"(N) : "memory"); }
DEV void fence_async_all() { asm volatile("fence.proxy.async;" ::: "memory"); }
DEV void flag_add(uint32_t* p) { asm volatile("red.relaxed.gpu.global.add.u32 [%0],1;" ::"l"(p) : "memory"); }
DEV uint32_t ld_acquire(const uint32_t* p) { uint32_t v; asm volatile("ld.acquire.gpu.global.u32 %0,[%1];" : "=r"(v) : "l"(p) : "memory"); return v; }
DEV void flag_wait(const uint32_t* p, uint32_t n) {
    for (uint32_t it = 0; ld_acquire(p) < n; __nanosleep(100)) if (++it > (SPIN_LIMIT << 3)) die();
    fence_async_all();
}
DEV void cp16(uint32_t dst, const void* src) { asm volatile("cp.async.cg.shared.global [%0],[%1],16;" ::"r"(dst), "l"(src) : "memory"); }
DEV void cp_commit() { asm volatile("cp.async.commit_group;" ::: "memory"); }
template <int N> DEV void cp_wait() { asm volatile("cp.async.wait_group %0;" ::"n"(N) : "memory"); }
DEV uint32_t lds32(uint32_t a) { uint32_t x; asm volatile("ld.shared.u32 %0,[%1];" : "=r"(x) : "r"(a) : "memory"); return x; }
DEV void fence_async() { asm volatile("fence.proxy.async.shared::cta;" ::: "memory"); }
DEV uint32_t pack2(float lo, float hi) { uint32_t r; asm("cvt.rn.bf16x2.f32 %0,%1,%2;" : "=r"(r) : "f"(hi), "f"(lo)); return r; }
DEV uint32_t prmt(uint32_t a, uint32_t b, uint32_t s) { uint32_t r; asm("prmt.b32 %0,%1,%2,%3;" : "=r"(r) : "r"(a), "r"(b), "r"(s)); return r; }
DEV float ex2(float x) { float r; asm("ex2.approx.ftz.f32 %0,%1;" : "=f"(r) : "f"(x)); return r; }
DEV float sqrt_approx(float x) { float r; asm("sqrt.approx.ftz.f32 %0,%1;" : "=f"(r) : "f"(x)); return r; }
DEV float rcp(float x) { float r; asm("rcp.approx.ftz.f32 %0,%1;" : "=f"(r) : "f"(x)); return r; }
DEV void lds128(uint32_t* r, uint32_t a) { asm volatile("ld.shared.v4.u32 {%0,%1,%2,%3},[%4];" : "=r"(r[0]), "=r"(r[1]), "=r"(r[2]), "=r"(r[3]) : "r"(a) : "memory"); }
DEV void lds64(uint32_t* r, uint32_t a) { asm volatile("ld.shared.v2.u32 {%0,%1},[%2];" : "=r"(r[0]), "=r"(r[1]) : "r"(a) : "memory"); }
DEV void lds64f(float& x, float& y, uint32_t a) { asm volatile("ld.shared.v2.f32 {%0,%1},[%2];" : "=f"(x), "=f"(y) : "r"(a) : "memory"); }
DEV void lds128f(float* r, uint32_t a) { asm volatile("ld.shared.v4.f32 {%0,%1,%2,%3},[%4];" : "=f"(r[0]), "=f"(r[1]), "=f"(r[2]), "=f"(r[3]) : "r"(a) : "memory"); }
DEV void sts128(uint32_t a, uint32_t x, uint32_t y, uint32_t z, uint32_t w) { asm volatile("st.shared.v4.u32 [%0],{%1,%2,%3,%4};" ::"r"(a), "r"(x), "r"(y), "r"(z), "r"(w) : "memory"); }
DEV void sts64(uint32_t a, uint32_t x, uint32_t y) { asm volatile("st.shared.v2.u32 [%0],{%1,%2};" ::"r"(a), "r"(x), "r"(y) : "memory"); }
DEV void sts32(uint32_t a, uint32_t x) { asm volatile("st.shared.u32 [%0],%1;" ::"r"(a), "r"(x) : "memory"); }
DEV void ldsm4(uint32_t* r, uint32_t a) { asm volatile("ldmatrix.sync.aligned.m8n8.x4.shared.b16 {%0,%1,%2,%3},[%4];" : "=r"(r[0]), "=r"(r[1]), "=r"(r[2]), "=r"(r[3]) : "r"(a) : "memory"); }
DEV void ldsm4t(uint32_t* r, uint32_t a) { asm volatile("ldmatrix.sync.aligned.m8n8.x4.trans.shared.b16 {%0,%1,%2,%3},[%4];" : "=r"(r[0]), "=r"(r[1]), "=r"(r[2]), "=r"(r[3]) : "r"(a) : "memory"); }
DEV void ldsm2(uint32_t* r, uint32_t a) { asm volatile("ldmatrix.sync.aligned.m8n8.x2.shared.b16 {%0,%1},[%2];" : "=r"(r[0]), "=r"(r[1]) : "r"(a) : "memory"); }
DEV void stsm4t(uint32_t a, uint32_t x, uint32_t y, uint32_t z, uint32_t w) { asm volatile("stmatrix.sync.aligned.m8n8.x4.trans.shared.b16 [%0],{%1,%2,%3,%4};" ::"r"(a), "r"(x), "r"(y), "r"(z), "r"(w) : "memory"); }
DEV void stsm4(uint32_t a, uint32_t x, uint32_t y, uint32_t z, uint32_t w) { asm volatile("stmatrix.sync.aligned.m8n8.x4.shared.b16 [%0],{%1,%2,%3,%4};" ::"r"(a), "r"(x), "r"(y), "r"(z), "r"(w) : "memory"); }
DEV void stsm2(uint32_t a, uint32_t x, uint32_t y) { asm volatile("stmatrix.sync.aligned.m8n8.x2.shared.b16 [%0],{%1,%2};" ::"r"(a), "r"(x), "r"(y) : "memory"); }
DEV void sts128f_if(uint32_t a, const float* v, bool p) {
    asm volatile("{.reg .pred p; setp.ne.u32 p,%5,0; @p st.shared.v4.f32 [%0],{%1,%2,%3,%4};}" ::"r"(a), "f"(v[0]), "f"(v[1]), "f"(v[2]), "f"(v[3]), "r"((uint32_t)p) : "memory");
}
DEV void stsm2t_if(uint32_t a, uint32_t x, uint32_t y, bool p) {
    asm volatile("{.reg .pred p; setp.ne.u32 p,%3,0; @p stmatrix.sync.aligned.m8n8.x2.trans.shared.b16 [%0],{%1,%2};}" ::"r"(a), "r"(x), "r"(y), "r"((uint32_t)p) : "memory");
}
DEV void stsm2t(uint32_t a, uint32_t x, uint32_t y) { asm volatile("stmatrix.sync.aligned.m8n8.x2.trans.shared.b16 [%0],{%1,%2};" ::"r"(a), "r"(x), "r"(y) : "memory"); }
DEV void mma16(float* d, uint32_t a0, uint32_t a1, uint32_t a2, uint32_t a3, uint32_t b0, uint32_t b1) {
    asm volatile("mma.sync.aligned.m16n8k16.row.col.f32.bf16.bf16.f32 {%0,%1,%2,%3},{%4,%5,%6,%7},{%8,%9},{%0,%1,%2,%3};"
                 : "+f"(d[0]), "+f"(d[1]), "+f"(d[2]), "+f"(d[3]) : "r"(a0), "r"(a1), "r"(a2), "r"(a3), "r"(b0), "r"(b1));
}
DEV void mma8(float* d, uint32_t a0, uint32_t a1, uint32_t b0) {
    asm volatile("mma.sync.aligned.m16n8k8.row.col.f32.bf16.bf16.f32 {%0,%1,%2,%3},{%4,%5},{%6},{%0,%1,%2,%3};"
                 : "+f"(d[0]), "+f"(d[1]), "+f"(d[2]), "+f"(d[3]) : "r"(a0), "r"(a1), "r"(b0));
}
DEV u64 mkdesc(uint32_t a, uint32_t lbo, uint32_t sbo) { return (u64)((a & 0x3ffff) >> 4) | ((u64)(lbo >> 4) << 16) | ((u64)(sbo >> 4) << 32); }
constexpr u64 SW128 = 1ull << 62;
DEV void wg_fence() { asm volatile("wgmma.fence.sync.aligned;" ::: "memory"); }
DEV void wg_commit() { asm volatile("wgmma.commit_group.sync.aligned;" ::: "memory"); }
template <int N> DEV void wg_wait() { asm volatile("wgmma.wait_group.sync.aligned %0;" ::"n"(N) : "memory"); }
template <int ACC> DEV void wgmma_n32_rs(float* d, const uint32_t* a, u64 desc) {
    asm volatile("wgmma.mma_async.sync.aligned.m64n32k16.f32.bf16.bf16 {%0,%1,%2,%3,%4,%5,%6,%7,%8,%9,%10,%11,%12,%13,%14,%15},{%16,%17,%18,%19},%20,%21,1,1,0;"
                 : "+f"(d[0]), "+f"(d[1]), "+f"(d[2]), "+f"(d[3]), "+f"(d[4]), "+f"(d[5]), "+f"(d[6]), "+f"(d[7]),
                   "+f"(d[8]), "+f"(d[9]), "+f"(d[10]), "+f"(d[11]), "+f"(d[12]), "+f"(d[13]), "+f"(d[14]), "+f"(d[15])
                 : "r"(a[0]), "r"(a[1]), "r"(a[2]), "r"(a[3]), "l"(desc), "n"(ACC));
}
template <int ACC> DEV void wgmma_n32_ss(float* d, u64 da, u64 desc) {
    asm volatile("wgmma.mma_async.sync.aligned.m64n32k16.f32.bf16.bf16 {%0,%1,%2,%3,%4,%5,%6,%7,%8,%9,%10,%11,%12,%13,%14,%15},%16,%17,%18,1,1,0,0;"
                 : "+f"(d[0]), "+f"(d[1]), "+f"(d[2]), "+f"(d[3]), "+f"(d[4]), "+f"(d[5]), "+f"(d[6]), "+f"(d[7]),
                   "+f"(d[8]), "+f"(d[9]), "+f"(d[10]), "+f"(d[11]), "+f"(d[12]), "+f"(d[13]), "+f"(d[14]), "+f"(d[15])
                 : "l"(da), "l"(desc), "n"(ACC));
}
template <int ACC> DEV void wgmma_n16_ss(float* d, u64 da, u64 desc) {
    asm volatile("wgmma.mma_async.sync.aligned.m64n16k16.f32.bf16.bf16 {%0,%1,%2,%3,%4,%5,%6,%7},%8,%9,%10,1,1,0,0;"
                 : "+f"(d[0]), "+f"(d[1]), "+f"(d[2]), "+f"(d[3]), "+f"(d[4]), "+f"(d[5]), "+f"(d[6]), "+f"(d[7])
                 : "l"(da), "l"(desc), "n"(ACC));
}
#define ACC8(o) "+f"(d[o]), "+f"(d[o + 1]), "+f"(d[o + 2]), "+f"(d[o + 3]), "+f"(d[o + 4]), "+f"(d[o + 5]), "+f"(d[o + 6]), "+f"(d[o + 7])
template <int ACC, int TB> DEV void wgmma_n64_rs(float* d, const uint32_t* a, u64 desc) {
    asm volatile("wgmma.mma_async.sync.aligned.m64n64k16.f32.bf16.bf16 {%0,%1,%2,%3,%4,%5,%6,%7,%8,%9,%10,%11,%12,%13,%14,%15,"
                 "%16,%17,%18,%19,%20,%21,%22,%23,%24,%25,%26,%27,%28,%29,%30,%31},{%32,%33,%34,%35},%36,%37,1,1,%38;"
                 : ACC8(0), ACC8(8), ACC8(16), ACC8(24) : "r"(a[0]), "r"(a[1]), "r"(a[2]), "r"(a[3]), "l"(desc), "n"(ACC), "n"(TB));
}
template <int ACC, int TB> DEV void wgmma_n80_rs(float* d, const uint32_t* a, u64 desc) {
    asm volatile("wgmma.mma_async.sync.aligned.m64n80k16.f32.bf16.bf16 {%0,%1,%2,%3,%4,%5,%6,%7,%8,%9,%10,%11,%12,%13,%14,%15,"
                 "%16,%17,%18,%19,%20,%21,%22,%23,%24,%25,%26,%27,%28,%29,%30,%31,%32,%33,%34,%35,%36,%37,%38,%39},{%40,%41,%42,%43},%44,%45,1,1,%46;"
                 : ACC8(0), ACC8(8), ACC8(16), ACC8(24), ACC8(32) : "r"(a[0]), "r"(a[1]), "r"(a[2]), "r"(a[3]), "l"(desc), "n"(ACC), "n"(TB));
}
template <int TA, int TB> DEV void wgmma_n64_ss(float* d, u64 da, u64 db, int acc) {
    asm volatile("{.reg .pred p; setp.ne.b32 p,%34,0; wgmma.mma_async.sync.aligned.m64n64k16.f32.bf16.bf16 {%0,%1,%2,%3,%4,%5,%6,%7,%8,%9,%10,%11,%12,%13,%14,%15,%16,%17,%18,%19,%20,%21,%22,%23,%24,%25,%26,%27,%28,%29,%30,%31},%32,%33,p,1,1,%35,%36;}"
                 : ACC8(0), ACC8(8), ACC8(16), ACC8(24) : "l"(da), "l"(db), "r"(acc), "n"(TA), "n"(TB));
}
template <int TA, int TB> DEV void wgmma_n128_ss(float* d, u64 da, u64 db, int acc) {
    asm volatile("{.reg .pred p; setp.ne.b32 p,%66,0; wgmma.mma_async.sync.aligned.m64n128k16.f32.bf16.bf16 {%0,%1,%2,%3,%4,%5,%6,%7,%8,%9,%10,%11,%12,%13,%14,%15,%16,%17,%18,%19,%20,%21,%22,%23,%24,%25,%26,%27,%28,%29,%30,%31,%32,%33,%34,%35,%36,%37,%38,%39,%40,%41,%42,%43,%44,%45,%46,%47,%48,%49,%50,%51,%52,%53,%54,%55,%56,%57,%58,%59,%60,%61,%62,%63},%64,%65,p,1,1,%67,%68;}"
                 : ACC8(0), ACC8(8), ACC8(16), ACC8(24), ACC8(32), ACC8(40), ACC8(48), ACC8(56) : "l"(da), "l"(db), "r"(acc), "n"(TA), "n"(TB));
}
template <int TA, int TB> DEV void wgmma_n192_ss(float* d, u64 da, u64 db, int acc) {
    asm volatile("{.reg .pred p; setp.ne.b32 p,%98,0; wgmma.mma_async.sync.aligned.m64n192k16.f32.bf16.bf16 {%0,%1,%2,%3,%4,%5,%6,%7,%8,%9,%10,%11,%12,%13,%14,%15,%16,%17,%18,%19,%20,%21,%22,%23,%24,%25,%26,%27,%28,%29,%30,%31,%32,%33,%34,%35,%36,%37,%38,%39,%40,%41,%42,%43,%44,%45,%46,%47,%48,%49,%50,%51,%52,%53,%54,%55,%56,%57,%58,%59,%60,%61,%62,%63,%64,%65,%66,%67,%68,%69,%70,%71,%72,%73,%74,%75,%76,%77,%78,%79,%80,%81,%82,%83,%84,%85,%86,%87,%88,%89,%90,%91,%92,%93,%94,%95},%96,%97,p,1,1,%99,%100;}"
                 : ACC8(0), ACC8(8), ACC8(16), ACC8(24), ACC8(32), ACC8(40), ACC8(48), ACC8(56), ACC8(64), ACC8(72), ACC8(80), ACC8(88) : "l"(da), "l"(db), "r"(acc), "n"(TA), "n"(TB));
}
template <int ACC> DEV void wgmma_n40_ss(float* d, u64 da, u64 desc) {
    asm volatile("wgmma.mma_async.sync.aligned.m64n40k16.f32.bf16.bf16 {%0,%1,%2,%3,%4,%5,%6,%7,%8,%9,%10,%11,%12,%13,%14,%15,%16,%17,%18,%19},%20,%21,%22,1,1,0,0;"
                 : ACC8(0), ACC8(8), "+f"(d[16]), "+f"(d[17]), "+f"(d[18]), "+f"(d[19]) : "l"(da), "l"(desc), "n"(ACC));
}
DEV void pdl_wait() { asm volatile("griddepcontrol.wait;" ::: "memory"); }
DEV void pdl_launch() { asm volatile("griddepcontrol.launch_dependents;" ::: "memory"); }
DEV uint32_t ldg32(const void* p) { uint32_t v; asm volatile("ld.global.nc.u32 %0,[%1];" : "=r"(v) : "l"(p)); return v; }
DEV void ld_acc(u64& a, u64& b, const void* p) {
    const uint32_t done = (uint32_t)a & (uint32_t)b & 32u;
    asm volatile("{.reg .pred p; setp.eq.u32 p,%3,0;\n"
                 "@p ld.relaxed.gpu.global.v2.u64 {%0,%1},[%2];}" : "+l"(a), "+l"(b) : "l"(p), "r"(done) : "memory");
}
DEV void ld_acc0(u64& a, u64& b, const void* p) {
    asm volatile("ld.relaxed.gpu.global.v2.u64 {%0,%1},[%2];" : "=l"(a), "=l"(b) : "l"(p) : "memory");
}
DEV uint32_t and3(uint32_t a, uint32_t b, uint32_t c) { uint32_t r; asm volatile("lop3.b32 %0,%1,%2,%3,0x80;" : "=r"(r) : "r"(a), "r"(b), "r"(c)); return r; }
DEV uint32_t absmax2(uint32_t a, uint32_t b) { uint32_t r; asm("max.xorsign.abs.bf16x2 %0,%1,%2;" : "=r"(r) : "r"(a), "r"(b)); return r; }
DEV float lds32f(uint32_t a) { float x; asm volatile("ld.shared.f32 %0,[%1];" : "=f"(x) : "r"(a) : "memory"); return x; }
DEV void red_add64(u64* p, uint32_t lo, uint32_t hi) {
    asm volatile("{.reg .b64 v; mov.b64 v,{%1,%2}; red.relaxed.gpu.global.add.u64 [%0],v;}" ::"l"(p), "r"(lo), "r"(hi) : "memory");
}
DEV float bf_round(float x) { return __bfloat162float(__float2bfloat16_rn(x)); }
DEV float bf_lo(uint32_t u) { return __uint_as_float(u << 16); }
DEV float bf_hi(uint32_t u) { return __uint_as_float(u & 0xffff0000u); }

#define GPROF(i, n)
#define PROFT(i)
#define STAMP(i)

DEV void unpack8(float* v, uint4 u) {
    v[0] = bf_lo(u.x); v[1] = bf_hi(u.x); v[2] = bf_lo(u.y); v[3] = bf_hi(u.y);
    v[4] = bf_lo(u.z); v[5] = bf_hi(u.z); v[6] = bf_lo(u.w); v[7] = bf_hi(u.w);
}
DEV int xn_off(int row, int chunk) { return (row >> 5) * 40960 + (chunk >> 3) * 4096 + (row & 31) * 128 + (((chunk ^ row) & 7) << 4); }

DEV void ln_row(float (&v)[3][8], int lane) {
    float s = 0.f;
#pragma unroll
    for (int c = 0; c < 3; c++)
#pragma unroll
        for (int j = 0; j < 8; j++) s += v[c][j];
#pragma unroll
    for (int o = 16; o; o >>= 1) s += __shfl_xor_sync(~0u, s, o);
    float mean = s * (1.f / D_), q = 0.f;
#pragma unroll
    for (int c = 0; c < 3; c++)
        if (c < 2 || lane < 16)
#pragma unroll
            for (int j = 0; j < 8; j++) { float d = v[c][j] - mean; q += d * d; }
#pragma unroll
    for (int o = 16; o; o >>= 1) q += __shfl_xor_sync(~0u, q, o);
    float mb = bf_round(mean);
    float inv = 1.f / bf_round(sqrtf(bf_round(bf_round(q * (1.f / D_)) + 1e-5f)));
#pragma unroll
    for (int c = 0; c < 3; c++)
#pragma unroll
        for (int j = 0; j < 8; j++) v[c][j] = bf_round(v[c][j] - mb) * inv;
}

__host__ __device__ constexpr int col_freq(int c) {
    return c == 320 ? 320 : c < 192 ? (c >> 6) * 128 + (c & 63) : c == 192 ? 192 : c < 256 ? 448 - c : c == 256 ? 64 : 384 - c;
}
DEV float rdft(int n, int k, int sn, int N) {
    float s, c;
    sincospif((float)((n * k) & (N - 1)) * (2.f / N), &s, &c);
    return !sn ? c : k ? s : (n & 1 ? -1.f : 1.f);
}

__global__ void __launch_bounds__(512) prep_kernel(const bf16* __restrict__ x, const bf16* __restrict__ Wq, const bf16* __restrict__ Wk,
                                                   const bf16* __restrict__ Wv, const bf16* __restrict__ Wo) {
    __shared__ float red[32], col[4][640];
    const int tid = threadIdx.x, lane = tid & 31, warp = tid >> 5, b = blockIdx.x, row = b * 16 + warp;
    TLS(0);
    pdl_launch();
    uint4 ux[3], uv[5], uo[8];
#pragma unroll
    for (int c = 0; c < 3; c++) ux[c] = c < 2 || lane < 16 ? *(const uint4*)(x + row * D_ + (c * 32 + lane) * 8) : make_uint4(0, 0, 0, 0);
#pragma unroll
    for (int i = 0; i < 5; i++) uv[i] = *(const uint4*)(Wv + (size_t)((b & 3) * 160 + i * 32 + (tid >> 4)) * 4096 + (b >> 2) * E_ + (tid & 15) * 8);
    if (tid < 320) {
#pragma unroll
        for (int r = 0; r < 8; r++) uo[r] = *(const uint4*)(Wo + (size_t)(b * 32 + tid / 80 * 8 + r) * D_ + tid % 80 * 8);
    }
    if (tid >= 504) prefetch_bulk((const char*)(tid & 4 ? Wk : Wq) + (b * 4 + (tid & 3)) * 10240, 10240);
    if (b < 3) ((uint4*)g_sync)[b * 512 + tid] = make_uint4(0, 0, 0, 0);
    for (int i = b * 512 + tid; i < ACC_LAYER; i += 128 * 512) ((uint4*)g_acc)[i] = make_uint4(0, 0, 0, 0);
    if (tid < 2 * YT_ROWS * D_ / 4 / 128) ((uint4*)g_yt)[b * (2 * YT_ROWS * D_ / 4 / 128) + tid] = make_uint4(0, 0, 0, 0);
    const int gid = tid < 104 ? b * 104 + tid : 1 << 20;
    if (gid < 4096) {
        const int inv = gid >> 11, ks = (gid >> 8) & 7, t = gid & 255, g = (t & 31) >> 2, q = t & 3, tile = t >> 5;
        uint32_t v[4];
#pragma unroll
        for (int j = 0; j < 4; j++) {
            float x[2];
#pragma unroll
            for (int u = 0; u < 2; u++) {
                const int m = inv ? 16 * tile + 2 * g + (j & 1) : 16 * ks + 8 * (j >> 1) + 2 * q + u;
                const int k2 = inv ? 8 * ks + 2 * q + u : 8 * tile + g, sn = inv ? j >> 1 : j & 1;
                x[u] = rdft(m, k2, sn, 128);
                if (sn && k2) x[u] = -x[u];
            }
            v[j] = pack2(x[0], x[1]);
        }
        g_f128[gid] = make_uint4(v[0], v[1], v[2], v[3]);
    } else if (gid < 5120) {
        const int id = gid - 4096, inv = id >> 9, ks = (id >> 7) & 3, t = id & 127, g = (t & 31) >> 2, q = t & 3, tile = t >> 5;
        uint32_t v[4];
#pragma unroll
        for (int j = 0; j < 4; j++) {
            float x[2];
#pragma unroll
            for (int u = 0; u < 2; u++) {
                const int a = inv ? 16 * tile + g + 8 * (j & 1) : 16 * ks + 8 * (j >> 1) + 2 * q + u;
                const int ka = inv ? 8 * ks + 2 * q + u : 8 * tile + g, sn = inv ? j >> 1 : j & 1;
                x[u] = rdft(a, ka, sn, 64);
            }
            v[j] = pack2(x[0], x[1]);
        }
        g_f64[id] = make_uint4(v[0], v[1], v[2], v[3]);
    } else if (gid < 5120 + 8192) {
        const int id = gid - 5120, inv = id >> 12, n = ((id >> 9) & 7) * 8 + ((id >> 3) & 7), k = ((id >> 6) & 7) * 8 + (id & 7);
        float s, c;
        sincospif((float)(((n >> 1) * (k >> 1)) & 31) * (1.f / 16), &s, &c);
        if (inv) s = -s;
        g_g32[id] = __float2bfloat16_rn((n & 1) == (k & 1) ? c : (k & 1) ? s : -s);
    }
    {
        float v[3][8];
#pragma unroll
        for (int c = 0; c < 3; c++) unpack8(v[c], ux[c]);
        ln_row(v, lane);
#pragma unroll
        for (int c = 0; c < 3; c++)
            if (c < 2 || lane < 16)
                *(uint4*)(g_xn + xn_off(row, c * 32 + lane)) =
                    make_uint4(pack2(v[c][0], v[c][1]), pack2(v[c][2], v[c][3]), pack2(v[c][4], v[c][5]), pack2(v[c][6], v[c][7]));
    }
    float sv = 0.f;
#pragma unroll
    for (int i = 0; i < 5; i++) {
        float w[8];
        unpack8(w, uv[i]);
#pragma unroll
        for (int j = 0; j < 8; j++) sv += w[j] * w[j];
    }
    if (tid < 320) {
        float a[8] = {0.f, 0.f, 0.f, 0.f, 0.f, 0.f, 0.f, 0.f};
#pragma unroll
        for (int r = 0; r < 8; r++) {
            float w[8];
            unpack8(w, uo[r]);
#pragma unroll
            for (int j = 0; j < 8; j++) a[j] += w[j] * w[j];
        }
#pragma unroll
        for (int j = 0; j < 8; j++) col[tid / 80][tid % 80 * 8 + j] = a[j];
    }
    __syncthreads();
    float so = (col[0][tid] + col[1][tid]) + (col[2][tid] + col[3][tid]);
    if (tid < 128) so = fmaxf(so, (col[0][512 + tid] + col[1][512 + tid]) + (col[2][512 + tid] + col[3][512 + tid]));
#pragma unroll
    for (int o = 16; o; o >>= 1) { sv += __shfl_xor_sync(~0u, sv, o); so = fmaxf(so, __shfl_xor_sync(~0u, so, o)); }
    if (lane == 0) { red[warp] = sv; red[16 + warp] = so; }
    __syncthreads();
    if (tid == 0) {
        float a = 0.f, c = 0.f;
        for (int i = 0; i < 16; i++) { a += red[i]; c = fmaxf(c, red[16 + i]); }
        g_nrm[b] = a; g_nrm[128 + b] = c;
    }
    TLE(0);
}

DEV void filter_tile(const bf16* __restrict__ wr, const bf16* __restrict__ wi, int ka, int c) {
    const int kn = ka ? 2048 - ka : 32, kc = col_freq(c);
    const unsigned short* pr = (const unsigned short*)wr + kc;
    const unsigned short* pi = (const unsigned short*)wi + kc;
#pragma unroll 1
    for (int i = 0; i < 4; i += 2) {
        unsigned short a[32], b[32];
#pragma unroll
        for (int n = 0; n < 32; n++) {
            const int k = ((n & 1 ? kn : ka) + 64 * (4 * (2 * (i + (n >> 4)) + ((n >> 1) & 1)) + ((n >> 2) & 3))) & 2047;
            a[n] = __ldg(pr + k * NCOL); b[n] = __ldg(pi + k * NCOL);
        }
#pragma unroll
        for (int n = 0; n < 32; n += 4)
            *(uint4*)(g_wt + c * 8192 + (i + (n >> 4)) * 2048 + (ka * 4 + ((n >> 2) & 3)) * 16) =
                make_uint4(a[n] | ((uint32_t)b[n] << 16), a[n + 1] | ((uint32_t)b[n + 1] << 16), a[n + 2] | ((uint32_t)b[n + 2] << 16), a[n + 3] | ((uint32_t)b[n + 3] << 16));
    }
}

namespace wk {
constexpr int STAGE = 49152, NST = 4, OFF_OUT = 3 * STAGE, OFF_RED = 4 * STAGE, OFF_BAR = OFF_RED + 32768, SMEM = OFF_BAR + 128;
constexpr int NPB = 11;
__host__ __device__ constexpr int pb_start(int b) { return b ? 6 * b - 2 : 0; }
#define NOB 7
#define SPLIT_A 3
#define SPLIT_B 11
constexpr int N_P = NPB * H_, I_F = N_P, I_OB = I_F + 32, I_OT = I_OB + NOB * 5, I_SA = I_OT + (30 - 3 * NOB) * 10;
constexpr int I_SB = I_SA + 10 * SPLIT_A, N_ITEMS = I_SB + 10 * SPLIT_B;
DEV void ot_decode(int id, int& b, int& nt, int& k0, int& k1) {
    const int base = id < I_SA ? I_OT : id < I_SB ? I_SA : I_SB, j = (id - base) / 10;
    nt = (id - base) % 10;
    if (id < I_SA) { b = 3 * NOB + j; k0 = 0; k1 = 22; }
    else if (id < I_SB) { b = 30; k0 = 22 * j / SPLIT_A; k1 = 22 * (j + 1) / SPLIT_A; }
    else { b = 31; k0 = 22 * j / SPLIT_B; k1 = 22 * (j + 1) / SPLIT_B; }
}
enum { SY_TICKET = 0, SY_O = 32, SY_P = 128 };
}
struct Ring {
    int st; uint32_t ph;
    DEV uint32_t par() const { return (ph >> st) & 1; }
    DEV void next(int n) { ph ^= 1u << st; st = st + 1 >= n ? 0 : st + 1; }
};
struct Maps { CUtensorMap wq2, wv1, wo2, wo1, x6, x4, o6, o2; const bf16 *wr, *wi; };

template <int NSG> DEV void proj_tile(uint32_t sb, uint32_t bar, Ring& rg, int wg, int id) {
    using namespace wk;
    float acc[NSG * 16];
#pragma unroll
    for (int i = 0; i < NSG * 16; i++) acc[i] = 0.f;
    const int lane = threadIdx.x & 31, ww = (threadIdx.x >> 5) & 3;
    for (int kb = 0; kb < 10; kb++, rg.next(3)) {
        const int st = rg.st;
        if (kb) mbar_wait(bar + 8 * st, rg.par());
        const u64 da = mkdesc(sb + st * STAGE + wg * 8192, 0, 1024) | SW128, db = mkdesc(sb + st * STAGE + 24576, 0, 1024) | SW128;
        wg_fence();
#pragma unroll
        for (int ks = 0; ks < 4; ks++) {
            if (NSG == 4) wgmma_n128_ss<1, 0>(acc, da + ks * 128, db + ks * 2, 1);
            if (NSG == 6) wgmma_n192_ss<1, 0>(acc, da + ks * 128, db + ks * 2, 1);
        }
        wg_commit();
        wg_wait<0>();
        mbar_arrive_elect(bar + 8 * (NST + st));
    }
    const uint32_t out = sb + OFF_OUT + wg * 24576;
    bar_sync(5 + wg, 160);
    const uint32_t la = out + (wg < 2 ? (lane >> 4) * 1024 + ww * 256 + (lane & 15) * 16 : ww * 1024 + ((lane >> 3) & 1) * 512 + (lane >> 4) * 128 + (lane & 7) * 16);
#pragma unroll
    for (int j = 0; j < 2 * NSG; j++) {
        const float* c = acc + 8 * j;
        const uint32_t p0 = pack2(c[0], c[1]), p1 = pack2(c[2], c[3]), p2 = pack2(c[4], c[5]), p3 = pack2(c[6], c[7]);
        if (wg < 2) stsm4t(la + j * 2048, p0, p1, p2, p3);
        else stsm4(la + (j >> 1) * 4096 + (j & 1) * 256, p0, p1, p2, p3);
    }
    if ((threadIdx.x & 127) == 0) sts32(bar + 80 + 4 * wg, id);
    fence_async();
    bar_arrive(1 + wg, 160);
}

DEV uint32_t resid(uint32_t u, float a, float b) { return pack2(bf_lo(u) + bf_round(a), bf_hi(u) + bf_round(b)); }

template <bool SIDE>
DEV void worker(uint32_t sb, const Maps& maps, const bf16* __restrict__ x, bf16* __restrict__ x1, int layer, int fix, int nfix) {
    using namespace wk;
    const uint32_t bar = sb + OFF_BAR, slot = bar + 64;
    const int tid = threadIdx.x, lane = tid & 31, warp = __shfl_sync(~0u, tid >> 5, 0);
    uint32_t* sy = g_sync + layer * SYNC_LAYER;
    if (tid == 0) {
        for (int i = 0; i < NST; i++) { mbar_init(bar + 8 * i, 1); mbar_init(bar + 8 * (NST + i), 12); }
        asm volatile("fence.mbarrier_init.release.cluster;" ::: "memory");
    }
    __syncthreads();
    if (warp > 12) {
        const int wg = warp - 13;
        bar_arrive(5 + wg, 160);
        for (;;) {
            bar_sync(1 + wg, 160);
            const int id = (int)lds32(bar + 80 + 4 * wg);
            if (id < 0) break;
            const int s0 = pb_start(id >> 5), ns = pb_start((id >> 5) + 1) - s0;
            if (lane == 0) {
                for (int j = 0; j < ns; j++)
                    bulk_s2g(g_p + (size_t)(((s0 + j) * H_ + (id & 31)) * 3 + wg) * 4096, sb + OFF_OUT + wg * 24576 + j * 4096, 4096);
                bulk_commit();
                bulk_wait<0>();
                flag_add(sy + SY_P + id);
            }
            __syncwarp();
            bar_arrive(5 + wg, 160);
        }
    } else if (warp == 12) {
        if (lane == 0) {
            Ring rg = {0, 7u};
            auto acquire = [&]() { mbar_wait(bar + 8 * (NST + rg.st), rg.par()); return sb + rg.st * STAGE; };
            if (fix >= 0) {
                for (int kb = 0; kb < 3; kb++) {
                    tma3d(sb + kb * STAGE, &maps.wq2, 0, kb * 64, 2 * (fix & 31), bar + 8 * kb);
                    tma3d(sb + kb * STAGE + 16384, &maps.wv1, 0, kb * 64, 2 * (fix & 31), bar + 8 * kb);
                }
                asm volatile("prefetch.tensormap [%0];" ::"l"(&maps.x4) : "memory");
            } else {
                asm volatile("prefetch.tensormap [%0];" ::"l"(&maps.wo1) : "memory");
                asm volatile("prefetch.tensormap [%0];" ::"l"(&maps.o2) : "memory");
            }
            if (SIDE) flag_wait(g_started + layer, 1); else pdl_wait();
            for (;;) {
                int id = fix >= 0 ? fix : nfix + (int)atomicAdd(sy + SY_TICKET, 1u);
                if (layer && id >= I_F) id += I_OB - I_F;
                if (id >= N_ITEMS) id = -1;
                if (id >= 0) { TLI(id, 0, gtime()); TLI(id, 3, blockIdx.x + (SIDE ? 1000 : 0)); }
                uint32_t d = acquire();
                sts32(slot + 4 * rg.st, id);
                if (id < 0) { mbar_arrive(bar + 8 * rg.st); break; }
                if (id < N_P) {
                    const int b = id >> 5, h = id & 31;
                    for (int kb = 0; kb < 10; kb++, rg.next(3)) {
                        if (kb) d = acquire();
                        const uint32_t fb = bar + 8 * rg.st;
                        mbar_expect(fb, b ? 49152 : 40960);
                        tma3d(d + 24576, b ? &maps.x6 : &maps.x4, 0, 2 * kb, pb_start(b), fb);
                        if (fix < 0 || kb >= 3) {
                            tma3d(d, &maps.wq2, 0, kb * 64, 2 * h, fb);
                            tma3d(d + 16384, &maps.wv1, 0, kb * 64, 2 * h, fb);
                        }
                    }
                    fix = -1;
                } else if (id < I_OB) {
                    mbar_arrive(bar + 8 * rg.st);
                    mbar_wait(bar + 8 * (NST + rg.st), rg.par() ^ 1);
                    rg.next(NST);
                } else if (id < I_OT) {
                    const int b = (id - I_OB) / 5, nt = (id - I_OB) % 5;
                    for (int j = 0; j < 6; j++) flag_wait(sy + SY_O + 6 * b + j, 64);
                    for (int kb = 0; kb < 64; kb++, rg.next(NST)) {
                        if (kb) d = acquire();
                        const uint32_t fb = bar + 8 * rg.st;
                        mbar_expect(fb, 40960);
                        tma3d(d, &maps.o6, 0, 2 * kb, 6 * b, fb);
                        tma3d(d + 24576, &maps.wo2, 0, kb * 64, 2 * nt, fb);
                    }
                } else {
                    int b, nt, k0, k1;
                    ot_decode(id, b, nt, k0, k1);
                    for (int kb = k0; kb < k1; kb++, rg.next(NST)) {
                        if (kb > k0) d = acquire();
                        const uint32_t fb = bar + 8 * rg.st;
                        mbar_expect(fb, 49152);
                        tma3d(d + 24576, &maps.wo1, 0, 3 * kb * 64, nt, fb);
                        if (kb == k0) for (int j = 0; j < 2; j++) flag_wait(sy + SY_O + 2 * b + j, 64);
                        for (int u = 0; u < 3; u++) tma3d(d + u * 8192, &maps.o2, 0, 2 * (3 * kb + u), 2 * b, fb);
                    }
                }
            }
        }
    } else {
        const int wg = warp >> 2, g = lane >> 2, q = lane & 3;
        Ring rg = {0, 0u};
        bool stores_done = false;
        for (;;) {
            mbar_wait(bar + 8 * rg.st, rg.par());
            const int id = (int)lds32(slot + 4 * rg.st);
            if ((id < 0 || id >= N_P) && !stores_done) {
                bar_sync(5 + wg, 160);
                if ((tid & 127) == 0) sts32(bar + 80 + 4 * wg, ~0u);
                bar_arrive(1 + wg, 160);
                stores_done = true;
                bar_sync(4, 384);
                mbar_arrive_elect(bar + 8 * (NST + 3));
            }
            if (id < 0) break;
            if (tid == 0) TLI(id, 1, gtime());
            if (id < N_P) {
                const int b = id >> 5;
                if (b == 0) proj_tile<4>(sb, bar, rg, wg, id);
                else proj_tile<6>(sb, bar, rg, wg, id);
            } else if (id < I_OB) {
                if (tid < NCOL) filter_tile(maps.wr, maps.wi, id - I_F, tid);
                __syncwarp();
                mbar_arrive_elect(bar + 8 * (NST + rg.st));
                rg.next(NST);
            } else if (id < I_OT) {
                const int b = (id - I_OB) / 5, nt = (id - I_OB) % 5;
                const size_t o = (size_t)(192 * b + 16 * warp + g) * D_ + nt * 128 + 2 * q;
                float acc[64];
#pragma unroll
                for (int i = 0; i < 64; i++) acc[i] = 0.f;
                for (int kb = 0; kb < 64; kb++, rg.next(NST)) {
                    const int st = rg.st;
                    if (kb) mbar_wait(bar + 8 * st, rg.par());
                    const u64 da = mkdesc(sb + st * STAGE + wg * 8192, 128, 1024), db = mkdesc(sb + st * STAGE + 24576, 8192, 1024) | SW128;
                    wg_fence();
#pragma unroll
                    for (int ks = 0; ks < 4; ks++) wgmma_n128_ss<0, 1>(acc, da + ks * 16, db + ks * 128, 1);
                    wg_commit();
                    wg_wait<0>();
                    mbar_arrive_elect(bar + 8 * (NST + st));
                }
                uint32_t xr[32];
#pragma unroll
                for (int t = 0; t < 32; t++) xr[t] = ldg32(x + o + 8 * (t >> 1) + (t & 1) * 8 * D_);
#pragma unroll
                for (int t = 0; t < 32; t++) *(uint32_t*)(x1 + o + 8 * (t >> 1) + (t & 1) * 8 * D_) = resid(xr[t], acc[2 * t], acc[2 * t + 1]);
            } else {
                int b, nt, k0, k1;
                ot_decode(id, b, nt, k0, k1);
                const size_t o = (size_t)(64 * b + 16 * (warp & 3) + g) * D_ + nt * 64 + 2 * q;
                float acc[32];
                uint32_t xr[16];
#pragma unroll
                for (int t = 0; t < 16; t++) xr[t] = wg == 0 && id < I_SA ? ldg32(x + o + 8 * (t >> 1) + (t & 1) * 8 * D_) : 0;
#pragma unroll
                for (int i = 0; i < 32; i++) acc[i] = 0.f;
                for (int kb = k0; kb < k1; kb++, rg.next(NST)) {
                    const int st = rg.st;
                    if (kb > k0) mbar_wait(bar + 8 * st, rg.par());
                    const u64 da = mkdesc(sb + st * STAGE + wg * 8192, 128, 1024), db = mkdesc(sb + st * STAGE + 24576 + wg * 8192, 0, 1024) | SW128;
                    wg_fence();
#pragma unroll
                    for (int ks = 0; ks < 4; ks++) wgmma_n64_ss<0, 1>(acc, da + ks * 16, db + ks * 128, 1);
                    wg_commit();
                    wg_wait<0>();
                    mbar_arrive_elect(bar + 8 * (NST + st));
                }
                const uint32_t ra = sb + OFF_RED + (tid & 127) * 16;
                if (wg) {
#pragma unroll
                    for (int t = 0; t < 8; t++)
                        sts128(ra + (wg - 1) * 16384 + t * 2048, __float_as_uint(acc[4 * t]), __float_as_uint(acc[4 * t + 1]), __float_as_uint(acc[4 * t + 2]), __float_as_uint(acc[4 * t + 3]));
                }
                bar_sync(4, 384);
                if (wg == 0) {
#pragma unroll
                    for (int t = 0; t < 8; t++) {
                        float u[4], v[4];
                        lds128f(u, ra + t * 2048); lds128f(v, ra + 16384 + t * 2048);
#pragma unroll
                        for (int i = 0; i < 4; i++) acc[4 * t + i] += u[i] + v[i];
                    }
                }
                bar_sync(4, 384);
                if (wg == 0) {
                    if (id < I_SA) {
#pragma unroll
                        for (int t = 0; t < 16; t++) *(uint32_t*)(x1 + o + 8 * (t >> 1) + (t & 1) * 8 * D_) = resid(xr[t], acc[2 * t], acc[2 * t + 1]);
                    } else {
                        float* y = g_yt + (layer * YT_ROWS - (S_ - YT_ROWS)) * D_ + o;
#pragma unroll
                        for (int t = 0; t < 16; t++)
                            asm volatile("red.relaxed.gpu.global.add.v2.f32 [%0],{%1,%2};" ::"l"(y + 8 * (t >> 1) + (t & 1) * 8 * D_), "f"(acc[2 * t]), "f"(acc[2 * t + 1]) : "memory");
                    }
                }
            }
            if (tid == 0) TLI(id, 2, gtime());
        }
    }
}

__global__ void __launch_bounds__(512, 1) side_kernel(const __grid_constant__ Maps maps, const bf16* __restrict__ x, bf16* __restrict__ x1, int layer, int nfix) {
    extern __shared__ __align__(1024) unsigned char smem[];
    pdl_launch();
    TLS(3 + 5 * layer);
    worker<true>(s2u(smem), maps, x, x1, layer, -1, nfix);
    __syncwarp();
    pdl_wait();
    TLE(3 + 5 * layer);
}

constexpr float C5A = 0.30901699437494742f, C5B = -0.80901699437494742f, S5A = 0.95105651629515357f, S5B = 0.58778525229247313f;
template <int SGN> DEV void dft5(const float (&tr)[5], const float (&ti)[5], float (&zr)[5], float (&zi)[5]) {
    const float ar = tr[1] + tr[4], ai = ti[1] + ti[4], br = tr[2] + tr[3], bi = ti[2] + ti[3];
    const float cr = tr[1] - tr[4], ci = ti[1] - ti[4], dr = tr[2] - tr[3], di = ti[2] - ti[3];
    zr[0] = tr[0] + ar + br; zi[0] = ti[0] + ai + bi;
    const float m1r = tr[0] + C5A * ar + C5B * br, m1i = ti[0] + C5A * ai + C5B * bi;
    const float m2r = tr[0] + C5B * ar + C5A * br, m2i = ti[0] + C5B * ai + C5A * bi;
    const float n1r = SGN * (S5A * cr + S5B * dr), n1i = SGN * (S5A * ci + S5B * di);
    const float n2r = SGN * (S5B * cr - S5A * dr), n2i = SGN * (S5B * ci - S5A * di);
    zr[1] = m1r + n1i; zi[1] = m1i - n1r; zr[4] = m1r - n1i; zi[4] = m1i + n1r;
    zr[2] = m2r + n2i; zi[2] = m2i - n2r; zr[3] = m2r - n2i; zi[3] = m2i + n2r;
}
DEV void ln40(float (&v)[40]) {
    float s = 0.f;
#pragma unroll
    for (int i = 0; i < 40; i++) s += v[i];
#pragma unroll
    for (int o = 8; o; o >>= 1) s += __shfl_xor_sync(~0u, s, o);
    const float mean = s * (1.f / D_);
    float q = 0.f;
#pragma unroll
    for (int i = 0; i < 40; i++) { const float d = v[i] - mean; q += d * d; }
#pragma unroll
    for (int o = 8; o; o >>= 1) q += __shfl_xor_sync(~0u, q, o);
    const float mb = bf_round(mean);
    const float inv = 1.f / bf_round(sqrtf(bf_round(bf_round(q * (1.f / D_)) + 1e-5f)));
#pragma unroll
    for (int i = 0; i < 40; i++) v[i] = bf_round(v[i] - mb) * inv;
}
__global__ void __launch_bounds__(256) rowfft_kernel(const bf16* __restrict__ x0, bf16* __restrict__ x, const bf16* __restrict__ Wq,
                                                     const bf16* __restrict__ Wk, const bf16* __restrict__ Wv, int layer) {
    extern __shared__ __align__(1024) unsigned char smem[];
    const uint32_t sb = s2u(smem), sx = sb + 23552, sy = sx + 20480, bar = sy + 40960;
    const int tid = threadIdx.x, lane = tid & 31, q = lane & 3, blk = blockIdx.x, k2 = tid >> 2;
    if (tid == 0) TLI(800 + blk, 0, gtime());
    float twr[5], twi[5];
#pragma unroll
    for (int r = 1; r < 5; r++) { sincospif((float)(r * k2) * (-1.f / 320), &twi[r], &twr[r]); }
    uint32_t f[8][4];
#pragma unroll
    for (int ks = 0; ks < 8; ks++) { const uint4 u = g_f128[ks * 256 + tid]; f[ks][0] = u.x; f[ks][1] = u.y; f[ks][2] = u.z; f[ks][3] = u.w; }
    const bool split = blk * 16 >= S_ - YT_ROWS;
    if (tid == 0) {
        mbar_init(bar, 1);
        asm volatile("fence.mbarrier_init.release.cluster;" ::: "memory");
        mbar_expect(bar, split ? 61440 : 20480);
        if (split) bulk_g2s(sx, x0 + (size_t)blk * 16 * D_, 20480, bar);
    }
    __syncthreads();
    pdl_wait();
    pdl_launch();
    TLS(4 + 5 * layer);
    if (tid == 0) TLI(800 + blk, 1, gtime());
    if (tid == 0 && blk == 0) g_started[layer] = 0;
    if (tid == 0) {
        if (split) bulk_g2s(sy, g_yt + (layer * YT_ROWS + blk * 16 - (S_ - YT_ROWS)) * D_, 40960, bar);
        else bulk_g2s(sx, x + (size_t)blk * 16 * D_, 20480, bar);
    }
    mbar_wait(bar, 0);
    {
        const int rho = tid >> 4, j = tid & 15;
        float v[40];
#pragma unroll
        for (int i = 0; i < 5; i++) {
            uint32_t u[4];
            lds128(u, sx + tid * 80 + i * 16);
            if (split) {
                float p[8];
                lds128f(p, sy + tid * 160 + i * 32); lds128f(p + 4, sy + tid * 160 + i * 32 + 16);
#pragma unroll
                for (int k = 0; k < 4; k++) u[k] = resid(u[k], p[2 * k], p[2 * k + 1]);
                sts128(sx + tid * 80 + i * 16, u[0], u[1], u[2], u[3]);
            }
            unpack8(v + 8 * i, make_uint4(u[0], u[1], u[2], u[3]));
        }
        if (layer == 0 && tid < 12) prefetch_bulk((const char*)(tid < 4 ? Wk : tid < 8 ? Wq : Wv) + (blk * 4 + (tid & 3)) * 10240, 10240);
        ln40(v);
        const uint32_t a = sb + ((rho >> 1) & 1) * 2304 + j * 144 + (2 * (rho >> 2) + (rho & 1)) * 16;
#pragma unroll
        for (int r = 0; r < 5; r++)
            sts128(a + r * 4608, pack2(v[r], v[5 + r]), pack2(v[10 + r], v[15 + r]), pack2(v[20 + r], v[25 + r]), pack2(v[30 + r], v[35 + r]));
    }
    fence_async();
    __syncthreads();
    if (tid == 0) TLI(800 + blk, 2, gtime());
    if (tid == 0 && split) { bulk_s2g(x + (size_t)blk * 16 * D_, sx, 20480); bulk_commit(); }
    float acc[40];
    const u64 db = mkdesc(sb, 144, 2304);
    wg_fence();
    wgmma_n80_rs<0, 0>(acc, f[0], db);
#pragma unroll
    for (int ks = 1; ks < 8; ks++) wgmma_n80_rs<1, 0>(acc, f[ks], db + ks * 18);
    wg_commit();
    wg_wait<0>();
    unsigned char* zp = g_z + (blk >> 1) * 128 + ((((blk & 1) * 4 + q) ^ ((blk >> 1) & 7)) << 4);
    uint32_t o[5][4];
#pragma unroll
    for (int u = 0; u < 4; u++) {
        float tr[5], ti[5], zr[5], zi[5];
#pragma unroll
        for (int r = 0; r < 5; r++) {
            const float yr = acc[8 * r + 4 * (u >> 1) + (u & 1)], yi = k2 ? acc[8 * r + 4 * (u >> 1) + 2 + (u & 1)] : 0.f;
            tr[r] = r ? yr * twr[r] - yi * twi[r] : yr;
            ti[r] = r ? yr * twi[r] + yi * twr[r] : yi;
        }
        dft5<1>(tr, ti, zr, zi);
#pragma unroll
        for (int j = 0; j < 5; j++) o[j][u] = pack2(zr[j], j < 3 ? zi[j] : -zi[j]);
    }
#pragma unroll
    for (int j = 0; j < 5; j++)
        if (j < 3 || k2) *(uint4*)(zp + (64 * j + k2) * 8192) = make_uint4(o[j][0], o[j][1], o[j][2], o[j][3]);
    if (k2 == 0) {
#pragma unroll
        for (int u = 0; u < 4; u++) {
            float tr[5], ti[5], zr[5], zi[5];
            const float cr[5] = {1.f, -C5B, C5A, -C5A, C5B}, ci[5] = {0.f, -S5B, -S5A, -S5A, -S5B};
#pragma unroll
            for (int r = 0; r < 5; r++) { const float y = acc[8 * r + 4 * (u >> 1) + 2 + (u & 1)]; tr[r] = y * cr[r]; ti[r] = y * ci[r]; }
            dft5<1>(tr, ti, zr, zi);
            o[0][u] = pack2(zr[0], zi[0]); o[1][u] = pack2(zr[1], zi[1]); o[2][u] = pack2(zr[2], 0.f);
        }
        *(uint4*)(zp + 256 * 8192) = make_uint4(o[0][0], o[0][1], o[0][2], o[0][3]);
        *(uint4*)(zp + 192 * 8192) = make_uint4(o[1][0], o[1][1], o[1][2], o[1][3]);
        *(uint4*)(zp + 320 * 8192) = make_uint4(o[2][0], o[2][1], o[2][2], o[2][3]);
    }
    if (tid == 0) bulk_wait<0>();
    TLE(4 + 5 * layer);
    if (tid == 0) TLI(800 + blk, 3, gtime());
}

constexpr int CF_SMEM = 16384 + 3 * 16384 + 64;
__global__ void __launch_bounds__(384) colfft_kernel(int layer) {
    extern __shared__ __align__(1024) unsigned char smem[];
    const uint32_t sb = s2u(smem), bar = sb + 65536;
    const int tid = threadIdx.x, lane = tid & 31, q = lane & 3, wg = __shfl_sync(~0u, tid >> 7, 0), t = tid & 127, ka = t >> 2;
    const int col = blockIdx.x * 3 + wg;
    const uint32_t d0 = sb + 16384 + wg * 16384, d1 = d0 + 8192;
    if (tid == 0) {
        for (int i = 0; i < 4; i++) mbar_init(bar + 8 * i, 1);
        asm volatile("fence.mbarrier_init.release.cluster;" ::: "memory");
    }
    float twr[8], twi[8];
#pragma unroll
    for (int i = 0; i < 8; i++) sincospif((float)((4 * i + q) * (ka ? ka : -32)) * (1.f / 1024), &twi[i], &twr[i]);
    __syncthreads();
    if (tid == 0) { mbar_expect(bar + 24, 16384); bulk_g2s(sb, g_g32, 16384, bar + 24); }
    uint32_t f[4][4], w[16];
#pragma unroll
    for (int ks = 0; ks < 4; ks++) { const uint4 u = g_f64[ks * 128 + t]; f[ks][0] = u.x; f[ks][1] = u.y; f[ks][2] = u.z; f[ks][3] = u.w; }
#pragma unroll
    for (int i = 0; i < 4; i++) { const uint4 u = *(const uint4*)(g_wt + col * 8192 + i * 2048 + t * 16); w[4 * i] = u.x; w[4 * i + 1] = u.y; w[4 * i + 2] = u.z; w[4 * i + 3] = u.w; }
    pdl_wait();
    pdl_launch();
    TLS(5 + 5 * layer);
    if (t == 0) {
        mbar_expect(bar + 8 * wg, 8192);
        bulk_g2s(d0, g_z + col * 8192, 8192, bar + 8 * wg);
    }
    float acc[32];
    uint32_t a[4][4];
    mbar_wait(bar + 8 * wg, 0);
    {
        const u64 db = mkdesc(d0, 0, 1024) | SW128;
        wg_fence();
        wgmma_n64_rs<0, 1>(acc, f[0], db);
#pragma unroll
        for (int ks = 1; ks < 4; ks++) wgmma_n64_rs<1, 1>(acc, f[ks], db + ks * 128);
        wg_commit();
        wg_wait<0>();
    }
#pragma unroll
    for (int ks = 0; ks < 4; ks++) { const uint4 u = g_f64[512 + ks * 128 + t]; f[ks][0] = u.x; f[ks][1] = u.y; f[ks][2] = u.z; f[ks][3] = u.w; }
#pragma unroll
    for (int i = 0; i < 8; i++) {
        const float c0 = acc[4 * i], c1 = acc[4 * i + 1], c2 = acc[4 * i + 2], c3 = acc[4 * i + 3];
        const float pr = c0 + c3, pi = c1 - c2, nr = ka ? c0 - c3 : c2, ni = ka ? c1 + c2 : c3;
        a[i >> 1][2 * (i & 1)] = ka ? pack2(pr * twr[i] + pi * twi[i], pi * twr[i] - pr * twi[i]) : pack2(c0, c1);
        a[i >> 1][2 * (i & 1) + 1] = pack2(nr * twr[i] - ni * twi[i], ni * twr[i] + nr * twi[i]);
    }
    mbar_wait(bar + 24, 0);
    {
        const u64 db = mkdesc(sb, 128, 1024);
        wg_fence();
        wgmma_n64_rs<0, 0>(acc, a[0], db);
#pragma unroll
        for (int ks = 1; ks < 4; ks++) wgmma_n64_rs<1, 0>(acc, a[ks], db + ks * 16);
        wg_commit();
        wg_wait<0>();
    }
    constexpr float NORM = 1.f / (2048.f * 640.f);
#pragma unroll
    for (int i = 0; i < 16; i++) {
        const float zr = acc[2 * i] * NORM, zi = acc[2 * i + 1] * NORM, wr = bf_lo(w[i]), wi = bf_hi(w[i]);
        a[i >> 2][i & 3] = pack2(zr * wr - zi * wi, zr * wi + zi * wr);
    }
    {
        const u64 db = mkdesc(sb + 8192, 128, 1024);
        wg_fence();
        wgmma_n64_rs<0, 0>(acc, a[0], db);
#pragma unroll
        for (int ks = 1; ks < 4; ks++) wgmma_n64_rs<1, 0>(acc, a[ks], db + ks * 16);
        wg_commit();
        wg_wait<0>();
    }
    const uint32_t row = (t >> 5) * 2048 + (lane & 15) * 128;
#pragma unroll
    for (int i = 0; i < 8; i++) {
        const float c0 = acc[4 * i], c1 = acc[4 * i + 1], c2 = acc[4 * i + 2], c3 = acc[4 * i + 3];
        const float pr = c0 * twr[i] - c1 * twi[i], pi = c1 * twr[i] + c0 * twi[i];
        const float nr = c2 * twr[i] + c3 * twi[i], ni = c3 * twr[i] - c2 * twi[i];
        a[i >> 1][2 * (i & 1)] = ka ? pack2(pr + nr, pi + ni) : pack2(c0, c1);
        a[i >> 1][2 * (i & 1) + 1] = ka ? pack2(ni - pi, pr - nr) : pack2(nr, ni);
    }
#pragma unroll
    for (int i = 0; i < 4; i++) stsm4(d1 + row + (((2 * i + (lane >> 4)) ^ (lane & 7)) << 4), a[i][0], a[i][1], a[i][2], a[i][3]);
    fence_async();
    bar_sync(1 + wg, 128);
    {
        const u64 db = mkdesc(d1, 0, 1024) | SW128;
        wg_fence();
        wgmma_n64_rs<0, 1>(acc, f[0], db);
#pragma unroll
        for (int ks = 1; ks < 4; ks++) wgmma_n64_rs<1, 1>(acc, f[ks], db + ks * 128);
        wg_commit();
        wg_wait<0>();
    }
#pragma unroll
    for (int i = 0; i < 4; i++)
        stsm4(d0 + row + (((2 * i + (lane >> 4)) ^ (lane & 7)) << 4), pack2(acc[8 * i], acc[8 * i + 1]), pack2(acc[8 * i + 2], acc[8 * i + 3]),
              pack2(acc[8 * i + 4], acc[8 * i + 5]), pack2(acc[8 * i + 6], acc[8 * i + 7]));
    fence_async();
    bar_sync(1 + wg, 128);
    if (t == 0) {
        bulk_s2g(g_z + col * 8192, d0, 8192);
        asm volatile("cp.async.bulk.commit_group;" ::: "memory");
        asm volatile("cp.async.bulk.wait_group 0;" ::: "memory");
    }
    TLE(5 + 5 * layer);
}

__global__ void __launch_bounds__(256) rowifft_kernel(const bf16* __restrict__ x, bf16* __restrict__ out, int last) {
    extern __shared__ __align__(1024) unsigned char smem[];
    const uint32_t sb = s2u(smem), sx = sb + 20480, sy = sx + 20480, bar = sy + 16 * 1296;
    const int tid = threadIdx.x, lane = tid & 31, q = lane & 3, blk = blockIdx.x, k2 = tid >> 2, warp = tid >> 5;
    float twr[5], twi[5];
#pragma unroll
    for (int r = 1; r < 5; r++) { sincospif((float)(r * k2) * (1.f / 320), &twi[r], &twr[r]); twr[r] *= 2.f; twi[r] *= 2.f; }
    uint32_t f[8][4];
#pragma unroll
    for (int ks = 0; ks < 8; ks++) { const uint4 u = g_f128[2048 + ks * 256 + tid]; f[ks][0] = u.x; f[ks][1] = u.y; f[ks][2] = u.z; f[ks][3] = u.w; }
    if (tid == 0) {
        mbar_init(bar, 1);
        asm volatile("fence.mbarrier_init.release.cluster;" ::: "memory");
        mbar_expect(bar, 20480);
        bulk_g2s(sx, x + (size_t)blk * 16 * D_, 20480, bar);
    }
    pdl_wait();
    pdl_launch();
    TLS(6 + 5 * last);
    const unsigned char* zp = g_z + (blk >> 1) * 128 + ((((blk & 1) * 4 + q) ^ ((blk >> 1) & 7)) << 4);
    uint4 z[6];
#pragma unroll
    for (int j = 0; j < 5; j++) z[j] = *(const uint4*)(zp + (64 * j + k2) * 8192);
    z[5] = k2 ? make_uint4(0, 0, 0, 0) : *(const uint4*)(zp + 320 * 8192);
    float acc[40];
#pragma unroll
    for (int u = 0; u < 4; u++) {
        float yr[6], yi[6], tr[5], ti[5], zr[5], zi[5];
#pragma unroll
        for (int j = 0; j < 6; j++) { const uint32_t v = u == 0 ? z[j].x : u == 1 ? z[j].y : u == 2 ? z[j].z : z[j].w; yr[j] = bf_lo(v); yi[j] = bf_hi(v); }
#pragma unroll
        for (int j = 0; j < 5; j++) { tr[j] = yr[j]; ti[j] = j < 3 ? yi[j] : -yi[j]; }
        dft5<-1>(tr, ti, zr, zi);
        const float c1[5] = {1.f, C5A, C5B, C5B, C5A}, s1[5] = {0.f, S5A, S5B, -S5B, -S5A};
        const float c2[5] = {1.f, C5B, C5A, C5A, C5B}, s2[5] = {0.f, S5B, -S5A, S5A, -S5B};
        const float c3[5] = {1.f, -C5B, C5A, -C5A, C5B}, s3[5] = {0.f, S5B, S5A, S5A, S5B};
        const float c4[5] = {1.f, -C5A, C5B, -C5B, C5A}, s4[5] = {0.f, S5A, -S5B, -S5B, S5A};
#pragma unroll
        for (int r = 0; r < 5; r++) {
            float er = r ? zr[r] * twr[r] - zi[r] * twi[r] : 2.f * zr[0], ei = r ? zr[r] * twi[r] + zi[r] * twr[r] : 2.f * zi[0];
            if (k2 == 0) {
                er = yr[0] + 2.f * (yr[1] * c1[r] - yi[1] * s1[r] + yr[2] * c2[r] - yi[2] * s2[r]);
                ei = (r & 1 ? -yr[5] : yr[5]) + 2.f * (yr[4] * c3[r] - yi[4] * s3[r] + yr[3] * c4[r] - yi[3] * s4[r]);
            }
            acc[8 * r + 4 * (u >> 1) + (u & 1)] = er;
            acc[8 * r + 4 * (u >> 1) + 2 + (u & 1)] = ei;
        }
    }
#pragma unroll
    for (int r = 0; r < 5; r++)
        stsm4(sb + (2 * warp + ((lane >> 3) & 1)) * 1280 + (2 * r + (lane >> 4)) * 128 + (lane & 7) * 16, pack2(acc[8 * r], acc[8 * r + 1]),
              pack2(acc[8 * r + 2], acc[8 * r + 3]), pack2(acc[8 * r + 4], acc[8 * r + 5]), pack2(acc[8 * r + 6], acc[8 * r + 7]));
    fence_async();
    __syncthreads();
    const u64 db = mkdesc(sb, 1280, 128);
    wg_fence();
    wgmma_n80_rs<0, 1>(acc, f[0], db);
#pragma unroll
    for (int ks = 1; ks < 8; ks++) wgmma_n80_rs<1, 1>(acc, f[ks], db + ks * 160);
    wg_commit();
    wg_wait<0>();
#pragma unroll
    for (int u = 0; u < 4; u++) {
        float e[10];
#pragma unroll
        for (int r = 0; r < 5; r++) { e[r] = acc[8 * r + 4 * (u >> 1) + (u & 1)]; e[5 + r] = acc[8 * r + 4 * (u >> 1) + 2 + (u & 1)]; }
#pragma unroll
        for (int i = 0; i < 5; i++) sts32(sy + (4 * q + u) * 1296 + k2 * 20 + i * 4, pack2(e[2 * i], e[2 * i + 1]));
    }
    __syncthreads();
    const int rho = tid >> 4, j = tid & 15;
    float v[40];
    mbar_wait(bar, 0);
#pragma unroll
    for (int i = 0; i < 5; i++) {
        uint32_t y[4], u[4];
        lds128(y, sy + rho * 1296 + j * 80 + i * 16);
        lds128(u, sx + tid * 80 + i * 16);
#pragma unroll
        for (int k = 0; k < 4; k++) u[k] = pack2(bf_lo(u[k]) + bf_lo(y[k]), bf_hi(u[k]) + bf_hi(y[k]));
        sts128(sx + tid * 80 + i * 16, u[0], u[1], u[2], u[3]);
        unpack8(v + 8 * i, make_uint4(u[0], u[1], u[2], u[3]));
    }
    if (!last) {
        ln40(v);
#pragma unroll
        for (int i = 0; i < 5; i++) {
            const int c = j * 5 + i;
            sts128(sb + (c >> 3) * 2048 + rho * 128 + (((c ^ rho) & 7) << 4), pack2(v[8 * i], v[8 * i + 1]), pack2(v[8 * i + 2], v[8 * i + 3]),
                   pack2(v[8 * i + 4], v[8 * i + 5]), pack2(v[8 * i + 6], v[8 * i + 7]));
        }
    }
    fence_async();
    __syncthreads();
    if (lane == 0) {
        if (warp == 7) bulk_s2g(out + (size_t)blk * 16 * D_, sx, 20480);
        else if (!last && warp < 5) {
            unsigned char* p = g_xn + (blk >> 1) * 40960 + warp * 8192 + (blk & 1) * 2048;
            bulk_s2g(p, sb + warp * 4096, 2048);
            bulk_s2g(p + 4096, sb + warp * 4096 + 2048, 2048);
        }
        bulk_commit();
        bulk_wait<0>();
    }
    TLE(6 + 5 * last);
}

namespace rec {
#define NS 3
constexpr int OFF_X = 0;
constexpr int OFF_WO = 81920;
constexpr int OFF_WS = OFF_WO + 65536;
constexpr int OFF_XCH = OFF_WS + NS * 4096;
constexpr int OFF_MEMB = OFF_XCH + 12288;
constexpr int OFF_VX = OFF_MEMB + 10240;
constexpr int OFF_VM = OFF_VX + 16384;
constexpr int OFF_Q = OFF_VM + 4096;
constexpr int OFF_K = OFF_Q + 10240;
constexpr int OFF_OST = OFF_WO + 49152;
constexpr int OFF_PX = OFF_OST + 8192;
constexpr int OFF_PT = OFF_PX + 2560;
constexpr int OFF_PS = OFF_K + 10240;
constexpr int OFF_OB = OFF_PS + 1280;
constexpr int OFF_MX = OFF_OB + 2048;
constexpr int OFF_BAR = OFF_MX + 64;
constexpr int OFF_PROF = OFF_BAR + 256;
constexpr int SMEM = OFF_PROF + 4096 > wk::SMEM ? OFF_PROF + 4096 : wk::SMEM;
enum { B_XT = 0, B_VM = 2, B_VX = 4, B_XD = 6, B_X1 = 8, B_GO = 10, B_PXF = 12, B_PXE = 13, B_FIN = 14, B_ST = 15, B_MEM = 16   };
enum { NB_W2 = 0, NB_XCH = 1, NB_QK = 2, NB_WIN = 3, NB_ATT = 4, NB_X = 5, NB_PRO = 6, NB_W1 = 7, NB_PAIR = 8  , NB_KF = 12, NB_LD = 13, NB_KX = 15 };
#define STAG 3
#define NOX 0
#define NW1 4
#define NW1B 0
template <int N> struct IC { static constexpr int value = N; };
template <int N, int I = 0, class F> DEV void static_for(F&& f) { if constexpr (I < N) { f(IC<I>{}); static_for<N, I + 1>(f); } }
constexpr float SM_SCALE = 0.08838834764831845f * 1.4426950408889634f;
}

__global__ void __launch_bounds__(512, 1) rec_kernel(const __grid_constant__ Maps maps, const bf16* __restrict__ x, bf16* __restrict__ x1, const bf16* __restrict__ mem0, const bf16* __restrict__ Wq, const bf16* __restrict__ Wk,
                                                     const bf16* __restrict__ Wv, const bf16* __restrict__ Wo, int layer, int delay, int delay2) {
    using namespace rec;
    extern __shared__ __align__(1024) unsigned char smem[];
    const uint32_t sb = s2u(smem);
    pdl_launch();
    if (blockIdx.x >= 3 * H_) {
        worker<false>(sb, maps, x, x1, layer, blockIdx.x - 3 * H_, gridDim.x - 3 * H_);
        return;
    }
    const int tid = threadIdx.x, lane = tid & 31, warp = __shfl_sync(~0u, tid >> 5, 0);
    const int g = lane >> 2, q = lane & 3;
    const int h = blockIdx.x / 3;
    const uint32_t bar = sb + OFF_BAR;
    STAMP(2 * layer);
    TLS(2 + 5 * layer);
    if (tid == 0) TLI(690 + blockIdx.x, 0, gtime());
    if (tid == 0) {
        for (int i = 0; i < 2; i++) {
            mbar_init(bar + 8 * (B_XT + i), 1); mbar_init(bar + 8 * (B_VX + i), 1);
            mbar_init(bar + 8 * (B_XD + i), 8); mbar_init(bar + 8 * (B_X1 + i), 1); mbar_init(bar + 8 * (B_VM + i), 1);
        }
        mbar_init(bar + 8 * B_PXF, 1); mbar_init(bar + 8 * B_PXE, 2); mbar_init(bar + 8 * B_ST, 2); mbar_init(bar + 8 * B_GO, 1);
        for (int i = 0; i < 5; i++) mbar_init(bar + 8 * (B_MEM + i), 4);
        mbar_init(bar + 8 * B_FIN, 48);
        asm volatile("fence.mbarrier_init.release.cluster;" ::: "memory");
    }
    asm volatile("barrier.cluster.arrive.aligned; barrier.cluster.wait.aligned;" ::: "memory");
    const bool never = delay < 0;

    if (warp < 8) {
        asm volatile("setmaxnreg.inc.sync.aligned.u32 184;");
        const uint32_t rank = cta_rank();
        const int wg = warp >> 2;
        uint32_t fa[20 - NS][4], fb[20][4];
        const uint32_t l16 = opaque(sb + lane * 16);
        uint32_t dst = opaque(rank < 2 ? sb + OFF_Q + wg * 10240 + (warp & 3) * 256 + (lane & 15) * 16 + (lane >> 4) * 1024
                                       : sb + OFF_VM + warp * 256 + lane * 4);
        int dstep = rank < 2 ? 5120 : 2048;
        uint32_t& sfd = dst;
        const uint32_t ws = OFF_WS + warp * 512, xo = OFF_XCH + warp * 512, xi = OFF_XCH + (warp ^ 4) * 512, mb = OFF_MEMB + wg * 512;
        {
            const int t = tid & 127;
            const bf16* src = (rank == 2 ? Wv + wg * 64 : (wg ? Wk : Wq) + rank * 64) + h * E_ + (size_t)(t >> 3) * 4096 + (t & 7) * 8;
            constexpr int SA = OFF_X + 40960, SB = OFF_VX;
            const uint32_t sdst = sb + (wg ? SB : SA) + (t >> 3) * 128 + (((t & 7) ^ ((t >> 3) & 7)) << 4);
            const uint32_t ra = sb + wg * 4096 + ((lane >> 4) * 8 + (lane & 7)) * 128 + (((2 * (warp & 3) + ((lane >> 3) & 1)) ^ (lane & 7)) << 4);
            auto issue = [&](int rd) {
#pragma unroll 1
                for (int i = 0; i < 8; i++, src += 16 * 4096) cp16(sdst + (rd & 1) * 16384 + i * 2048, src);
                cp_commit();
            };
            issue(0); issue(1);
#pragma unroll
            for (int rd = 0; rd < 5; rd++) {
                if (rd < 4) cp_wait<1>(); else cp_wait<0>();
                bar_sync(NB_XCH, 256);
#pragma unroll
                for (int i = 0; i < 4; i++) {
                    const int n = rd * 4 + i, o = (rd & 1) * 16384 + (i >> 1) * 8192 + (i & 1) * 2048;
                    if (n < NS) {
                        uint32_t f[4];
                        ldsm4t(f, ra + SA + o);
                        sts128(l16 + ws + n * 4096, f[0], f[1], f[2], f[3]);
                    } else ldsm4t(fa[n - NS], ra + SA + o);
                    ldsm4t(fb[n], ra + SB + o);
                }
                if (rd < 3) { bar_sync(NB_XCH, 256); issue(rd + 2); }
            }
            fence_async();
            bar_sync(NB_PRO, 288);
        }
        uint32_t xlo = (uint32_t)mkdesc(sb + OFF_X + wg * 64, 0, 0);
        const uint32_t xtog = xlo ^ (uint32_t)mkdesc(sb + OFF_X + 40960 + wg * 64, 0, 0);
        uint32_t p8 = 0;
        bar_sync(NB_LD, 288);
        for (int s = -1;; s++) {
            uint32_t t[NS ? NS : 1][4];
            {
                float acc[16];
                auto xproj = [&](auto I0, auto I1) {
                    const u64 desc = (u64)xlo | (64ull << 32) | SW128;
                    wg_fence();
#pragma unroll
                    for (int i = I0.value; i < I1.value; i++) {
                        const u64 db = desc + (i >> 1) * 256 + (i & 1) * 2;
                        if (i == 0) wgmma_n32_rs<0>(acc, fb[i], db);
                        else if (!NOX) wgmma_n32_rs<1>(acc, fb[i], db);
                    }
                    wg_commit();
                    wg_wait<0>();
                };
                if (s >= 0 && rank < 2) { fence_async(); bar_arrive(NB_W1, 512); bar_sync(NB_X, 384); }
                bar_sync_if<NB_W1, 480>(s >= 0 && rank == 2);
                if (s == NSEG - 1) break;
                xproj(IC<0>{}, IC<NW1>{});
                if (warp == 4 && s >= 0) PROFT(15);
                bar_sync_if<NB_W2, 384>(s >= 0 && rank < 2);
                if (NW1B > 0) xproj(IC<NW1>{}, IC<NW1 + NW1B>{});
                bar_sync_if<NB_WIN, 384>(s >= 0 && rank == 2);
                xproj(IC<NW1 + NW1B>{}, IC<20>{});
                if (warp == 4 && s >= 0) PROFT(12);
                sts128f_if(l16 + xo, acc + 8, !wg); sts128f_if(l16 + xo + 4096, acc + 12, !wg);
                sts128f_if(l16 + xo, acc, wg); sts128f_if(l16 + xo + 4096, acc + 4, wg);
                bar_sync(NB_PAIR + (warp & 3), 64);
                float u[8];
#pragma unroll
                for (int i = 0; i < 8; i++) acc[i] = wg ? acc[8 + i] : acc[i];
                lds128f(u, l16 + xi); lds128f(u + 4, l16 + xi + 4096);
#pragma unroll
                for (int i = 0; i < NS; i++) lds128(t[i], l16 + ws + i * 4096);
#pragma unroll
                for (int i = 0; i < 8; i++) u[i] += acc[i];
                if (rank < 2) {
                    stsm4t(dst + (wg ? 3072 : 11264), pack2(u[0], u[1]), pack2(u[2], u[3]), pack2(u[4], u[5]), pack2(u[6], u[7]));
                } else {
                    stsm4(l16 + (l16 & 256) + OFF_VX + 4096 + (warp & 3) * 1024 + wg * 256 + p8 * 1024,
                          pack2(u[0], u[1]), pack2(u[4], u[5]), pack2(u[2], u[3]), pack2(u[6], u[7]));
                    bar_arrive(NB_KF, 288);
                }
                bar_arrive(NB_KX, 384);
                xlo ^= xtog;
                if (warp == 4 && s >= 0) PROFT(3);
            }
            float da[4] = {0.f, 0.f, 0.f, 0.f}, db[4] = {0.f, 0.f, 0.f, 0.f}, ea[4] = {0.f, 0.f, 0.f, 0.f}, eb[4] = {0.f, 0.f, 0.f, 0.f};
            uint32_t b[10][4];
            const uint32_t mp = p8 >> 3;
            while (!mbar_try(bar + 8 * B_MEM, mp)) {}
            lds128(b[0], l16 + mb); lds128(b[1], l16 + mb + 1024);
            bool rdy = mbar_try(bar + 8 * (B_MEM + 1), mp, 1);
            const uint32_t xb0 = mapa(bar + 8 * B_VM + p8, 0), xb1 = mapa(bar + 8 * B_VM + p8, 1);
            SFENCE();
            float is;
#pragma unroll
            for (int j = 0; j < 10; j++) {
#pragma unroll
                for (int x = 0; x < 2; x++) {
                    const int i = 2 * j + x;
                    const uint32_t* f = i < NS ? t[i] : fa[i - NS];
                    mma16(NS > 2 && x && j ? ea : da, f[0], f[1], f[2], f[3], b[j][2 * x], b[j][2 * x + 1]);
                    mma16(NS > 2 && x && j ? eb : db, fb[i][0], fb[i][1], fb[i][2], fb[i][3], b[j][2 * x], b[j][2 * x + 1]);
                    SFENCE();
                    if (x == 0 && j < 8 && !(j & 1)) {
                        if (__builtin_expect(!rdy, 0)) while (!mbar_try(bar + 8 * (B_MEM + 1 + (j >> 1)), mp)) {}
                        lds128(b[j + 2], l16 + mb + (j + 2) * 1024);
                    }
                    if (x == 1 && j < 8 && !(j & 1)) lds128(b[j + 3], l16 + mb + (j + 3) * 1024);
                    if (x == 0 && j < 6 && (j & 1)) rdy = mbar_try(bar + 8 * (B_MEM + 2 + (j >> 1)), mp, 1);
                    if (x == 0 && j == 8) is = lds32f(sb + OFF_MX + 16);
                }
                if (j == 0 && warp == 4) PROFT(16);
            }
            if (warp == 4) PROFT(20);
            if (NS > 2) {
#pragma unroll
                for (int i = 0; i < 4; i++) { da[i] += ea[i]; db[i] += eb[i]; }
            }
            sts128f_if(l16 + xo + 8192, db, !wg); sts128f_if(l16 + xo + 8192, da, wg);
            bar_sync(NB_PAIR + (warp & 3), 64);
            float u[4];
            lds128f(u, l16 + xi + 8192);
#pragma unroll
            for (int i = 0; i < 4; i++) da[i] = (wg ? db[i] : da[i]) * is;
            const uint32_t p0 = pack2(fmaf(u[0], is, da[0]), fmaf(u[1], is, da[1])), p1 = pack2(fmaf(u[2], is, da[2]), fmaf(u[3], is, da[3]));
            stsm2t_if(dst, p0, p1, rank < 2);
            bar_arrive_if<NB_QK, 384>(rank < 2);
            if (rank == 2) {
                st_async1(mapa(dst, 0), p0, xb0); st_async1(mapa(dst, 1), p0, xb1);
                st_async1(mapa(dst + 128, 0), p1, xb0); st_async1(mapa(dst + 128, 1), p1, xb1);
                sts32(dst, p0); sts32(dst + 128, p1);
                bar_arrive(NB_QK, 384);
            }
            if (warp == 4) PROFT(17);
            dst += dstep; dstep = -dstep; p8 ^= 8;
        }
    } else if (warp < 12) {
        asm volatile("setmaxnreg.dec.sync.aligned.u32 96;");
        const uint32_t rank = cta_rank();
        const int w = warp - 8;
        uint32_t amax = 0;
        {
            const int t = tid & 127, nr = rank == 2 ? 4 : 3;
            for (int r = 0; r < nr; r++) {
                const bf16* src = Wo + (size_t)(h * E_) * D_ + (r < 3 ? 192 * r + 64 * rank : 576);
#pragma unroll 1
                for (int i = 0; i < 8; i++) {
                    const int e = i * 16 + (t >> 3);
                    cp16(sb + OFF_WO + r * 16384 + e * 128 + (((t & 7) ^ (e & 6)) << 4), src + e * D_ + (t & 7) * 8);
                }
            }
            cp_commit();
            uint32_t m0[5][4];
#pragma unroll
            for (int it = 0; it < 5; it++)
#pragma unroll
                for (int j = 0; j < 4; j++) m0[it][j] = ldg32(mem0 + g * D_ + (it * 4 + w) * 32 + 2 * q + 8 * j);
#pragma unroll
            for (int it = 0; it < 5; it++) {
                sts128(sb + OFF_MEMB + (it * 4 + w) * 512 + lane * 16, m0[it][0], m0[it][1], m0[it][2], m0[it][3]);
                amax = absmax2(amax, absmax2(absmax2(m0[it][0], m0[it][1]), absmax2(m0[it][2], m0[it][3])));
            }
            if (tid == 256) { sts32(sb + OFF_MX + 16, 0x3f800000u); sts128(sb + OFF_MX + 48, 0x3f803f80u, 0x3f803f80u, 0x3f803f80u, 0x3f803f80u); }
            __syncwarp();
            if (lane < 5) mbar_arrive(bar + 8 * (B_MEM + lane));
            __syncwarp();
            cp_wait<0>();
            bar_sync(NB_ATT, 128);
            for (int r = 0; r < nr; r++) {
                uint32_t u[8][4];
                const uint32_t p = sb + OFF_WO + r * 16384 + 2 * q * 128 + (((2 * w + (g & 1)) ^ (2 * q)) << 4) + (g >> 1) * 4;
#pragma unroll
                for (int ks = 0; ks < 8; ks++)
#pragma unroll
                    for (int j = 0; j < 4; j++) u[ks][j] = lds32(p + (16 * ks + (j & 1) * 8 + (j >> 1)) * 128);
                bar_sync(NB_ATT, 128);
#pragma unroll
                for (int ks = 0; ks < 8; ks++)
                    sts128(sb + OFF_WO + (r * 4 + w) * 4096 + ks * 512 + lane * 16, prmt(u[ks][0], u[ks][2], 0x5410), prmt(u[ks][0], u[ks][2], 0x7632),
                           prmt(u[ks][1], u[ks][3], 0x5410), prmt(u[ks][1], u[ks][3], 0x7632));
            }
        }
        if (w == 0) TLI(690 + blockIdx.x, 3, gtime());
        pdl_wait();
        float cw;
        {
            const float4 a = ((const float4*)g_nrm)[lane], c = ((const float4*)g_nrm)[32 + lane];
            float sm = sqrt_approx((a.x + a.y) + (a.z + a.w)) * sqrt_approx((c.x + c.y) + (c.z + c.w)), mxv = sm;
#pragma unroll 1
            for (int o = 16; o; o >>= 1) { sm += __shfl_xor_sync(~0u, sm, o); mxv = fmaxf(mxv, __shfl_xor_sync(~0u, mxv, o)); }
            cw = 26.5f * fmaxf(sm, 8.f * mxv);
        }
        if (w == 0) {
            mbar_expect_elect(bar + 8 * B_X1, 1280);
            mbar_expect_elect(bar + 8 * B_VM, rank < 2 ? 2048 : 0);
            mbar_expect_elect(bar + 8 * B_VX, rank < 2 ? 8192 : 4096);
        }
        {
            const int kind = rank;
            const uint32_t l16 = opaque(sb + lane * 16), lw = opaque(sb + lane * 16 + w * 512);
            const uint32_t pa = opaque(sb + OFF_PS + rank * 512 + lane * 4 + w * 128);
            uint32_t lq = opaque(sb + OFF_Q + (lane & 7) * 16 + ((lane >> 3) & 1) * 256 + (lane >> 4) * 128);
            const uint32_t lv = opaque(sb + OFF_VX + w * 2048 + (lane & 7) * 16 + ((lane >> 3) & 1) * 512 + (lane >> 4) * 128);
            const uint32_t lo = opaque(sb + OFF_WO + w * 4096 + lane * 16);
            uint32_t& sfd = lq;
            const char* rp = (const char*)(g_acc + layer * ACC_LAYER) + (4 * rank + w) * 4096 + opaque((q >> 1) * 1024 + ((q & 1) * 8 + g) * 8);
            const char* lp = (const char*)(g_acc + layer * ACC_LAYER) + opaque(w * 8192 + (lane >> 3) * 1024 + (lane & 7) * 16);
            const uint32_t arm = bar + 8 * (w == 0 ? B_X1 + 1 : w == 1 ? B_VX + 1 : w == 2 ? B_XT : B_VM + 1);
            const uint32_t armb = w == 0 ? 1280 : (w == 1 ? 4096 : w == 2 ? 40960 : 0) + (rank == 2 ? 0 : w == 3 ? 2048 : 4096);
            float isig = 1.f;
            for (int s = 0; s < NSEG - 1; s++) {
                const uint32_t pb = s & 1, ph = (s >> 1) & 1, x1 = bar + 8 * (B_X1 + pb);
                uint32_t kf[8];
                bar_sync(NB_KX, 384);
                ldsm4(kf, lw + OFF_K + 1024 + w * 512 + pb * 5120); ldsm4(kf + 4, lw + OFF_K + 1536 + w * 512 + pb * 5120);
                sts32(sb + OFF_MX + w * 4, __reduce_max_sync(~0u, max(amax & 0x7fff0000u, (amax << 16) & 0x7fff0000u)));
                const uint32_t va = lv + pb * 8192, vma = lw + OFF_VM + pb * 2048;
                uint32_t wf[8][4], vf[2][2][4], vm[4], one[4];
                mbar_spin(bar + 8 * (B_VX + pb), ph);
#pragma unroll
                for (int t = 0; t < 2; t++)
#pragma unroll
                    for (int j = 0; j < 2; j++) ldsm4(vf[t][j], va + t * 1024 + j * 256);
                lds128(one, sb + OFF_MX + 48);
                auto scores = [&](auto MM) {
                    constexpr int mm = MM.value;
                    uint32_t qf[8], mf[8];
                    const uint32_t qa = lq + pb * 5120, ka = l16 + OFF_K + pb * 5120;
                    const uint32_t pa0 = mapa(pa, rank ^ 1), pa1 = mapa(pa, 2), pa2 = mapa(pa, rank);
                    const uint32_t xb0 = mapa(x1, rank ^ 1), xb1 = mapa(x1, 2), xb2 = mapa(x1, rank);
                    const uint32_t pm = 640 - rank * 384;
                    SFENCE();
                    if (w == 0) PROFT(2);
                    bar_sync(NB_QK, 384);
                    ldsm4(qf, qa); ldsm4(qf + 4, qa + 512);
                    if (mm) { ldsm4(mf, ka); ldsm4(mf + 4, ka + 512); }
                    SFENCE();
                    float c[4][4];
#pragma unroll
                    for (int i = 0; i < 4; i++) c[i][0] = c[i][1] = c[i][2] = c[i][3] = 0.f;
#pragma unroll
                    for (int i = 0; i < (mm ? 8 : 4); i++) {
                        const int hf = mm ? i >> 2 : i >> 1;
                        const uint32_t* f = (mm && (i & 2) ? mf : kf) + 4 * hf + 2 * (i & 1);
                        mma16(c[i & 3], qf[4 * hf], qf[4 * hf + 1], qf[4 * hf + 2], qf[4 * hf + 3], f[0], f[1]);
                    }
                    SFENCE();
                    bar_arrive(NB_W1, 512);
                    const uint32_t y = mm ? pack2(c[0][0] + c[1][2], c[0][1] + c[1][3])
                                          : pack2((c[0][0] + c[1][2]) + (c[2][0] + c[3][2]), (c[0][1] + c[1][3]) + (c[2][1] + c[3][3]));
                    st_async1(pa0, y, xb0); st_async1(pa1, y, xb1);
                    if (mm) {
                        const uint32_t z = pack2(c[2][0] + c[3][2], c[2][1] + c[3][3]);
                        st_async1(pa0 + pm, z, xb0); st_async1(pa1 + pm, z, xb1); st_async1(pa2 + pm, z, xb2);
                    }
                    st_async1(pa2, y, xb2);
                    if (w == 0) PROFT(5);
                };
                if (kind == 2) bar_sync(NB_QK, 384);
                else if (w == 3) scores(IC<1>{});
                else scores(IC<0>{});
                float m4[4];
                lds128f(m4, sb + OFF_MX);
                bar_arrive_if<NB_W1, 480>(kind == 2);
                mbar_spin(x1, ph);
                if (w == 0) PROFT(6);
                float sc[10];
                {
                    uint32_t u[4], v[4], m[2];
                    ldsm4(u, l16 + OFF_PS); ldsm4(v, l16 + OFF_PS + 512); ldsm2(m, l16 + OFF_PS + 1024);
                    SFENCE();
                    m4[0] = fmaxf(fmaxf(m4[0], m4[1]), fmaxf(m4[2], m4[3])) * isig;
                    SFENCE();
#pragma unroll
                    for (int i = 0; i < 4; i++) { sc[2 * i] = bf_lo(u[i]) + bf_lo(v[i]); sc[2 * i + 1] = bf_hi(u[i]) + bf_hi(v[i]); }
                    sc[8] = bf_lo(m[0]) + bf_lo(m[1]); sc[9] = bf_hi(m[0]) + bf_hi(m[1]);
                }
                float mx = fmaxf(fmaxf(fmaxf(fmaxf(sc[0], sc[1]), fmaxf(sc[2], sc[3])), fmaxf(fmaxf(sc[4], sc[5]), fmaxf(sc[6], sc[7]))), fmaxf(sc[8], sc[9]));
                auto fetch = [&](int i) { lds128(wf[i], lo + i * 512); };
                {
                    float m1 = __shfl_xor_sync(~0u, mx, 1), m2 = __shfl_xor_sync(~0u, mx, 2), m3 = __shfl_xor_sync(~0u, mx, 3);
                    mbar_spin(bar + 8 * (B_VM + pb), ph);
                    ldsm4(vm, vma);
                    mx = fmaxf(fmaxf(mx, m1), fmaxf(m2, m3)) * SM_SCALE;
                }
#pragma unroll
                for (int i = 0; i < 10; i++) sc[i] = fmaf(sc[i], SM_SCALE, -mx);
                float o0[4] = {0.f, 0.f, 0.f, 0.f}, o1[4] = {0.f, 0.f, 0.f, 0.f}, rs[4] = {0.f, 0.f, 0.f, 0.f};
                sc[8] = ex2(sc[8]); fetch(0); fetch(1); sc[9] = ex2(sc[9]);
                SFENCE();
                fetch(2); sc[0] = ex2(sc[0]); fetch(3); fetch(4); sc[1] = ex2(sc[1]); fetch(5); fetch(6); sc[2] = ex2(sc[2]);
                SFENCE();
                {
                    const uint32_t p = pack2(sc[8], sc[9]);
                    sc[3] = ex2(sc[3]); fetch(7);
                    mma8(o0, vm[0], vm[1], p);
                    mma8(o1, vm[2], vm[3], p);
                    sc[4] = ex2(sc[4]);
                    mma8(rs, one[0], one[1], p);
                    sc[5] = ex2(sc[5]);
                }
                SFENCE();
                {
                    const uint32_t p0 = pack2(sc[0], sc[1]), p1 = pack2(sc[2], sc[3]);
                    sc[6] = ex2(sc[6]);
                    mma16(o0, vf[0][0][0], vf[0][0][1], vf[0][0][2], vf[0][0][3], p0, p1);
                    SFENCE();
                    sc[7] = ex2(sc[7]);
                    mma16(o1, vf[1][0][0], vf[1][0][1], vf[1][0][2], vf[1][0][3], p0, p1);
                    SFENCE();
                    mma16(rs, one[0], one[1], one[2], one[3], p0, p1);
                    SFENCE();
                }
                {
                    const uint32_t p0 = pack2(sc[4], sc[5]), p1 = pack2(sc[6], sc[7]);
                    mma16(o0, vf[0][1][0], vf[0][1][1], vf[0][1][2], vf[0][1][3], p0, p1);
                    mma16(o1, vf[1][1][0], vf[1][1][1], vf[1][1][2], vf[1][1][3], p0, p1);
                    SFENCE();
                    mma16(rs, one[0], one[1], one[2], one[3], p0, p1);
                }
                const uint32_t e = max((__float_as_uint(cw * fmaxf(m4[0], 1.f)) >> 23) & 255u, 31u);
                SFENCE();
                stsm4t(lw + OFF_OB, pack2(o0[0], o0[1]), pack2(o0[2], o0[3]), pack2(o1[0], o1[1]), pack2(o1[2], o1[3]));
                if (w == 0) PROFT(13);
                bar_sync(NB_ATT, 128);
                uint32_t ob[16];
#pragma unroll
                for (int j = 0; j < 4; j++) ldsm4(ob + 4 * j, l16 + OFF_OB + j * 512);
                SFENCE();
                const float sig = __uint_as_float((278u - e) << 23);
                isig = __uint_as_float((e - 30u) << 23);
                const float sg0 = rcp(rs[0]) * sig, sg1 = rcp(rs[1]) * sig;
                SFENCE();
                auto tile = [&](uint32_t next, const char* p, auto LAST) {
                    float c[4][4];
#pragma unroll
                    for (int i = 0; i < 4; i++) c[i][0] = c[i][1] = c[i][2] = c[i][3] = 0.f;
#pragma unroll
                    for (int ks = 0; ks < 8; ks++) {
                        mma16(c[ks & 3], wf[ks][0], wf[ks][1], wf[ks][2], wf[ks][3], ob[2 * ks], ob[2 * ks + 1]);
                        if ((ks & 3) == 0) SFENCE();
                        if ((ks & 3) == 3 && !LAST.value) {
                            SFENCE();
#pragma unroll
                            for (int i = ks; i >= ks - 3; i--) { lds128(wf[i], next + i * 512); if (i == ks - 2) SFENCE(); }
                            if (ks == 3) SFENCE();
                        }
                    }
                    SFENCE();
                    if (LAST.value) { bar_arrive_if<NB_WIN, 256>(kind < 2); bar_arrive_if<NB_WIN, 384>(kind == 2); }
                    uint32_t v[4];
#pragma unroll
                    for (int i = 0; i < 4; i++)
                        v[i] = (__float_as_uint(fmaf((c[0][i] + c[1][i]) + (c[2][i] + c[3][i]), i & 1 ? sg1 : sg0, 12582912.f)) << 6) + (i < 2);
                    red_add64((u64*)p, v[0], v[2]);
                    red_add64((u64*)(p + 2048), v[1], v[3]);
                };
                tile(lo + 16384, rp, IC<0>{});
                if (w == 0) PROFT(7);
                tile(lo + 32768, rp + 49152, IC<0>{});
                if (kind == 2) tile(lo + 49152, rp + 98304, IC<0>{});
                tile(0, rp + (kind == 2 ? 28 * 4096 : 98304), IC<1>{});
                if (w == 0) PROFT(8);
                sts32(sb + OFF_MX + 16, __float_as_uint(isig));
                mbar_expect_elect(arm ^ (8 * pb), armb - (w == 2 && s == NSEG - 2 ? 40960 : 0));
                u64 y[20];
                uint32_t b[20];
                bool done[5] = {false, false, false, false, false};
                float z = isig;
                mbar_spin(bar + 8 * B_GO, pb);
                if (w == 0) PROFT(9);
                do {
#pragma unroll
                    for (int i = 0; i < 10; i++) {
                        if (STAG && (i == 2 || i == 4 || i == 7)) {
#pragma unroll
                            for (int k = 0; k < STAG; k++) asm volatile("ex2.approx.ftz.f32 %0,%0;" : "+f"(z));
                            asm volatile("{.reg .pred p; setp.ne.u32 p,%1,0; @p mov.b32 %0,%2;}" : "+r"(sfd) : "r"((uint32_t)never), "f"(z));
                            SFENCE();
                        }
                        ld_acc0(y[2 * i], y[2 * i + 1], lp + (i >> 1) * 32768 + (i & 1) * 4096);
                        if (STAG && (i == 1 || i == 3 || i == 6)) SFENCE();
                    }
                    uint32_t ok = 32u, late = 32u;
                    static_for<5>([&](auto IT) {
                        constexpr int it = IT.value;
                        if (it == 2) late = and3((uint32_t)y[8], (uint32_t)y[10], (uint32_t)y[12]);
                        else if (it == 3) late &= and3((uint32_t)y[14], (uint32_t)y[16], (uint32_t)y[18]);
                        else ok = and3(ok, (uint32_t)y[4 * it], it == 4 ? late : (uint32_t)y[4 * it + 2]);
                        if (it < 4) SFENCE();
                        if (it == 2 || it == 3) ok = and3(ok, (uint32_t)y[4 * it], (uint32_t)y[4 * it + 2]);
                        ok = and3(ok, (uint32_t)y[4 * it + 1], (uint32_t)y[4 * it + 3]);
                        const bool all = __all_sync(~0u, ok);
#pragma unroll
                        for (int j = 0; j < 4; j++) {
                            const u64 v = y[4 * it + j];
                            b[4 * it + j] = pack2((float)(int)(uint32_t)v, (float)(int)(uint32_t)(v >> 32));
                        }
                        sts128(lw + OFF_MEMB + it * 2048, b[4 * it], b[4 * it + 1], b[4 * it + 2], b[4 * it + 3]);
                        mbar_arrive_elect_if(bar + 8 * (B_MEM + it), all && !done[it]);
                        done[it] = all;
                        SFENCE();
                        if (it == 0 && w == 0) PROFT(10);
                    });
                } while (!done[4]);
                if (w == 0) PROFT(11);
                amax = b[0];
#pragma unroll
                for (int i = 1; i < 19; i += 2) amax = absmax2(amax, absmax2(b[i], b[i + 1]));
                amax = absmax2(amax, b[19]);
                const int adv = (s & 7) == 7 ? 163840 - 896 : 128;
                rp += adv; lp += adv;
            }
        }
        bar_sync(NB_KX, 384);
        bar_sync(NB_QK, 384);
        if (rank < 2) { bar_arrive(NB_W1, 512); bar_arrive(NB_WIN, 256); } else bar_arrive(NB_W1, 480);
    } else {
        asm volatile("setmaxnreg.dec.sync.aligned.u32 %0;" ::"n"(48));
        const uint32_t rank = cta_rank();
        const int w = warp - 12;
        pdl_wait();
        if (blockIdx.x == 2 && w == 3) asm volatile("st.release.gpu.global.u32 [%0],1;" ::"l"(g_started + layer) : "memory");
        uint32_t* sy = g_sync + layer * SYNC_LAYER;
        if (w == 1) TLI(690 + blockIdx.x, 1, gtime());
        if (w == 1) {
            mbar_expect_elect(bar + 8 * B_XT, 40960);
            bulk_g2s_elect(sb + OFF_X, g_xn, 40960, bar + 8 * B_XT);
            bar_sync(NB_PRO, 288);
            TLI(690 + blockIdx.x, 2, gtime());
            if (rank == 2) mbar_spin(bar + 8 * B_ST, 0);
            else mbar_arrive_remote_elect(mapa(bar + 8 * B_ST, 2));
            mbar_spin(bar + 8 * B_XT, 0);
            bar_arrive(NB_LD, 288);
            mbar_expect_elect(bar + 8 * (B_XT + 1), rank < 2 ? 45056 : 40960);
        }
        if (rank == 2) {
            if (w == 0) {
                for (int s = -1; s < NSEG - 1; s++) {
                    const uint32_t pb = s & 1, va = sb + OFF_VX + (pb ^ 1) * 8192 + 4096, vb = bar + 8 * (B_VX + (pb ^ 1));
                    bar_sync(NB_KF, 288);
                    fence_async();
                    bulk_s2s_elect(mapa(va, 0), va, 4096, mapa(vb, 0));
                    bulk_s2s_elect(mapa(va, 1), va, 4096, mapa(vb, 1));
                    if (s >= 0) mbar_spin(bar + 8 * (B_XD + pb), (s >> 1) & 1);
                    bar_sync(NB_W1, 480);
                }
            } else if (w == 1) {
                const unsigned char *pn = g_p + h * 12288, *px = g_xn + 40960;
                const uint32_t* pf = sy + wk::SY_P + h;
                for (int s = -1, nb = -1; s < NSEG - 1; s++, pn += H_ * 12288, px += 40960) {
                    const uint32_t pb = s & 1, xt = bar + 8 * (B_XT + pb), qa = sb + OFF_Q + (pb ^ 1) * 5120 + 1024;
                    if (s >= 0) mbar_spin(bar + 8 * (B_X1 + pb), (s >> 1) & 1);
                    if (s + 2 < NSEG) bulk_g2s_all3_elect(sb + OFF_X + pb * 40960, px, 40960, xt);
                    if (s == nb) {
                        while (__any_sync(~0u, ld_acquire(pf) < 3)) {}
                        pf += H_;
                        nb += s < 0 ? 4 : 6;
                    }
                    bulk_g2s_all3_elect(sb + OFF_VX + (pb ^ 1) * 8192, pn + 8192, 4096, bar + 8 * (B_VX + (pb ^ 1)));
                    bulk_g2s_elect(mapa(qa, 0), pn, 4096, mapa(xt, 0));
                    bulk_g2s_elect(mapa(qa, 1), pn + 4096, 4096, mapa(xt, 1));
                    mbar_spin(xt, ((s + 2) >> 1) & 1);
                    bar_sync(NB_W1, 480);
                }
                mbar_spin(bar + 8 * (B_VX + 1), 1);
            } else if (w == 2) {
                uint32_t* hp = sy + 1024;
                const char* pf = lane < 5 ? (const char*)(g_acc + layer * ACC_LAYER) + (5 * h + lane) * 1024 : (const char*)hp;
                const int pfa = lane < 5 ? 163840 : 1024;
                const uint32_t go = mapa(bar + 8 * B_GO, min(lane, 2));
                if (lane < 6) for (int i = 0; i < 8; i++) prefetch_l2(pf + i * 128);
                __syncwarp();
                for (int s = 0; s < NSEG - 1; s++, hp += 32) {
                    bar_sync(NB_W1, 480);
                    mbar_spin(bar + 8 * (B_X1 + (s & 1)), (s >> 1) & 1);
                    uint32_t t = gtime32(), t0 = clk(), c, tm;
                    asm volatile("{.reg .pred p; elect.sync _|p, 0xffffffff; @p red.relaxed.gpu.global.max.u32 [%0+4],%1; @p red.relaxed.gpu.global.add.u32 [%0],1;}"
                                 ::"l"(hp), "r"(t) : "memory");
                    if (h == 0) TLI(940 + s, 0, t);
                    if (lane < 6 && s < NSEG - 8) prefetch_l2(pf + ((s >> 3) + 1) * pfa + (s & 7) * 128);
                    __syncwarp();
                    while (clk() - t0 < (uint32_t)delay2) {}
                    do asm volatile("ld.relaxed.gpu.global.v2.u32 {%0,%1},[%2];" : "=r"(c), "=r"(tm) : "l"(hp) : "memory"); while (__any_sync(~0u, c != H_));
                    const uint32_t wait = min(tm - t, 10000u) * 7 / 4 + delay;
                    while (clk() - t0 < wait) {}
                    if (lane < 3) mbar_arrive_remote(go);
                    __syncwarp();
                }
                bar_sync(NB_W1, 480);
            }
        } else {
            if (w < 2) sts32(sb + OFF_PT + w * 768 + 640 + lane * 4, 0u);
            const uint32_t px = opaque(sb + OFF_PX + (w & 1) * 1280 + lane * 8);
            const uint32_t pt = opaque(sb + OFF_PT + (w & 1) * 768 + lane * 4);
            uint32_t os = opaque(sb + OFF_OST + (lane >> 4) * 1024 + w * 256 + (lane & 15) * 16);
            uint32_t& sfd = os;
            const int lim = opaque(8 * w + g + 8 - 2 * q);
            unsigned char* op = g_o + h * 8192 + rank * 2048;
            uint32_t* oc = sy + wk::SY_O - 1;
            auto report = [&]() {
                __syncwarp();
                asm volatile("{.reg .pred p; elect.sync _|p, 0xffffffff; @p red.relaxed.gpu.global.add.u32 [%0],1;}" ::"l"(oc) : "memory");
                oc++;
            };
            auto store_o = [&](int n) {
                bulk_s2g_elect(op, sb + OFF_OST + (n & 1) * 4096, 2048);
                bulk_s2g_elect(op + 4096, sb + OFF_OST + (n & 1) * 4096 + 2048, 2048);
                bulk_commit();
                op += H_ * 8192;
                bulk_wait<1>();
                report();
            };
            for (int s = 0; s < NSEG; s++) {
                const uint32_t pb = s & 1, ph = (s >> 1) & 1;
                if ((w >> 1) != rank) { if (s >= 1) mbar_spin(bar + 8 * B_PXE, pb ^ 1); }
                else if (w & 1) mbar_spin(bar + 8 * (B_XT + (pb ^ 1)), ((s + 1) >> 1) & 1);
                else mbar_expect_elect(bar + 8 * B_PXF, rank ? 2560 : 1536);
                const u64 dq = mkdesc(sb + OFF_Q + pb * 5120 + 1024, 128, 512), dk = mkdesc(sb + OFF_K + pb * 5120, 128, 1024);
                SFENCE();
                bar_sync(NB_W1, 512);
                float c[20];
                wg_fence();
                wgmma_n40_ss<0>(c, dq, dk);
#pragma unroll
                for (int ks = 1; ks < 4; ks++) wgmma_n40_ss<1>(c, dq + ks * 16, dk + ks * 16);
                wg_commit();
                bar_arrive(NB_X, 384);
                wg_wait<0>();
                if ((w >> 1) != rank) {
                    const uint32_t pa = mapa(px, rank ^ 1), pf = mapa(bar + 8 * B_PXF, rank ^ 1);
#pragma unroll
                    for (int nt = 0; nt < 5; nt++)
                        if (nt < 3 || rank == 0) st_async2(pa + nt * 256, __float_as_uint(c[4 * nt]), __float_as_uint(c[4 * nt + 1]), pf);
                    if ((w & 1) && s) store_o(s - 1);
                    mbar_spin(bar + 8 * (w & 1 ? B_VX : B_VM) + 8 * pb, ph);
                } else {
                    mbar_spin(bar + 8 * B_PXF, pb);
                    float u[10];
#pragma unroll
                    for (int nt = 0; nt < 5; nt++) lds64f(u[2 * nt], u[2 * nt + 1], px + nt * 256);
#pragma unroll
                    for (int i = 0; i < 10; i++) u[i] = 8 * (i >> 1) + (i & 1) <= lim ? u[i] + c[4 * (i >> 1) + (i & 1)] : -INFINITY;
                    float mx = fmaxf(fmaxf(fmaxf(fmaxf(u[0], u[1]), fmaxf(u[2], u[3])), fmaxf(fmaxf(u[4], u[5]), fmaxf(u[6], u[7]))), fmaxf(u[8], u[9]));
                    const float m1 = __shfl_xor_sync(~0u, mx, 1), m2 = __shfl_xor_sync(~0u, mx, 2), m3 = __shfl_xor_sync(~0u, mx, 3);
                    mx = fmaxf(fmaxf(mx, m1), fmaxf(m2, m3)) * SM_SCALE;
#pragma unroll
                    for (int i = 0; i < 10; i++) u[i] = ex2(fmaf(u[i], SM_SCALE, -mx));
                    float sum = (((u[0] + u[1]) + (u[2] + u[3])) + ((u[4] + u[5]) + (u[6] + u[7]))) + (u[8] + u[9]);
                    const float s1 = __shfl_xor_sync(~0u, sum, 1), s2 = __shfl_xor_sync(~0u, sum, 2), s3 = __shfl_xor_sync(~0u, sum, 3);
                    sum = rcp((sum + s1) + (s2 + s3));
#pragma unroll
                    for (int nt = 0; nt < 5; nt++) sts32(pt + (nt ? nt - 1 : 4) * 128, pack2(u[2 * nt] * sum, u[2 * nt + 1] * sum));
                }
                float acc[2][8];
                const u64 dv = mkdesc(sb + OFF_VX + pb * 8192, 128, 512), dp = mkdesc(sb + OFF_PT, 128, 768);
                const u64 dm = mkdesc(sb + OFF_VM + pb * 2048, 0, 128);
                fence_async();
                bar_sync(NB_WIN, 256);
                wg_fence();
#pragma unroll
                for (int m = 0; m < 2; m++) {
                    wgmma_n16_ss<0>(acc[m], dv + m * 256, dp);
                    wgmma_n16_ss<1>(acc[m], dv + m * 256 + 16, dp + 16);
                    wgmma_n16_ss<1>(acc[m], dm + m * 64, dp + 32);
                }
                wg_commit();
                bar_arrive_if<NB_W2, 384>(s < NSEG - 1);
                wg_wait<0>();
#pragma unroll
                for (int m = 0; m < 2; m++)
                    stsm4t(os + pb * 4096 + m * 2048, pack2(acc[m][0], acc[m][1]), pack2(acc[m][2], acc[m][3]), pack2(acc[m][4], acc[m][5]), pack2(acc[m][6], acc[m][7]));
                fence_async();
                mbar_arrive_remote_elect(mapa(bar + 8 * (B_XD + pb), 2));
                if ((w >> 1) == rank) mbar_arrive_remote_elect(mapa(bar + 8 * B_PXE, rank ^ 1));
            }
            bar_sync(NB_W2, 128);
            if (w == 3 - 2 * rank) {
                store_o(NSEG - 1);
                bulk_wait<0>();
                report();
            }
        }
    }
    __syncwarp();
    if (lane < 3) mbar_arrive_remote(mapa(bar + 8 * B_FIN, lane));
    mbar_wait(bar + 8 * B_FIN, 0);
    TLE(2 + 5 * layer);
}

int g_delay = 2501050, g_layers = 2;

void make_map(CUtensorMap* m, CUtensorMapDataType dt, const void* p, const cuuint64_t* dim, const cuuint64_t* str, const cuuint32_t* box, CUtensorMapSwizzle sw) {
    typedef CUresult (*Fn)(CUtensorMap*, CUtensorMapDataType, cuuint32_t, void*, const cuuint64_t*, const cuuint64_t*, const cuuint32_t*,
                           const cuuint32_t*, CUtensorMapInterleave, CUtensorMapSwizzle, CUtensorMapL2promotion, CUtensorMapFloatOOBfill);
    static Fn fn = nullptr;
    if (!fn) {
        cudaDriverEntryPointQueryResult qr;
        cudaGetDriverEntryPoint("cuTensorMapEncodeTiled", (void**)&fn, cudaEnableDefault, &qr);
    }
    const cuuint32_t es[3] = {1, 1, 1};
    fn(m, dt, 3, (void*)p, dim, str, box, es, CU_TENSOR_MAP_INTERLEAVE_NONE, sw, CU_TENSOR_MAP_L2_PROMOTION_L2_128B, CU_TENSOR_MAP_FLOAT_OOB_FILL_NONE);
}
void map_weight(CUtensorMap* m, const bf16* p, int rows, int cols, int ng, int br = 64) {
    const cuuint64_t dim[3] = {64, (cuuint64_t)rows, (cuuint64_t)cols / 64}, str[2] = {(cuuint64_t)cols * 2, 128};
    const cuuint32_t box[3] = {64, (cuuint32_t)br, (cuuint32_t)ng};
    make_map(m, CU_TENSOR_MAP_DATA_TYPE_BFLOAT16, p, dim, str, box, CU_TENSOR_MAP_SWIZZLE_128B);
}
void map_pieces(CUtensorMap* m, const void* p, int np, int ns) {
    const cuuint64_t dim[3] = {256, (cuuint64_t)np * 2, NSEG}, str[2] = {2048, (cuuint64_t)np * 4096};
    const cuuint32_t box[3] = {256, 2, (cuuint32_t)ns};
    make_map(m, CU_TENSOR_MAP_DATA_TYPE_UINT64, p, dim, str, box, CU_TENSOR_MAP_SWIZZLE_NONE);
}

template <class... P, class... A> void launch(void (*k)(P...), int grid, int block, int smem, int cluster, bool pdl, A... args) {
    cudaLaunchConfig_t c = {};
    c.gridDim = dim3(grid); c.blockDim = dim3(block); c.dynamicSmemBytes = smem; c.stream = cudaStreamPerThread;
    cudaLaunchAttribute at[2];
    int n = 0;
    if (cluster > 1) { at[n].id = cudaLaunchAttributeClusterDimension; at[n].val.clusterDim.x = cluster; at[n].val.clusterDim.y = 1; at[n].val.clusterDim.z = 1; n++; }
    if (pdl) { at[n].id = cudaLaunchAttributeProgrammaticStreamSerialization; at[n].val.programmaticStreamSerializationAllowed = 1; n++; }
    c.attrs = at; c.numAttrs = n;
    cudaLaunchKernelEx(&c, k, args...);
}

int max_clusters() {
    cudaLaunchConfig_t c = {};
    c.gridDim = dim3(3 * H_); c.blockDim = dim3(512); c.dynamicSmemBytes = rec::SMEM;
    cudaLaunchAttribute at[1];
    at[0].id = cudaLaunchAttributeClusterDimension; at[0].val.clusterDim.x = 3; at[0].val.clusterDim.y = 1; at[0].val.clusterDim.z = 1;
    c.attrs = at; c.numAttrs = 1;
    int n = 0;
    cudaOccupancyMaxActiveClusters(&n, rec_kernel, &c);
    return n;
}

}

extern "C" void kernel_launch(void* const* d_in, const int* in_sizes, int n_in, void* d_out, int out_size) {
    const bf16* x = (const bf16*)d_in[0];
    const bf16* mem0 = (const bf16*)d_in[1];
    const bf16* Wq = (const bf16*)d_in[2];
    const bf16* Wk = (const bf16*)d_in[3];
    const bf16* Wv = (const bf16*)d_in[4];
    const bf16* Wo = (const bf16*)d_in[5];
    const bf16* wr = (const bf16*)d_in[8];
    const bf16* wi = (const bf16*)d_in[9];
    cudaFuncSetAttribute(rec_kernel, cudaFuncAttributeMaxDynamicSharedMemorySize, rec::SMEM);
    cudaFuncSetAttribute(side_kernel, cudaFuncAttributeMaxDynamicSharedMemorySize, wk::SMEM);
    cudaFuncSetAttribute(colfft_kernel, cudaFuncAttributeMaxDynamicSharedMemorySize, CF_SMEM);
    Maps maps;
    void *pxn, *po;
    cudaGetSymbolAddress(&pxn, g_xn);
    cudaGetSymbolAddress(&po, g_o);
    map_weight(&maps.wq2, Wq, D_, 4096, 2); map_weight(&maps.wv1, Wv, D_, 4096, 1);
    map_weight(&maps.wo2, Wo, 4096, D_, 2); map_weight(&maps.wo1, Wo, 4096, D_, 1, 192);
    map_pieces(&maps.x6, pxn, 10, 6); map_pieces(&maps.x4, pxn, 10, 4);
    map_pieces(&maps.o6, po, 64, 6); map_pieces(&maps.o2, po, 64, 2);
    bf16 *x1, *x2;
    cudaGetSymbolAddress((void**)&x1, g_x1);
    cudaGetSymbolAddress((void**)&x2, g_x2);
    constexpr int ONE_PER_SM = 120 * 1024;
    cudaFuncSetAttribute(rowfft_kernel, cudaFuncAttributeMaxDynamicSharedMemorySize, ONE_PER_SM);
    cudaFuncSetAttribute(rowifft_kernel, cudaFuncAttributeMaxDynamicSharedMemorySize, ONE_PER_SM);
    static int ncl = 0, nsm = 0;
    if (!ncl) { ncl = max_clusters(); cudaDeviceGetAttribute(&nsm, cudaDevAttrMultiProcessorCount, 0); }
    maps.wr = wr; maps.wi = wi;
    launch(prep_kernel, 128, 512, 0, 1, false, x, Wq, Wk, Wv, Wo);
    for (int layer = 0; layer < g_layers; layer++) {
        const bf16* xin = layer ? x2 : x;
        launch(rec_kernel, 3 * ncl, 512, rec::SMEM, 3, true, maps, xin, x1, mem0, Wq, Wk, Wv, Wo, layer, g_delay % 10000, g_delay / 10000);
        launch(side_kernel, nsm - 3 * (ncl - H_), 512, wk::SMEM, 1, true, maps, xin, x1, layer, 3 * (ncl - H_));
        launch(rowfft_kernel, 128, 256, ONE_PER_SM, 1, true, xin, x1, Wq, Wk, Wv, layer);
        launch(colfft_kernel, 107, 384, CF_SMEM, 1, true, layer);
        launch(rowifft_kernel, 128, 256, ONE_PER_SM, 1, true, (const bf16*)x1, layer ? (bf16*)d_out : x2, layer);
    }
}
```

```cpp
#include <cuda_runtime.h>
#include <cuda_bf16.h>
#include <cuda.h>
#include <stdint.h>

#define DEV __device__ __forceinline__
typedef unsigned long long u64;
typedef __nv_bfloat16 bf16;

namespace {

constexpr int S_ = 2048, D_ = 640, H_ = 32, E_ = 128, NSEG = 64;

__device__ __align__(1024) unsigned char g_xn[S_ * D_ * 2];
__device__ __align__(1024) unsigned char g_o[S_ * H_ * E_ * 2];
constexpr int ACC_LAYER = 32 * 5120;
__device__ __align__(4096) u64 g_acc[2 * ACC_LAYER];
__device__ __align__(16) float g_nrm[256];
__device__ __align__(1024) unsigned char g_p[NSEG * H_ * 3 * 4096];
constexpr int SYNC_LAYER = 1024 + 64 * 32;
__device__ __align__(128) uint32_t g_sync[2 * SYNC_LAYER];
__device__ uint32_t g_started[2];
__device__ __align__(1024) bf16 g_x1[S_ * D_];
__device__ __align__(1024) bf16 g_x2[S_ * D_];
constexpr int YT_ROWS = 128;
__device__ __align__(1024) float g_yt[2 * YT_ROWS * D_];
constexpr int NCOL = 321;
__device__ __align__(1024) unsigned char g_z[NCOL * 8192];
__device__ __align__(1024) unsigned char g_wt[NCOL * 8192];
__device__ __align__(1024) uint4 g_f128[2 * 8 * 256];
__device__ __align__(1024) uint4 g_f64[2 * 4 * 128];
__device__ __align__(1024) bf16 g_g32[2 * 4096];
#define TLI(id, k, v)
#define TLS(i)
#define TLE(i)

DEV uint32_t s2u(const void* p) { return (uint32_t)__cvta_generic_to_shared(p); }
DEV uint32_t clk() { uint32_t c; asm volatile("mov.u32 %0,%%clock;" : "=r"(c)::"memory"); return c; }
DEV uint32_t gtime32() { uint32_t t; asm volatile("mov.u32 %0,%%globaltimer_lo;" : "=r"(t)::"memory"); return t; }
DEV uint32_t cta_rank() { uint32_t r; asm volatile("mov.u32 %0,%%cluster_ctarank;" : "=r"(r)); return __shfl_sync(~0u, r, 0); }
DEV uint32_t mapa(uint32_t a, uint32_t r) { uint32_t o; asm("mapa.shared::cluster.u32 %0,%1,%2;" : "=r"(o) : "r"(a), "r"(r)); return o; }
DEV void mbar_init(uint32_t b, uint32_t n) { asm volatile("mbarrier.init.shared::cta.b64 [%0],%1;" ::"r"(b), "r"(n) : "memory"); }
DEV bool mbar_try(uint32_t b, uint32_t par, int) {
    uint32_t ok;
    asm volatile("{.reg .pred p; mbarrier.test_wait.parity.shared::cta.b64 p,[%1],%2; selp.u32 %0,1,0,p;}" : "=r"(ok) : "r"(b), "r"(par) : "memory");
    return ok;
}
DEV bool mbar_try(uint32_t b, uint32_t par) {
    uint32_t ok;
    asm volatile("{.reg .pred p; mbarrier.try_wait.parity.shared::cta.b64 p,[%1],%2; selp.u32 %0,1,0,p;}" : "=r"(ok) : "r"(b), "r"(par) : "memory");
    return ok;
}
constexpr uint32_t SPIN_LIMIT = 1u << 18;
DEV void die() { __trap(); }
DEV void mbar_wait(uint32_t b, uint32_t par) {
    uint32_t n = 0;
    while (!mbar_try(b, par)) if (++n > SPIN_LIMIT) die();
}
DEV void mbar_spin(uint32_t b, uint32_t par) { while (!mbar_try(b, par)) {} }
DEV uint32_t opaque(uint32_t x) { return __shfl_xor_sync(~0u, x, 0); }
#define SFENCE() asm volatile("{.reg .pred p; setp.ne.u32 p,%1,0; @p mov.u32 %0,%%clock;}" : "+r"(sfd) : "r"((uint32_t)never) : "memory")
DEV void mbar_arrive(uint32_t b) { asm volatile("mbarrier.arrive.shared::cta.b64 _,[%0];" ::"r"(b) : "memory"); }
DEV void mbar_arrive_elect(uint32_t b) { asm volatile("{.reg .pred p; elect.sync _|p, 0xffffffff; @p mbarrier.arrive.shared::cta.b64 _,[%0];}" ::"r"(b) : "memory"); }
DEV void mbar_arrive_elect_if(uint32_t b, bool c) {
    asm volatile("{.reg .pred p, q; setp.ne.u32 q,%1,0; elect.sync _|p, 0xffffffff; and.pred p,p,q; @p mbarrier.arrive.shared::cta.b64 _,[%0];}" ::"r"(b), "r"((uint32_t)c) : "memory");
}
DEV void mbar_expect_elect(uint32_t b, uint32_t tx) {
    asm volatile("{.reg .pred p; elect.sync _|p, 0xffffffff; @p mbarrier.arrive.expect_tx.shared::cta.b64 _,[%0],%1;}" ::"r"(b), "r"(tx) : "memory");
}
DEV void mbar_arrive_remote_elect(uint32_t b) { asm volatile("{.reg .pred p; elect.sync _|p, 0xffffffff; @p mbarrier.arrive.shared::cluster.b64 _,[%0];}" ::"r"(b) : "memory"); }
DEV bool elect() { uint32_t r; asm volatile("{.reg .pred p; elect.sync _|p, 0xffffffff; selp.u32 %0,1,0,p;}" : "=r"(r)); return r; }
DEV void mbar_arrive_remote(uint32_t b) { asm volatile("mbarrier.arrive.shared::cluster.b64 _,[%0];" ::"r"(b) : "memory"); }
DEV void mbar_expect(uint32_t b, uint32_t tx) { asm volatile("mbarrier.arrive.expect_tx.shared::cta.b64 _,[%0],%1;" ::"r"(b), "r"(tx) : "memory"); }
DEV void bar_sync(int id, int n) { asm volatile("bar.sync %0,%1;" ::"r"(id), "r"(n) : "memory"); }
DEV void bar_arrive(int id, int n) { asm volatile("bar.arrive %0,%1;" ::"r"(id), "r"(n) : "memory"); }
template <int ID, int N> DEV void bar_arrive_if(bool p) {
    asm volatile("{.reg .pred p; setp.ne.u32 p,%0,0; @p bar.arrive %1,%2;}" ::"r"((uint32_t)p), "n"(ID), "n"(N) : "memory");
}
DEV void prefetch_bulk(const void* p, uint32_t bytes) { asm volatile("cp.async.bulk.prefetch.L2.global [%0],%1;" ::"l"(p), "r"(bytes) : "memory"); }
DEV void prefetch_l2(const void* p) { asm volatile("prefetch.global.L2 [%0];" ::"l"(p) : "memory"); }
template <int ID, int N> DEV void bar_sync_if(bool p) {
    asm volatile("{.reg .pred p; setp.ne.u32 p,%0,0; @p bar.sync %1,%2;}" ::"r"((uint32_t)p), "n"(ID), "n"(N) : "memory");
}
DEV void st_remote(uint32_t a, uint32_t x) { asm volatile("st.relaxed.cluster.shared::cluster.u32 [%0],%1;" ::"r"(a), "r"(x) : "memory"); }
DEV void st_async1(uint32_t a, uint32_t x, uint32_t b) {
    asm volatile("st.async.shared::cluster.mbarrier::complete_tx::bytes.u32 [%0],%1,[%2];" ::"r"(a), "r"(x), "r"(b) : "memory");
}
DEV void st_async2(uint32_t a, uint32_t x, uint32_t y, uint32_t b) {
    asm volatile("st.async.shared::cluster.mbarrier::complete_tx::bytes.v2.u32 [%0],{%1,%2},[%3];" ::"r"(a), "r"(x), "r"(y), "r"(b) : "memory");
}
DEV void st_async4(uint32_t a, uint32_t x, uint32_t y, uint32_t z, uint32_t w, uint32_t b) {
    asm volatile("st.async.shared::cluster.mbarrier::complete_tx::bytes.v4.u32 [%0],{%1,%2,%3,%4},[%5];" ::"r"(a), "r"(x), "r"(y), "r"(z), "r"(w), "r"(b) : "memory");
}
DEV void bulk_g2s(uint32_t dst, const void* src, uint32_t bytes, uint32_t b) {
    asm volatile("cp.async.bulk.shared::cluster.global.mbarrier::complete_tx::bytes [%0],[%1],%2,[%3];" ::"r"(dst), "l"(src), "r"(bytes), "r"(b) : "memory");
}
DEV void bulk_g2s_elect(uint32_t dst, const void* src, uint32_t bytes, uint32_t b) {
    asm volatile("{.reg .pred p; elect.sync _|p, 0xffffffff; @p cp.async.bulk.shared::cluster.global.mbarrier::complete_tx::bytes [%0],[%1],%2,[%3];}"
                 ::"r"(dst), "l"(src), "r"(bytes), "r"(b) : "memory");
}
DEV void bulk_g2s_all3_elect(uint32_t dst, const void* src, uint32_t bytes, uint32_t b) {
    asm volatile("{.reg .pred p; elect.sync _|p, 0xffffffff; @p cp.async.bulk.shared::cluster.global.mbarrier::complete_tx::bytes.multicast::cluster [%0],[%1],%2,[%3],%4;}"
                 ::"r"(dst), "l"(src), "r"(bytes), "r"(b), "h"((unsigned short)7) : "memory");
}
DEV void bulk_s2s_elect(uint32_t dst, uint32_t src, uint32_t bytes, uint32_t b) {
    asm volatile("{.reg .pred p; elect.sync _|p, 0xffffffff; @p cp.async.bulk.shared::cluster.shared::cta.mbarrier::complete_tx::bytes [%0],[%1],%2,[%3];}"
                 ::"r"(dst), "r"(src), "r"(bytes), "r"(b) : "memory");
}
DEV void bulk_s2g_elect(void* dst, uint32_t src, uint32_t bytes) {
    asm volatile("{.reg .pred p; elect.sync _|p, 0xffffffff; @p cp.async.bulk.global.shared::cta.bulk_group [%0],[%1],%2;}" ::"l"(dst), "r"(src), "r"(bytes) : "memory");
}
DEV void bulk_s2s(uint32_t dst, uint32_t src, uint32_t bytes, uint32_t b) {
    asm volatile("cp.async.bulk.shared::cluster.shared::cta.mbarrier::complete_tx::bytes [%0],[%1],%2,[%3];" ::"r"(dst), "r"(src), "r"(bytes), "r"(b) : "memory");
}
DEV void bulk_s2g(void* dst, uint32_t src, uint32_t bytes) {
    asm volatile("cp.async.bulk.global.shared::cta.bulk_group [%0],[%1],%2;" ::"l"(dst), "r"(src), "r"(bytes) : "memory");
}
DEV void tma3d(uint32_t dst, const CUtensorMap* m, int c0, int c1, int c2, uint32_t b) {
    asm volatile("cp.async.bulk.tensor.3d.shared::cluster.global.mbarrier::complete_tx::bytes [%0],[%1,{%3,%4,%5}],[%2];"
                 ::"r"(dst), "l"(m), "r"(b), "r"(c0), "r"(c1), "r"(c2) : "memory");
}
DEV void bulk_commit() { asm volatile("cp.async.bulk.commit_group;" ::: "memory"); }
template <int N> DEV void bulk_wait() { asm volatile("cp.async.bulk.wait_group %0;" ::"n"(N) : "memory"); }
template <int N> DEV void bulk_wait_read() { asm volatile("cp.async.bulk.wait_group.read %0;" ::"n"(N) : "memory"); }
DEV void flag_add(uint32_t* p) { asm volatile("red.relaxed.gpu.global.add.u32 [%0],1;" ::"l"(p) : "memory"); }
DEV uint32_t ld_acquire(const uint32_t* p) { uint32_t v; asm volatile("ld.acquire.gpu.global.u32 %0,[%1];" : "=r"(v) : "l"(p) : "memory"); return v; }
DEV void flag_wait(const uint32_t* p, uint32_t n) {
    for (uint32_t it = 0; ld_acquire(p) < n; __nanosleep(40)) if (++it > (SPIN_LIMIT << 3)) die();
}
DEV void cp16(uint32_t dst, const void* src) { asm volatile("cp.async.cg.shared.global [%0],[%1],16;" ::"r"(dst), "l"(src) : "memory"); }
DEV void cp_commit() { asm volatile("cp.async.commit_group;" ::: "memory"); }
template <int N> DEV void cp_wait() { asm volatile("cp.async.wait_group %0;" ::"n"(N) : "memory"); }
DEV uint32_t lds32(uint32_t a) { uint32_t x; asm volatile("ld.shared.u32 %0,[%1];" : "=r"(x) : "r"(a) : "memory"); return x; }
DEV void fence_async() { asm volatile("fence.proxy.async.shared::cta;" ::: "memory"); }
DEV uint32_t pack2(float lo, float hi) { uint32_t r; asm("cvt.rn.bf16x2.f32 %0,%1,%2;" : "=r"(r) : "f"(hi), "f"(lo)); return r; }
DEV uint32_t prmt(uint32_t a, uint32_t b, uint32_t s) { uint32_t r; asm("prmt.b32 %0,%1,%2,%3;" : "=r"(r) : "r"(a), "r"(b), "r"(s)); return r; }
DEV float ex2(float x) { float r; asm("ex2.approx.ftz.f32 %0,%1;" : "=f"(r) : "f"(x)); return r; }
DEV float sqrt_approx(float x) { float r; asm("sqrt.approx.ftz.f32 %0,%1;" : "=f"(r) : "f"(x)); return r; }
DEV float rcp(float x) { float r; asm("rcp.approx.ftz.f32 %0,%1;" : "=f"(r) : "f"(x)); return r; }
DEV void lds128(uint32_t* r, uint32_t a) { asm volatile("ld.shared.v4.u32 {%0,%1,%2,%3},[%4];" : "=r"(r[0]), "=r"(r[1]), "=r"(r[2]), "=r"(r[3]) : "r"(a) : "memory"); }
DEV void lds64(uint32_t* r, uint32_t a) { asm volatile("ld.shared.v2.u32 {%0,%1},[%2];" : "=r"(r[0]), "=r"(r[1]) : "r"(a) : "memory"); }
DEV void lds64f(float& x, float& y, uint32_t a) { asm volatile("ld.shared.v2.f32 {%0,%1},[%2];" : "=f"(x), "=f"(y) : "r"(a) : "memory"); }
DEV void lds128f(float* r, uint32_t a) { asm volatile("ld.shared.v4.f32 {%0,%1,%2,%3},[%4];" : "=f"(r[0]), "=f"(r[1]), "=f"(r[2]), "=f"(r[3]) : "r"(a) : "memory"); }
DEV void sts128(uint32_t a, uint32_t x, uint32_t y, uint32_t z, uint32_t w) { asm volatile("st.shared.v4.u32 [%0],{%1,%2,%3,%4};" ::"r"(a), "r"(x), "r"(y), "r"(z), "r"(w) : "memory"); }
DEV void sts64(uint32_t a, uint32_t x, uint32_t y) { asm volatile("st.shared.v2.u32 [%0],{%1,%2};" ::"r"(a), "r"(x), "r"(y) : "memory"); }
DEV void sts32(uint32_t a, uint32_t x) { asm volatile("st.shared.u32 [%0],%1;" ::"r"(a), "r"(x) : "memory"); }
DEV void ldsm4(uint32_t* r, uint32_t a) { asm volatile("ldmatrix.sync.aligned.m8n8.x4.shared.b16 {%0,%1,%2,%3},[%4];" : "=r"(r[0]), "=r"(r[1]), "=r"(r[2]), "=r"(r[3]) : "r"(a) : "memory"); }
DEV void ldsm4t(uint32_t* r, uint32_t a) { asm volatile("ldmatrix.sync.aligned.m8n8.x4.trans.shared.b16 {%0,%1,%2,%3},[%4];" : "=r"(r[0]), "=r"(r[1]), "=r"(r[2]), "=r"(r[3]) : "r"(a) : "memory"); }
DEV void ldsm2(uint32_t* r, uint32_t a) { asm volatile("ldmatrix.sync.aligned.m8n8.x2.shared.b16 {%0,%1},[%2];" : "=r"(r[0]), "=r"(r[1]) : "r"(a) : "memory"); }
DEV void stsm4t(uint32_t a, uint32_t x, uint32_t y, uint32_t z, uint32_t w) { asm volatile("stmatrix.sync.aligned.m8n8.x4.trans.shared.b16 [%0],{%1,%2,%3,%4};" ::"r"(a), "r"(x), "r"(y), "r"(z), "r"(w) : "memory"); }
DEV void stsm4(uint32_t a, uint32_t x, uint32_t y, uint32_t z, uint32_t w) { asm volatile("stmatrix.sync.aligned.m8n8.x4.shared.b16 [%0],{%1,%2,%3,%4};" ::"r"(a), "r"(x), "r"(y), "r"(z), "r"(w) : "memory"); }
DEV void stsm2(uint32_t a, uint32_t x, uint32_t y) { asm volatile("stmatrix.sync.aligned.m8n8.x2.shared.b16 [%0],{%1,%2};" ::"r"(a), "r"(x), "r"(y) : "memory"); }
DEV void sts128f_if(uint32_t a, const float* v, bool p) {
    asm volatile("{.reg .pred p; setp.ne.u32 p,%5,0; @p st.shared.v4.f32 [%0],{%1,%2,%3,%4};}" ::"r"(a), "f"(v[0]), "f"(v[1]), "f"(v[2]), "f"(v[3]), "r"((uint32_t)p) : "memory");
}
DEV void stsm2t_if(uint32_t a, uint32_t x, uint32_t y, bool p) {
    asm volatile("{.reg .pred p; setp.ne.u32 p,%3,0; @p stmatrix.sync.aligned.m8n8.x2.trans.shared.b16 [%0],{%1,%2};}" ::"r"(a), "r"(x), "r"(y), "r"((uint32_t)p) : "memory");
}
DEV void stsm2t(uint32_t a, uint32_t x, uint32_t y) { asm volatile("stmatrix.sync.aligned.m8n8.x2.trans.shared.b16 [%0],{%1,%2};" ::"r"(a), "r"(x), "r"(y) : "memory"); }
DEV void mma16(float* d, uint32_t a0, uint32_t a1, uint32_t a2, uint32_t a3, uint32_t b0, uint32_t b1) {
    asm volatile("mma.sync.aligned.m16n8k16.row.col.f32.bf16.bf16.f32 {%0,%1,%2,%3},{%4,%5,%6,%7},{%8,%9},{%0,%1,%2,%3};"
                 : "+f"(d[0]), "+f"(d[1]), "+f"(d[2]), "+f"(d[3]) : "r"(a0), "r"(a1), "r"(a2), "r"(a3), "r"(b0), "r"(b1));
}
DEV void mma8(float* d, uint32_t a0, uint32_t a1, uint32_t b0) {
    asm volatile("mma.sync.aligned.m16n8k8.row.col.f32.bf16.bf16.f32 {%0,%1,%2,%3},{%4,%5},{%6},{%0,%1,%2,%3};"
                 : "+f"(d[0]), "+f"(d[1]), "+f"(d[2]), "+f"(d[3]) : "r"(a0), "r"(a1), "r"(b0));
}
DEV u64 mkdesc(uint32_t a, uint32_t lbo, uint32_t sbo) { return (u64)((a & 0x3ffff) >> 4) | ((u64)(lbo >> 4) << 16) | ((u64)(sbo >> 4) << 32); }
constexpr u64 SW128 = 1ull << 62;
DEV void wg_fence() { asm volatile("wgmma.fence.sync.aligned;" ::: "memory"); }
DEV void wg_commit() { asm volatile("wgmma.commit_group.sync.aligned;" ::: "memory"); }
template <int N> DEV void wg_wait() { asm volatile("wgmma.wait_group.sync.aligned %0;" ::"n"(N) : "memory"); }
template <int ACC> DEV void wgmma_n32_rs(float* d, const uint32_t* a, u64 desc) {
    asm volatile("wgmma.mma_async.sync.aligned.m64n32k16.f32.bf16.bf16 {%0,%1,%2,%3,%4,%5,%6,%7,%8,%9,%10,%11,%12,%13,%14,%15},{%16,%17,%18,%19},%20,%21,1,1,0;"
                 : "+f"(d[0]), "+f"(d[1]), "+f"(d[2]), "+f"(d[3]), "+f"(d[4]), "+f"(d[5]), "+f"(d[6]), "+f"(d[7]),
                   "+f"(d[8]), "+f"(d[9]), "+f"(d[10]), "+f"(d[11]), "+f"(d[12]), "+f"(d[13]), "+f"(d[14]), "+f"(d[15])
                 : "r"(a[0]), "r"(a[1]), "r"(a[2]), "r"(a[3]), "l"(desc), "n"(ACC));
}
template <int ACC> DEV void wgmma_n32_ss(float* d, u64 da, u64 desc) {
    asm volatile("wgmma.mma_async.sync.aligned.m64n32k16.f32.bf16.bf16 {%0,%1,%2,%3,%4,%5,%6,%7,%8,%9,%10,%11,%12,%13,%14,%15},%16,%17,%18,1,1,0,0;"
                 : "+f"(d[0]), "+f"(d[1]), "+f"(d[2]), "+f"(d[3]), "+f"(d[4]), "+f"(d[5]), "+f"(d[6]), "+f"(d[7]),
                   "+f"(d[8]), "+f"(d[9]), "+f"(d[10]), "+f"(d[11]), "+f"(d[12]), "+f"(d[13]), "+f"(d[14]), "+f"(d[15])
                 : "l"(da), "l"(desc), "n"(ACC));
}
template <int ACC> DEV void wgmma_n16_ss(float* d, u64 da, u64 desc) {
    asm volatile("wgmma.mma_async.sync.aligned.m64n16k16.f32.bf16.bf16 {%0,%1,%2,%3,%4,%5,%6,%7},%8,%9,%10,1,1,0,0;"
                 : "+f"(d[0]), "+f"(d[1]), "+f"(d[2]), "+f"(d[3]), "+f"(d[4]), "+f"(d[5]), "+f"(d[6]), "+f"(d[7])
                 : "l"(da), "l"(desc), "n"(ACC));
}
#define ACC8(o) "+f"(d[o]), "+f"(d[o + 1]), "+f"(d[o + 2]), "+f"(d[o + 3]), "+f"(d[o + 4]), "+f"(d[o + 5]), "+f"(d[o + 6]), "+f"(d[o + 7])
template <int ACC, int TB> DEV void wgmma_n64_rs(float* d, const uint32_t* a, u64 desc) {
    asm volatile("wgmma.mma_async.sync.aligned.m64n64k16.f32.bf16.bf16 {%0,%1,%2,%3,%4,%5,%6,%7,%8,%9,%10,%11,%12,%13,%14,%15,"
                 "%16,%17,%18,%19,%20,%21,%22,%23,%24,%25,%26,%27,%28,%29,%30,%31},{%32,%33,%34,%35},%36,%37,1,1,%38;"
                 : ACC8(0), ACC8(8), ACC8(16), ACC8(24) : "r"(a[0]), "r"(a[1]), "r"(a[2]), "r"(a[3]), "l"(desc), "n"(ACC), "n"(TB));
}
template <int ACC, int TB> DEV void wgmma_n80_rs(float* d, const uint32_t* a, u64 desc) {
    asm volatile("wgmma.mma_async.sync.aligned.m64n80k16.f32.bf16.bf16 {%0,%1,%2,%3,%4,%5,%6,%7,%8,%9,%10,%11,%12,%13,%14,%15,"
                 "%16,%17,%18,%19,%20,%21,%22,%23,%24,%25,%26,%27,%28,%29,%30,%31,%32,%33,%34,%35,%36,%37,%38,%39},{%40,%41,%42,%43},%44,%45,1,1,%46;"
                 : ACC8(0), ACC8(8), ACC8(16), ACC8(24), ACC8(32) : "r"(a[0]), "r"(a[1]), "r"(a[2]), "r"(a[3]), "l"(desc), "n"(ACC), "n"(TB));
}
template <int TA, int TB> DEV void wgmma_n64_ss(float* d, u64 da, u64 db, int acc) {
    asm volatile("{.reg .pred p; setp.ne.b32 p,%34,0; wgmma.mma_async.sync.aligned.m64n64k16.f32.bf16.bf16 {%0,%1,%2,%3,%4,%5,%6,%7,%8,%9,%10,%11,%12,%13,%14,%15,%16,%17,%18,%19,%20,%21,%22,%23,%24,%25,%26,%27,%28,%29,%30,%31},%32,%33,p,1,1,%35,%36;}"
                 : ACC8(0), ACC8(8), ACC8(16), ACC8(24) : "l"(da), "l"(db), "r"(acc), "n"(TA), "n"(TB));
}
template <int TA, int TB> DEV void wgmma_n128_ss(float* d, u64 da, u64 db, int acc) {
    asm volatile("{.reg .pred p; setp.ne.b32 p,%66,0; wgmma.mma_async.sync.aligned.m64n128k16.f32.bf16.bf16 {%0,%1,%2,%3,%4,%5,%6,%7,%8,%9,%10,%11,%12,%13,%14,%15,%16,%17,%18,%19,%20,%21,%22,%23,%24,%25,%26,%27,%28,%29,%30,%31,%32,%33,%34,%35,%36,%37,%38,%39,%40,%41,%42,%43,%44,%45,%46,%47,%48,%49,%50,%51,%52,%53,%54,%55,%56,%57,%58,%59,%60,%61,%62,%63},%64,%65,p,1,1,%67,%68;}"
                 : ACC8(0), ACC8(8), ACC8(16), ACC8(24), ACC8(32), ACC8(40), ACC8(48), ACC8(56) : "l"(da), "l"(db), "r"(acc), "n"(TA), "n"(TB));
}
template <int TA, int TB> DEV void wgmma_n192_ss(float* d, u64 da, u64 db, int acc) {
    asm volatile("{.reg .pred p; setp.ne.b32 p,%98,0; wgmma.mma_async.sync.aligned.m64n192k16.f32.bf16.bf16 {%0,%1,%2,%3,%4,%5,%6,%7,%8,%9,%10,%11,%12,%13,%14,%15,%16,%17,%18,%19,%20,%21,%22,%23,%24,%25,%26,%27,%28,%29,%30,%31,%32,%33,%34,%35,%36,%37,%38,%39,%40,%41,%42,%43,%44,%45,%46,%47,%48,%49,%50,%51,%52,%53,%54,%55,%56,%57,%58,%59,%60,%61,%62,%63,%64,%65,%66,%67,%68,%69,%70,%71,%72,%73,%74,%75,%76,%77,%78,%79,%80,%81,%82,%83,%84,%85,%86,%87,%88,%89,%90,%91,%92,%93,%94,%95},%96,%97,p,1,1,%99,%100;}"
                 : ACC8(0), ACC8(8), ACC8(16), ACC8(24), ACC8(32), ACC8(40), ACC8(48), ACC8(56), ACC8(64), ACC8(72), ACC8(80), ACC8(88) : "l"(da), "l"(db), "r"(acc), "n"(TA), "n"(TB));
}
template <int ACC> DEV void wgmma_n40_ss(float* d, u64 da, u64 desc) {
    asm volatile("wgmma.mma_async.sync.aligned.m64n40k16.f32.bf16.bf16 {%0,%1,%2,%3,%4,%5,%6,%7,%8,%9,%10,%11,%12,%13,%14,%15,%16,%17,%18,%19},%20,%21,%22,1,1,0,0;"
                 : ACC8(0), ACC8(8), "+f"(d[16]), "+f"(d[17]), "+f"(d[18]), "+f"(d[19]) : "l"(da), "l"(desc), "n"(ACC));
}
DEV void pdl_wait() { asm volatile("griddepcontrol.wait;" ::: "memory"); }
DEV void pdl_launch() { asm volatile("griddepcontrol.launch_dependents;" ::: "memory"); }
DEV uint32_t ldg32(const void* p) { uint32_t v; asm volatile("ld.global.nc.u32 %0,[%1];" : "=r"(v) : "l"(p)); return v; }
DEV void ld_acc(u64& a, u64& b, const void* p) {
    const uint32_t done = (uint32_t)a & (uint32_t)b & 32u;
    asm volatile("{.reg .pred p; setp.eq.u32 p,%3,0;\n"
                 "@p ld.relaxed.gpu.global.v2.u64 {%0,%1},[%2];}" : "+l"(a), "+l"(b) : "l"(p), "r"(done) : "memory");
}
DEV void ld_acc0(u64& a, u64& b, const void* p) {
    asm volatile("ld.relaxed.gpu.global.v2.u64 {%0,%1},[%2];" : "=l"(a), "=l"(b) : "l"(p) : "memory");
}
DEV uint32_t and3(uint32_t a, uint32_t b, uint32_t c) { uint32_t r; asm volatile("lop3.b32 %0,%1,%2,%3,0x80;" : "=r"(r) : "r"(a), "r"(b), "r"(c)); return r; }
DEV uint32_t absmax2(uint32_t a, uint32_t b) { uint32_t r; asm("max.xorsign.abs.bf16x2 %0,%1,%2;" : "=r"(r) : "r"(a), "r"(b)); return r; }
DEV float lds32f(uint32_t a) { float x; asm volatile("ld.shared.f32 %0,[%1];" : "=f"(x) : "r"(a) : "memory"); return x; }
DEV void red_add64(u64* p, uint32_t lo, uint32_t hi) {
    asm volatile("{.reg .b64 v; mov.b64 v,{%1,%2}; red.relaxed.gpu.global.add.u64 [%0],v;}" ::"l"(p), "r"(lo), "r"(hi) : "memory");
}
DEV float bf_round(float x) { return __bfloat162float(__float2bfloat16_rn(x)); }
DEV float bf_lo(uint32_t u) { return __uint_as_float(u << 16); }
DEV float bf_hi(uint32_t u) { return __uint_as_float(u & 0xffff0000u); }

#define GPROF(i, n)
#define PROFT(i)
#define STAMP(i)

DEV void unpack8(float* v, uint4 u) {
    v[0] = bf_lo(u.x); v[1] = bf_hi(u.x); v[2] = bf_lo(u.y); v[3] = bf_hi(u.y);
    v[4] = bf_lo(u.z); v[5] = bf_hi(u.z); v[6] = bf_lo(u.w); v[7] = bf_hi(u.w);
}
DEV int xn_off(int row, int chunk) { return (row >> 5) * 40960 + (chunk >> 3) * 4096 + (row & 31) * 128 + (((chunk ^ row) & 7) << 4); }

DEV void ln_row(float (&v)[3][8], int lane) {
    float s = 0.f;
#pragma unroll
    for (int c = 0; c < 3; c++)
#pragma unroll
        for (int j = 0; j < 8; j++) s += v[c][j];
#pragma unroll
    for (int o = 16; o; o >>= 1) s += __shfl_xor_sync(~0u, s, o);
    float mean = s * (1.f / D_), q = 0.f;
#pragma unroll
    for (int c = 0; c < 3; c++)
        if (c < 2 || lane < 16)
#pragma unroll
            for (int j = 0; j < 8; j++) { float d = v[c][j] - mean; q += d * d; }
#pragma unroll
    for (int o = 16; o; o >>= 1) q += __shfl_xor_sync(~0u, q, o);
    float mb = bf_round(mean);
    float inv = 1.f / bf_round(sqrtf(bf_round(bf_round(q * (1.f / D_)) + 1e-5f)));
#pragma unroll
    for (int c = 0; c < 3; c++)
#pragma unroll
        for (int j = 0; j < 8; j++) v[c][j] = bf_round(v[c][j] - mb) * inv;
}

__host__ __device__ constexpr int col_freq(int c) {
    return c == 320 ? 320 : c < 192 ? (c >> 6) * 128 + (c & 63) : c == 192 ? 192 : c < 256 ? 448 - c : c == 256 ? 64 : 384 - c;
}
DEV float rdft(int n, int k, int sn, int N) {
    float s, c;
    sincospif((float)((n * k) & (N - 1)) * (2.f / N), &s, &c);
    return !sn ? c : k ? s : (n & 1 ? -1.f : 1.f);
}

__global__ void __launch_bounds__(512) prep_kernel(const bf16* __restrict__ x, const bf16* __restrict__ Wq, const bf16* __restrict__ Wk,
                                                   const bf16* __restrict__ Wv, const bf16* __restrict__ Wo) {
    __shared__ float red[32], col[4][640];
    const int tid = threadIdx.x, lane = tid & 31, warp = tid >> 5, b = blockIdx.x, row = b * 16 + warp;
    TLS(0);
    pdl_launch();
    uint4 ux[3], uv[5], uo[8];
#pragma unroll
    for (int c = 0; c < 3; c++) ux[c] = c < 2 || lane < 16 ? *(const uint4*)(x + row * D_ + (c * 32 + lane) * 8) : make_uint4(0, 0, 0, 0);
#pragma unroll
    for (int i = 0; i < 5; i++) uv[i] = *(const uint4*)(Wv + (size_t)((b & 3) * 160 + i * 32 + (tid >> 4)) * 4096 + (b >> 2) * E_ + (tid & 15) * 8);
    if (tid < 320) {
#pragma unroll
        for (int r = 0; r < 8; r++) uo[r] = *(const uint4*)(Wo + (size_t)(b * 32 + tid / 80 * 8 + r) * D_ + tid % 80 * 8);
    }
    if (tid >= 504) prefetch_bulk((const char*)(tid & 4 ? Wk : Wq) + (b * 4 + (tid & 3)) * 10240, 10240);
    if (b < 3) ((uint4*)g_sync)[b * 512 + tid] = make_uint4(0, 0, 0, 0);
    for (int i = b * 512 + tid; i < ACC_LAYER; i += 128 * 512) ((uint4*)g_acc)[i] = make_uint4(0, 0, 0, 0);
    if (tid < 2 * YT_ROWS * D_ / 4 / 128) ((uint4*)g_yt)[b * (2 * YT_ROWS * D_ / 4 / 128) + tid] = make_uint4(0, 0, 0, 0);
    const int gid = tid < 104 ? b * 104 + tid : 1 << 20;
    if (gid < 4096) {
        const int inv = gid >> 11, ks = (gid >> 8) & 7, t = gid & 255, g = (t & 31) >> 2, q = t & 3, tile = t >> 5;
        uint32_t v[4];
#pragma unroll
        for (int j = 0; j < 4; j++) {
            float x[2];
#pragma unroll
            for (int u = 0; u < 2; u++) {
                const int m = inv ? 16 * tile + 2 * g + (j & 1) : 16 * ks + 8 * (j >> 1) + 2 * q + u;
                const int k2 = inv ? 8 * ks + 2 * q + u : 8 * tile + g, sn = inv ? j >> 1 : j & 1;
                x[u] = rdft(m, k2, sn, 128);
                if (sn && k2) x[u] = -x[u];
            }
            v[j] = pack2(x[0], x[1]);
        }
        g_f128[gid] = make_uint4(v[0], v[1], v[2], v[3]);
    } else if (gid < 5120) {
        const int id = gid - 4096, inv = id >> 9, ks = (id >> 7) & 3, t = id & 127, g = (t & 31) >> 2, q = t & 3, tile = t >> 5;
        uint32_t v[4];
#pragma unroll
        for (int j = 0; j < 4; j++) {
            float x[2];
#pragma unroll
            for (int u = 0; u < 2; u++) {
                const int a = inv ? 16 * tile + g + 8 * (j & 1) : 16 * ks + 8 * (j >> 1) + 2 * q + u;
                const int ka = inv ? 8 * ks + 2 * q + u : 8 * tile + g, sn = inv ? j >> 1 : j & 1;
                x[u] = rdft(a, ka, sn, 64);
            }
            v[j] = pack2(x[0], x[1]);
        }
        g_f64[id] = make_uint4(v[0], v[1], v[2], v[3]);
    } else if (gid < 5120 + 8192) {
        const int id = gid - 5120, inv = id >> 12, n = ((id >> 9) & 7) * 8 + ((id >> 3) & 7), k = ((id >> 6) & 7) * 8 + (id & 7);
        float s, c;
        sincospif((float)(((n >> 1) * (k >> 1)) & 31) * (1.f / 16), &s, &c);
        if (inv) s = -s;
        g_g32[id] = __float2bfloat16_rn((n & 1) == (k & 1) ? c : (k & 1) ? s : -s);
    }
    {
        float v[3][8];
#pragma unroll
        for (int c = 0; c < 3; c++) unpack8(v[c], ux[c]);
        ln_row(v, lane);
#pragma unroll
        for (int c = 0; c < 3; c++)
            if (c < 2 || lane < 16)
                *(uint4*)(g_xn + xn_off(row, c * 32 + lane)) =
                    make_uint4(pack2(v[c][0], v[c][1]), pack2(v[c][2], v[c][3]), pack2(v[c][4], v[c][5]), pack2(v[c][6], v[c][7]));
    }
    float sv = 0.f;
#pragma unroll
    for (int i = 0; i < 5; i++) {
        float w[8];
        unpack8(w, uv[i]);
#pragma unroll
        for (int j = 0; j < 8; j++) sv += w[j] * w[j];
    }
    if (tid < 320) {
        float a[8] = {0.f, 0.f, 0.f, 0.f, 0.f, 0.f, 0.f, 0.f};
#pragma unroll
        for (int r = 0; r < 8; r++) {
            float w[8];
            unpack8(w, uo[r]);
#pragma unroll
            for (int j = 0; j < 8; j++) a[j] += w[j] * w[j];
        }
#pragma unroll
        for (int j = 0; j < 8; j++) col[tid / 80][tid % 80 * 8 + j] = a[j];
    }
    __syncthreads();
    float so = (col[0][tid] + col[1][tid]) + (col[2][tid] + col[3][tid]);
    if (tid < 128) so = fmaxf(so, (col[0][512 + tid] + col[1][512 + tid]) + (col[2][512 + tid] + col[3][512 + tid]));
#pragma unroll
    for (int o = 16; o; o >>= 1) { sv += __shfl_xor_sync(~0u, sv, o); so = fmaxf(so, __shfl_xor_sync(~0u, so, o)); }
    if (lane == 0) { red[warp] = sv; red[16 + warp] = so; }
    __syncthreads();
    if (tid == 0) {
        float a = 0.f, c = 0.f;
        for (int i = 0; i < 16; i++) { a += red[i]; c = fmaxf(c, red[16 + i]); }
        g_nrm[b] = a; g_nrm[128 + b] = c;
    }
    TLE(0);
}

DEV void filter_tile(const bf16* __restrict__ wr, const bf16* __restrict__ wi, int ka, int c) {
    const int kn = ka ? 2048 - ka : 32, kc = col_freq(c);
    const unsigned short* pr = (const unsigned short*)wr + kc;
    const unsigned short* pi = (const unsigned short*)wi + kc;
#pragma unroll 1
    for (int i = 0; i < 4; i += 2) {
        unsigned short a[32], b[32];
#pragma unroll
        for (int n = 0; n < 32; n++) {
            const int k = ((n & 1 ? kn : ka) + 64 * (4 * (2 * (i + (n >> 4)) + ((n >> 1) & 1)) + ((n >> 2) & 3))) & 2047;
            a[n] = __ldg(pr + k * NCOL); b[n] = __ldg(pi + k * NCOL);
        }
#pragma unroll
        for (int n = 0; n < 32; n += 4)
            *(uint4*)(g_wt + c * 8192 + (i + (n >> 4)) * 2048 + (ka * 4 + ((n >> 2) & 3)) * 16) =
                make_uint4(a[n] | ((uint32_t)b[n] << 16), a[n + 1] | ((uint32_t)b[n + 1] << 16), a[n + 2] | ((uint32_t)b[n + 2] << 16), a[n + 3] | ((uint32_t)b[n + 3] << 16));
    }
}

namespace wk {
constexpr int STAGE = 49152, NST = 4, OFF_OUT = 3 * STAGE, OFF_RED = 4 * STAGE, OFF_BAR = OFF_RED + 32768, SMEM = OFF_BAR + 128;
constexpr int NPB = 11;
__host__ __device__ constexpr int pb_start(int b) { return b ? 6 * b - 2 : 0; }
#define NOB 7
#define SPLIT_A 2
#define SPLIT_B 9
constexpr int N_P = NPB * H_, I_F = N_P, I_OB = I_F + 32, I_OT = I_OB + NOB * 5, I_SA = I_OT + (30 - 3 * NOB) * 10;
constexpr int I_SB = I_SA + 10 * SPLIT_A, N_ITEMS = I_SB + 10 * SPLIT_B;
DEV void ot_decode(int id, int& b, int& nt, int& k0, int& k1) {
    const int base = id < I_SA ? I_OT : id < I_SB ? I_SA : I_SB, j = (id - base) / 10;
    nt = (id - base) % 10;
    if (id < I_SA) { b = 3 * NOB + j; k0 = 0; k1 = 22; }
    else if (id < I_SB) { b = 30; k0 = 22 * j / SPLIT_A; k1 = 22 * (j + 1) / SPLIT_A; }
    else { b = 31; k0 = 22 * j / SPLIT_B; k1 = 22 * (j + 1) / SPLIT_B; }
}
enum { SY_TICKET = 0, SY_O = 32, SY_P = 128 };
}
struct Ring {
    int st; uint32_t ph;
    DEV uint32_t par() const { return (ph >> st) & 1; }
    DEV void next(int n) { ph ^= 1u << st; st = st + 1 >= n ? 0 : st + 1; }
};
struct Maps { CUtensorMap wq2, wv1, wo2, wo1, x6, x4, o6, o2; const bf16 *wr, *wi; };

template <int NSG> DEV void proj_tile(uint32_t sb, uint32_t bar, Ring& rg, int wg, int id) {
    using namespace wk;
    float acc[NSG * 16];
#pragma unroll
    for (int i = 0; i < NSG * 16; i++) acc[i] = 0.f;
    const int lane = threadIdx.x & 31, ww = (threadIdx.x >> 5) & 3;
    for (int kb = 0; kb < 10; kb++, rg.next(3)) {
        const int st = rg.st;
        if (kb) mbar_wait(bar + 8 * st, rg.par());
        const u64 da = mkdesc(sb + st * STAGE + wg * 8192, 0, 1024) | SW128, db = mkdesc(sb + st * STAGE + 24576, 0, 1024) | SW128;
        wg_fence();
#pragma unroll
        for (int ks = 0; ks < 4; ks++) {
            if (NSG == 4) wgmma_n128_ss<1, 0>(acc, da + ks * 128, db + ks * 2, 1);
            if (NSG == 6) wgmma_n192_ss<1, 0>(acc, da + ks * 128, db + ks * 2, 1);
        }
        wg_commit();
        wg_wait<0>();
        mbar_arrive_elect(bar + 8 * (NST + st));
    }
    const uint32_t out = sb + OFF_OUT + wg * 24576;
    bar_sync(5 + wg, 160);
    const uint32_t la = out + (wg < 2 ? (lane >> 4) * 1024 + ww * 256 + (lane & 15) * 16 : ww * 1024 + ((lane >> 3) & 1) * 512 + (lane >> 4) * 128 + (lane & 7) * 16);
#pragma unroll
    for (int j = 0; j < 2 * NSG; j++) {
        const float* c = acc + 8 * j;
        const uint32_t p0 = pack2(c[0], c[1]), p1 = pack2(c[2], c[3]), p2 = pack2(c[4], c[5]), p3 = pack2(c[6], c[7]);
        if (wg < 2) stsm4t(la + j * 2048, p0, p1, p2, p3);
        else stsm4(la + (j >> 1) * 4096 + (j & 1) * 256, p0, p1, p2, p3);
    }
    if ((threadIdx.x & 127) == 0) sts32(bar + 80 + 4 * wg, id);
    fence_async();
    bar_arrive(1 + wg, 160);
}

DEV uint32_t resid(uint32_t u, float a, float b) { return pack2(bf_lo(u) + bf_round(a), bf_hi(u) + bf_round(b)); }

template <bool SIDE>
DEV void worker(uint32_t sb, const Maps& maps, const bf16* __restrict__ x, bf16* __restrict__ x1, int layer, int fix, int nfix) {
    using namespace wk;
    const uint32_t bar = sb + OFF_BAR, slot = bar + 64;
    const int tid = threadIdx.x, lane = tid & 31, warp = __shfl_sync(~0u, tid >> 5, 0);
    uint32_t* sy = g_sync + layer * SYNC_LAYER;
    if (tid == 0) {
        for (int i = 0; i < NST; i++) { mbar_init(bar + 8 * i, 1); mbar_init(bar + 8 * (NST + i), 12); }
        asm volatile("fence.mbarrier_init.release.cluster;" ::: "memory");
    }
    __syncthreads();
    if (warp > 12) {
        const int wg = warp - 13;
        bar_arrive(5 + wg, 160);
        for (;;) {
            bar_sync(1 + wg, 160);
            const int id = (int)lds32(bar + 80 + 4 * wg);
            if (id < 0) break;
            const int s0 = pb_start(id >> 5), ns = pb_start((id >> 5) + 1) - s0;
            if (lane == 0) {
                for (int j = 0; j < ns; j++)
                    bulk_s2g(g_p + (size_t)(((s0 + j) * H_ + (id & 31)) * 3 + wg) * 4096, sb + OFF_OUT + wg * 24576 + j * 4096, 4096);
                bulk_commit();
                bulk_wait<0>();
                flag_add(sy + SY_P + id);
            }
            __syncwarp();
            bar_arrive(5 + wg, 160);
        }
    } else if (warp == 12) {
        if (lane == 0) {
            Ring rg = {0, 7u};
            auto acquire = [&]() { mbar_wait(bar + 8 * (NST + rg.st), rg.par()); return sb + rg.st * STAGE; };
            if (fix >= 0 && fix < N_P) {
                for (int kb = 0; kb < 3; kb++) {
                    tma3d(sb + kb * STAGE, &maps.wq2, 0, kb * 64, 2 * (fix & 31), bar + 8 * kb);
                    tma3d(sb + kb * STAGE + 16384, &maps.wv1, 0, kb * 64, 2 * (fix & 31), bar + 8 * kb);
                }
                asm volatile("prefetch.tensormap [%0];" ::"l"(&maps.x4) : "memory");
            }
            if (SIDE) flag_wait(g_started + layer, 1); else pdl_wait();
            for (;;) {
                int id = fix;
                if (id < 0) {
                    id = nfix + (int)atomicAdd(sy + SY_TICKET, 1u);
                    if (layer && id >= I_F) id += I_OB - I_F;
                    if (id >= I_SB) id = -1;
                }
                if (id >= 0) { TLI(id, 0, gtime()); TLI(id, 3, blockIdx.x + (SIDE ? 1000 : 0)); }
                uint32_t d = acquire();
                sts32(slot + 4 * rg.st, id);
                if (id < 0) { mbar_arrive(bar + 8 * rg.st); if (SIDE) pdl_launch(); break; }
                if (id < N_P) {
                    const int b = id >> 5, h = id & 31;
                    for (int kb = 0; kb < 10; kb++, rg.next(3)) {
                        if (kb) d = acquire();
                        const uint32_t fb = bar + 8 * rg.st;
                        mbar_expect(fb, b ? 49152 : 40960);
                        tma3d(d + 24576, b ? &maps.x6 : &maps.x4, 0, 2 * kb, pb_start(b), fb);
                        if (fix < 0 || kb >= 3) {
                            tma3d(d, &maps.wq2, 0, kb * 64, 2 * h, fb);
                            tma3d(d + 16384, &maps.wv1, 0, kb * 64, 2 * h, fb);
                        }
                    }
                } else if (id < I_OB) {
                    mbar_arrive(bar + 8 * rg.st);
                    mbar_wait(bar + 8 * (NST + rg.st), rg.par() ^ 1);
                    rg.next(NST);
                } else if (id < I_OT) {
                    const int b = (id - I_OB) / 5, nt = (id - I_OB) % 5;
                    for (int j = 0; j < 6; j++) flag_wait(sy + SY_O + 6 * b + j, 64);
                    for (int kb = 0; kb < 64; kb++, rg.next(NST)) {
                        if (kb) d = acquire();
                        const uint32_t fb = bar + 8 * rg.st;
                        mbar_expect(fb, 40960);
                        tma3d(d, &maps.o6, 0, 2 * kb, 6 * b, fb);
                        tma3d(d + 24576, &maps.wo2, 0, kb * 64, 2 * nt, fb);
                    }
                } else {
                    int b, nt, k0, k1;
                    ot_decode(id, b, nt, k0, k1);
                    for (int kb = k0; kb < k1; kb++, rg.next(NST)) {
                        if (kb > k0) d = acquire();
                        const uint32_t fb = bar + 8 * rg.st;
                        mbar_expect(fb, 49152);
                        tma3d(d + 24576, &maps.wo1, 0, 3 * kb * 64, nt, fb);
                        if (kb == k0) for (int j = 0; j < 2; j++) flag_wait(sy + SY_O + 2 * b + j, 64);
                        for (int u = 0; u < 3; u++) tma3d(d + u * 8192, &maps.o2, 0, 2 * (3 * kb + u), 2 * b, fb);
                    }
                }
                fix = -1;
            }
        }
    } else {
        const int wg = warp >> 2, g = lane >> 2, q = lane & 3;
        Ring rg = {0, 0u};
        bool stores_done = false;
        for (;;) {
            mbar_wait(bar + 8 * rg.st, rg.par());
            const int id = (int)lds32(slot + 4 * rg.st);
            if ((id < 0 || id >= N_P) && !stores_done) {
                bar_sync(5 + wg, 160);
                if ((tid & 127) == 0) sts32(bar + 80 + 4 * wg, ~0u);
                bar_arrive(1 + wg, 160);
                stores_done = true;
                bar_sync(4, 384);
                mbar_arrive_elect(bar + 8 * (NST + 3));
            }
            if (id < 0) break;
            if (tid == 0) TLI(id, 1, gtime());
            if (id < N_P) {
                const int b = id >> 5;
                if (b == 0) proj_tile<4>(sb, bar, rg, wg, id);
                else proj_tile<6>(sb, bar, rg, wg, id);
            } else if (id < I_OB) {
                if (tid < NCOL) filter_tile(maps.wr, maps.wi, id - I_F, tid);
                __syncwarp();
                mbar_arrive_elect(bar + 8 * (NST + rg.st));
                rg.next(NST);
            } else if (id < I_OT) {
                const int b = (id - I_OB) / 5, nt = (id - I_OB) % 5;
                const size_t o = (size_t)(192 * b + 16 * warp + g) * D_ + nt * 128 + 2 * q;
                float acc[64];
#pragma unroll
                for (int i = 0; i < 64; i++) acc[i] = 0.f;
                for (int kb = 0; kb < 64; kb++, rg.next(NST)) {
                    const int st = rg.st;
                    if (kb) mbar_wait(bar + 8 * st, rg.par());
                    const u64 da = mkdesc(sb + st * STAGE + wg * 8192, 128, 1024), db = mkdesc(sb + st * STAGE + 24576, 8192, 1024) | SW128;
                    wg_fence();
#pragma unroll
                    for (int ks = 0; ks < 4; ks++) wgmma_n128_ss<0, 1>(acc, da + ks * 16, db + ks * 128, 1);
                    wg_commit();
                    wg_wait<0>();
                    mbar_arrive_elect(bar + 8 * (NST + st));
                }
                uint32_t xr[32];
#pragma unroll
                for (int t = 0; t < 32; t++) xr[t] = ldg32(x + o + 8 * (t >> 1) + (t & 1) * 8 * D_);
#pragma unroll
                for (int t = 0; t < 32; t++) *(uint32_t*)(x1 + o + 8 * (t >> 1) + (t & 1) * 8 * D_) = resid(xr[t], acc[2 * t], acc[2 * t + 1]);
            } else {
                int b, nt, k0, k1;
                ot_decode(id, b, nt, k0, k1);
                const size_t o = (size_t)(64 * b + 16 * (warp & 3) + g) * D_ + nt * 64 + 2 * q;
                float acc[32];
                uint32_t xr[16];
#pragma unroll
                for (int t = 0; t < 16; t++) xr[t] = wg == 0 && id < I_SA ? ldg32(x + o + 8 * (t >> 1) + (t & 1) * 8 * D_) : 0;
#pragma unroll
                for (int i = 0; i < 32; i++) acc[i] = 0.f;
                for (int kb = k0; kb < k1; kb++, rg.next(NST)) {
                    const int st = rg.st;
                    if (kb > k0) mbar_wait(bar + 8 * st, rg.par());
                    const u64 da = mkdesc(sb + st * STAGE + wg * 8192, 128, 1024), db = mkdesc(sb + st * STAGE + 24576 + wg * 8192, 0, 1024) | SW128;
                    wg_fence();
#pragma unroll
                    for (int ks = 0; ks < 4; ks++) wgmma_n64_ss<0, 1>(acc, da + ks * 16, db + ks * 128, 1);
                    wg_commit();
                    wg_wait<0>();
                    mbar_arrive_elect(bar + 8 * (NST + st));
                }
                const uint32_t ra = sb + OFF_RED + (tid & 127) * 16;
                if (wg) {
#pragma unroll
                    for (int t = 0; t < 8; t++)
                        sts128(ra + (wg - 1) * 16384 + t * 2048, __float_as_uint(acc[4 * t]), __float_as_uint(acc[4 * t + 1]), __float_as_uint(acc[4 * t + 2]), __float_as_uint(acc[4 * t + 3]));
                }
                bar_sync(4, 384);
                if (wg == 0) {
#pragma unroll
                    for (int t = 0; t < 8; t++) {
                        float u[4], v[4];
                        lds128f(u, ra + t * 2048); lds128f(v, ra + 16384 + t * 2048);
#pragma unroll
                        for (int i = 0; i < 4; i++) acc[4 * t + i] += u[i] + v[i];
                    }
                }
                bar_sync(4, 384);
                if (wg == 0) {
                    if (id < I_SA) {
#pragma unroll
                        for (int t = 0; t < 16; t++) *(uint32_t*)(x1 + o + 8 * (t >> 1) + (t & 1) * 8 * D_) = resid(xr[t], acc[2 * t], acc[2 * t + 1]);
                    } else {
                        float* y = g_yt + (layer * YT_ROWS - (S_ - YT_ROWS)) * D_ + o;
#pragma unroll
                        for (int t = 0; t < 16; t++)
                            asm volatile("red.relaxed.gpu.global.add.v2.f32 [%0],{%1,%2};" ::"l"(y + 8 * (t >> 1) + (t & 1) * 8 * D_), "f"(acc[2 * t]), "f"(acc[2 * t + 1]) : "memory");
                    }
                }
            }
            if (tid == 0) TLI(id, 2, gtime());
        }
    }
}

__global__ void __launch_bounds__(512, 1) side_kernel(const __grid_constant__ Maps maps, const bf16* __restrict__ x, bf16* __restrict__ x1, int layer, int nfix) {
    extern __shared__ __align__(1024) unsigned char smem[];
    TLS(3 + 5 * layer);
    worker<true>(s2u(smem), maps, x, x1, layer, -1, nfix);
    __syncwarp();
    if (blockIdx.x == 0) pdl_wait();
    TLE(3 + 5 * layer);
}

constexpr float C5A = 0.30901699437494742f, C5B = -0.80901699437494742f, S5A = 0.95105651629515357f, S5B = 0.58778525229247313f;
template <int SGN> DEV void dft5(const float (&tr)[5], const float (&ti)[5], float (&zr)[5], float (&zi)[5]) {
    const float ar = tr[1] + tr[4], ai = ti[1] + ti[4], br = tr[2] + tr[3], bi = ti[2] + ti[3];
    const float cr = tr[1] - tr[4], ci = ti[1] - ti[4], dr = tr[2] - tr[3], di = ti[2] - ti[3];
    zr[0] = tr[0] + ar + br; zi[0] = ti[0] + ai + bi;
    const float m1r = tr[0] + C5A * ar + C5B * br, m1i = ti[0] + C5A * ai + C5B * bi;
    const float m2r = tr[0] + C5B * ar + C5A * br, m2i = ti[0] + C5B * ai + C5A * bi;
    const float n1r = SGN * (S5A * cr + S5B * dr), n1i = SGN * (S5A * ci + S5B * di);
    const float n2r = SGN * (S5B * cr - S5A * dr), n2i = SGN * (S5B * ci - S5A * di);
    zr[1] = m1r + n1i; zi[1] = m1i - n1r; zr[4] = m1r - n1i; zi[4] = m1i + n1r;
    zr[2] = m2r + n2i; zi[2] = m2i - n2r; zr[3] = m2r - n2i; zi[3] = m2i + n2r;
}
DEV void ln40(float (&v)[40]) {
    float s = 0.f;
#pragma unroll
    for (int i = 0; i < 40; i++) s += v[i];
#pragma unroll
    for (int o = 8; o; o >>= 1) s += __shfl_xor_sync(~0u, s, o);
    const float mean = s * (1.f / D_);
    float q = 0.f;
#pragma unroll
    for (int i = 0; i < 40; i++) { const float d = v[i] - mean; q += d * d; }
#pragma unroll
    for (int o = 8; o; o >>= 1) q += __shfl_xor_sync(~0u, q, o);
    const float mb = bf_round(mean);
    const float inv = 1.f / bf_round(sqrtf(bf_round(bf_round(q * (1.f / D_)) + 1e-5f)));
#pragma unroll
    for (int i = 0; i < 40; i++) v[i] = bf_round(v[i] - mb) * inv;
}
__global__ void __launch_bounds__(256) rowfft_kernel(const bf16* __restrict__ x0, bf16* __restrict__ x, const bf16* __restrict__ Wq,
                                                     const bf16* __restrict__ Wk, const bf16* __restrict__ Wv, int layer) {
    extern __shared__ __align__(1024) unsigned char smem[];
    const uint32_t sb = s2u(smem), sx = sb + 23552, sy = sx + 20480, bar = sy + 40960;
    const int tid = threadIdx.x, lane = tid & 31, q = lane & 3, blk = 127 - blockIdx.x, k2 = tid >> 2;
    if (tid == 0) TLI(800 + blk, 0, gtime());
    float twr[5], twi[5];
#pragma unroll
    for (int r = 1; r < 5; r++) { sincospif((float)(r * k2) * (-1.f / 320), &twi[r], &twr[r]); }
    uint32_t f[8][4];
#pragma unroll
    for (int ks = 0; ks < 8; ks++) { const uint4 u = g_f128[ks * 256 + tid]; f[ks][0] = u.x; f[ks][1] = u.y; f[ks][2] = u.z; f[ks][3] = u.w; }
    const bool split = blk * 16 >= S_ - YT_ROWS;
    if (tid == 0) {
        mbar_init(bar, 1);
        asm volatile("fence.mbarrier_init.release.cluster;" ::: "memory");
        mbar_expect(bar, split ? 61440 : 20480);
        if (split) bulk_g2s(sx, x0 + (size_t)blk * 16 * D_, 20480, bar);
    }
    __syncthreads();
    pdl_wait();
    pdl_launch();
    TLS(4 + 5 * layer);
    if (tid == 0) TLI(800 + blk, 1, gtime());
    if (tid == 0 && blk == 0) g_started[layer] = 0;
    if (tid == 0) {
        if (split) bulk_g2s(sy, g_yt + (layer * YT_ROWS + blk * 16 - (S_ - YT_ROWS)) * D_, 40960, bar);
        else bulk_g2s(sx, x + (size_t)blk * 16 * D_, 20480, bar);
    }
    mbar_wait(bar, 0);
    {
        const int rho = tid >> 4, j = tid & 15;
        float v[40];
#pragma unroll
        for (int i = 0; i < 5; i++) {
            uint32_t u[4];
            lds128(u, sx + tid * 80 + i * 16);
            if (split) {
                float p[8];
                lds128f(p, sy + tid * 160 + i * 32); lds128f(p + 4, sy + tid * 160 + i * 32 + 16);
#pragma unroll
                for (int k = 0; k < 4; k++) u[k] = resid(u[k], p[2 * k], p[2 * k + 1]);
                sts128(sx + tid * 80 + i * 16, u[0], u[1], u[2], u[3]);
            }
            unpack8(v + 8 * i, make_uint4(u[0], u[1], u[2], u[3]));
        }
        if (layer == 0 && tid < 12) prefetch_bulk((const char*)(tid < 4 ? Wk : tid < 8 ? Wq : Wv) + (blk * 4 + (tid & 3)) * 10240, 10240);
        ln40(v);
        const uint32_t a = sb + ((rho >> 1) & 1) * 2304 + j * 144 + (2 * (rho >> 2) + (rho & 1)) * 16;
#pragma unroll
        for (int r = 0; r < 5; r++)
            sts128(a + r * 4608, pack2(v[r], v[5 + r]), pack2(v[10 + r], v[15 + r]), pack2(v[20 + r], v[25 + r]), pack2(v[30 + r], v[35 + r]));
    }
    fence_async();
    __syncthreads();
    if (tid == 0) TLI(800 + blk, 2, gtime());
    if (tid == 0 && split) { bulk_s2g(x + (size_t)blk * 16 * D_, sx, 20480); bulk_commit(); }
    float acc[40];
    const u64 db = mkdesc(sb, 144, 2304);
    wg_fence();
    wgmma_n80_rs<0, 0>(acc, f[0], db);
#pragma unroll
    for (int ks = 1; ks < 8; ks++) wgmma_n80_rs<1, 0>(acc, f[ks], db + ks * 18);
    wg_commit();
    wg_wait<0>();
    unsigned char* zp = g_z + (blk >> 1) * 128 + ((((blk & 1) * 4 + q) ^ ((blk >> 1) & 7)) << 4);
    uint32_t o[5][4];
#pragma unroll
    for (int u = 0; u < 4; u++) {
        float tr[5], ti[5], zr[5], zi[5];
#pragma unroll
        for (int r = 0; r < 5; r++) {
            const float yr = acc[8 * r + 4 * (u >> 1) + (u & 1)], yi = k2 ? acc[8 * r + 4 * (u >> 1) + 2 + (u & 1)] : 0.f;
            tr[r] = r ? yr * twr[r] - yi * twi[r] : yr;
            ti[r] = r ? yr * twi[r] + yi * twr[r] : yi;
        }
        dft5<1>(tr, ti, zr, zi);
#pragma unroll
        for (int j = 0; j < 5; j++) o[j][u] = pack2(zr[j], j < 3 ? zi[j] : -zi[j]);
    }
#pragma unroll
    for (int j = 0; j < 5; j++)
        if (j < 3 || k2) *(uint4*)(zp + (64 * j + k2) * 8192) = make_uint4(o[j][0], o[j][1], o[j][2], o[j][3]);
    if (k2 == 0) {
#pragma unroll
        for (int u = 0; u < 4; u++) {
            float tr[5], ti[5], zr[5], zi[5];
            const float cr[5] = {1.f, -C5B, C5A, -C5A, C5B}, ci[5] = {0.f, -S5B, -S5A, -S5A, -S5B};
#pragma unroll
            for (int r = 0; r < 5; r++) { const float y = acc[8 * r + 4 * (u >> 1) + 2 + (u & 1)]; tr[r] = y * cr[r]; ti[r] = y * ci[r]; }
            dft5<1>(tr, ti, zr, zi);
            o[0][u] = pack2(zr[0], zi[0]); o[1][u] = pack2(zr[1], zi[1]); o[2][u] = pack2(zr[2], 0.f);
        }
        *(uint4*)(zp + 256 * 8192) = make_uint4(o[0][0], o[0][1], o[0][2], o[0][3]);
        *(uint4*)(zp + 192 * 8192) = make_uint4(o[1][0], o[1][1], o[1][2], o[1][3]);
        *(uint4*)(zp + 320 * 8192) = make_uint4(o[2][0], o[2][1], o[2][2], o[2][3]);
    }
    if (tid == 0) bulk_wait<0>();
    TLE(4 + 5 * layer);
    if (tid == 0) TLI(800 + blk, 3, gtime());
}

constexpr int CF_SMEM = 16384 + 3 * 16384 + 64;
__global__ void __launch_bounds__(384) colfft_kernel(int layer) {
    extern __shared__ __align__(1024) unsigned char smem[];
    const uint32_t sb = s2u(smem), bar = sb + 65536;
    const int tid = threadIdx.x, lane = tid & 31, q = lane & 3, wg = __shfl_sync(~0u, tid >> 7, 0), t = tid & 127, ka = t >> 2;
    const int col = blockIdx.x * 3 + wg;
    const uint32_t d0 = sb + 16384 + wg * 16384, d1 = d0 + 8192;
    if (tid == 0) {
        for (int i = 0; i < 4; i++) mbar_init(bar + 8 * i, 1);
        asm volatile("fence.mbarrier_init.release.cluster;" ::: "memory");
    }
    float twr[8], twi[8];
#pragma unroll
    for (int i = 0; i < 8; i++) sincospif((float)((4 * i + q) * (ka ? ka : -32)) * (1.f / 1024), &twi[i], &twr[i]);
    __syncthreads();
    if (tid == 0) { mbar_expect(bar + 24, 16384); bulk_g2s(sb, g_g32, 16384, bar + 24); }
    uint32_t f[4][4], w[16];
#pragma unroll
    for (int ks = 0; ks < 4; ks++) { const uint4 u = g_f64[ks * 128 + t]; f[ks][0] = u.x; f[ks][1] = u.y; f[ks][2] = u.z; f[ks][3] = u.w; }
#pragma unroll
    for (int i = 0; i < 4; i++) { const uint4 u = *(const uint4*)(g_wt + col * 8192 + i * 2048 + t * 16); w[4 * i] = u.x; w[4 * i + 1] = u.y; w[4 * i + 2] = u.z; w[4 * i + 3] = u.w; }
    pdl_wait();
    pdl_launch();
    TLS(5 + 5 * layer);
    if (t == 0) {
        mbar_expect(bar + 8 * wg, 8192);
        bulk_g2s(d0, g_z + col * 8192, 8192, bar + 8 * wg);
    }
    float acc[32];
    uint32_t a[4][4];
    mbar_wait(bar + 8 * wg, 0);
    {
        const u64 db = mkdesc(d0, 0, 1024) | SW128;
        wg_fence();
        wgmma_n64_rs<0, 1>(acc, f[0], db);
#pragma unroll
        for (int ks = 1; ks < 4; ks++) wgmma_n64_rs<1, 1>(acc, f[ks], db + ks * 128);
        wg_commit();
        wg_wait<0>();
    }
#pragma unroll
    for (int ks = 0; ks < 4; ks++) { const uint4 u = g_f64[512 + ks * 128 + t]; f[ks][0] = u.x; f[ks][1] = u.y; f[ks][2] = u.z; f[ks][3] = u.w; }
#pragma unroll
    for (int i = 0; i < 8; i++) {
        const float c0 = acc[4 * i], c1 = acc[4 * i + 1], c2 = acc[4 * i + 2], c3 = acc[4 * i + 3];
        const float pr = c0 + c3, pi = c1 - c2, nr = ka ? c0 - c3 : c2, ni = ka ? c1 + c2 : c3;
        a[i >> 1][2 * (i & 1)] = ka ? pack2(pr * twr[i] + pi * twi[i], pi * twr[i] - pr * twi[i]) : pack2(c0, c1);
        a[i >> 1][2 * (i & 1) + 1] = pack2(nr * twr[i] - ni * twi[i], ni * twr[i] + nr * twi[i]);
    }
    mbar_wait(bar + 24, 0);
    {
        const u64 db = mkdesc(sb, 128, 1024);
        wg_fence();
        wgmma_n64_rs<0, 0>(acc, a[0], db);
#pragma unroll
        for (int ks = 1; ks < 4; ks++) wgmma_n64_rs<1, 0>(acc, a[ks], db + ks * 16);
        wg_commit();
        wg_wait<0>();
    }
    constexpr float NORM = 1.f / (2048.f * 640.f);
#pragma unroll
    for (int i = 0; i < 16; i++) {
        const float zr = acc[2 * i] * NORM, zi = acc[2 * i + 1] * NORM, wr = bf_lo(w[i]), wi = bf_hi(w[i]);
        a[i >> 2][i & 3] = pack2(zr * wr - zi * wi, zr * wi + zi * wr);
    }
    {
        const u64 db = mkdesc(sb + 8192, 128, 1024);
        wg_fence();
        wgmma_n64_rs<0, 0>(acc, a[0], db);
#pragma unroll
        for (int ks = 1; ks < 4; ks++) wgmma_n64_rs<1, 0>(acc, a[ks], db + ks * 16);
        wg_commit();
        wg_wait<0>();
    }
    const uint32_t row = (t >> 5) * 2048 + (lane & 15) * 128;
#pragma unroll
    for (int i = 0; i < 8; i++) {
        const float c0 = acc[4 * i], c1 = acc[4 * i + 1], c2 = acc[4 * i + 2], c3 = acc[4 * i + 3];
        const float pr = c0 * twr[i] - c1 * twi[i], pi = c1 * twr[i] + c0 * twi[i];
        const float nr = c2 * twr[i] + c3 * twi[i], ni = c3 * twr[i] - c2 * twi[i];
        a[i >> 1][2 * (i & 1)] = ka ? pack2(pr + nr, pi + ni) : pack2(c0, c1);
        a[i >> 1][2 * (i & 1) + 1] = ka ? pack2(ni - pi, pr - nr) : pack2(nr, ni);
    }
#pragma unroll
    for (int i = 0; i < 4; i++) stsm4(d1 + row + (((2 * i + (lane >> 4)) ^ (lane & 7)) << 4), a[i][0], a[i][1], a[i][2], a[i][3]);
    fence_async();
    bar_sync(1 + wg, 128);
    {
        const u64 db = mkdesc(d1, 0, 1024) | SW128;
        wg_fence();
        wgmma_n64_rs<0, 1>(acc, f[0], db);
#pragma unroll
        for (int ks = 1; ks < 4; ks++) wgmma_n64_rs<1, 1>(acc, f[ks], db + ks * 128);
        wg_commit();
        wg_wait<0>();
    }
#pragma unroll
    for (int i = 0; i < 4; i++)
        stsm4(d0 + row + (((2 * i + (lane >> 4)) ^ (lane & 7)) << 4), pack2(acc[8 * i], acc[8 * i + 1]), pack2(acc[8 * i + 2], acc[8 * i + 3]),
              pack2(acc[8 * i + 4], acc[8 * i + 5]), pack2(acc[8 * i + 6], acc[8 * i + 7]));
    fence_async();
    bar_sync(1 + wg, 128);
    if (t == 0) {
        bulk_s2g(g_z + col * 8192, d0, 8192);
        asm volatile("cp.async.bulk.commit_group;" ::: "memory");
        asm volatile("cp.async.bulk.wait_group 0;" ::: "memory");
    }
    TLE(5 + 5 * layer);
}

__global__ void __launch_bounds__(256) rowifft_kernel(const bf16* __restrict__ x, bf16* __restrict__ out, int last) {
    extern __shared__ __align__(1024) unsigned char smem[];
    const uint32_t sb = s2u(smem), sx = sb + 20480, sy = sx + 20480, bar = sy + 16 * 1296;
    const int tid = threadIdx.x, lane = tid & 31, q = lane & 3, blk = blockIdx.x, k2 = tid >> 2, warp = tid >> 5;
    float twr[5], twi[5];
#pragma unroll
    for (int r = 1; r < 5; r++) { sincospif((float)(r * k2) * (1.f / 320), &twi[r], &twr[r]); twr[r] *= 2.f; twi[r] *= 2.f; }
    uint32_t f[8][4];
#pragma unroll
    for (int ks = 0; ks < 8; ks++) { const uint4 u = g_f128[2048 + ks * 256 + tid]; f[ks][0] = u.x; f[ks][1] = u.y; f[ks][2] = u.z; f[ks][3] = u.w; }
    if (tid == 0) {
        mbar_init(bar, 1);
        asm volatile("fence.mbarrier_init.release.cluster;" ::: "memory");
        mbar_expect(bar, 20480);
        bulk_g2s(sx, x + (size_t)blk * 16 * D_, 20480, bar);
    }
    pdl_wait();
    pdl_launch();
    TLS(6 + 5 * last);
    const unsigned char* zp = g_z + (blk >> 1) * 128 + ((((blk & 1) * 4 + q) ^ ((blk >> 1) & 7)) << 4);
    uint4 z[6];
#pragma unroll
    for (int j = 0; j < 5; j++) z[j] = *(const uint4*)(zp + (64 * j + k2) * 8192);
    z[5] = k2 ? make_uint4(0, 0, 0, 0) : *(const uint4*)(zp + 320 * 8192);
    float acc[40];
#pragma unroll
    for (int u = 0; u < 4; u++) {
        float yr[6], yi[6], tr[5], ti[5], zr[5], zi[5];
#pragma unroll
        for (int j = 0; j < 6; j++) { const uint32_t v = u == 0 ? z[j].x : u == 1 ? z[j].y : u == 2 ? z[j].z : z[j].w; yr[j] = bf_lo(v); yi[j] = bf_hi(v); }
#pragma unroll
        for (int j = 0; j < 5; j++) { tr[j] = yr[j]; ti[j] = j < 3 ? yi[j] : -yi[j]; }
        dft5<-1>(tr, ti, zr, zi);
        const float c1[5] = {1.f, C5A, C5B, C5B, C5A}, s1[5] = {0.f, S5A, S5B, -S5B, -S5A};
        const float c2[5] = {1.f, C5B, C5A, C5A, C5B}, s2[5] = {0.f, S5B, -S5A, S5A, -S5B};
        const float c3[5] = {1.f, -C5B, C5A, -C5A, C5B}, s3[5] = {0.f, S5B, S5A, S5A, S5B};
        const float c4[5] = {1.f, -C5A, C5B, -C5B, C5A}, s4[5] = {0.f, S5A, -S5B, -S5B, S5A};
#pragma unroll
        for (int r = 0; r < 5; r++) {
            float er = r ? zr[r] * twr[r] - zi[r] * twi[r] : 2.f * zr[0], ei = r ? zr[r] * twi[r] + zi[r] * twr[r] : 2.f * zi[0];
            if (k2 == 0) {
                er = yr[0] + 2.f * (yr[1] * c1[r] - yi[1] * s1[r] + yr[2] * c2[r] - yi[2] * s2[r]);
                ei = (r & 1 ? -yr[5] : yr[5]) + 2.f * (yr[4] * c3[r] - yi[4] * s3[r] + yr[3] * c4[r] - yi[3] * s4[r]);
            }
            acc[8 * r + 4 * (u >> 1) + (u & 1)] = er;
            acc[8 * r + 4 * (u >> 1) + 2 + (u & 1)] = ei;
        }
    }
#pragma unroll
    for (int r = 0; r < 5; r++)
        stsm4(sb + (2 * warp + ((lane >> 3) & 1)) * 1280 + (2 * r + (lane >> 4)) * 128 + (lane & 7) * 16, pack2(acc[8 * r], acc[8 * r + 1]),
              pack2(acc[8 * r + 2], acc[8 * r + 3]), pack2(acc[8 * r + 4], acc[8 * r + 5]), pack2(acc[8 * r + 6], acc[8 * r + 7]));
    fence_async();
    __syncthreads();
    const u64 db = mkdesc(sb, 1280, 128);
    wg_fence();
    wgmma_n80_rs<0, 1>(acc, f[0], db);
#pragma unroll
    for (int ks = 1; ks < 8; ks++) wgmma_n80_rs<1, 1>(acc, f[ks], db + ks * 160);
    wg_commit();
    wg_wait<0>();
#pragma unroll
    for (int u = 0; u < 4; u++) {
        float e[10];
#pragma unroll
        for (int r = 0; r < 5; r++) { e[r] = acc[8 * r + 4 * (u >> 1) + (u & 1)]; e[5 + r] = acc[8 * r + 4 * (u >> 1) + 2 + (u & 1)]; }
#pragma unroll
        for (int i = 0; i < 5; i++) sts32(sy + (4 * q + u) * 1296 + k2 * 20 + i * 4, pack2(e[2 * i], e[2 * i + 1]));
    }
    __syncthreads();
    const int rho = tid >> 4, j = tid & 15;
    float v[40];
    mbar_wait(bar, 0);
#pragma unroll
    for (int i = 0; i < 5; i++) {
        uint32_t y[4], u[4];
        lds128(y, sy + rho * 1296 + j * 80 + i * 16);
        lds128(u, sx + tid * 80 + i * 16);
#pragma unroll
        for (int k = 0; k < 4; k++) u[k] = pack2(bf_lo(u[k]) + bf_lo(y[k]), bf_hi(u[k]) + bf_hi(y[k]));
        sts128(sx + tid * 80 + i * 16, u[0], u[1], u[2], u[3]);
        unpack8(v + 8 * i, make_uint4(u[0], u[1], u[2], u[3]));
    }
    if (!last) {
        ln40(v);
#pragma unroll
        for (int i = 0; i < 5; i++) {
            const int c = j * 5 + i;
            sts128(sb + (c >> 3) * 2048 + rho * 128 + (((c ^ rho) & 7) << 4), pack2(v[8 * i], v[8 * i + 1]), pack2(v[8 * i + 2], v[8 * i + 3]),
                   pack2(v[8 * i + 4], v[8 * i + 5]), pack2(v[8 * i + 6], v[8 * i + 7]));
        }
    }
    fence_async();
    __syncthreads();
    if (lane == 0) {
        if (warp == 7) bulk_s2g(out + (size_t)blk * 16 * D_, sx, 20480);
        else if (!last && warp < 5) {
            unsigned char* p = g_xn + (blk >> 1) * 40960 + warp * 8192 + (blk & 1) * 2048;
            bulk_s2g(p, sb + warp * 4096, 2048);
            bulk_s2g(p + 4096, sb + warp * 4096 + 2048, 2048);
        }
        bulk_commit();
        bulk_wait<0>();
    }
    TLE(6 + 5 * last);
}

namespace rec {
#define NS 3
constexpr int OFF_X = 0;
constexpr int OFF_WO = 81920;
constexpr int OFF_WS = OFF_WO + 65536;
constexpr int OFF_XCH = OFF_WS + NS * 4096;
constexpr int OFF_MEMB = OFF_XCH + 12288;
constexpr int OFF_VX = OFF_MEMB + 10240;
constexpr int OFF_VM = OFF_VX + 16384;
constexpr int OFF_Q = OFF_VM + 4096;
constexpr int OFF_K = OFF_Q + 10240;
constexpr int OFF_OST = OFF_WO + 49152;
constexpr int OFF_PX = OFF_OST + 8192;
constexpr int OFF_PT = OFF_PX + 2560;
constexpr int OFF_PS = OFF_K + 10240;
constexpr int OFF_OB = OFF_PS + 1280;
constexpr int OFF_MX = OFF_OB + 2048;
constexpr int OFF_BAR = OFF_MX + 64;
constexpr int OFF_PROF = OFF_BAR + 256;
constexpr int SMEM = OFF_PROF + 4096 > wk::SMEM ? OFF_PROF + 4096 : wk::SMEM;
enum { B_XT = 0, B_VM = 2, B_VX = 4, B_XD = 6, B_X1 = 8, B_GO = 10, B_PXF = 12, B_PXE = 13, B_FIN = 14, B_ST = 15, B_MEM = 16   };
enum { NB_W2 = 0, NB_XCH = 1, NB_QK = 2, NB_WIN = 3, NB_ATT = 4, NB_X = 5, NB_PRO = 6, NB_W1 = 7, NB_PAIR = 8  , NB_KF = 12, NB_LD = 13, NB_KX = 15 };
#define STAG 3
#define NOX 0
#define NW1 4
#define NW1B 0
template <int N> struct IC { static constexpr int value = N; };
template <int N, int I = 0, class F> DEV void static_for(F&& f) { if constexpr (I < N) { f(IC<I>{}); static_for<N, I + 1>(f); } }
constexpr float SM_SCALE = 0.08838834764831845f * 1.4426950408889634f;
}

__global__ void __launch_bounds__(512, 1) rec_kernel(const __grid_constant__ Maps maps, const bf16* __restrict__ x, bf16* __restrict__ x1, const bf16* __restrict__ mem0, const bf16* __restrict__ Wq, const bf16* __restrict__ Wk,
                                                     const bf16* __restrict__ Wv, const bf16* __restrict__ Wo, int layer, int delay, int delay2) {
    using namespace rec;
    extern __shared__ __align__(1024) unsigned char smem[];
    const uint32_t sb = s2u(smem);
    pdl_launch();
    if (blockIdx.x < 3 * H_) {
    const int tid = threadIdx.x, lane = tid & 31, warp = __shfl_sync(~0u, tid >> 5, 0);
    const int g = lane >> 2, q = lane & 3;
    const int h = blockIdx.x / 3;
    const uint32_t bar = sb + OFF_BAR;
    STAMP(2 * layer);
    TLS(2 + 5 * layer);
    if (tid == 0) TLI(690 + blockIdx.x, 0, gtime());
    if (tid == 0) {
        for (int i = 0; i < 2; i++) {
            mbar_init(bar + 8 * (B_XT + i), 1); mbar_init(bar + 8 * (B_VX + i), 1);
            mbar_init(bar + 8 * (B_XD + i), 8); mbar_init(bar + 8 * (B_X1 + i), 1); mbar_init(bar + 8 * (B_VM + i), 1);
        }
        mbar_init(bar + 8 * B_PXF, 1); mbar_init(bar + 8 * B_PXE, 2); mbar_init(bar + 8 * B_ST, 2); mbar_init(bar + 8 * B_GO, 1);
        for (int i = 0; i < 5; i++) mbar_init(bar + 8 * (B_MEM + i), 4);
        mbar_init(bar + 8 * B_FIN, 48);
        asm volatile("fence.mbarrier_init.release.cluster;" ::: "memory");
    }
    asm volatile("barrier.cluster.arrive.aligned; barrier.cluster.wait.aligned;" ::: "memory");
    const bool never = delay < 0;

    if (warp < 8) {
        asm volatile("setmaxnreg.inc.sync.aligned.u32 184;");
        const uint32_t rank = cta_rank();
        const int wg = warp >> 2;
        uint32_t fa[20 - NS][4], fb[20][4];
        const uint32_t l16 = opaque(sb + lane * 16);
        uint32_t dst = opaque(rank < 2 ? sb + OFF_Q + wg * 10240 + (warp & 3) * 256 + (lane & 15) * 16 + (lane >> 4) * 1024
                                       : sb + OFF_VM + warp * 256 + lane * 4);
        int dstep = rank < 2 ? 5120 : 2048;
        uint32_t& sfd = dst;
        const uint32_t ws = OFF_WS + warp * 512, xo = OFF_XCH + warp * 512, xi = OFF_XCH + (warp ^ 4) * 512, mb = OFF_MEMB + wg * 512;
        {
            const int t = tid & 127;
            const bf16* src = (rank == 2 ? Wv + wg * 64 : (wg ? Wk : Wq) + rank * 64) + h * E_ + (size_t)(t >> 3) * 4096 + (t & 7) * 8;
            constexpr int SA = OFF_X + 40960, SB = OFF_VX;
            const uint32_t sdst = sb + (wg ? SB : SA) + (t >> 3) * 128 + (((t & 7) ^ ((t >> 3) & 7)) << 4);
            const uint32_t ra = sb + wg * 4096 + ((lane >> 4) * 8 + (lane & 7)) * 128 + (((2 * (warp & 3) + ((lane >> 3) & 1)) ^ (lane & 7)) << 4);
            auto issue = [&](int rd) {
#pragma unroll 1
                for (int i = 0; i < 8; i++, src += 16 * 4096) cp16(sdst + (rd & 1) * 16384 + i * 2048, src);
                cp_commit();
            };
            issue(0); issue(1);
#pragma unroll
            for (int rd = 0; rd < 5; rd++) {
                if (rd < 4) cp_wait<1>(); else cp_wait<0>();
                bar_sync(NB_XCH, 256);
#pragma unroll
                for (int i = 0; i < 4; i++) {
                    const int n = rd * 4 + i, o = (rd & 1) * 16384 + (i >> 1) * 8192 + (i & 1) * 2048;
                    if (n < NS) {
                        uint32_t f[4];
                        ldsm4t(f, ra + SA + o);
                        sts128(l16 + ws + n * 4096, f[0], f[1], f[2], f[3]);
                    } else ldsm4t(fa[n - NS], ra + SA + o);
                    ldsm4t(fb[n], ra + SB + o);
                }
                if (rd < 3) { bar_sync(NB_XCH, 256); issue(rd + 2); }
            }
            fence_async();
            bar_sync(NB_PRO, 288);
        }
        uint32_t xlo = (uint32_t)mkdesc(sb + OFF_X + wg * 64, 0, 0);
        const uint32_t xtog = xlo ^ (uint32_t)mkdesc(sb + OFF_X + 40960 + wg * 64, 0, 0);
        uint32_t p8 = 0;
        bar_sync(NB_LD, 288);
        for (int s = -1;; s++) {
            uint32_t t[NS ? NS : 1][4];
            {
                float acc[16];
                auto xproj = [&](auto I0, auto I1) {
                    const u64 desc = (u64)xlo | (64ull << 32) | SW128;
                    wg_fence();
#pragma unroll
                    for (int i = I0.value; i < I1.value; i++) {
                        const u64 db = desc + (i >> 1) * 256 + (i & 1) * 2;
                        if (i == 0) wgmma_n32_rs<0>(acc, fb[i], db);
                        else if (!NOX) wgmma_n32_rs<1>(acc, fb[i], db);
                    }
                    wg_commit();
                    wg_wait<0>();
                };
                if (s >= 0 && rank < 2) { fence_async(); bar_arrive(NB_W1, 512); bar_sync(NB_X, 384); }
                bar_sync_if<NB_W1, 480>(s >= 0 && rank == 2);
                if (s == NSEG - 1) break;
                xproj(IC<0>{}, IC<NW1>{});
                if (warp == 4 && s >= 0) PROFT(15);
                bar_sync_if<NB_W2, 384>(s >= 0 && rank < 2);
                if (NW1B > 0) xproj(IC<NW1>{}, IC<NW1 + NW1B>{});
                bar_sync_if<NB_WIN, 384>(s >= 0 && rank == 2);
                xproj(IC<NW1 + NW1B>{}, IC<20>{});
                if (warp == 4 && s >= 0) PROFT(12);
                sts128f_if(l16 + xo, acc + 8, !wg); sts128f_if(l16 + xo + 4096, acc + 12, !wg);
                sts128f_if(l16 + xo, acc, wg); sts128f_if(l16 + xo + 4096, acc + 4, wg);
                bar_sync(NB_PAIR + (warp & 3), 64);
                float u[8];
#pragma unroll
                for (int i = 0; i < 8; i++) acc[i] = wg ? acc[8 + i] : acc[i];
                lds128f(u, l16 + xi); lds128f(u + 4, l16 + xi + 4096);
#pragma unroll
                for (int i = 0; i < NS; i++) lds128(t[i], l16 + ws + i * 4096);
#pragma unroll
                for (int i = 0; i < 8; i++) u[i] += acc[i];
                if (rank < 2) {
                    stsm4t(dst + (wg ? 3072 : 11264), pack2(u[0], u[1]), pack2(u[2], u[3]), pack2(u[4], u[5]), pack2(u[6], u[7]));
                } else {
                    stsm4(l16 + (l16 & 256) + OFF_VX + 4096 + (warp & 3) * 1024 + wg * 256 + p8 * 1024,
                          pack2(u[0], u[1]), pack2(u[4], u[5]), pack2(u[2], u[3]), pack2(u[6], u[7]));
                    bar_arrive(NB_KF, 288);
                }
                bar_arrive(NB_KX, 384);
                xlo ^= xtog;
                if (warp == 4 && s >= 0) PROFT(3);
            }
            float da[4] = {0.f, 0.f, 0.f, 0.f}, db[4] = {0.f, 0.f, 0.f, 0.f}, ea[4] = {0.f, 0.f, 0.f, 0.f}, eb[4] = {0.f, 0.f, 0.f, 0.f};
            uint32_t b[10][4];
            const uint32_t mp = p8 >> 3;
            while (!mbar_try(bar + 8 * B_MEM, mp)) {}
            lds128(b[0], l16 + mb); lds128(b[1], l16 + mb + 1024);
            bool rdy = mbar_try(bar + 8 * (B_MEM + 1), mp, 1);
            const uint32_t xb0 = mapa(bar + 8 * B_VM + p8, 0), xb1 = mapa(bar + 8 * B_VM + p8, 1);
            SFENCE();
            float is;
#pragma unroll
            for (int j = 0; j < 10; j++) {
#pragma unroll
                for (int x = 0; x < 2; x++) {
                    const int i = 2 * j + x;
                    const uint32_t* f = i < NS ? t[i] : fa[i - NS];
                    mma16(NS > 2 && x && j ? ea : da, f[0], f[1], f[2], f[3], b[j][2 * x], b[j][2 * x + 1]);
                    mma16(NS > 2 && x && j ? eb : db, fb[i][0], fb[i][1], fb[i][2], fb[i][3], b[j][2 * x], b[j][2 * x + 1]);
                    SFENCE();
                    if (x == 0 && j < 8 && !(j & 1)) {
                        if (__builtin_expect(!rdy, 0)) while (!mbar_try(bar + 8 * (B_MEM + 1 + (j >> 1)), mp)) {}
                        lds128(b[j + 2], l16 + mb + (j + 2) * 1024);
                    }
                    if (x == 1 && j < 8 && !(j & 1)) lds128(b[j + 3], l16 + mb + (j + 3) * 1024);
                    if (x == 0 && j < 6 && (j & 1)) rdy = mbar_try(bar + 8 * (B_MEM + 2 + (j >> 1)), mp, 1);
                    if (x == 0 && j == 8) is = lds32f(sb + OFF_MX + 16);
                }
                if (j == 0 && warp == 4) PROFT(16);
            }
            if (warp == 4) PROFT(20);
            if (NS > 2) {
#pragma unroll
                for (int i = 0; i < 4; i++) { da[i] += ea[i]; db[i] += eb[i]; }
            }
            sts128f_if(l16 + xo + 8192, db, !wg); sts128f_if(l16 + xo + 8192, da, wg);
            bar_sync(NB_PAIR + (warp & 3), 64);
            float u[4];
            lds128f(u, l16 + xi + 8192);
#pragma unroll
            for (int i = 0; i < 4; i++) da[i] = (wg ? db[i] : da[i]) * is;
            const uint32_t p0 = pack2(fmaf(u[0], is, da[0]), fmaf(u[1], is, da[1])), p1 = pack2(fmaf(u[2], is, da[2]), fmaf(u[3], is, da[3]));
            stsm2t_if(dst, p0, p1, rank < 2);
            bar_arrive_if<NB_QK, 384>(rank < 2);
            if (rank == 2) {
                st_async1(mapa(dst, 0), p0, xb0); st_async1(mapa(dst, 1), p0, xb1);
                st_async1(mapa(dst + 128, 0), p1, xb0); st_async1(mapa(dst + 128, 1), p1, xb1);
                sts32(dst, p0); sts32(dst + 128, p1);
                bar_arrive(NB_QK, 384);
            }
            if (warp == 4) PROFT(17);
            dst += dstep; dstep = -dstep; p8 ^= 8;
        }
    } else if (warp < 12) {
        asm volatile("setmaxnreg.dec.sync.aligned.u32 96;");
        const uint32_t rank = cta_rank();
        const int w = warp - 8;
        uint32_t amax = 0;
        {
            const int t = tid & 127, nr = rank == 2 ? 4 : 3;
            for (int r = 0; r < nr; r++) {
                const bf16* src = Wo + (size_t)(h * E_) * D_ + (r < 3 ? 192 * r + 64 * rank : 576);
#pragma unroll 1
                for (int i = 0; i < 8; i++) {
                    const int e = i * 16 + (t >> 3);
                    cp16(sb + OFF_WO + r * 16384 + e * 128 + (((t & 7) ^ (e & 6)) << 4), src + e * D_ + (t & 7) * 8);
                }
            }
            cp_commit();
            uint32_t m0[5][4];
#pragma unroll
            for (int it = 0; it < 5; it++)
#pragma unroll
                for (int j = 0; j < 4; j++) m0[it][j] = ldg32(mem0 + g * D_ + (it * 4 + w) * 32 + 2 * q + 8 * j);
#pragma unroll
            for (int it = 0; it < 5; it++) {
                sts128(sb + OFF_MEMB + (it * 4 + w) * 512 + lane * 16, m0[it][0], m0[it][1], m0[it][2], m0[it][3]);
                amax = absmax2(amax, absmax2(absmax2(m0[it][0], m0[it][1]), absmax2(m0[it][2], m0[it][3])));
            }
            if (tid == 256) { sts32(sb + OFF_MX + 16, 0x3f800000u); sts128(sb + OFF_MX + 48, 0x3f803f80u, 0x3f803f80u, 0x3f803f80u, 0x3f803f80u); }
            __syncwarp();
            if (lane < 5) mbar_arrive(bar + 8 * (B_MEM + lane));
            __syncwarp();
            cp_wait<0>();
            bar_sync(NB_ATT, 128);
            for (int r = 0; r < nr; r++) {
                uint32_t u[8][4];
                const uint32_t p = sb + OFF_WO + r * 16384 + 2 * q * 128 + (((2 * w + (g & 1)) ^ (2 * q)) << 4) + (g >> 1) * 4;
#pragma unroll
                for (int ks = 0; ks < 8; ks++)
#pragma unroll
                    for (int j = 0; j < 4; j++) u[ks][j] = lds32(p + (16 * ks + (j & 1) * 8 + (j >> 1)) * 128);
                bar_sync(NB_ATT, 128);
#pragma unroll
                for (int ks = 0; ks < 8; ks++)
                    sts128(sb + OFF_WO + (r * 4 + w) * 4096 + ks * 512 + lane * 16, prmt(u[ks][0], u[ks][2], 0x5410), prmt(u[ks][0], u[ks][2], 0x7632),
                           prmt(u[ks][1], u[ks][3], 0x5410), prmt(u[ks][1], u[ks][3], 0x7632));
            }
        }
        if (w == 0) TLI(690 + blockIdx.x, 3, gtime());
        pdl_wait();
        float cw;
        {
            const float4 a = ((const float4*)g_nrm)[lane], c = ((const float4*)g_nrm)[32 + lane];
            float sm = sqrt_approx((a.x + a.y) + (a.z + a.w)) * sqrt_approx((c.x + c.y) + (c.z + c.w)), mxv = sm;
#pragma unroll 1
            for (int o = 16; o; o >>= 1) { sm += __shfl_xor_sync(~0u, sm, o); mxv = fmaxf(mxv, __shfl_xor_sync(~0u, mxv, o)); }
            cw = 26.5f * fmaxf(sm, 8.f * mxv);
        }
        if (w == 0) {
            mbar_expect_elect(bar + 8 * B_X1, 1280);
            mbar_expect_elect(bar + 8 * B_VM, rank < 2 ? 2048 : 0);
            mbar_expect_elect(bar + 8 * B_VX, rank < 2 ? 8192 : 4096);
        }
        {
            const int kind = rank;
            const uint32_t l16 = opaque(sb + lane * 16), lw = opaque(sb + lane * 16 + w * 512);
            const uint32_t pa = opaque(sb + OFF_PS + rank * 512 + lane * 4 + w * 128);
            uint32_t lq = opaque(sb + OFF_Q + (lane & 7) * 16 + ((lane >> 3) & 1) * 256 + (lane >> 4) * 128);
            const uint32_t lv = opaque(sb + OFF_VX + w * 2048 + (lane & 7) * 16 + ((lane >> 3) & 1) * 512 + (lane >> 4) * 128);
            const uint32_t lo = opaque(sb + OFF_WO + w * 4096 + lane * 16);
            uint32_t& sfd = lq;
            const char* rp = (const char*)(g_acc + layer * ACC_LAYER) + (4 * rank + w) * 4096 + opaque((q >> 1) * 1024 + ((q & 1) * 8 + g) * 8);
            const char* lp = (const char*)(g_acc + layer * ACC_LAYER) + opaque(w * 8192 + (lane >> 3) * 1024 + (lane & 7) * 16);
            const uint32_t arm = bar + 8 * (w == 0 ? B_X1 + 1 : w == 1 ? B_VX + 1 : w == 2 ? B_XT : B_VM + 1);
            const uint32_t armb = w == 0 ? 1280 : (w == 1 ? 4096 : w == 2 ? 40960 : 0) + (rank == 2 ? 0 : w == 3 ? 2048 : 4096);
            float isig = 1.f;
            for (int s = 0; s < NSEG - 1; s++) {
                const uint32_t pb = s & 1, ph = (s >> 1) & 1, x1 = bar + 8 * (B_X1 + pb);
                uint32_t kf[8];
                bar_sync(NB_KX, 384);
                ldsm4(kf, lw + OFF_K + 1024 + w * 512 + pb * 5120); ldsm4(kf + 4, lw + OFF_K + 1536 + w * 512 + pb * 5120);
                sts32(sb + OFF_MX + w * 4, __reduce_max_sync(~0u, max(amax & 0x7fff0000u, (amax << 16) & 0x7fff0000u)));
                const uint32_t va = lv + pb * 8192, vma = lw + OFF_VM + pb * 2048;
                uint32_t wf[8][4], vf[2][2][4], vm[4], one[4];
                mbar_spin(bar + 8 * (B_VX + pb), ph);
#pragma unroll
                for (int t = 0; t < 2; t++)
#pragma unroll
                    for (int j = 0; j < 2; j++) ldsm4(vf[t][j], va + t * 1024 + j * 256);
                lds128(one, sb + OFF_MX + 48);
                auto scores = [&](auto MM) {
                    constexpr int mm = MM.value;
                    uint32_t qf[8], mf[8];
                    const uint32_t qa = lq + pb * 5120, ka = l16 + OFF_K + pb * 5120;
                    const uint32_t pa0 = mapa(pa, rank ^ 1), pa1 = mapa(pa, 2), pa2 = mapa(pa, rank);
                    const uint32_t xb0 = mapa(x1, rank ^ 1), xb1 = mapa(x1, 2), xb2 = mapa(x1, rank);
                    const uint32_t pm = 640 - rank * 384;
                    SFENCE();
                    if (w == 0) PROFT(2);
                    bar_sync(NB_QK, 384);
                    ldsm4(qf, qa); ldsm4(qf + 4, qa + 512);
                    if (mm) { ldsm4(mf, ka); ldsm4(mf + 4, ka + 512); }
                    SFENCE();
                    float c[4][4];
#pragma unroll
                    for (int i = 0; i < 4; i++) c[i][0] = c[i][1] = c[i][2] = c[i][3] = 0.f;
#pragma unroll
                    for (int i = 0; i < (mm ? 8 : 4); i++) {
                        const int hf = mm ? i >> 2 : i >> 1;
                        const uint32_t* f = (mm && (i & 2) ? mf : kf) + 4 * hf + 2 * (i & 1);
                        mma16(c[i & 3], qf[4 * hf], qf[4 * hf + 1], qf[4 * hf + 2], qf[4 * hf + 3], f[0], f[1]);
                    }
                    SFENCE();
                    bar_arrive(NB_W1, 512);
                    const uint32_t y = mm ? pack2(c[0][0] + c[1][2], c[0][1] + c[1][3])
                                          : pack2((c[0][0] + c[1][2]) + (c[2][0] + c[3][2]), (c[0][1] + c[1][3]) + (c[2][1] + c[3][3]));
                    st_async1(pa0, y, xb0); st_async1(pa1, y, xb1);
                    if (mm) {
                        const uint32_t z = pack2(c[2][0] + c[3][2], c[2][1] + c[3][3]);
                        st_async1(pa0 + pm, z, xb0); st_async1(pa1 + pm, z, xb1); st_async1(pa2 + pm, z, xb2);
                    }
                    st_async1(pa2, y, xb2);
                    if (w == 0) PROFT(5);
                };
                if (kind == 2) bar_sync(NB_QK, 384);
                else if (w == 3) scores(IC<1>{});
                else scores(IC<0>{});
                float m4[4];
                lds128f(m4, sb + OFF_MX);
                bar_arrive_if<NB_W1, 480>(kind == 2);
                mbar_spin(x1, ph);
                if (w == 0) PROFT(6);
                float sc[10];
                {
                    uint32_t u[4], v[4], m[2];
                    ldsm4(u, l16 + OFF_PS); ldsm4(v, l16 + OFF_PS + 512); ldsm2(m, l16 + OFF_PS + 1024);
                    SFENCE();
                    m4[0] = fmaxf(fmaxf(m4[0], m4[1]), fmaxf(m4[2], m4[3])) * isig;
                    SFENCE();
#pragma unroll
                    for (int i = 0; i < 4; i++) { sc[2 * i] = bf_lo(u[i]) + bf_lo(v[i]); sc[2 * i + 1] = bf_hi(u[i]) + bf_hi(v[i]); }
                    sc[8] = bf_lo(m[0]) + bf_lo(m[1]); sc[9] = bf_hi(m[0]) + bf_hi(m[1]);
                }
                float mx = fmaxf(fmaxf(fmaxf(fmaxf(sc[0], sc[1]), fmaxf(sc[2], sc[3])), fmaxf(fmaxf(sc[4], sc[5]), fmaxf(sc[6], sc[7]))), fmaxf(sc[8], sc[9]));
                auto fetch = [&](int i) { lds128(wf[i], lo + i * 512); };
                {
                    float m1 = __shfl_xor_sync(~0u, mx, 1), m2 = __shfl_xor_sync(~0u, mx, 2), m3 = __shfl_xor_sync(~0u, mx, 3);
                    mbar_spin(bar + 8 * (B_VM + pb), ph);
                    ldsm4(vm, vma);
                    mx = fmaxf(fmaxf(mx, m1), fmaxf(m2, m3)) * SM_SCALE;
                }
#pragma unroll
                for (int i = 0; i < 10; i++) sc[i] = fmaf(sc[i], SM_SCALE, -mx);
                float o0[4] = {0.f, 0.f, 0.f, 0.f}, o1[4] = {0.f, 0.f, 0.f, 0.f}, rs[4] = {0.f, 0.f, 0.f, 0.f};
                sc[8] = ex2(sc[8]); fetch(0); fetch(1); sc[9] = ex2(sc[9]);
                SFENCE();
                fetch(2); sc[0] = ex2(sc[0]); fetch(3); fetch(4); sc[1] = ex2(sc[1]); fetch(5); fetch(6); sc[2] = ex2(sc[2]);
                SFENCE();
                {
                    const uint32_t p = pack2(sc[8], sc[9]);
                    sc[3] = ex2(sc[3]); fetch(7);
                    mma8(o0, vm[0], vm[1], p);
                    mma8(o1, vm[2], vm[3], p);
                    sc[4] = ex2(sc[4]);
                    mma8(rs, one[0], one[1], p);
                    sc[5] = ex2(sc[5]);
                }
                SFENCE();
                {
                    const uint32_t p0 = pack2(sc[0], sc[1]), p1 = pack2(sc[2], sc[3]);
                    sc[6] = ex2(sc[6]);
                    mma16(o0, vf[0][0][0], vf[0][0][1], vf[0][0][2], vf[0][0][3], p0, p1);
                    SFENCE();
                    sc[7] = ex2(sc[7]);
                    mma16(o1, vf[1][0][0], vf[1][0][1], vf[1][0][2], vf[1][0][3], p0, p1);
                    SFENCE();
                    mma16(rs, one[0], one[1], one[2], one[3], p0, p1);
                    SFENCE();
                }
                {
                    const uint32_t p0 = pack2(sc[4], sc[5]), p1 = pack2(sc[6], sc[7]);
                    mma16(o0, vf[0][1][0], vf[0][1][1], vf[0][1][2], vf[0][1][3], p0, p1);
                    mma16(o1, vf[1][1][0], vf[1][1][1], vf[1][1][2], vf[1][1][3], p0, p1);
                    SFENCE();
                    mma16(rs, one[0], one[1], one[2], one[3], p0, p1);
                }
                const uint32_t e = max((__float_as_uint(cw * fmaxf(m4[0], 1.f)) >> 23) & 255u, 31u);
                SFENCE();
                stsm4t(lw + OFF_OB, pack2(o0[0], o0[1]), pack2(o0[2], o0[3]), pack2(o1[0], o1[1]), pack2(o1[2], o1[3]));
                if (w == 0) PROFT(13);
                bar_sync(NB_ATT, 128);
                uint32_t ob[16];
#pragma unroll
                for (int j = 0; j < 4; j++) ldsm4(ob + 4 * j, l16 + OFF_OB + j * 512);
                SFENCE();
                const float sig = __uint_as_float((278u - e) << 23);
                isig = __uint_as_float((e - 30u) << 23);
                const float sg0 = rcp(rs[0]) * sig, sg1 = rcp(rs[1]) * sig;
                SFENCE();
                auto tile = [&](uint32_t next, const char* p, auto LAST) {
                    float c[4][4];
#pragma unroll
                    for (int i = 0; i < 4; i++) c[i][0] = c[i][1] = c[i][2] = c[i][3] = 0.f;
#pragma unroll
                    for (int ks = 0; ks < 8; ks++) {
                        mma16(c[ks & 3], wf[ks][0], wf[ks][1], wf[ks][2], wf[ks][3], ob[2 * ks], ob[2 * ks + 1]);
                        if ((ks & 3) == 0) SFENCE();
                        if ((ks & 3) == 3 && !LAST.value) {
                            SFENCE();
#pragma unroll
                            for (int i = ks; i >= ks - 3; i--) { lds128(wf[i], next + i * 512); if (i == ks - 2) SFENCE(); }
                            if (ks == 3) SFENCE();
                        }
                    }
                    SFENCE();
                    if (LAST.value) { bar_arrive_if<NB_WIN, 256>(kind < 2); bar_arrive_if<NB_WIN, 384>(kind == 2); }
                    uint32_t v[4];
#pragma unroll
                    for (int i = 0; i < 4; i++)
                        v[i] = (__float_as_uint(fmaf((c[0][i] + c[1][i]) + (c[2][i] + c[3][i]), i & 1 ? sg1 : sg0, 12582912.f)) << 6) + (i < 2);
                    red_add64((u64*)p, v[0], v[2]);
                    red_add64((u64*)(p + 2048), v[1], v[3]);
                };
                tile(lo + 16384, rp, IC<0>{});
                if (w == 0) PROFT(7);
                tile(lo + 32768, rp + 49152, IC<0>{});
                if (kind == 2) tile(lo + 49152, rp + 98304, IC<0>{});
                tile(0, rp + (kind == 2 ? 28 * 4096 : 98304), IC<1>{});
                if (w == 0) PROFT(8);
                sts32(sb + OFF_MX + 16, __float_as_uint(isig));
                mbar_expect_elect(arm ^ (8 * pb), armb - (w == 2 && s == NSEG - 2 ? 40960 : 0));
                u64 y[20];
                uint32_t b[20];
                bool done[5] = {false, false, false, false, false};
                float z = isig;
                mbar_spin(bar + 8 * B_GO, pb);
                if (w == 0) PROFT(9);
                do {
#pragma unroll
                    for (int i = 0; i < 10; i++) {
                        if (STAG && (i == 2 || i == 4 || i == 7)) {
#pragma unroll
                            for (int k = 0; k < STAG; k++) asm volatile("ex2.approx.ftz.f32 %0,%0;" : "+f"(z));
                            asm volatile("{.reg .pred p; setp.ne.u32 p,%1,0; @p mov.b32 %0,%2;}" : "+r"(sfd) : "r"((uint32_t)never), "f"(z));
                            SFENCE();
                        }
                        ld_acc0(y[2 * i], y[2 * i + 1], lp + (i >> 1) * 32768 + (i & 1) * 4096);
                        if (STAG && (i == 1 || i == 3 || i == 6)) SFENCE();
                    }
                    uint32_t ok = 32u, late = 32u;
                    static_for<5>([&](auto IT) {
                        constexpr int it = IT.value;
                        if (it == 2) late = and3((uint32_t)y[8], (uint32_t)y[10], (uint32_t)y[12]);
                        else if (it == 3) late &= and3((uint32_t)y[14], (uint32_t)y[16], (uint32_t)y[18]);
                        else ok = and3(ok, (uint32_t)y[4 * it], it == 4 ? late : (uint32_t)y[4 * it + 2]);
                        if (it < 4) SFENCE();
                        if (it == 2 || it == 3) ok = and3(ok, (uint32_t)y[4 * it], (uint32_t)y[4 * it + 2]);
                        ok = and3(ok, (uint32_t)y[4 * it + 1], (uint32_t)y[4 * it + 3]);
                        const bool all = __all_sync(~0u, ok);
#pragma unroll
                        for (int j = 0; j < 4; j++) {
                            const u64 v = y[4 * it + j];
                            b[4 * it + j] = pack2((float)(int)(uint32_t)v, (float)(int)(uint32_t)(v >> 32));
                        }
                        sts128(lw + OFF_MEMB + it * 2048, b[4 * it], b[4 * it + 1], b[4 * it + 2], b[4 * it + 3]);
                        mbar_arrive_elect_if(bar + 8 * (B_MEM + it), all && !done[it]);
                        done[it] = all;
                        SFENCE();
                        if (it == 0 && w == 0) PROFT(10);
                    });
                } while (!done[4]);
                if (w == 0) PROFT(11);
                amax = b[0];
#pragma unroll
                for (int i = 1; i < 19; i += 2) amax = absmax2(amax, absmax2(b[i], b[i + 1]));
                amax = absmax2(amax, b[19]);
                const int adv = (s & 7) == 7 ? 163840 - 896 : 128;
                rp += adv; lp += adv;
            }
        }
        asm volatile("prefetch.tensormap [%0];" ::"l"(w & 1 ? &maps.wo1 : &maps.o2) : "memory");
        bar_sync(NB_KX, 384);
        bar_sync(NB_QK, 384);
        if (rank < 2) { bar_arrive(NB_W1, 512); bar_arrive(NB_WIN, 256); } else bar_arrive(NB_W1, 480);
    } else {
        asm volatile("setmaxnreg.dec.sync.aligned.u32 %0;" ::"n"(48));
        const uint32_t rank = cta_rank();
        const int w = warp - 12;
        pdl_wait();
        if (blockIdx.x == 2 && w == 3) asm volatile("st.release.gpu.global.u32 [%0],1;" ::"l"(g_started + layer) : "memory");
        uint32_t* sy = g_sync + layer * SYNC_LAYER;
        if (w == 1) TLI(690 + blockIdx.x, 1, gtime());
        if (w == 1) {
            mbar_expect_elect(bar + 8 * B_XT, 40960);
            bulk_g2s_elect(sb + OFF_X, g_xn, 40960, bar + 8 * B_XT);
            bar_sync(NB_PRO, 288);
            TLI(690 + blockIdx.x, 2, gtime());
            if (rank == 2) mbar_spin(bar + 8 * B_ST, 0);
            else mbar_arrive_remote_elect(mapa(bar + 8 * B_ST, 2));
            mbar_spin(bar + 8 * B_XT, 0);
            bar_arrive(NB_LD, 288);
            mbar_expect_elect(bar + 8 * (B_XT + 1), rank < 2 ? 45056 : 40960);
        }
        if (rank == 2) {
            if (w == 0) {
                for (int s = -1; s < NSEG - 1; s++) {
                    const uint32_t pb = s & 1, va = sb + OFF_VX + (pb ^ 1) * 8192 + 4096, vb = bar + 8 * (B_VX + (pb ^ 1));
                    bar_sync(NB_KF, 288);
                    fence_async();
                    bulk_s2s_elect(mapa(va, 0), va, 4096, mapa(vb, 0));
                    bulk_s2s_elect(mapa(va, 1), va, 4096, mapa(vb, 1));
                    if (s >= 0) mbar_spin(bar + 8 * (B_XD + pb), (s >> 1) & 1);
                    bar_sync(NB_W1, 480);
                }
            } else if (w == 1) {
                const unsigned char *pn = g_p + h * 12288, *px = g_xn + 40960;
                const uint32_t* pf = sy + wk::SY_P + h;
                for (int s = -1, nb = -1; s < NSEG - 1; s++, pn += H_ * 12288, px += 40960) {
                    const uint32_t pb = s & 1, xt = bar + 8 * (B_XT + pb), qa = sb + OFF_Q + (pb ^ 1) * 5120 + 1024;
                    if (s >= 0) mbar_spin(bar + 8 * (B_X1 + pb), (s >> 1) & 1);
                    if (s + 2 < NSEG) bulk_g2s_all3_elect(sb + OFF_X + pb * 40960, px, 40960, xt);
                    if (s == nb) {
                        while (__any_sync(~0u, ld_acquire(pf) < 3)) {}
                        pf += H_;
                        nb += s < 0 ? 4 : 6;
                    }
                    bulk_g2s_all3_elect(sb + OFF_VX + (pb ^ 1) * 8192, pn + 8192, 4096, bar + 8 * (B_VX + (pb ^ 1)));
                    bulk_g2s_elect(mapa(qa, 0), pn, 4096, mapa(xt, 0));
                    bulk_g2s_elect(mapa(qa, 1), pn + 4096, 4096, mapa(xt, 1));
                    mbar_spin(xt, ((s + 2) >> 1) & 1);
                    bar_sync(NB_W1, 480);
                }
                mbar_spin(bar + 8 * (B_VX + 1), 1);
            } else if (w == 2) {
                uint32_t* hp = sy + 1024;
                const char* pf = lane < 5 ? (const char*)(g_acc + layer * ACC_LAYER) + (5 * h + lane) * 1024 : (const char*)hp;
                const int pfa = lane < 5 ? 163840 : 1024;
                const uint32_t go = mapa(bar + 8 * B_GO, min(lane, 2));
                if (lane < 6) for (int i = 0; i < 8; i++) prefetch_l2(pf + i * 128);
                __syncwarp();
                for (int s = 0; s < NSEG - 1; s++, hp += 32) {
                    bar_sync(NB_W1, 480);
                    mbar_spin(bar + 8 * (B_X1 + (s & 1)), (s >> 1) & 1);
                    uint32_t t = gtime32(), t0 = clk(), c, tm;
                    asm volatile("{.reg .pred p; elect.sync _|p, 0xffffffff; @p red.relaxed.gpu.global.max.u32 [%0+4],%1; @p red.relaxed.gpu.global.add.u32 [%0],1;}"
                                 ::"l"(hp), "r"(t) : "memory");
                    if (h == 0) TLI(940 + s, 0, t);
                    if (lane < 6 && s < NSEG - 8) prefetch_l2(pf + ((s >> 3) + 1) * pfa + (s & 7) * 128);
                    __syncwarp();
                    while (clk() - t0 < (uint32_t)delay2) {}
                    do asm volatile("ld.relaxed.gpu.global.v2.u32 {%0,%1},[%2];" : "=r"(c), "=r"(tm) : "l"(hp) : "memory"); while (__any_sync(~0u, c != H_));
                    const uint32_t wait = min(tm - t, 10000u) * 7 / 4 + delay;
                    while (clk() - t0 < wait) {}
                    if (lane < 3) mbar_arrive_remote(go);
                    __syncwarp();
                }
                bar_sync(NB_W1, 480);
            }
        } else {
            if (w < 2) sts32(sb + OFF_PT + w * 768 + 640 + lane * 4, 0u);
            const uint32_t px = opaque(sb + OFF_PX + (w & 1) * 1280 + lane * 8);
            const uint32_t pt = opaque(sb + OFF_PT + (w & 1) * 768 + lane * 4);
            uint32_t os = opaque(sb + OFF_OST + (lane >> 4) * 1024 + w * 256 + (lane & 15) * 16);
            uint32_t& sfd = os;
            const int lim = opaque(8 * w + g + 8 - 2 * q);
            unsigned char* op = g_o + h * 8192 + rank * 2048;
            uint32_t* oc = sy + wk::SY_O;
            auto report = [&]() {
                bulk_wait<0>();
                __syncwarp();
                asm volatile("{.reg .pred p; elect.sync _|p, 0xffffffff; @p red.relaxed.gpu.global.add.u32 [%0],1;}" ::"l"(oc) : "memory");
                oc++;
            };
            auto store_o = [&](int n) {
                bulk_s2g_elect(op, sb + OFF_OST + (n & 1) * 4096, 2048);
                bulk_s2g_elect(op + 4096, sb + OFF_OST + (n & 1) * 4096 + 2048, 2048);
                bulk_commit();
                op += H_ * 8192;
            };
            for (int s = 0; s < NSEG; s++) {
                const uint32_t pb = s & 1, ph = (s >> 1) & 1;
                if ((w >> 1) != rank) { if (s >= 1) mbar_spin(bar + 8 * B_PXE, pb ^ 1); }
                else if (w & 1) mbar_spin(bar + 8 * (B_XT + (pb ^ 1)), ((s + 1) >> 1) & 1);
                else mbar_expect_elect(bar + 8 * B_PXF, rank ? 2560 : 1536);
                const u64 dq = mkdesc(sb + OFF_Q + pb * 5120 + 1024, 128, 512), dk = mkdesc(sb + OFF_K + pb * 5120, 128, 1024);
                SFENCE();
                bar_sync(NB_W1, 512);
                float c[20];
                wg_fence();
                wgmma_n40_ss<0>(c, dq, dk);
#pragma unroll
                for (int ks = 1; ks < 4; ks++) wgmma_n40_ss<1>(c, dq + ks * 16, dk + ks * 16);
                wg_commit();
                bar_arrive(NB_X, 384);
                wg_wait<0>();
                if ((w >> 1) != rank) {
                    const uint32_t pa = mapa(px, rank ^ 1), pf = mapa(bar + 8 * B_PXF, rank ^ 1);
#pragma unroll
                    for (int nt = 0; nt < 5; nt++)
                        if (nt < 3 || rank == 0) st_async2(pa + nt * 256, __float_as_uint(c[4 * nt]), __float_as_uint(c[4 * nt + 1]), pf);
                    if ((w & 1) && s) store_o(s - 1);
                    mbar_spin(bar + 8 * (w & 1 ? B_VX : B_VM) + 8 * pb, ph);
                } else {
                    mbar_spin(bar + 8 * B_PXF, pb);
                    float u[10];
#pragma unroll
                    for (int nt = 0; nt < 5; nt++) lds64f(u[2 * nt], u[2 * nt + 1], px + nt * 256);
#pragma unroll
                    for (int i = 0; i < 10; i++) u[i] = 8 * (i >> 1) + (i & 1) <= lim ? u[i] + c[4 * (i >> 1) + (i & 1)] : -INFINITY;
                    float mx = fmaxf(fmaxf(fmaxf(fmaxf(u[0], u[1]), fmaxf(u[2], u[3])), fmaxf(fmaxf(u[4], u[5]), fmaxf(u[6], u[7]))), fmaxf(u[8], u[9]));
                    const float m1 = __shfl_xor_sync(~0u, mx, 1), m2 = __shfl_xor_sync(~0u, mx, 2), m3 = __shfl_xor_sync(~0u, mx, 3);
                    mx = fmaxf(fmaxf(mx, m1), fmaxf(m2, m3)) * SM_SCALE;
#pragma unroll
                    for (int i = 0; i < 10; i++) u[i] = ex2(fmaf(u[i], SM_SCALE, -mx));
                    float sum = (((u[0] + u[1]) + (u[2] + u[3])) + ((u[4] + u[5]) + (u[6] + u[7]))) + (u[8] + u[9]);
                    const float s1 = __shfl_xor_sync(~0u, sum, 1), s2 = __shfl_xor_sync(~0u, sum, 2), s3 = __shfl_xor_sync(~0u, sum, 3);
                    sum = rcp((sum + s1) + (s2 + s3));
#pragma unroll
                    for (int nt = 0; nt < 5; nt++) sts32(pt + (nt ? nt - 1 : 4) * 128, pack2(u[2 * nt] * sum, u[2 * nt + 1] * sum));
                }
                float acc[2][8];
                const u64 dv = mkdesc(sb + OFF_VX + pb * 8192, 128, 512), dp = mkdesc(sb + OFF_PT, 128, 768);
                const u64 dm = mkdesc(sb + OFF_VM + pb * 2048, 0, 128);
                fence_async();
                bar_sync(NB_WIN, 256);
                wg_fence();
#pragma unroll
                for (int m = 0; m < 2; m++) {
                    wgmma_n16_ss<0>(acc[m], dv + m * 256, dp);
                    wgmma_n16_ss<1>(acc[m], dv + m * 256 + 16, dp + 16);
                    wgmma_n16_ss<1>(acc[m], dm + m * 64, dp + 32);
                }
                wg_commit();
                bar_arrive_if<NB_W2, 384>(s < NSEG - 1);
                wg_wait<0>();
#pragma unroll
                for (int m = 0; m < 2; m++)
                    stsm4t(os + pb * 4096 + m * 2048, pack2(acc[m][0], acc[m][1]), pack2(acc[m][2], acc[m][3]), pack2(acc[m][4], acc[m][5]), pack2(acc[m][6], acc[m][7]));
                fence_async();
                mbar_arrive_remote_elect(mapa(bar + 8 * (B_XD + pb), 2));
                if ((w >> 1) == rank) mbar_arrive_remote_elect(mapa(bar + 8 * B_PXE, rank ^ 1));
                else if ((w & 1) && s) report();
            }
            bar_sync(NB_W2, 128);
            if (w == 3 - 2 * rank) {
                store_o(NSEG - 1);
                report();
            }
        }
    }
    __syncwarp();
    if (lane < 3) mbar_arrive_remote(mapa(bar + 8 * B_FIN, lane));
    mbar_wait(bar + 8 * B_FIN, 0);
    TLE(2 + 5 * layer);
    fence_async();
    if (warp < 8) asm volatile("setmaxnreg.dec.sync.aligned.u32 128;"); else asm volatile("setmaxnreg.inc.sync.aligned.u32 128;");
    }
    const int b = blockIdx.x;
    worker<false>(sb, maps, x, x1, layer, b >= 3 * H_ ? b - 3 * H_ : b < 10 * SPLIT_B ? wk::I_SB + b : -1, gridDim.x - 3 * H_);
}

int g_delay = 2501050, g_layers = 2;

void make_map(CUtensorMap* m, CUtensorMapDataType dt, const void* p, const cuuint64_t* dim, const cuuint64_t* str, const cuuint32_t* box, CUtensorMapSwizzle sw) {
    typedef CUresult (*Fn)(CUtensorMap*, CUtensorMapDataType, cuuint32_t, void*, const cuuint64_t*, const cuuint64_t*, const cuuint32_t*,
                           const cuuint32_t*, CUtensorMapInterleave, CUtensorMapSwizzle, CUtensorMapL2promotion, CUtensorMapFloatOOBfill);
    static Fn fn = nullptr;
    if (!fn) {
        cudaDriverEntryPointQueryResult qr;
        cudaGetDriverEntryPoint("cuTensorMapEncodeTiled", (void**)&fn, cudaEnableDefault, &qr);
    }
    const cuuint32_t es[3] = {1, 1, 1};
    fn(m, dt, 3, (void*)p, dim, str, box, es, CU_TENSOR_MAP_INTERLEAVE_NONE, sw, CU_TENSOR_MAP_L2_PROMOTION_L2_128B, CU_TENSOR_MAP_FLOAT_OOB_FILL_NONE);
}
void map_weight(CUtensorMap* m, const bf16* p, int rows, int cols, int ng, int br = 64) {
    const cuuint64_t dim[3] = {64, (cuuint64_t)rows, (cuuint64_t)cols / 64}, str[2] = {(cuuint64_t)cols * 2, 128};
    const cuuint32_t box[3] = {64, (cuuint32_t)br, (cuuint32_t)ng};
    make_map(m, CU_TENSOR_MAP_DATA_TYPE_BFLOAT16, p, dim, str, box, CU_TENSOR_MAP_SWIZZLE_128B);
}
void map_pieces(CUtensorMap* m, const void* p, int np, int ns) {
    const cuuint64_t dim[3] = {256, (cuuint64_t)np * 2, NSEG}, str[2] = {2048, (cuuint64_t)np * 4096};
    const cuuint32_t box[3] = {256, 2, (cuuint32_t)ns};
    make_map(m, CU_TENSOR_MAP_DATA_TYPE_UINT64, p, dim, str, box, CU_TENSOR_MAP_SWIZZLE_NONE);
}

template <class... P, class... A> void launch(void (*k)(P...), int grid, int block, int smem, int cluster, bool pdl, A... args) {
    cudaLaunchConfig_t c = {};
    c.gridDim = dim3(grid); c.blockDim = dim3(block); c.dynamicSmemBytes = smem; c.stream = cudaStreamPerThread;
    cudaLaunchAttribute at[2];
    int n = 0;
    if (cluster > 1) { at[n].id = cudaLaunchAttributeClusterDimension; at[n].val.clusterDim.x = cluster; at[n].val.clusterDim.y = 1; at[n].val.clusterDim.z = 1; n++; }
    if (pdl) { at[n].id = cudaLaunchAttributeProgrammaticStreamSerialization; at[n].val.programmaticStreamSerializationAllowed = 1; n++; }
    c.attrs = at; c.numAttrs = n;
    cudaLaunchKernelEx(&c, k, args...);
}

int max_clusters() {
    cudaLaunchConfig_t c = {};
    c.gridDim = dim3(3 * H_); c.blockDim = dim3(512); c.dynamicSmemBytes = rec::SMEM;
    cudaLaunchAttribute at[1];
    at[0].id = cudaLaunchAttributeClusterDimension; at[0].val.clusterDim.x = 3; at[0].val.clusterDim.y = 1; at[0].val.clusterDim.z = 1;
    c.attrs = at; c.numAttrs = 1;
    int n = 0;
    cudaOccupancyMaxActiveClusters(&n, rec_kernel, &c);
    return n;
}

}

extern "C" void kernel_launch(void* const* d_in, const int* in_sizes, int n_in, void* d_out, int out_size) {
    const bf16* x = (const bf16*)d_in[0];
    const bf16* mem0 = (const bf16*)d_in[1];
    const bf16* Wq = (const bf16*)d_in[2];
    const bf16* Wk = (const bf16*)d_in[3];
    const bf16* Wv = (const bf16*)d_in[4];
    const bf16* Wo = (const bf16*)d_in[5];
    const bf16* wr = (const bf16*)d_in[8];
    const bf16* wi = (const bf16*)d_in[9];
    cudaFuncSetAttribute(rec_kernel, cudaFuncAttributeMaxDynamicSharedMemorySize, rec::SMEM);
    cudaFuncSetAttribute(side_kernel, cudaFuncAttributeMaxDynamicSharedMemorySize, wk::SMEM);
    cudaFuncSetAttribute(colfft_kernel, cudaFuncAttributeMaxDynamicSharedMemorySize, CF_SMEM);
    Maps maps;
    void *pxn, *po;
    cudaGetSymbolAddress(&pxn, g_xn);
    cudaGetSymbolAddress(&po, g_o);
    map_weight(&maps.wq2, Wq, D_, 4096, 2); map_weight(&maps.wv1, Wv, D_, 4096, 1);
    map_weight(&maps.wo2, Wo, 4096, D_, 2); map_weight(&maps.wo1, Wo, 4096, D_, 1, 192);
    map_pieces(&maps.x6, pxn, 10, 6); map_pieces(&maps.x4, pxn, 10, 4);
    map_pieces(&maps.o6, po, 64, 6); map_pieces(&maps.o2, po, 64, 2);
    bf16 *x1, *x2;
    cudaGetSymbolAddress((void**)&x1, g_x1);
    cudaGetSymbolAddress((void**)&x2, g_x2);
    constexpr int ONE_PER_SM = 120 * 1024;
    cudaFuncSetAttribute(rowfft_kernel, cudaFuncAttributeMaxDynamicSharedMemorySize, ONE_PER_SM);
    cudaFuncSetAttribute(rowifft_kernel, cudaFuncAttributeMaxDynamicSharedMemorySize, ONE_PER_SM);
    static int ncl = 0, nsm = 0;
    if (!ncl) { ncl = max_clusters(); cudaDeviceGetAttribute(&nsm, cudaDevAttrMultiProcessorCount, 0); }
    maps.wr = wr; maps.wi = wi;
    launch(prep_kernel, 128, 512, 0, 1, false, x, Wq, Wk, Wv, Wo);
    for (int layer = 0; layer < g_layers; layer++) {
        const bf16* xin = layer ? x2 : x;
        launch(rec_kernel, 3 * ncl, 512, rec::SMEM, 3, true, maps, xin, x1, mem0, Wq, Wk, Wv, Wo, layer, g_delay % 10000, g_delay / 10000);
        launch(side_kernel, max(nsm - 3 * ncl, 1), 512, wk::SMEM, 1, true, maps, xin, x1, layer, 3 * (ncl - H_));
        launch(rowfft_kernel, 128, 256, ONE_PER_SM, 1, true, xin, x1, Wq, Wk, Wv, layer);
        launch(colfft_kernel, 107, 384, CF_SMEM, 1, true, layer);
        launch(rowifft_kernel, 128, 256, ONE_PER_SM, 1, true, (const bf16*)x1, layer ? (bf16*)d_out : x2, layer);
    }
}
```

```cpp
#include <cuda_runtime.h>
#include <cuda_bf16.h>
#include <cuda.h>
#include <stdint.h>

#define DEV __device__ __forceinline__
typedef unsigned long long u64;
typedef __nv_bfloat16 bf16;

namespace {

constexpr int S_ = 2048, D_ = 640, H_ = 32, E_ = 128, NSEG = 64;

__device__ __align__(1024) unsigned char g_xn[S_ * D_ * 2];
__device__ __align__(1024) unsigned char g_o[S_ * H_ * E_ * 2];
constexpr int ACC_LAYER = 32 * 5120;
__device__ __align__(4096) u64 g_acc[2 * ACC_LAYER];
__device__ __align__(16) float g_nrm[256];
__device__ __align__(1024) unsigned char g_p[NSEG * H_ * 3 * 4096];
constexpr int SYNC_LAYER = 1024 + 64 * 32;
__device__ __align__(128) uint32_t g_sync[2 * SYNC_LAYER];
__device__ uint32_t g_started[2];
__device__ __align__(1024) bf16 g_x1[S_ * D_];
__device__ __align__(1024) bf16 g_x2[S_ * D_];
constexpr int YT_ROWS = 128;
__device__ __align__(1024) float g_yt[2 * YT_ROWS * D_];
constexpr int NCOL = 321;
__device__ __align__(1024) unsigned char g_z[NCOL * 8192];
__device__ __align__(1024) unsigned char g_wt[NCOL * 8192];
__device__ __align__(1024) uint4 g_f128[2 * 8 * 256];
__device__ __align__(1024) uint4 g_f64[2 * 4 * 128];
__device__ __align__(1024) bf16 g_g32[2 * 4096];
#define TLI(id, k, v)
#define TLS(i)
#define TLE(i)

DEV uint32_t s2u(const void* p) { return (uint32_t)__cvta_generic_to_shared(p); }
DEV uint32_t clk() { uint32_t c; asm volatile("mov.u32 %0,%%clock;" : "=r"(c)::"memory"); return c; }
DEV uint32_t gtime32() { uint32_t t; asm volatile("mov.u32 %0,%%globaltimer_lo;" : "=r"(t)::"memory"); return t; }
DEV uint32_t cta_rank() { uint32_t r; asm volatile("mov.u32 %0,%%cluster_ctarank;" : "=r"(r)); return __shfl_sync(~0u, r, 0); }
DEV uint32_t mapa(uint32_t a, uint32_t r) { uint32_t o; asm("mapa.shared::cluster.u32 %0,%1,%2;" : "=r"(o) : "r"(a), "r"(r)); return o; }
DEV void mbar_init(uint32_t b, uint32_t n) { asm volatile("mbarrier.init.shared::cta.b64 [%0],%1;" ::"r"(b), "r"(n) : "memory"); }
DEV bool mbar_try(uint32_t b, uint32_t par, int) {
    uint32_t ok;
    asm volatile("{.reg .pred p; mbarrier.test_wait.parity.shared::cta.b64 p,[%1],%2; selp.u32 %0,1,0,p;}" : "=r"(ok) : "r"(b), "r"(par) : "memory");
    return ok;
}
DEV bool mbar_try(uint32_t b, uint32_t par) {
    uint32_t ok;
    asm volatile("{.reg .pred p; mbarrier.try_wait.parity.shared::cta.b64 p,[%1],%2; selp.u32 %0,1,0,p;}" : "=r"(ok) : "r"(b), "r"(par) : "memory");
    return ok;
}
constexpr uint32_t SPIN_LIMIT = 1u << 18;
DEV void die() { __trap(); }
DEV void mbar_wait(uint32_t b, uint32_t par) {
    uint32_t n = 0;
    while (!mbar_try(b, par)) if (++n > SPIN_LIMIT) die();
}
DEV void mbar_spin(uint32_t b, uint32_t par) { while (!mbar_try(b, par)) {} }
DEV uint32_t opaque(uint32_t x) { return __shfl_xor_sync(~0u, x, 0); }
#define SFENCE() asm volatile("{.reg .pred p; setp.ne.u32 p,%1,0; @p mov.u32 %0,%%clock;}" : "+r"(sfd) : "r"((uint32_t)never) : "memory")
DEV void mbar_arrive(uint32_t b) { asm volatile("mbarrier.arrive.shared::cta.b64 _,[%0];" ::"r"(b) : "memory"); }
DEV void mbar_arrive_elect(uint32_t b) { asm volatile("{.reg .pred p; elect.sync _|p, 0xffffffff; @p mbarrier.arrive.shared::cta.b64 _,[%0];}" ::"r"(b) : "memory"); }
DEV void mbar_arrive_elect_if(uint32_t b, bool c) {
    asm volatile("{.reg .pred p, q; setp.ne.u32 q,%1,0; elect.sync _|p, 0xffffffff; and.pred p,p,q; @p mbarrier.arrive.shared::cta.b64 _,[%0];}" ::"r"(b), "r"((uint32_t)c) : "memory");
}
DEV void mbar_expect_elect(uint32_t b, uint32_t tx) {
    asm volatile("{.reg .pred p; elect.sync _|p, 0xffffffff; @p mbarrier.arrive.expect_tx.shared::cta.b64 _,[%0],%1;}" ::"r"(b), "r"(tx) : "memory");
}
DEV void mbar_arrive_remote_elect(uint32_t b) { asm volatile("{.reg .pred p; elect.sync _|p, 0xffffffff; @p mbarrier.arrive.shared::cluster.b64 _,[%0];}" ::"r"(b) : "memory"); }
DEV bool elect() { uint32_t r; asm volatile("{.reg .pred p; elect.sync _|p, 0xffffffff; selp.u32 %0,1,0,p;}" : "=r"(r)); return r; }
DEV void mbar_arrive_remote(uint32_t b) { asm volatile("mbarrier.arrive.shared::cluster.b64 _,[%0];" ::"r"(b) : "memory"); }
DEV void mbar_expect(uint32_t b, uint32_t tx) { asm volatile("mbarrier.arrive.expect_tx.shared::cta.b64 _,[%0],%1;" ::"r"(b), "r"(tx) : "memory"); }
DEV void bar_sync(int id, int n) { asm volatile("bar.sync %0,%1;" ::"r"(id), "r"(n) : "memory"); }
DEV void bar_arrive(int id, int n) { asm volatile("bar.arrive %0,%1;" ::"r"(id), "r"(n) : "memory"); }
template <int ID, int N> DEV void bar_arrive_if(bool p) {
    asm volatile("{.reg .pred p; setp.ne.u32 p,%0,0; @p bar.arrive %1,%2;}" ::"r"((uint32_t)p), "n"(ID), "n"(N) : "memory");
}
DEV void prefetch_bulk(const void* p, uint32_t bytes) { asm volatile("cp.async.bulk.prefetch.L2.global [%0],%1;" ::"l"(p), "r"(bytes) : "memory"); }
DEV void prefetch_l2(const void* p) { asm volatile("prefetch.global.L2 [%0];" ::"l"(p) : "memory"); }
template <int ID, int N> DEV void bar_sync_if(bool p) {
    asm volatile("{.reg .pred p; setp.ne.u32 p,%0,0; @p bar.sync %1,%2;}" ::"r"((uint32_t)p), "n"(ID), "n"(N) : "memory");
}
DEV void st_remote(uint32_t a, uint32_t x) { asm volatile("st.relaxed.cluster.shared::cluster.u32 [%0],%1;" ::"r"(a), "r"(x) : "memory"); }
DEV void st_async1(uint32_t a, uint32_t x, uint32_t b) {
    asm volatile("st.async.shared::cluster.mbarrier::complete_tx::bytes.u32 [%0],%1,[%2];" ::"r"(a), "r"(x), "r"(b) : "memory");
}
DEV void st_async2(uint32_t a, uint32_t x, uint32_t y, uint32_t b) {
    asm volatile("st.async.shared::cluster.mbarrier::complete_tx::bytes.v2.u32 [%0],{%1,%2},[%3];" ::"r"(a), "r"(x), "r"(y), "r"(b) : "memory");
}
DEV void st_async4(uint32_t a, uint32_t x, uint32_t y, uint32_t z, uint32_t w, uint32_t b) {
    asm volatile("st.async.shared::cluster.mbarrier::complete_tx::bytes.v4.u32 [%0],{%1,%2,%3,%4},[%5];" ::"r"(a), "r"(x), "r"(y), "r"(z), "r"(w), "r"(b) : "memory");
}
DEV void bulk_g2s(uint32_t dst, const void* src, uint32_t bytes, uint32_t b) {
    asm volatile("cp.async.bulk.shared::cluster.global.mbarrier::complete_tx::bytes [%0],[%1],%2,[%3];" ::"r"(dst), "l"(src), "r"(bytes), "r"(b) : "memory");
}
DEV void bulk_g2s_elect(uint32_t dst, const void* src, uint32_t bytes, uint32_t b) {
    asm volatile("{.reg .pred p; elect.sync _|p, 0xffffffff; @p cp.async.bulk.shared::cluster.global.mbarrier::complete_tx::bytes [%0],[%1],%2,[%3];}"
                 ::"r"(dst), "l"(src), "r"(bytes), "r"(b) : "memory");
}
DEV void bulk_g2s_all3_elect(uint32_t dst, const void* src, uint32_t bytes, uint32_t b) {
    asm volatile("{.reg .pred p; elect.sync _|p, 0xffffffff; @p cp.async.bulk.shared::cluster.global.mbarrier::complete_tx::bytes.multicast::cluster [%0],[%1],%2,[%3],%4;}"
                 ::"r"(dst), "l"(src), "r"(bytes), "r"(b), "h"((unsigned short)7) : "memory");
}
DEV void bulk_s2s_elect(uint32_t dst, uint32_t src, uint32_t bytes, uint32_t b) {
    asm volatile("{.reg .pred p; elect.sync _|p, 0xffffffff; @p cp.async.bulk.shared::cluster.shared::cta.mbarrier::complete_tx::bytes [%0],[%1],%2,[%3];}"
                 ::"r"(dst), "r"(src), "r"(bytes), "r"(b) : "memory");
}
DEV void bulk_s2g_elect(void* dst, uint32_t src, uint32_t bytes) {
    asm volatile("{.reg .pred p; elect.sync _|p, 0xffffffff; @p cp.async.bulk.global.shared::cta.bulk_group [%0],[%1],%2;}" ::"l"(dst), "r"(src), "r"(bytes) : "memory");
}
DEV void bulk_s2s(uint32_t dst, uint32_t src, uint32_t bytes, uint32_t b) {
    asm volatile("cp.async.bulk.shared::cluster.shared::cta.mbarrier::complete_tx::bytes [%0],[%1],%2,[%3];" ::"r"(dst), "r"(src), "r"(bytes), "r"(b) : "memory");
}
DEV void bulk_s2g(void* dst, uint32_t src, uint32_t bytes) {
    asm volatile("cp.async.bulk.global.shared::cta.bulk_group [%0],[%1],%2;" ::"l"(dst), "r"(src), "r"(bytes) : "memory");
}
DEV void tma3d(uint32_t dst, const CUtensorMap* m, int c0, int c1, int c2, uint32_t b) {
    asm volatile("cp.async.bulk.tensor.3d.shared::cluster.global.mbarrier::complete_tx::bytes [%0],[%1,{%3,%4,%5}],[%2];"
                 ::"r"(dst), "l"(m), "r"(b), "r"(c0), "r"(c1), "r"(c2) : "memory");
}
DEV void bulk_commit() { asm volatile("cp.async.bulk.commit_group;" ::: "memory"); }
template <int N> DEV void bulk_wait() { asm volatile("cp.async.bulk.wait_group %0;" ::"n"(N) : "memory"); }
template <int N> DEV void bulk_wait_read() { asm volatile("cp.async.bulk.wait_group.read %0;" ::"n"(N) : "memory"); }
DEV void flag_add(uint32_t* p) { asm volatile("red.relaxed.gpu.global.add.u32 [%0],1;" ::"l"(p) : "memory"); }
DEV uint32_t ld_acquire(const uint32_t* p) { uint32_t v; asm volatile("ld.acquire.gpu.global.u32 %0,[%1];" : "=r"(v) : "l"(p) : "memory"); return v; }
DEV void flag_wait(const uint32_t* p, uint32_t n) {
    for (uint32_t it = 0; ld_acquire(p) < n; __nanosleep(40)) if (++it > (SPIN_LIMIT << 3)) die();
}
DEV void cp16(uint32_t dst, const void* src) { asm volatile("cp.async.cg.shared.global [%0],[%1],16;" ::"r"(dst), "l"(src) : "memory"); }
DEV void cp_commit() { asm volatile("cp.async.commit_group;" ::: "memory"); }
template <int N> DEV void cp_wait() { asm volatile("cp.async.wait_group %0;" ::"n"(N) : "memory"); }
DEV uint32_t lds32(uint32_t a) { uint32_t x; asm volatile("ld.shared.u32 %0,[%1];" : "=r"(x) : "r"(a) : "memory"); return x; }
DEV void fence_async() { asm volatile("fence.proxy.async.shared::cta;" ::: "memory"); }
DEV uint32_t pack2(float lo, float hi) { uint32_t r; asm("cvt.rn.bf16x2.f32 %0,%1,%2;" : "=r"(r) : "f"(hi), "f"(lo)); return r; }
DEV uint32_t prmt(uint32_t a, uint32_t b, uint32_t s) { uint32_t r; asm("prmt.b32 %0,%1,%2,%3;" : "=r"(r) : "r"(a), "r"(b), "r"(s)); return r; }
DEV float ex2(float x) { float r; asm("ex2.approx.ftz.f32 %0,%1;" : "=f"(r) : "f"(x)); return r; }
DEV float sqrt_approx(float x) { float r; asm("sqrt.approx.ftz.f32 %0,%1;" : "=f"(r) : "f"(x)); return r; }
DEV float rcp(float x) { float r; asm("rcp.approx.ftz.f32 %0,%1;" : "=f"(r) : "f"(x)); return r; }
DEV void lds128(uint32_t* r, uint32_t a) { asm volatile("ld.shared.v4.u32 {%0,%1,%2,%3},[%4];" : "=r"(r[0]), "=r"(r[1]), "=r"(r[2]), "=r"(r[3]) : "r"(a) : "memory"); }
DEV void lds64(uint32_t* r, uint32_t a) { asm volatile("ld.shared.v2.u32 {%0,%1},[%2];" : "=r"(r[0]), "=r"(r[1]) : "r"(a) : "memory"); }
DEV void lds64f(float& x, float& y, uint32_t a) { asm volatile("ld.shared.v2.f32 {%0,%1},[%2];" : "=f"(x), "=f"(y) : "r"(a) : "memory"); }
DEV void lds128f(float* r, uint32_t a) { asm volatile("ld.shared.v4.f32 {%0,%1,%2,%3},[%4];" : "=f"(r[0]), "=f"(r[1]), "=f"(r[2]), "=f"(r[3]) : "r"(a) : "memory"); }
DEV void sts128(uint32_t a, uint32_t x, uint32_t y, uint32_t z, uint32_t w) { asm volatile("st.shared.v4.u32 [%0],{%1,%2,%3,%4};" ::"r"(a), "r"(x), "r"(y), "r"(z), "r"(w) : "memory"); }
DEV void sts64(uint32_t a, uint32_t x, uint32_t y) { asm volatile("st.shared.v2.u32 [%0],{%1,%2};" ::"r"(a), "r"(x), "r"(y) : "memory"); }
DEV void sts32(uint32_t a, uint32_t x) { asm volatile("st.shared.u32 [%0],%1;" ::"r"(a), "r"(x) : "memory"); }
DEV void ldsm4(uint32_t* r, uint32_t a) { asm volatile("ldmatrix.sync.aligned.m8n8.x4.shared.b16 {%0,%1,%2,%3},[%4];" : "=r"(r[0]), "=r"(r[1]), "=r"(r[2]), "=r"(r[3]) : "r"(a) : "memory"); }
DEV void ldsm4t(uint32_t* r, uint32_t a) { asm volatile("ldmatrix.sync.aligned.m8n8.x4.trans.shared.b16 {%0,%1,%2,%3},[%4];" : "=r"(r[0]), "=r"(r[1]), "=r"(r[2]), "=r"(r[3]) : "r"(a) : "memory"); }
DEV void ldsm2(uint32_t* r, uint32_t a) { asm volatile("ldmatrix.sync.aligned.m8n8.x2.shared.b16 {%0,%1},[%2];" : "=r"(r[0]), "=r"(r[1]) : "r"(a) : "memory"); }
DEV void stsm4t(uint32_t a, uint32_t x, uint32_t y, uint32_t z, uint32_t w) { asm volatile("stmatrix.sync.aligned.m8n8.x4.trans.shared.b16 [%0],{%1,%2,%3,%4};" ::"r"(a), "r"(x), "r"(y), "r"(z), "r"(w) : "memory"); }
DEV void stsm4(uint32_t a, uint32_t x, uint32_t y, uint32_t z, uint32_t w) { asm volatile("stmatrix.sync.aligned.m8n8.x4.shared.b16 [%0],{%1,%2,%3,%4};" ::"r"(a), "r"(x), "r"(y), "r"(z), "r"(w) : "memory"); }
DEV void stsm2(uint32_t a, uint32_t x, uint32_t y) { asm volatile("stmatrix.sync.aligned.m8n8.x2.shared.b16 [%0],{%1,%2};" ::"r"(a), "r"(x), "r"(y) : "memory"); }
DEV void sts128f_if(uint32_t a, const float* v, bool p) {
    asm volatile("{.reg .pred p; setp.ne.u32 p,%5,0; @p st.shared.v4.f32 [%0],{%1,%2,%3,%4};}" ::"r"(a), "f"(v[0]), "f"(v[1]), "f"(v[2]), "f"(v[3]), "r"((uint32_t)p) : "memory");
}
DEV void lds128f_if(float* v, uint32_t a, bool p) {
    asm volatile("{.reg .pred p; setp.ne.u32 p,%5,0; @p ld.shared.v4.f32 {%0,%1,%2,%3},[%4];}"
                 : "+f"(v[0]), "+f"(v[1]), "+f"(v[2]), "+f"(v[3]) : "r"(a), "r"((uint32_t)p) : "memory");
}
DEV void stsm2t_if(uint32_t a, uint32_t x, uint32_t y, bool p) {
    asm volatile("{.reg .pred p; setp.ne.u32 p,%3,0; @p stmatrix.sync.aligned.m8n8.x2.trans.shared.b16 [%0],{%1,%2};}" ::"r"(a), "r"(x), "r"(y), "r"((uint32_t)p) : "memory");
}
DEV void stsm2t(uint32_t a, uint32_t x, uint32_t y) { asm volatile("stmatrix.sync.aligned.m8n8.x2.trans.shared.b16 [%0],{%1,%2};" ::"r"(a), "r"(x), "r"(y) : "memory"); }
DEV void mma16(float* d, uint32_t a0, uint32_t a1, uint32_t a2, uint32_t a3, uint32_t b0, uint32_t b1) {
    asm volatile("mma.sync.aligned.m16n8k16.row.col.f32.bf16.bf16.f32 {%0,%1,%2,%3},{%4,%5,%6,%7},{%8,%9},{%0,%1,%2,%3};"
                 : "+f"(d[0]), "+f"(d[1]), "+f"(d[2]), "+f"(d[3]) : "r"(a0), "r"(a1), "r"(a2), "r"(a3), "r"(b0), "r"(b1));
}
DEV void mma8(float* d, uint32_t a0, uint32_t a1, uint32_t b0) {
    asm volatile("mma.sync.aligned.m16n8k8.row.col.f32.bf16.bf16.f32 {%0,%1,%2,%3},{%4,%5},{%6},{%0,%1,%2,%3};"
                 : "+f"(d[0]), "+f"(d[1]), "+f"(d[2]), "+f"(d[3]) : "r"(a0), "r"(a1), "r"(b0));
}
DEV u64 mkdesc(uint32_t a, uint32_t lbo, uint32_t sbo) { return (u64)((a & 0x3ffff) >> 4) | ((u64)(lbo >> 4) << 16) | ((u64)(sbo >> 4) << 32); }
constexpr u64 SW128 = 1ull << 62;
DEV void wg_fence() { asm volatile("wgmma.fence.sync.aligned;" ::: "memory"); }
DEV void wg_commit() { asm volatile("wgmma.commit_group.sync.aligned;" ::: "memory"); }
template <int N> DEV void wg_wait() { asm volatile("wgmma.wait_group.sync.aligned %0;" ::"n"(N) : "memory"); }
template <int ACC> DEV void wgmma_n32_rs(float* d, const uint32_t* a, u64 desc) {
    asm volatile("wgmma.mma_async.sync.aligned.m64n32k16.f32.bf16.bf16 {%0,%1,%2,%3,%4,%5,%6,%7,%8,%9,%10,%11,%12,%13,%14,%15},{%16,%17,%18,%19},%20,%21,1,1,0;"
                 : "+f"(d[0]), "+f"(d[1]), "+f"(d[2]), "+f"(d[3]), "+f"(d[4]), "+f"(d[5]), "+f"(d[6]), "+f"(d[7]),
                   "+f"(d[8]), "+f"(d[9]), "+f"(d[10]), "+f"(d[11]), "+f"(d[12]), "+f"(d[13]), "+f"(d[14]), "+f"(d[15])
                 : "r"(a[0]), "r"(a[1]), "r"(a[2]), "r"(a[3]), "l"(desc), "n"(ACC));
}
template <int ACC> DEV void wgmma_n32_ss(float* d, u64 da, u64 desc) {
    asm volatile("wgmma.mma_async.sync.aligned.m64n32k16.f32.bf16.bf16 {%0,%1,%2,%3,%4,%5,%6,%7,%8,%9,%10,%11,%12,%13,%14,%15},%16,%17,%18,1,1,0,0;"
                 : "+f"(d[0]), "+f"(d[1]), "+f"(d[2]), "+f"(d[3]), "+f"(d[4]), "+f"(d[5]), "+f"(d[6]), "+f"(d[7]),
                   "+f"(d[8]), "+f"(d[9]), "+f"(d[10]), "+f"(d[11]), "+f"(d[12]), "+f"(d[13]), "+f"(d[14]), "+f"(d[15])
                 : "l"(da), "l"(desc), "n"(ACC));
}
template <int ACC> DEV void wgmma_n16_ss(float* d, u64 da, u64 desc) {
    asm volatile("wgmma.mma_async.sync.aligned.m64n16k16.f32.bf16.bf16 {%0,%1,%2,%3,%4,%5,%6,%7},%8,%9,%10,1,1,0,0;"
                 : "+f"(d[0]), "+f"(d[1]), "+f"(d[2]), "+f"(d[3]), "+f"(d[4]), "+f"(d[5]), "+f"(d[6]), "+f"(d[7])
                 : "l"(da), "l"(desc), "n"(ACC));
}
#define ACC8(o) "+f"(d[o]), "+f"(d[o + 1]), "+f"(d[o + 2]), "+f"(d[o + 3]), "+f"(d[o + 4]), "+f"(d[o + 5]), "+f"(d[o + 6]), "+f"(d[o + 7])
template <int ACC, int TB> DEV void wgmma_n64_rs(float* d, const uint32_t* a, u64 desc) {
    asm volatile("wgmma.mma_async.sync.aligned.m64n64k16.f32.bf16.bf16 {%0,%1,%2,%3,%4,%5,%6,%7,%8,%9,%10,%11,%12,%13,%14,%15,"
                 "%16,%17,%18,%19,%20,%21,%22,%23,%24,%25,%26,%27,%28,%29,%30,%31},{%32,%33,%34,%35},%36,%37,1,1,%38;"
                 : ACC8(0), ACC8(8), ACC8(16), ACC8(24) : "r"(a[0]), "r"(a[1]), "r"(a[2]), "r"(a[3]), "l"(desc), "n"(ACC), "n"(TB));
}
template <int ACC, int TB> DEV void wgmma_n80_rs(float* d, const uint32_t* a, u64 desc) {
    asm volatile("wgmma.mma_async.sync.aligned.m64n80k16.f32.bf16.bf16 {%0,%1,%2,%3,%4,%5,%6,%7,%8,%9,%10,%11,%12,%13,%14,%15,"
                 "%16,%17,%18,%19,%20,%21,%22,%23,%24,%25,%26,%27,%28,%29,%30,%31,%32,%33,%34,%35,%36,%37,%38,%39},{%40,%41,%42,%43},%44,%45,1,1,%46;"
                 : ACC8(0), ACC8(8), ACC8(16), ACC8(24), ACC8(32) : "r"(a[0]), "r"(a[1]), "r"(a[2]), "r"(a[3]), "l"(desc), "n"(ACC), "n"(TB));
}
template <int TA, int TB> DEV void wgmma_n64_ss(float* d, u64 da, u64 db, int acc) {
    asm volatile("{.reg .pred p; setp.ne.b32 p,%34,0; wgmma.mma_async.sync.aligned.m64n64k16.f32.bf16.bf16 {%0,%1,%2,%3,%4,%5,%6,%7,%8,%9,%10,%11,%12,%13,%14,%15,%16,%17,%18,%19,%20,%21,%22,%23,%24,%25,%26,%27,%28,%29,%30,%31},%32,%33,p,1,1,%35,%36;}"
                 : ACC8(0), ACC8(8), ACC8(16), ACC8(24) : "l"(da), "l"(db), "r"(acc), "n"(TA), "n"(TB));
}
template <int TA, int TB> DEV void wgmma_n128_ss(float* d, u64 da, u64 db, int acc) {
    asm volatile("{.reg .pred p; setp.ne.b32 p,%66,0; wgmma.mma_async.sync.aligned.m64n128k16.f32.bf16.bf16 {%0,%1,%2,%3,%4,%5,%6,%7,%8,%9,%10,%11,%12,%13,%14,%15,%16,%17,%18,%19,%20,%21,%22,%23,%24,%25,%26,%27,%28,%29,%30,%31,%32,%33,%34,%35,%36,%37,%38,%39,%40,%41,%42,%43,%44,%45,%46,%47,%48,%49,%50,%51,%52,%53,%54,%55,%56,%57,%58,%59,%60,%61,%62,%63},%64,%65,p,1,1,%67,%68;}"
                 : ACC8(0), ACC8(8), ACC8(16), ACC8(24), ACC8(32), ACC8(40), ACC8(48), ACC8(56) : "l"(da), "l"(db), "r"(acc), "n"(TA), "n"(TB));
}
template <int TA, int TB> DEV void wgmma_n192_ss(float* d, u64 da, u64 db, int acc) {
    asm volatile("{.reg .pred p; setp.ne.b32 p,%98,0; wgmma.mma_async.sync.aligned.m64n192k16.f32.bf16.bf16 {%0,%1,%2,%3,%4,%5,%6,%7,%8,%9,%10,%11,%12,%13,%14,%15,%16,%17,%18,%19,%20,%21,%22,%23,%24,%25,%26,%27,%28,%29,%30,%31,%32,%33,%34,%35,%36,%37,%38,%39,%40,%41,%42,%43,%44,%45,%46,%47,%48,%49,%50,%51,%52,%53,%54,%55,%56,%57,%58,%59,%60,%61,%62,%63,%64,%65,%66,%67,%68,%69,%70,%71,%72,%73,%74,%75,%76,%77,%78,%79,%80,%81,%82,%83,%84,%85,%86,%87,%88,%89,%90,%91,%92,%93,%94,%95},%96,%97,p,1,1,%99,%100;}"
                 : ACC8(0), ACC8(8), ACC8(16), ACC8(24), ACC8(32), ACC8(40), ACC8(48), ACC8(56), ACC8(64), ACC8(72), ACC8(80), ACC8(88) : "l"(da), "l"(db), "r"(acc), "n"(TA), "n"(TB));
}
template <int ACC> DEV void wgmma_n40_ss(float* d, u64 da, u64 desc) {
    asm volatile("wgmma.mma_async.sync.aligned.m64n40k16.f32.bf16.bf16 {%0,%1,%2,%3,%4,%5,%6,%7,%8,%9,%10,%11,%12,%13,%14,%15,%16,%17,%18,%19},%20,%21,%22,1,1,0,0;"
                 : ACC8(0), ACC8(8), "+f"(d[16]), "+f"(d[17]), "+f"(d[18]), "+f"(d[19]) : "l"(da), "l"(desc), "n"(ACC));
}
DEV void pdl_wait() { asm volatile("griddepcontrol.wait;" ::: "memory"); }
DEV void pdl_launch() { asm volatile("griddepcontrol.launch_dependents;" ::: "memory"); }
DEV uint32_t ldg32(const void* p) { uint32_t v; asm volatile("ld.global.nc.u32 %0,[%1];" : "=r"(v) : "l"(p)); return v; }
DEV void ld_acc(u64& a, u64& b, const void* p) {
    const uint32_t done = (uint32_t)a & (uint32_t)b & 32u;
    asm volatile("{.reg .pred p; setp.eq.u32 p,%3,0;\n"
                 "@p ld.relaxed.gpu.global.v2.u64 {%0,%1},[%2];}" : "+l"(a), "+l"(b) : "l"(p), "r"(done) : "memory");
}
DEV void ld_acc0(u64& a, u64& b, const void* p) {
    asm volatile("ld.relaxed.gpu.global.v2.u64 {%0,%1},[%2];" : "=l"(a), "=l"(b) : "l"(p) : "memory");
}
DEV uint32_t and3(uint32_t a, uint32_t b, uint32_t c) { uint32_t r; asm volatile("lop3.b32 %0,%1,%2,%3,0x80;" : "=r"(r) : "r"(a), "r"(b), "r"(c)); return r; }
DEV uint32_t absmax2(uint32_t a, uint32_t b) { uint32_t r; asm("max.xorsign.abs.bf16x2 %0,%1,%2;" : "=r"(r) : "r"(a), "r"(b)); return r; }
DEV float lds32f(uint32_t a) { float x; asm volatile("ld.shared.f32 %0,[%1];" : "=f"(x) : "r"(a) : "memory"); return x; }
DEV void red_add64(u64* p, uint32_t lo, uint32_t hi) {
    asm volatile("{.reg .b64 v; mov.b64 v,{%1,%2}; red.relaxed.gpu.global.add.u64 [%0],v;}" ::"l"(p), "r"(lo), "r"(hi) : "memory");
}
DEV float bf_round(float x) { return __bfloat162float(__float2bfloat16_rn(x)); }
DEV float bf_lo(uint32_t u) { return __uint_as_float(u << 16); }
DEV float bf_hi(uint32_t u) { return __uint_as_float(u & 0xffff0000u); }

#define GPROF(i, n)
#define PROFT(i)
#define STAMP(i)

DEV void unpack8(float* v, uint4 u) {
    v[0] = bf_lo(u.x); v[1] = bf_hi(u.x); v[2] = bf_lo(u.y); v[3] = bf_hi(u.y);
    v[4] = bf_lo(u.z); v[5] = bf_hi(u.z); v[6] = bf_lo(u.w); v[7] = bf_hi(u.w);
}
DEV int xn_off(int row, int chunk) { return (row >> 5) * 40960 + (chunk >> 3) * 4096 + (row & 31) * 128 + (((chunk ^ row) & 7) << 4); }

DEV void ln_row(float (&v)[3][8], int lane) {
    float s = 0.f;
#pragma unroll
    for (int c = 0; c < 3; c++)
#pragma unroll
        for (int j = 0; j < 8; j++) s += v[c][j];
#pragma unroll
    for (int o = 16; o; o >>= 1) s += __shfl_xor_sync(~0u, s, o);
    float mean = s * (1.f / D_), q = 0.f;
#pragma unroll
    for (int c = 0; c < 3; c++)
        if (c < 2 || lane < 16)
#pragma unroll
            for (int j = 0; j < 8; j++) { float d = v[c][j] - mean; q += d * d; }
#pragma unroll
    for (int o = 16; o; o >>= 1) q += __shfl_xor_sync(~0u, q, o);
    float mb = bf_round(mean);
    float inv = 1.f / bf_round(sqrtf(bf_round(bf_round(q * (1.f / D_)) + 1e-5f)));
#pragma unroll
    for (int c = 0; c < 3; c++)
#pragma unroll
        for (int j = 0; j < 8; j++) v[c][j] = bf_round(v[c][j] - mb) * inv;
}

__host__ __device__ constexpr int col_freq(int c) {
    return c == 320 ? 320 : c < 192 ? (c >> 6) * 128 + (c & 63) : c == 192 ? 192 : c < 256 ? 448 - c : c == 256 ? 64 : 384 - c;
}
DEV float rdft(int n, int k, int sn, int N) {
    float s, c;
    sincospif((float)((n * k) & (N - 1)) * (2.f / N), &s, &c);
    return !sn ? c : k ? s : (n & 1 ? -1.f : 1.f);
}

__global__ void __launch_bounds__(512) prep_kernel(const bf16* __restrict__ x, const bf16* __restrict__ Wq, const bf16* __restrict__ Wk,
                                                   const bf16* __restrict__ Wv, const bf16* __restrict__ Wo) {
    __shared__ float red[32], col[4][640];
    const int tid = threadIdx.x, lane = tid & 31, warp = tid >> 5, b = blockIdx.x, row = b * 16 + warp;
    TLS(0);
    pdl_launch();
    uint4 ux[3], uv[5], uo[8];
#pragma unroll
    for (int c = 0; c < 3; c++) ux[c] = c < 2 || lane < 16 ? *(const uint4*)(x + row * D_ + (c * 32 + lane) * 8) : make_uint4(0, 0, 0, 0);
#pragma unroll
    for (int i = 0; i < 5; i++) uv[i] = *(const uint4*)(Wv + (size_t)((b & 3) * 160 + i * 32 + (tid >> 4)) * 4096 + (b >> 2) * E_ + (tid & 15) * 8);
    if (tid < 320) {
#pragma unroll
        for (int r = 0; r < 8; r++) uo[r] = *(const uint4*)(Wo + (size_t)(b * 32 + tid / 80 * 8 + r) * D_ + tid % 80 * 8);
    }
    if (tid >= 504) prefetch_bulk((const char*)(tid & 4 ? Wk : Wq) + (b * 4 + (tid & 3)) * 10240, 10240);
    if (b < 3) ((uint4*)g_sync)[b * 512 + tid] = make_uint4(0, 0, 0, 0);
    for (int i = b * 512 + tid; i < ACC_LAYER; i += 128 * 512) ((uint4*)g_acc)[i] = make_uint4(0, 0, 0, 0);
    if (tid < 2 * YT_ROWS * D_ / 4 / 128) ((uint4*)g_yt)[b * (2 * YT_ROWS * D_ / 4 / 128) + tid] = make_uint4(0, 0, 0, 0);
    const int gid = tid < 104 ? b * 104 + tid : 1 << 20;
    if (gid < 4096) {
        const int inv = gid >> 11, ks = (gid >> 8) & 7, t = gid & 255, g = (t & 31) >> 2, q = t & 3, tile = t >> 5;
        uint32_t v[4];
#pragma unroll
        for (int j = 0; j < 4; j++) {
            float x[2];
#pragma unroll
            for (int u = 0; u < 2; u++) {
                const int m = inv ? 16 * tile + 2 * g + (j & 1) : 16 * ks + 8 * (j >> 1) + 2 * q + u;
                const int k2 = inv ? 8 * ks + 2 * q + u : 8 * tile + g, sn = inv ? j >> 1 : j & 1;
                x[u] = rdft(m, k2, sn, 128);
                if (sn && k2) x[u] = -x[u];
            }
            v[j] = pack2(x[0], x[1]);
        }
        g_f128[gid] = make_uint4(v[0], v[1], v[2], v[3]);
    } else if (gid < 5120) {
        const int id = gid - 4096, inv = id >> 9, ks = (id >> 7) & 3, t = id & 127, g = (t & 31) >> 2, q = t & 3, tile = t >> 5;
        uint32_t v[4];
#pragma unroll
        for (int j = 0; j < 4; j++) {
            float x[2];
#pragma unroll
            for (int u = 0; u < 2; u++) {
                const int a = inv ? 16 * tile + g + 8 * (j & 1) : 16 * ks + 8 * (j >> 1) + 2 * q + u;
                const int ka = inv ? 8 * ks + 2 * q + u : 8 * tile + g, sn = inv ? j >> 1 : j & 1;
                x[u] = rdft(a, ka, sn, 64);
            }
            v[j] = pack2(x[0], x[1]);
        }
        g_f64[id] = make_uint4(v[0], v[1], v[2], v[3]);
    } else if (gid < 5120 + 8192) {
        const int id = gid - 5120, inv = id >> 12, n = ((id >> 9) & 7) * 8 + ((id >> 3) & 7), k = ((id >> 6) & 7) * 8 + (id & 7);
        float s, c;
        sincospif((float)(((n >> 1) * (k >> 1)) & 31) * (1.f / 16), &s, &c);
        if (inv) s = -s;
        g_g32[id] = __float2bfloat16_rn((n & 1) == (k & 1) ? c : (k & 1) ? s : -s);
    }
    {
        float v[3][8];
#pragma unroll
        for (int c = 0; c < 3; c++) unpack8(v[c], ux[c]);
        ln_row(v, lane);
#pragma unroll
        for (int c = 0; c < 3; c++)
            if (c < 2 || lane < 16)
                *(uint4*)(g_xn + xn_off(row, c * 32 + lane)) =
                    make_uint4(pack2(v[c][0], v[c][1]), pack2(v[c][2], v[c][3]), pack2(v[c][4], v[c][5]), pack2(v[c][6], v[c][7]));
    }
    float sv = 0.f;
#pragma unroll
    for (int i = 0; i < 5; i++) {
        float w[8];
        unpack8(w, uv[i]);
#pragma unroll
        for (int j = 0; j < 8; j++) sv += w[j] * w[j];
    }
    if (tid < 320) {
        float a[8] = {0.f, 0.f, 0.f, 0.f, 0.f, 0.f, 0.f, 0.f};
#pragma unroll
        for (int r = 0; r < 8; r++) {
            float w[8];
            unpack8(w, uo[r]);
#pragma unroll
            for (int j = 0; j < 8; j++) a[j] += w[j] * w[j];
        }
#pragma unroll
        for (int j = 0; j < 8; j++) col[tid / 80][tid % 80 * 8 + j] = a[j];
    }
    __syncthreads();
    float so = (col[0][tid] + col[1][tid]) + (col[2][tid] + col[3][tid]);
    if (tid < 128) so = fmaxf(so, (col[0][512 + tid] + col[1][512 + tid]) + (col[2][512 + tid] + col[3][512 + tid]));
#pragma unroll
    for (int o = 16; o; o >>= 1) { sv += __shfl_xor_sync(~0u, sv, o); so = fmaxf(so, __shfl_xor_sync(~0u, so, o)); }
    if (lane == 0) { red[warp] = sv; red[16 + warp] = so; }
    __syncthreads();
    if (tid == 0) {
        float a = 0.f, c = 0.f;
        for (int i = 0; i < 16; i++) { a += red[i]; c = fmaxf(c, red[16 + i]); }
        g_nrm[b] = a; g_nrm[128 + b] = c;
    }
    TLE(0);
}

DEV void filter_tile(const bf16* __restrict__ wr, const bf16* __restrict__ wi, int ka, int c) {
    const int kn = ka ? 2048 - ka : 32, kc = col_freq(c);
    const unsigned short* pr = (const unsigned short*)wr + kc;
    const unsigned short* pi = (const unsigned short*)wi + kc;
#pragma unroll 1
    for (int i = 0; i < 4; i += 2) {
        unsigned short a[32], b[32];
#pragma unroll
        for (int n = 0; n < 32; n++) {
            const int k = ((n & 1 ? kn : ka) + 64 * (4 * (2 * (i + (n >> 4)) + ((n >> 1) & 1)) + ((n >> 2) & 3))) & 2047;
            a[n] = __ldg(pr + k * NCOL); b[n] = __ldg(pi + k * NCOL);
        }
#pragma unroll
        for (int n = 0; n < 32; n += 4)
            *(uint4*)(g_wt + c * 8192 + (i + (n >> 4)) * 2048 + (ka * 4 + ((n >> 2) & 3)) * 16) =
                make_uint4(a[n] | ((uint32_t)b[n] << 16), a[n + 1] | ((uint32_t)b[n + 1] << 16), a[n + 2] | ((uint32_t)b[n + 2] << 16), a[n + 3] | ((uint32_t)b[n + 3] << 16));
    }
}

namespace wk {
constexpr int STAGE = 49152, NST = 4, OFF_OUT = 3 * STAGE, OFF_RED = 4 * STAGE, OFF_BAR = OFF_RED + 32768, SMEM = OFF_BAR + 128;
constexpr int NPB = 11;
__host__ __device__ constexpr int pb_start(int b) { return b ? 6 * b - 2 : 0; }
#define NOB 7
#define SPLIT_A 2
#define SPLIT_B 9
constexpr int N_P = NPB * H_, I_F = N_P, I_OB = I_F + 32, I_OT = I_OB + NOB * 5, I_SA = I_OT + (30 - 3 * NOB) * 10;
constexpr int I_SB = I_SA + 10 * SPLIT_A, N_ITEMS = I_SB + 10 * SPLIT_B;
DEV void ot_decode(int id, int& b, int& nt, int& k0, int& k1) {
    const int base = id < I_SA ? I_OT : id < I_SB ? I_SA : I_SB, j = (id - base) / 10;
    nt = (id - base) % 10;
    if (id < I_SA) { b = 3 * NOB + j; k0 = 0; k1 = 22; }
    else if (id < I_SB) { b = 30; k0 = 22 * j / SPLIT_A; k1 = 22 * (j + 1) / SPLIT_A; }
    else { b = 31; k0 = 22 * j / SPLIT_B; k1 = 22 * (j + 1) / SPLIT_B; }
}
enum { SY_TICKET = 0, SY_O = 32, SY_P = 128 };
}
struct Ring {
    int st; uint32_t ph;
    DEV uint32_t par() const { return (ph >> st) & 1; }
    DEV void next(int n) { ph ^= 1u << st; st = st + 1 >= n ? 0 : st + 1; }
};
struct Maps { CUtensorMap wq2, wv1, wo2, wo1, x6, x4, o6, o2; const bf16 *wr, *wi; };

template <int NSG> DEV void proj_tile(uint32_t sb, uint32_t bar, Ring& rg, int wg, int id) {
    using namespace wk;
    float acc[NSG * 16];
#pragma unroll
    for (int i = 0; i < NSG * 16; i++) acc[i] = 0.f;
    const int lane = threadIdx.x & 31, ww = (threadIdx.x >> 5) & 3;
    for (int kb = 0; kb < 10; kb++, rg.next(3)) {
        const int st = rg.st;
        if (kb) mbar_wait(bar + 8 * st, rg.par());
        const u64 da = mkdesc(sb + st * STAGE + wg * 8192, 0, 1024) | SW128, db = mkdesc(sb + st * STAGE + 24576, 0, 1024) | SW128;
        wg_fence();
#pragma unroll
        for (int ks = 0; ks < 4; ks++) {
            if (NSG == 4) wgmma_n128_ss<1, 0>(acc, da + ks * 128, db + ks * 2, 1);
            if (NSG == 6) wgmma_n192_ss<1, 0>(acc, da + ks * 128, db + ks * 2, 1);
        }
        wg_commit();
        wg_wait<0>();
        mbar_arrive_elect(bar + 8 * (NST + st));
    }
    const uint32_t out = sb + OFF_OUT + wg * 24576;
    bar_sync(5 + wg, 160);
    const uint32_t la = out + (wg < 2 ? (lane >> 4) * 1024 + ww * 256 + (lane & 15) * 16 : ww * 1024 + ((lane >> 3) & 1) * 512 + (lane >> 4) * 128 + (lane & 7) * 16);
#pragma unroll
    for (int j = 0; j < 2 * NSG; j++) {
        const float* c = acc + 8 * j;
        const uint32_t p0 = pack2(c[0], c[1]), p1 = pack2(c[2], c[3]), p2 = pack2(c[4], c[5]), p3 = pack2(c[6], c[7]);
        if (wg < 2) stsm4t(la + j * 2048, p0, p1, p2, p3);
        else stsm4(la + (j >> 1) * 4096 + (j & 1) * 256, p0, p1, p2, p3);
    }
    if ((threadIdx.x & 127) == 0) sts32(bar + 80 + 4 * wg, id);
    fence_async();
    bar_arrive(1 + wg, 160);
}

DEV uint32_t resid(uint32_t u, float a, float b) { return pack2(bf_lo(u) + bf_round(a), bf_hi(u) + bf_round(b)); }

template <bool SIDE>
DEV void worker(uint32_t sb, const Maps& maps, const bf16* __restrict__ x, bf16* __restrict__ x1, int layer, int fix, int nfix) {
    using namespace wk;
    const uint32_t bar = sb + OFF_BAR, slot = bar + 64;
    const int tid = threadIdx.x, lane = tid & 31, warp = __shfl_sync(~0u, tid >> 5, 0);
    uint32_t* sy = g_sync + layer * SYNC_LAYER;
    if (tid == 0) {
        for (int i = 0; i < NST; i++) { mbar_init(bar + 8 * i, 1); mbar_init(bar + 8 * (NST + i), 12); }
        asm volatile("fence.mbarrier_init.release.cluster;" ::: "memory");
    }
    __syncthreads();
    if (warp > 12) {
        const int wg = warp - 13;
        bar_arrive(5 + wg, 160);
        for (;;) {
            bar_sync(1 + wg, 160);
            const int id = (int)lds32(bar + 80 + 4 * wg);
            if (id < 0) break;
            const int s0 = pb_start(id >> 5), ns = pb_start((id >> 5) + 1) - s0;
            if (lane == 0) {
                for (int j = 0; j < ns; j++)
                    bulk_s2g(g_p + (size_t)(((s0 + j) * H_ + (id & 31)) * 3 + wg) * 4096, sb + OFF_OUT + wg * 24576 + j * 4096, 4096);
                bulk_commit();
                bulk_wait<0>();
                flag_add(sy + SY_P + id);
            }
            __syncwarp();
            bar_arrive(5 + wg, 160);
        }
    } else if (warp == 12) {
        if (lane == 0) {
            Ring rg = {0, 7u};
            auto acquire = [&]() { mbar_wait(bar + 8 * (NST + rg.st), rg.par()); return sb + rg.st * STAGE; };
            if (fix >= 0 && fix < N_P) {
                for (int kb = 0; kb < 3; kb++) {
                    tma3d(sb + kb * STAGE, &maps.wq2, 0, kb * 64, 2 * (fix & 31), bar + 8 * kb);
                    tma3d(sb + kb * STAGE + 16384, &maps.wv1, 0, kb * 64, 2 * (fix & 31), bar + 8 * kb);
                }
                asm volatile("prefetch.tensormap [%0];" ::"l"(&maps.x4) : "memory");
            }
            if (SIDE) flag_wait(g_started + layer, 1); else pdl_wait();
            for (;;) {
                int id = fix;
                if (id < 0) {
                    id = nfix + (int)atomicAdd(sy + SY_TICKET, 1u);
                    if (layer && id >= I_F) id += I_OB - I_F;
                    if (id >= I_SB) id = -1;
                }
                if (id >= 0) { TLI(id, 0, gtime()); TLI(id, 3, blockIdx.x + (SIDE ? 1000 : 0)); }
                uint32_t d = acquire();
                sts32(slot + 4 * rg.st, id);
                if (id < 0) { mbar_arrive(bar + 8 * rg.st); if (SIDE) pdl_launch(); break; }
                if (id < N_P) {
                    const int b = id >> 5, h = id & 31;
                    for (int kb = 0; kb < 10; kb++, rg.next(3)) {
                        if (kb) d = acquire();
                        const uint32_t fb = bar + 8 * rg.st;
                        mbar_expect(fb, b ? 49152 : 40960);
                        tma3d(d + 24576, b ? &maps.x6 : &maps.x4, 0, 2 * kb, pb_start(b), fb);
                        if (fix < 0 || kb >= 3) {
                            tma3d(d, &maps.wq2, 0, kb * 64, 2 * h, fb);
                            tma3d(d + 16384, &maps.wv1, 0, kb * 64, 2 * h, fb);
                        }
                    }
                } else if (id < I_OB) {
                    mbar_arrive(bar + 8 * rg.st);
                    mbar_wait(bar + 8 * (NST + rg.st), rg.par() ^ 1);
                    rg.next(NST);
                } else if (id < I_OT) {
                    const int b = (id - I_OB) / 5, nt = (id - I_OB) % 5;
                    for (int j = 0; j < 6; j++) flag_wait(sy + SY_O + 6 * b + j, 64);
                    for (int kb = 0; kb < 64; kb++, rg.next(NST)) {
                        if (kb) d = acquire();
                        const uint32_t fb = bar + 8 * rg.st;
                        mbar_expect(fb, 40960);
                        tma3d(d, &maps.o6, 0, 2 * kb, 6 * b, fb);
                        tma3d(d + 24576, &maps.wo2, 0, kb * 64, 2 * nt, fb);
                    }
                } else {
                    int b, nt, k0, k1;
                    ot_decode(id, b, nt, k0, k1);
                    for (int kb = k0; kb < k1; kb++, rg.next(NST)) {
                        if (kb > k0) d = acquire();
                        const uint32_t fb = bar + 8 * rg.st;
                        mbar_expect(fb, 49152);
                        tma3d(d + 24576, &maps.wo1, 0, 3 * kb * 64, nt, fb);
                        if (kb == k0) for (int j = 0; j < 2; j++) flag_wait(sy + SY_O + 2 * b + j, 64);
                        for (int u = 0; u < 3; u++) tma3d(d + u * 8192, &maps.o2, 0, 2 * (3 * kb + u), 2 * b, fb);
                    }
                }
                fix = -1;
            }
        }
    } else {
        const int wg = warp >> 2, g = lane >> 2, q = lane & 3;
        Ring rg = {0, 0u};
        bool stores_done = false;
        for (;;) {
            mbar_wait(bar + 8 * rg.st, rg.par());
            const int id = (int)lds32(slot + 4 * rg.st);
            if ((id < 0 || id >= N_P) && !stores_done) {
                bar_sync(5 + wg, 160);
                if ((tid & 127) == 0) sts32(bar + 80 + 4 * wg, ~0u);
                bar_arrive(1 + wg, 160);
                stores_done = true;
                bar_sync(4, 384);
                mbar_arrive_elect(bar + 8 * (NST + 3));
            }
            if (id < 0) break;
            if (tid == 0) TLI(id, 1, gtime());
            if (id < N_P) {
                const int b = id >> 5;
                if (b == 0) proj_tile<4>(sb, bar, rg, wg, id);
                else proj_tile<6>(sb, bar, rg, wg, id);
            } else if (id < I_OB) {
                if (tid < NCOL) filter_tile(maps.wr, maps.wi, id - I_F, tid);
                __syncwarp();
                mbar_arrive_elect(bar + 8 * (NST + rg.st));
                rg.next(NST);
            } else if (id < I_OT) {
                const int b = (id - I_OB) / 5, nt = (id - I_OB) % 5;
                const size_t o = (size_t)(192 * b + 16 * warp + g) * D_ + nt * 128 + 2 * q;
                float acc[64];
#pragma unroll
                for (int i = 0; i < 64; i++) acc[i] = 0.f;
                for (int kb = 0; kb < 64; kb++, rg.next(NST)) {
                    const int st = rg.st;
                    if (kb) mbar_wait(bar + 8 * st, rg.par());
                    const u64 da = mkdesc(sb + st * STAGE + wg * 8192, 128, 1024), db = mkdesc(sb + st * STAGE + 24576, 8192, 1024) | SW128;
                    wg_fence();
#pragma unroll
                    for (int ks = 0; ks < 4; ks++) wgmma_n128_ss<0, 1>(acc, da + ks * 16, db + ks * 128, 1);
                    wg_commit();
                    wg_wait<0>();
                    mbar_arrive_elect(bar + 8 * (NST + st));
                }
                uint32_t xr[32];
#pragma unroll
                for (int t = 0; t < 32; t++) xr[t] = ldg32(x + o + 8 * (t >> 1) + (t & 1) * 8 * D_);
#pragma unroll
                for (int t = 0; t < 32; t++) *(uint32_t*)(x1 + o + 8 * (t >> 1) + (t & 1) * 8 * D_) = resid(xr[t], acc[2 * t], acc[2 * t + 1]);
            } else {
                int b, nt, k0, k1;
                ot_decode(id, b, nt, k0, k1);
                const size_t o = (size_t)(64 * b + 16 * (warp & 3) + g) * D_ + nt * 64 + 2 * q;
                float acc[32];
                uint32_t xr[16];
#pragma unroll
                for (int t = 0; t < 16; t++) xr[t] = wg == 0 && id < I_SA ? ldg32(x + o + 8 * (t >> 1) + (t & 1) * 8 * D_) : 0;
#pragma unroll
                for (int i = 0; i < 32; i++) acc[i] = 0.f;
                for (int kb = k0; kb < k1; kb++, rg.next(NST)) {
                    const int st = rg.st;
                    if (kb > k0) mbar_wait(bar + 8 * st, rg.par());
                    const u64 da = mkdesc(sb + st * STAGE + wg * 8192, 128, 1024), db = mkdesc(sb + st * STAGE + 24576 + wg * 8192, 0, 1024) | SW128;
                    wg_fence();
#pragma unroll
                    for (int ks = 0; ks < 4; ks++) wgmma_n64_ss<0, 1>(acc, da + ks * 16, db + ks * 128, 1);
                    wg_commit();
                    wg_wait<0>();
                    mbar_arrive_elect(bar + 8 * (NST + st));
                }
                const uint32_t ra = sb + OFF_RED + (tid & 127) * 16;
                if (wg) {
#pragma unroll
                    for (int t = 0; t < 8; t++)
                        sts128(ra + (wg - 1) * 16384 + t * 2048, __float_as_uint(acc[4 * t]), __float_as_uint(acc[4 * t + 1]), __float_as_uint(acc[4 * t + 2]), __float_as_uint(acc[4 * t + 3]));
                }
                bar_sync(4, 384);
                if (wg == 0) {
#pragma unroll
                    for (int t = 0; t < 8; t++) {
                        float u[4], v[4];
                        lds128f(u, ra + t * 2048); lds128f(v, ra + 16384 + t * 2048);
#pragma unroll
                        for (int i = 0; i < 4; i++) acc[4 * t + i] += u[i] + v[i];
                    }
                }
                bar_sync(4, 384);
                if (wg == 0) {
                    if (id < I_SA) {
#pragma unroll
                        for (int t = 0; t < 16; t++) *(uint32_t*)(x1 + o + 8 * (t >> 1) + (t & 1) * 8 * D_) = resid(xr[t], acc[2 * t], acc[2 * t + 1]);
                    } else {
                        float* y = g_yt + (layer * YT_ROWS - (S_ - YT_ROWS)) * D_ + o;
#pragma unroll
                        for (int t = 0; t < 16; t++)
                            asm volatile("red.relaxed.gpu.global.add.v2.f32 [%0],{%1,%2};" ::"l"(y + 8 * (t >> 1) + (t & 1) * 8 * D_), "f"(acc[2 * t]), "f"(acc[2 * t + 1]) : "memory");
                    }
                }
            }
            if (tid == 0) TLI(id, 2, gtime());
        }
    }
}

__global__ void __launch_bounds__(512, 1) side_kernel(const __grid_constant__ Maps maps, const bf16* __restrict__ x, bf16* __restrict__ x1, int layer, int nfix) {
    extern __shared__ __align__(1024) unsigned char smem[];
    TLS(3 + 5 * layer);
    worker<true>(s2u(smem), maps, x, x1, layer, -1, nfix);
    __syncwarp();
    if (blockIdx.x == 0) pdl_wait();
    TLE(3 + 5 * layer);
}

constexpr float C5A = 0.30901699437494742f, C5B = -0.80901699437494742f, S5A = 0.95105651629515357f, S5B = 0.58778525229247313f;
template <int SGN> DEV void dft5(const float (&tr)[5], const float (&ti)[5], float (&zr)[5], float (&zi)[5]) {
    const float ar = tr[1] + tr[4], ai = ti[1] + ti[4], br = tr[2] + tr[3], bi = ti[2] + ti[3];
    const float cr = tr[1] - tr[4], ci = ti[1] - ti[4], dr = tr[2] - tr[3], di = ti[2] - ti[3];
    zr[0] = tr[0] + ar + br; zi[0] = ti[0] + ai + bi;
    const float m1r = tr[0] + C5A * ar + C5B * br, m1i = ti[0] + C5A * ai + C5B * bi;
    const float m2r = tr[0] + C5B * ar + C5A * br, m2i = ti[0] + C5B * ai + C5A * bi;
    const float n1r = SGN * (S5A * cr + S5B * dr), n1i = SGN * (S5A * ci + S5B * di);
    const float n2r = SGN * (S5B * cr - S5A * dr), n2i = SGN * (S5B * ci - S5A * di);
    zr[1] = m1r + n1i; zi[1] = m1i - n1r; zr[4] = m1r - n1i; zi[4] = m1i + n1r;
    zr[2] = m2r + n2i; zi[2] = m2i - n2r; zr[3] = m2r - n2i; zi[3] = m2i + n2r;
}
DEV void ln40(float (&v)[40]) {
    float s = 0.f;
#pragma unroll
    for (int i = 0; i < 40; i++) s += v[i];
#pragma unroll
    for (int o = 8; o; o >>= 1) s += __shfl_xor_sync(~0u, s, o);
    const float mean = s * (1.f / D_);
    float q = 0.f;
#pragma unroll
    for (int i = 0; i < 40; i++) { const float d = v[i] - mean; q += d * d; }
#pragma unroll
    for (int o = 8; o; o >>= 1) q += __shfl_xor_sync(~0u, q, o);
    const float mb = bf_round(mean);
    const float inv = 1.f / bf_round(sqrtf(bf_round(bf_round(q * (1.f / D_)) + 1e-5f)));
#pragma unroll
    for (int i = 0; i < 40; i++) v[i] = bf_round(v[i] - mb) * inv;
}
__global__ void __maxnreg__(120) rowfft_kernel(const bf16* __restrict__ x0, bf16* __restrict__ x, const bf16* __restrict__ Wq,
                                                     const bf16* __restrict__ Wk, const bf16* __restrict__ Wv, int layer) {
    extern __shared__ __align__(1024) unsigned char smem[];
    const uint32_t sb = s2u(smem), sx = sb + 23552, sy = sx + 20480, bar = sy + 40960;
    const int tid = threadIdx.x, lane = tid & 31, q = lane & 3, blk = 127 - blockIdx.x, k2 = tid >> 2;
    if (tid == 0) TLI(800 + blk, 0, gtime());
    float twr[5], twi[5];
#pragma unroll
    for (int r = 1; r < 5; r++) { sincospif((float)(r * k2) * (-1.f / 320), &twi[r], &twr[r]); }
    uint32_t f[8][4];
#pragma unroll
    for (int ks = 0; ks < 8; ks++) { const uint4 u = g_f128[ks * 256 + tid]; f[ks][0] = u.x; f[ks][1] = u.y; f[ks][2] = u.z; f[ks][3] = u.w; }
    const bool split = blk * 16 >= S_ - YT_ROWS;
    if (tid == 0) {
        mbar_init(bar, 1);
        asm volatile("fence.mbarrier_init.release.cluster;" ::: "memory");
        mbar_expect(bar, split ? 61440 : 20480);
        if (split) bulk_g2s(sx, x0 + (size_t)blk * 16 * D_, 20480, bar);
    }
    __syncthreads();
    pdl_wait();
    pdl_launch();
    TLS(4 + 5 * layer);
    if (tid == 0) TLI(800 + blk, 1, gtime());
    if (tid == 0 && blk == 0) g_started[layer] = 0;
    if (tid == 0) {
        if (split) bulk_g2s(sy, g_yt + (layer * YT_ROWS + blk * 16 - (S_ - YT_ROWS)) * D_, 40960, bar);
        else bulk_g2s(sx, x + (size_t)blk * 16 * D_, 20480, bar);
    }
    mbar_wait(bar, 0);
    {
        const int rho = tid >> 4, j = tid & 15;
        float v[40];
#pragma unroll
        for (int i = 0; i < 5; i++) {
            uint32_t u[4];
            lds128(u, sx + tid * 80 + i * 16);
            if (split) {
                float p[8];
                lds128f(p, sy + tid * 160 + i * 32); lds128f(p + 4, sy + tid * 160 + i * 32 + 16);
#pragma unroll
                for (int k = 0; k < 4; k++) u[k] = resid(u[k], p[2 * k], p[2 * k + 1]);
                sts128(sx + tid * 80 + i * 16, u[0], u[1], u[2], u[3]);
            }
            unpack8(v + 8 * i, make_uint4(u[0], u[1], u[2], u[3]));
        }
        if (layer == 0 && tid < 12) prefetch_bulk((const char*)(tid < 4 ? Wk : tid < 8 ? Wq : Wv) + (blk * 4 + (tid & 3)) * 10240, 10240);
        ln40(v);
        const uint32_t a = sb + ((rho >> 1) & 1) * 2304 + j * 144 + (2 * (rho >> 2) + (rho & 1)) * 16;
#pragma unroll
        for (int r = 0; r < 5; r++)
            sts128(a + r * 4608, pack2(v[r], v[5 + r]), pack2(v[10 + r], v[15 + r]), pack2(v[20 + r], v[25 + r]), pack2(v[30 + r], v[35 + r]));
    }
    fence_async();
    __syncthreads();
    if (tid == 0) TLI(800 + blk, 2, gtime());
    if (tid == 0 && split) { bulk_s2g(x + (size_t)blk * 16 * D_, sx, 20480); bulk_commit(); }
    float acc[40];
    const u64 db = mkdesc(sb, 144, 2304);
    wg_fence();
    wgmma_n80_rs<0, 0>(acc, f[0], db);
#pragma unroll
    for (int ks = 1; ks < 8; ks++) wgmma_n80_rs<1, 0>(acc, f[ks], db + ks * 18);
    wg_commit();
    wg_wait<0>();
    unsigned char* zp = g_z + (blk >> 1) * 128 + ((((blk & 1) * 4 + q) ^ ((blk >> 1) & 7)) << 4);
    uint32_t o[5][4];
#pragma unroll
    for (int u = 0; u < 4; u++) {
        float tr[5], ti[5], zr[5], zi[5];
#pragma unroll
        for (int r = 0; r < 5; r++) {
            const float yr = acc[8 * r + 4 * (u >> 1) + (u & 1)], yi = k2 ? acc[8 * r + 4 * (u >> 1) + 2 + (u & 1)] : 0.f;
            tr[r] = r ? yr * twr[r] - yi * twi[r] : yr;
            ti[r] = r ? yr * twi[r] + yi * twr[r] : yi;
        }
        dft5<1>(tr, ti, zr, zi);
#pragma unroll
        for (int j = 0; j < 5; j++) o[j][u] = pack2(zr[j], j < 3 ? zi[j] : -zi[j]);
    }
#pragma unroll
    for (int j = 0; j < 5; j++)
        if (j < 3 || k2) *(uint4*)(zp + (64 * j + k2) * 8192) = make_uint4(o[j][0], o[j][1], o[j][2], o[j][3]);
    if (k2 == 0) {
#pragma unroll
        for (int u = 0; u < 4; u++) {
            float tr[5], ti[5], zr[5], zi[5];
            const float cr[5] = {1.f, -C5B, C5A, -C5A, C5B}, ci[5] = {0.f, -S5B, -S5A, -S5A, -S5B};
#pragma unroll
            for (int r = 0; r < 5; r++) { const float y = acc[8 * r + 4 * (u >> 1) + 2 + (u & 1)]; tr[r] = y * cr[r]; ti[r] = y * ci[r]; }
            dft5<1>(tr, ti, zr, zi);
            o[0][u] = pack2(zr[0], zi[0]); o[1][u] = pack2(zr[1], zi[1]); o[2][u] = pack2(zr[2], 0.f);
        }
        *(uint4*)(zp + 256 * 8192) = make_uint4(o[0][0], o[0][1], o[0][2], o[0][3]);
        *(uint4*)(zp + 192 * 8192) = make_uint4(o[1][0], o[1][1], o[1][2], o[1][3]);
        *(uint4*)(zp + 320 * 8192) = make_uint4(o[2][0], o[2][1], o[2][2], o[2][3]);
    }
    if (tid == 0) bulk_wait_read<0>();
    TLE(4 + 5 * layer);
    if (tid == 0) TLI(800 + blk, 3, gtime());
}

constexpr int CF_SMEM = 16384 + 8192 + 3 * 24576 + 64;
__global__ void __maxnreg__(88) colfft_kernel(int layer) {
    extern __shared__ __align__(1024) unsigned char smem[];
    const uint32_t sb = s2u(smem), bar = sb + 98304;
    const int tid = threadIdx.x, lane = tid & 31, q = lane & 3, wg = __shfl_sync(~0u, tid >> 7, 0), t = tid & 127, ka = t >> 2;
    asm volatile("setmaxnreg.inc.sync.aligned.u32 88;");
    const int col = blockIdx.x * 3 + wg;
    const uint32_t d0 = sb + 24576 + wg * 24576, d1 = d0 + 8192;
    if (tid == 0) {
        for (int i = 0; i < 4; i++) mbar_init(bar + 8 * i, 1);
        asm volatile("fence.mbarrier_init.release.cluster;" ::: "memory");
        mbar_expect(bar + 24, 49152);
        for (int i = 0; i < 3; i++) bulk_g2s(d0 + i * 24576 + 16384, g_wt + (col + i) * 8192, 8192, bar + 24);
        bulk_g2s(sb, g_g32, 16384, bar + 24);
        bulk_g2s(sb + 16384, g_f64 + 512, 8192, bar + 24);
    }
    uint32_t a[4][4];
#pragma unroll
    for (int ks = 0; ks < 4; ks++) { const uint4 u = g_f64[ks * 128 + t]; a[ks][0] = u.x; a[ks][1] = u.y; a[ks][2] = u.z; a[ks][3] = u.w; }
    float twr[8], twi[8];
#pragma unroll
    for (int i = 0; i < 8; i++) sincospif((float)((4 * i + q) * (ka ? ka : -32)) * (1.f / 1024), &twi[i], &twr[i]);
    __syncthreads();
    pdl_wait();
    pdl_launch();
    TLS(5 + 5 * layer);
    if (t == 0) {
        mbar_expect(bar + 8 * wg, 8192);
        bulk_g2s(d0, g_z + col * 8192, 8192, bar + 8 * wg);
    }
    float acc[32];
    mbar_wait(bar + 8 * wg, 0);
    {
        const u64 db = mkdesc(d0, 0, 1024) | SW128;
        wg_fence();
        wgmma_n64_rs<0, 1>(acc, a[0], db);
#pragma unroll
        for (int ks = 1; ks < 4; ks++) wgmma_n64_rs<1, 1>(acc, a[ks], db + ks * 128);
        wg_commit();
        wg_wait<0>();
    }
#pragma unroll
    for (int i = 0; i < 8; i++) {
        const float c0 = acc[4 * i], c1 = acc[4 * i + 1], c2 = acc[4 * i + 2], c3 = acc[4 * i + 3];
        const float pr = c0 + c3, pi = c1 - c2, nr = ka ? c0 - c3 : c2, ni = ka ? c1 + c2 : c3;
        a[i >> 1][2 * (i & 1)] = ka ? pack2(pr * twr[i] + pi * twi[i], pi * twr[i] - pr * twi[i]) : pack2(c0, c1);
        a[i >> 1][2 * (i & 1) + 1] = pack2(nr * twr[i] - ni * twi[i], ni * twr[i] + nr * twi[i]);
    }
    mbar_wait(bar + 24, 0);
    {
        const u64 db = mkdesc(sb, 128, 1024);
        wg_fence();
        wgmma_n64_rs<0, 0>(acc, a[0], db);
#pragma unroll
        for (int ks = 1; ks < 4; ks++) wgmma_n64_rs<1, 0>(acc, a[ks], db + ks * 16);
        wg_commit();
        wg_wait<0>();
    }
    constexpr float NORM = 1.f / (2048.f * 640.f);
#pragma unroll
    for (int i = 0; i < 4; i++) lds128(a[i], d0 + 16384 + i * 2048 + t * 16);
#pragma unroll
    for (int i = 0; i < 16; i++) {
        const float zr = acc[2 * i] * NORM, zi = acc[2 * i + 1] * NORM, wr = bf_lo(a[i >> 2][i & 3]), wi = bf_hi(a[i >> 2][i & 3]);
        a[i >> 2][i & 3] = pack2(zr * wr - zi * wi, zr * wi + zi * wr);
    }
    {
        const u64 db = mkdesc(sb + 8192, 128, 1024);
        wg_fence();
        wgmma_n64_rs<0, 0>(acc, a[0], db);
#pragma unroll
        for (int ks = 1; ks < 4; ks++) wgmma_n64_rs<1, 0>(acc, a[ks], db + ks * 16);
        wg_commit();
        wg_wait<0>();
    }
    const uint32_t row = (t >> 5) * 2048 + (lane & 15) * 128;
#pragma unroll
    for (int i = 0; i < 8; i++) {
        const float c0 = acc[4 * i], c1 = acc[4 * i + 1], c2 = acc[4 * i + 2], c3 = acc[4 * i + 3];
        const float pr = c0 * twr[i] - c1 * twi[i], pi = c1 * twr[i] + c0 * twi[i];
        const float nr = c2 * twr[i] + c3 * twi[i], ni = c3 * twr[i] - c2 * twi[i];
        a[i >> 1][2 * (i & 1)] = ka ? pack2(pr + nr, pi + ni) : pack2(c0, c1);
        a[i >> 1][2 * (i & 1) + 1] = ka ? pack2(ni - pi, pr - nr) : pack2(nr, ni);
    }
#pragma unroll
    for (int i = 0; i < 4; i++) stsm4(d1 + row + (((2 * i + (lane >> 4)) ^ (lane & 7)) << 4), a[i][0], a[i][1], a[i][2], a[i][3]);
#pragma unroll
    for (int i = 0; i < 4; i++) lds128(a[i], sb + 16384 + i * 2048 + t * 16);
    fence_async();
    bar_sync(1 + wg, 128);
    {
        const u64 db = mkdesc(d1, 0, 1024) | SW128;
        wg_fence();
        wgmma_n64_rs<0, 1>(acc, a[0], db);
#pragma unroll
        for (int ks = 1; ks < 4; ks++) wgmma_n64_rs<1, 1>(acc, a[ks], db + ks * 128);
        wg_commit();
        wg_wait<0>();
    }
#pragma unroll
    for (int i = 0; i < 4; i++)
        stsm4(d0 + row + (((2 * i + (lane >> 4)) ^ (lane & 7)) << 4), pack2(acc[8 * i], acc[8 * i + 1]), pack2(acc[8 * i + 2], acc[8 * i + 3]),
              pack2(acc[8 * i + 4], acc[8 * i + 5]), pack2(acc[8 * i + 6], acc[8 * i + 7]));
    fence_async();
    bar_sync(1 + wg, 128);
    if (t == 0) {
        bulk_s2g(g_z + col * 8192, d0, 8192);
        asm volatile("cp.async.bulk.commit_group;" ::: "memory");
        bulk_wait_read<0>();
    }
    TLE(5 + 5 * layer);
}

__global__ void __maxnreg__(120) rowifft_kernel(const bf16* __restrict__ x, bf16* __restrict__ out, int last) {
    extern __shared__ __align__(1024) unsigned char smem[];
    const uint32_t sb = s2u(smem), sx = sb + 20480, sy = sx + 20480, bar = sy + 16 * 1296;
    const int tid = threadIdx.x, lane = tid & 31, q = lane & 3, blk = blockIdx.x, k2 = tid >> 2, warp = tid >> 5;
    float twr[5], twi[5];
#pragma unroll
    for (int r = 1; r < 5; r++) { sincospif((float)(r * k2) * (1.f / 320), &twi[r], &twr[r]); twr[r] *= 2.f; twi[r] *= 2.f; }
    uint32_t f[8][4];
#pragma unroll
    for (int ks = 0; ks < 8; ks++) { const uint4 u = g_f128[2048 + ks * 256 + tid]; f[ks][0] = u.x; f[ks][1] = u.y; f[ks][2] = u.z; f[ks][3] = u.w; }
    if (tid == 0) {
        mbar_init(bar, 1);
        asm volatile("fence.mbarrier_init.release.cluster;" ::: "memory");
        mbar_expect(bar, 20480);
        bulk_g2s(sx, x + (size_t)blk * 16 * D_, 20480, bar);
    }
    pdl_wait();
    pdl_launch();
    TLS(6 + 5 * last);
    const unsigned char* zp = g_z + (blk >> 1) * 128 + ((((blk & 1) * 4 + q) ^ ((blk >> 1) & 7)) << 4);
    uint4 z[6];
#pragma unroll
    for (int j = 0; j < 5; j++) z[j] = *(const uint4*)(zp + (64 * j + k2) * 8192);
    z[5] = k2 ? make_uint4(0, 0, 0, 0) : *(const uint4*)(zp + 320 * 8192);
    float acc[40];
#pragma unroll
    for (int u = 0; u < 4; u++) {
        float yr[6], yi[6], tr[5], ti[5], zr[5], zi[5];
#pragma unroll
        for (int j = 0; j < 6; j++) { const uint32_t v = u == 0 ? z[j].x : u == 1 ? z[j].y : u == 2 ? z[j].z : z[j].w; yr[j] = bf_lo(v); yi[j] = bf_hi(v); }
#pragma unroll
        for (int j = 0; j < 5; j++) { tr[j] = yr[j]; ti[j] = j < 3 ? yi[j] : -yi[j]; }
        dft5<-1>(tr, ti, zr, zi);
        const float c1[5] = {1.f, C5A, C5B, C5B, C5A}, s1[5] = {0.f, S5A, S5B, -S5B, -S5A};
        const float c2[5] = {1.f, C5B, C5A, C5A, C5B}, s2[5] = {0.f, S5B, -S5A, S5A, -S5B};
        const float c3[5] = {1.f, -C5B, C5A, -C5A, C5B}, s3[5] = {0.f, S5B, S5A, S5A, S5B};
        const float c4[5] = {1.f, -C5A, C5B, -C5B, C5A}, s4[5] = {0.f, S5A, -S5B, -S5B, S5A};
#pragma unroll
        for (int r = 0; r < 5; r++) {
            float er = r ? zr[r] * twr[r] - zi[r] * twi[r] : 2.f * zr[0], ei = r ? zr[r] * twi[r] + zi[r] * twr[r] : 2.f * zi[0];
            if (k2 == 0) {
                er = yr[0] + 2.f * (yr[1] * c1[r] - yi[1] * s1[r] + yr[2] * c2[r] - yi[2] * s2[r]);
                ei = (r & 1 ? -yr[5] : yr[5]) + 2.f * (yr[4] * c3[r] - yi[4] * s3[r] + yr[3] * c4[r] - yi[3] * s4[r]);
            }
            acc[8 * r + 4 * (u >> 1) + (u & 1)] = er;
            acc[8 * r + 4 * (u >> 1) + 2 + (u & 1)] = ei;
        }
    }
#pragma unroll
    for (int r = 0; r < 5; r++)
        stsm4(sb + (2 * warp + ((lane >> 3) & 1)) * 1280 + (2 * r + (lane >> 4)) * 128 + (lane & 7) * 16, pack2(acc[8 * r], acc[8 * r + 1]),
              pack2(acc[8 * r + 2], acc[8 * r + 3]), pack2(acc[8 * r + 4], acc[8 * r + 5]), pack2(acc[8 * r + 6], acc[8 * r + 7]));
    fence_async();
    __syncthreads();
    const u64 db = mkdesc(sb, 1280, 128);
    wg_fence();
    wgmma_n80_rs<0, 1>(acc, f[0], db);
#pragma unroll
    for (int ks = 1; ks < 8; ks++) wgmma_n80_rs<1, 1>(acc, f[ks], db + ks * 160);
    wg_commit();
    wg_wait<0>();
#pragma unroll
    for (int u = 0; u < 4; u++) {
        float e[10];
#pragma unroll
        for (int r = 0; r < 5; r++) { e[r] = acc[8 * r + 4 * (u >> 1) + (u & 1)]; e[5 + r] = acc[8 * r + 4 * (u >> 1) + 2 + (u & 1)]; }
#pragma unroll
        for (int i = 0; i < 5; i++) sts32(sy + (4 * q + u) * 1296 + k2 * 20 + i * 4, pack2(e[2 * i], e[2 * i + 1]));
    }
    __syncthreads();
    const int rho = tid >> 4, j = tid & 15;
    float v[40];
    mbar_wait(bar, 0);
#pragma unroll
    for (int i = 0; i < 5; i++) {
        uint32_t y[4], u[4];
        lds128(y, sy + rho * 1296 + j * 80 + i * 16);
        lds128(u, sx + tid * 80 + i * 16);
#pragma unroll
        for (int k = 0; k < 4; k++) u[k] = pack2(bf_lo(u[k]) + bf_lo(y[k]), bf_hi(u[k]) + bf_hi(y[k]));
        sts128(sx + tid * 80 + i * 16, u[0], u[1], u[2], u[3]);
        unpack8(v + 8 * i, make_uint4(u[0], u[1], u[2], u[3]));
    }
    if (!last) {
        ln40(v);
#pragma unroll
        for (int i = 0; i < 5; i++) {
            const int c = j * 5 + i;
            sts128(sb + (c >> 3) * 2048 + rho * 128 + (((c ^ rho) & 7) << 4), pack2(v[8 * i], v[8 * i + 1]), pack2(v[8 * i + 2], v[8 * i + 3]),
                   pack2(v[8 * i + 4], v[8 * i + 5]), pack2(v[8 * i + 6], v[8 * i + 7]));
        }
    }
    fence_async();
    __syncthreads();
    if (lane == 0) {
        if (warp == 7) bulk_s2g(out + (size_t)blk * 16 * D_, sx, 20480);
        else if (!last && warp < 5) {
            unsigned char* p = g_xn + (blk >> 1) * 40960 + warp * 8192 + (blk & 1) * 2048;
            bulk_s2g(p, sb + warp * 4096, 2048);
            bulk_s2g(p + 4096, sb + warp * 4096 + 2048, 2048);
        }
        bulk_commit();
        bulk_wait_read<0>();
    }
    TLE(6 + 5 * last);
}

namespace rec {
#define NS 3
constexpr int OFF_X = 0;
constexpr int OFF_WO = 81920;
constexpr int OFF_WS = OFF_WO + 65536;
constexpr int OFF_XCH = OFF_WS + NS * 4096;
constexpr int OFF_MEMB = OFF_XCH + 12288;
constexpr int OFF_VX = OFF_MEMB + 10240;
constexpr int OFF_VM = OFF_VX + 16384;
constexpr int OFF_Q = OFF_VM + 4096;
constexpr int OFF_K = OFF_Q + 10240;
constexpr int OFF_OST = OFF_WO + 49152;
constexpr int OFF_PX = OFF_OST + 8192;
constexpr int OFF_PT = OFF_PX + 2560;
constexpr int OFF_PS = OFF_K + 10240;
constexpr int OFF_OB = OFF_PS + 1280;
constexpr int OFF_MX = OFF_OB + 2048;
constexpr int OFF_BAR = OFF_MX + 64;
constexpr int OFF_PROF = OFF_BAR + 256;
constexpr int SMEM = OFF_PROF + 4096 > wk::SMEM ? OFF_PROF + 4096 : wk::SMEM;
enum { B_XT = 0, B_VM = 2, B_VX = 4, B_XD = 6, B_X1 = 8, B_GO = 10, B_PXF = 12, B_PXE = 13, B_FIN = 14, B_ST = 15, B_MEM = 16   };
enum { NB_W2 = 0, NB_XCH = 1, NB_QK = 2, NB_WIN = 3, NB_ATT = 4, NB_X = 5, NB_PRO = 6, NB_W1 = 7, NB_PAIR = 8  , NB_KF = 12, NB_LD = 13, NB_KX = 15 };
#define TPOS 1
#define LATE 1
#define STAG 585
#define NOX 0
#define NW1 4
#define NW1B 0
template <int N> struct IC { static constexpr int value = N; };
template <int N, int I = 0, class F> DEV void static_for(F&& f) { if constexpr (I < N) { f(IC<I>{}); static_for<N, I + 1>(f); } }
constexpr float SM_SCALE = 0.08838834764831845f * 1.4426950408889634f;
}

__global__ void __launch_bounds__(512, 1) rec_kernel(const __grid_constant__ Maps maps, const bf16* __restrict__ x, bf16* __restrict__ x1, const bf16* __restrict__ mem0, const bf16* __restrict__ Wq, const bf16* __restrict__ Wk,
                                                     const bf16* __restrict__ Wv, const bf16* __restrict__ Wo, int layer, int delay, int delay2) {
    using namespace rec;
    extern __shared__ __align__(1024) unsigned char smem[];
    const uint32_t sb = s2u(smem);
    pdl_launch();
    if (blockIdx.x < 3 * H_) {
    const int tid = threadIdx.x, lane = tid & 31, warp = __shfl_sync(~0u, tid >> 5, 0);
    const int g = lane >> 2, q = lane & 3;
    const int h = blockIdx.x / 3;
    const uint32_t bar = sb + OFF_BAR;
    STAMP(2 * layer);
    TLS(2 + 5 * layer);
    if (tid == 0) TLI(690 + blockIdx.x, 0, gtime());
    if (tid == 0) {
        for (int i = 0; i < 2; i++) {
            mbar_init(bar + 8 * (B_XT + i), 1); mbar_init(bar + 8 * (B_VX + i), 1);
            mbar_init(bar + 8 * (B_XD + i), 8); mbar_init(bar + 8 * (B_X1 + i), 1); mbar_init(bar + 8 * (B_VM + i), 1);
        }
        mbar_init(bar + 8 * B_PXF, 1); mbar_init(bar + 8 * B_PXE, 2); mbar_init(bar + 8 * B_ST, 2); mbar_init(bar + 8 * B_GO, 1);
        for (int i = 0; i < 5; i++) mbar_init(bar + 8 * (B_MEM + i), 4);
        mbar_init(bar + 8 * B_FIN, 48);
        asm volatile("fence.mbarrier_init.release.cluster;" ::: "memory");
    }
    asm volatile("barrier.cluster.arrive.aligned; barrier.cluster.wait.aligned;" ::: "memory");
    const bool never = delay < 0;

    if (warp < 8) {
        asm volatile("setmaxnreg.inc.sync.aligned.u32 184;");
        const uint32_t rank = cta_rank();
        const int wg = warp >> 2;
        uint32_t fa[20 - NS][4], fb[20][4];
        const uint32_t l16 = opaque(sb + lane * 16);
        uint32_t dst = opaque(rank < 2 ? sb + OFF_Q + wg * 10240 + (warp & 3) * 256 + (lane & 15) * 16 + (lane >> 4) * 1024
                                       : sb + OFF_VM + warp * 256 + lane * 4);
        int dstep = rank < 2 ? 5120 : 2048;
        uint32_t& sfd = dst;
        const uint32_t ws = OFF_WS + warp * 512, xo = OFF_XCH + warp * 512, xi = OFF_XCH + (warp ^ 4) * 512, mb = OFF_MEMB + wg * 512;
        {
            const int t = tid & 127;
            const bf16* src = (rank == 2 ? Wv + wg * 64 : (wg ? Wk : Wq) + rank * 64) + h * E_ + (size_t)(t >> 3) * 4096 + (t & 7) * 8;
            constexpr int SA = OFF_X + 40960, SB = OFF_VX;
            const uint32_t sdst = sb + (wg ? SB : SA) + (t >> 3) * 128 + (((t & 7) ^ ((t >> 3) & 7)) << 4);
            const uint32_t ra = sb + wg * 4096 + ((lane >> 4) * 8 + (lane & 7)) * 128 + (((2 * (warp & 3) + ((lane >> 3) & 1)) ^ (lane & 7)) << 4);
            auto issue = [&](int rd) {
#pragma unroll 1
                for (int i = 0; i < 8; i++, src += 16 * 4096) cp16(sdst + (rd & 1) * 16384 + i * 2048, src);
                cp_commit();
            };
            issue(0); issue(1);
#pragma unroll
            for (int rd = 0; rd < 5; rd++) {
                if (rd < 4) cp_wait<1>(); else cp_wait<0>();
                bar_sync(NB_XCH, 256);
#pragma unroll
                for (int i = 0; i < 4; i++) {
                    const int n = rd * 4 + i, o = (rd & 1) * 16384 + (i >> 1) * 8192 + (i & 1) * 2048;
                    if (n < NS) {
                        uint32_t f[4];
                        ldsm4t(f, ra + SA + o);
                        sts128(l16 + ws + n * 4096, f[0], f[1], f[2], f[3]);
                    } else ldsm4t(fa[n - NS], ra + SA + o);
                    ldsm4t(fb[n], ra + SB + o);
                }
                if (rd < 3) { bar_sync(NB_XCH, 256); issue(rd + 2); }
            }
            fence_async();
            bar_sync(NB_PRO, 288);
        }
        uint32_t xlo = (uint32_t)mkdesc(sb + OFF_X + wg * 64, 0, 0);
        const uint32_t xtog = xlo ^ (uint32_t)mkdesc(sb + OFF_X + 40960 + wg * 64, 0, 0);
        uint32_t p8 = 0;
        bar_sync(NB_LD, 288);
        for (int s = -1;; s++) {
            uint32_t t[NS ? NS : 1][4];
            {
                float acc[16];
                auto xproj = [&](auto I0, auto I1) {
                    const u64 desc = (u64)xlo | (64ull << 32) | SW128;
                    wg_fence();
#pragma unroll
                    for (int i = I0.value; i < I1.value; i++) {
                        const u64 db = desc + (i >> 1) * 256 + (i & 1) * 2;
                        if (i == 0) wgmma_n32_rs<0>(acc, fb[i], db);
                        else if (!NOX) wgmma_n32_rs<1>(acc, fb[i], db);
                    }
                    wg_commit();
                    if (TPOS == 0 ? I0.value == 0 : I1.value == 20) {
#pragma unroll
                        for (int i = 0; i < NS; i++) lds128(t[i], l16 + ws + i * 4096);
                    }
                    wg_wait<0>();
                };
                if (s >= 0 && rank < 2) { fence_async(); bar_arrive(NB_W1, 512); bar_sync(NB_X, 384); }
                bar_sync_if<NB_W1, 480>(s >= 0 && rank == 2);
                if (s == NSEG - 1) break;
                xproj(IC<0>{}, IC<NW1>{});
                if (warp == 4 && s >= 0) PROFT(15);
                bar_sync_if<NB_W2, 384>(s >= 0 && rank < 2);
                if (NW1B > 0) xproj(IC<NW1>{}, IC<NW1 + NW1B>{});
                bar_sync_if<NB_WIN, 384>(s >= 0 && rank == 2);
                xproj(IC<NW1 + NW1B>{}, IC<20>{});
                if (warp == 4 && s >= 0) PROFT(12);
                sts128f_if(l16 + xo, acc + 8, !wg); sts128f_if(l16 + xo + 4096, acc + 12, !wg);
                sts128f_if(l16 + xo, acc, wg); sts128f_if(l16 + xo + 4096, acc + 4, wg);
                bar_sync(NB_PAIR + (warp & 3), 64);
                lds128f_if(acc + 8, l16 + xi, !wg); lds128f_if(acc + 12, l16 + xi + 4096, !wg);
                lds128f_if(acc, l16 + xi, wg); lds128f_if(acc + 4, l16 + xi + 4096, wg);
                float u[8];
#pragma unroll
                for (int i = 0; i < 8; i++) u[i] = acc[i] + acc[8 + i];
                if (rank < 2) {
                    stsm4t(dst + (wg ? 3072 : 11264), pack2(u[0], u[1]), pack2(u[2], u[3]), pack2(u[4], u[5]), pack2(u[6], u[7]));
                } else {
                    stsm4(l16 + (l16 & 256) + OFF_VX + 4096 + (warp & 3) * 1024 + wg * 256 + p8 * 1024,
                          pack2(u[0], u[1]), pack2(u[4], u[5]), pack2(u[2], u[3]), pack2(u[6], u[7]));
                    bar_arrive(NB_KF, 288);
                }
                bar_arrive(NB_KX, 384);
                xlo ^= xtog;
                if (warp == 4 && s >= 0) PROFT(3);
            }
            float da[4] = {0.f, 0.f, 0.f, 0.f}, db[4] = {0.f, 0.f, 0.f, 0.f}, ea[4] = {0.f, 0.f, 0.f, 0.f}, eb[4] = {0.f, 0.f, 0.f, 0.f};
            uint32_t b[10][4];
            const uint32_t mp = p8 >> 3;
            while (!mbar_try(bar + 8 * B_MEM, mp)) {}
            lds128(b[0], l16 + mb); lds128(b[1], l16 + mb + 1024);
            bool rdy;
            const uint32_t xb0 = mapa(bar + 8 * B_VM + p8, 0), xb1 = mapa(bar + 8 * B_VM + p8, 1);
            SFENCE();
            float is;
#pragma unroll
            for (int j = 0; j < 10; j++) {
#pragma unroll
                for (int x = 0; x < 2; x++) {
                    const int i = 2 * j + x;
                    const uint32_t* f = i < NS ? t[i] : fa[i - NS];
                    mma16(NS > 2 && x && j ? ea : da, f[0], f[1], f[2], f[3], b[j][2 * x], b[j][2 * x + 1]);
                    mma16(NS > 2 && x && j ? eb : db, fb[i][0], fb[i][1], fb[i][2], fb[i][3], b[j][2 * x], b[j][2 * x + 1]);
                    SFENCE();
                    if (x == 0 && j < 8 && !(j & 1)) rdy = mbar_try(bar + 8 * (B_MEM + 1 + (j >> 1)), mp, 1);
                    if (x == LATE && j < 8 && (j & 1) == 1 - LATE) {
                        if (__builtin_expect(!rdy, 0)) while (!mbar_try(bar + 8 * (B_MEM + 1 + (j >> 1)), mp)) {}
                        lds128(b[(j | 1) + 1], l16 + mb + ((j | 1) + 1) * 1024);
                        lds128(b[(j | 1) + 2], l16 + mb + ((j | 1) + 2) * 1024);
                    }
                    if (x == 0 && j == 8) is = lds32f(sb + OFF_MX + 16);
                }
                if (j == 0 && warp == 4) PROFT(16);
            }
            if (warp == 4) PROFT(20);
            if (NS > 2) {
#pragma unroll
                for (int i = 0; i < 4; i++) { da[i] += ea[i]; db[i] += eb[i]; }
            }
            sts128f_if(l16 + xo + 8192, db, !wg); sts128f_if(l16 + xo + 8192, da, wg);
            bar_sync(NB_PAIR + (warp & 3), 64);
            lds128f_if(db, l16 + xi + 8192, !wg); lds128f_if(da, l16 + xi + 8192, wg);
            const uint32_t p0 = pack2((da[0] + db[0]) * is, (da[1] + db[1]) * is), p1 = pack2((da[2] + db[2]) * is, (da[3] + db[3]) * is);
            stsm2t_if(dst, p0, p1, rank < 2);
            bar_arrive_if<NB_QK, 384>(rank < 2);
            if (rank == 2) {
                st_async1(mapa(dst, 0), p0, xb0); st_async1(mapa(dst, 1), p0, xb1);
                st_async1(mapa(dst + 128, 0), p1, xb0); st_async1(mapa(dst + 128, 1), p1, xb1);
                sts32(dst, p0); sts32(dst + 128, p1);
                bar_arrive(NB_QK, 384);
            }
            if (warp == 4) PROFT(17);
            dst += dstep; dstep = -dstep; p8 ^= 8;
        }
    } else if (warp < 12) {
        asm volatile("setmaxnreg.dec.sync.aligned.u32 96;");
        const uint32_t rank = cta_rank();
        const int w = warp - 8;
        uint32_t amax = 0;
        {
            const int t = tid & 127, nr = rank == 2 ? 4 : 3;
            for (int r = 0; r < nr; r++) {
                const bf16* src = Wo + (size_t)(h * E_) * D_ + (r < 3 ? 192 * r + 64 * rank : 576);
#pragma unroll 1
                for (int i = 0; i < 8; i++) {
                    const int e = i * 16 + (t >> 3);
                    cp16(sb + OFF_WO + r * 16384 + e * 128 + (((t & 7) ^ (e & 6)) << 4), src + e * D_ + (t & 7) * 8);
                }
            }
            cp_commit();
            uint32_t m0[5][4];
#pragma unroll
            for (int it = 0; it < 5; it++)
#pragma unroll
                for (int j = 0; j < 4; j++) m0[it][j] = ldg32(mem0 + g * D_ + (it * 4 + w) * 32 + 2 * q + 8 * j);
#pragma unroll
            for (int it = 0; it < 5; it++) {
                sts128(sb + OFF_MEMB + (it * 4 + w) * 512 + lane * 16, m0[it][0], m0[it][1], m0[it][2], m0[it][3]);
                amax = absmax2(amax, absmax2(absmax2(m0[it][0], m0[it][1]), absmax2(m0[it][2], m0[it][3])));
            }
            if (tid == 256) { sts32(sb + OFF_MX + 16, 0x3f800000u); sts128(sb + OFF_MX + 48, 0x3f803f80u, 0x3f803f80u, 0x3f803f80u, 0x3f803f80u); }
            __syncwarp();
            if (lane < 5) mbar_arrive(bar + 8 * (B_MEM + lane));
            __syncwarp();
            cp_wait<0>();
            bar_sync(NB_ATT, 128);
            for (int r = 0; r < nr; r++) {
                uint32_t u[8][4];
                const uint32_t p = sb + OFF_WO + r * 16384 + 2 * q * 128 + (((2 * w + (g & 1)) ^ (2 * q)) << 4) + (g >> 1) * 4;
#pragma unroll
                for (int ks = 0; ks < 8; ks++)
#pragma unroll
                    for (int j = 0; j < 4; j++) u[ks][j] = lds32(p + (16 * ks + (j & 1) * 8 + (j >> 1)) * 128);
                bar_sync(NB_ATT, 128);
#pragma unroll
                for (int ks = 0; ks < 8; ks++)
                    sts128(sb + OFF_WO + (r * 4 + w) * 4096 + ks * 512 + lane * 16, prmt(u[ks][0], u[ks][2], 0x5410), prmt(u[ks][0], u[ks][2], 0x7632),
                           prmt(u[ks][1], u[ks][3], 0x5410), prmt(u[ks][1], u[ks][3], 0x7632));
            }
        }
        if (w == 0) TLI(690 + blockIdx.x, 3, gtime());
        pdl_wait();
        float cw;
        {
            const float4 a = ((const float4*)g_nrm)[lane], c = ((const float4*)g_nrm)[32 + lane];
            float sm = sqrt_approx((a.x + a.y) + (a.z + a.w)) * sqrt_approx((c.x + c.y) + (c.z + c.w)), mxv = sm;
#pragma unroll 1
            for (int o = 16; o; o >>= 1) { sm += __shfl_xor_sync(~0u, sm, o); mxv = fmaxf(mxv, __shfl_xor_sync(~0u, mxv, o)); }
            cw = 26.5f * fmaxf(sm, 8.f * mxv);
        }
        if (w == 0) {
            mbar_expect_elect(bar + 8 * B_X1, 1280);
            mbar_expect_elect(bar + 8 * B_VM, rank < 2 ? 2048 : 0);
            mbar_expect_elect(bar + 8 * B_VX, rank < 2 ? 8192 : 4096);
        }
        {
            const int kind = rank;
            const uint32_t l16 = opaque(sb + lane * 16), lw = opaque(sb + lane * 16 + w * 512);
            const uint32_t pa = opaque(sb + OFF_PS + rank * 512 + lane * 4 + w * 128);
            uint32_t lq = opaque(sb + OFF_Q + (lane & 7) * 16 + ((lane >> 3) & 1) * 256 + (lane >> 4) * 128);
            const uint32_t lv = opaque(sb + OFF_VX + w * 2048 + (lane & 7) * 16 + ((lane >> 3) & 1) * 512 + (lane >> 4) * 128);
            const uint32_t lo = opaque(sb + OFF_WO + w * 4096 + lane * 16);
            uint32_t& sfd = lq;
            const char* rp = (const char*)(g_acc + layer * ACC_LAYER) + (4 * rank + w) * 4096 + opaque((q >> 1) * 1024 + ((q & 1) * 8 + g) * 8);
            const char* lp = (const char*)(g_acc + layer * ACC_LAYER) + opaque(w * 8192 + (lane >> 3) * 1024 + (lane & 7) * 16);
            const uint32_t arm = bar + 8 * (w == 0 ? B_X1 + 1 : w == 1 ? B_VX + 1 : w == 2 ? B_XT : B_VM + 1);
            const uint32_t armb = w == 0 ? 1280 : (w == 1 ? 4096 : w == 2 ? 40960 : 0) + (rank == 2 ? 0 : w == 3 ? 2048 : 4096);
            float isig = 1.f;
            for (int s = 0; s < NSEG - 1; s++) {
                const uint32_t pb = s & 1, ph = (s >> 1) & 1, x1 = bar + 8 * (B_X1 + pb);
                uint32_t kf[8];
                bar_sync(NB_KX, 384);
                ldsm4(kf, lw + OFF_K + 1024 + w * 512 + pb * 5120); ldsm4(kf + 4, lw + OFF_K + 1536 + w * 512 + pb * 5120);
                sts32(sb + OFF_MX + w * 4, __reduce_max_sync(~0u, max(amax & 0x7fff0000u, (amax << 16) & 0x7fff0000u)));
                const uint32_t va = lv + pb * 8192, vma = lw + OFF_VM + pb * 2048;
                uint32_t wf[8][4], vf[2][2][4], vm[4], one[4];
                mbar_spin(bar + 8 * (B_VX + pb), ph);
#pragma unroll
                for (int t = 0; t < 2; t++)
#pragma unroll
                    for (int j = 0; j < 2; j++) ldsm4(vf[t][j], va + t * 1024 + j * 256);
                lds128(one, sb + OFF_MX + 48);
                auto scores = [&](auto MM) {
                    constexpr int mm = MM.value;
                    uint32_t qf[8], mf[8];
                    const uint32_t qa = lq + pb * 5120, ka = l16 + OFF_K + pb * 5120;
                    const uint32_t pa0 = mapa(pa, rank ^ 1), pa1 = mapa(pa, 2), pa2 = mapa(pa, rank);
                    const uint32_t xb0 = mapa(x1, rank ^ 1), xb1 = mapa(x1, 2), xb2 = mapa(x1, rank);
                    const uint32_t pm = 640 - rank * 384;
                    SFENCE();
                    if (w == 0) PROFT(2);
                    bar_sync(NB_QK, 384);
                    ldsm4(qf, qa); ldsm4(qf + 4, qa + 512);
                    if (mm) { ldsm4(mf, ka); ldsm4(mf + 4, ka + 512); }
                    SFENCE();
                    float c[4][4];
#pragma unroll
                    for (int i = 0; i < 4; i++) c[i][0] = c[i][1] = c[i][2] = c[i][3] = 0.f;
#pragma unroll
                    for (int i = 0; i < (mm ? 8 : 4); i++) {
                        const int hf = mm ? i >> 2 : i >> 1;
                        const uint32_t* f = (mm && (i & 2) ? mf : kf) + 4 * hf + 2 * (i & 1);
                        mma16(c[i & 3], qf[4 * hf], qf[4 * hf + 1], qf[4 * hf + 2], qf[4 * hf + 3], f[0], f[1]);
                    }
                    SFENCE();
                    bar_arrive(NB_W1, 512);
                    const uint32_t y = mm ? pack2(c[0][0] + c[1][2], c[0][1] + c[1][3])
                                          : pack2((c[0][0] + c[1][2]) + (c[2][0] + c[3][2]), (c[0][1] + c[1][3]) + (c[2][1] + c[3][3]));
                    st_async1(pa0, y, xb0); st_async1(pa1, y, xb1);
                    if (mm) {
                        const uint32_t z = pack2(c[2][0] + c[3][2], c[2][1] + c[3][3]);
                        st_async1(pa0 + pm, z, xb0); st_async1(pa1 + pm, z, xb1); st_async1(pa2 + pm, z, xb2);
                    }
                    st_async1(pa2, y, xb2);
                    if (w == 0) PROFT(5);
                };
                if (kind == 2) bar_sync(NB_QK, 384);
                else if (w == 3) scores(IC<1>{});
                else scores(IC<0>{});
                float m4[4];
                lds128f(m4, sb + OFF_MX);
                bar_arrive_if<NB_W1, 480>(kind == 2);
                mbar_spin(x1, ph);
                if (w == 0) PROFT(6);
                float sc[10];
                {
                    uint32_t u[4], v[4], m[2];
                    ldsm4(u, l16 + OFF_PS); ldsm4(v, l16 + OFF_PS + 512); ldsm2(m, l16 + OFF_PS + 1024);
                    SFENCE();
                    m4[0] = fmaxf(fmaxf(m4[0], m4[1]), fmaxf(m4[2], m4[3])) * isig;
                    SFENCE();
#pragma unroll
                    for (int i = 0; i < 4; i++) { sc[2 * i] = bf_lo(u[i]) + bf_lo(v[i]); sc[2 * i + 1] = bf_hi(u[i]) + bf_hi(v[i]); }
                    sc[8] = bf_lo(m[0]) + bf_lo(m[1]); sc[9] = bf_hi(m[0]) + bf_hi(m[1]);
                }
                float mx = fmaxf(fmaxf(fmaxf(fmaxf(sc[0], sc[1]), fmaxf(sc[2], sc[3])), fmaxf(fmaxf(sc[4], sc[5]), fmaxf(sc[6], sc[7]))), fmaxf(sc[8], sc[9]));
                auto fetch = [&](int i) { lds128(wf[i], lo + i * 512); };
                {
                    float m1 = __shfl_xor_sync(~0u, mx, 1), m2 = __shfl_xor_sync(~0u, mx, 2), m3 = __shfl_xor_sync(~0u, mx, 3);
                    mbar_spin(bar + 8 * (B_VM + pb), ph);
                    ldsm4(vm, vma);
                    mx = fmaxf(fmaxf(mx, m1), fmaxf(m2, m3)) * SM_SCALE;
                }
#pragma unroll
                for (int i = 0; i < 10; i++) sc[i] = fmaf(sc[i], SM_SCALE, -mx);
                float o0[4] = {0.f, 0.f, 0.f, 0.f}, o1[4] = {0.f, 0.f, 0.f, 0.f}, rs[4] = {0.f, 0.f, 0.f, 0.f};
                sc[8] = ex2(sc[8]); fetch(0); fetch(1); sc[9] = ex2(sc[9]);
                SFENCE();
                fetch(2); sc[0] = ex2(sc[0]); fetch(3); fetch(4); sc[1] = ex2(sc[1]); fetch(5); fetch(6); sc[2] = ex2(sc[2]);
                SFENCE();
                {
                    const uint32_t p = pack2(sc[8], sc[9]);
                    sc[3] = ex2(sc[3]); fetch(7);
                    mma8(o0, vm[0], vm[1], p);
                    mma8(o1, vm[2], vm[3], p);
                    sc[4] = ex2(sc[4]);
                    mma8(rs, one[0], one[1], p);
                    sc[5] = ex2(sc[5]);
                }
                SFENCE();
                {
                    const uint32_t p0 = pack2(sc[0], sc[1]), p1 = pack2(sc[2], sc[3]);
                    sc[6] = ex2(sc[6]);
                    mma16(o0, vf[0][0][0], vf[0][0][1], vf[0][0][2], vf[0][0][3], p0, p1);
                    SFENCE();
                    sc[7] = ex2(sc[7]);
                    mma16(o1, vf[1][0][0], vf[1][0][1], vf[1][0][2], vf[1][0][3], p0, p1);
                    SFENCE();
                    mma16(rs, one[0], one[1], one[2], one[3], p0, p1);
                    SFENCE();
                }
                {
                    const uint32_t p0 = pack2(sc[4], sc[5]), p1 = pack2(sc[6], sc[7]);
                    mma16(o0, vf[0][1][0], vf[0][1][1], vf[0][1][2], vf[0][1][3], p0, p1);
                    mma16(o1, vf[1][1][0], vf[1][1][1], vf[1][1][2], vf[1][1][3], p0, p1);
                    SFENCE();
                    mma16(rs, one[0], one[1], one[2], one[3], p0, p1);
                }
                const uint32_t e = max((__float_as_uint(cw * fmaxf(m4[0], 1.f)) >> 23) & 255u, 31u);
                SFENCE();
                stsm4t(lw + OFF_OB, pack2(o0[0], o0[1]), pack2(o0[2], o0[3]), pack2(o1[0], o1[1]), pack2(o1[2], o1[3]));
                if (w == 0) PROFT(13);
                bar_sync(NB_ATT, 128);
                uint32_t ob[16];
#pragma unroll
                for (int j = 0; j < 4; j++) ldsm4(ob + 4 * j, l16 + OFF_OB + j * 512);
                SFENCE();
                const float sig = __uint_as_float((278u - e) << 23);
                isig = __uint_as_float((e - 30u) << 23);
                const float sg0 = rcp(rs[0]) * sig, sg1 = rcp(rs[1]) * sig;
                SFENCE();
                auto tile = [&](uint32_t next, const char* p, auto LAST) {
                    float c[4][4];
#pragma unroll
                    for (int i = 0; i < 4; i++) c[i][0] = c[i][1] = c[i][2] = c[i][3] = 0.f;
#pragma unroll
                    for (int ks = 0; ks < 8; ks++) {
                        mma16(c[ks & 3], wf[ks][0], wf[ks][1], wf[ks][2], wf[ks][3], ob[2 * ks], ob[2 * ks + 1]);
                        if ((ks & 3) == 0) SFENCE();
                        if ((ks & 3) == 3 && !LAST.value) {
                            SFENCE();
#pragma unroll
                            for (int i = ks; i >= ks - 3; i--) { lds128(wf[i], next + i * 512); if (i == ks - 2) SFENCE(); }
                            if (ks == 3) SFENCE();
                        }
                    }
                    SFENCE();
                    if (LAST.value) { bar_arrive_if<NB_WIN, 256>(kind < 2); bar_arrive_if<NB_WIN, 384>(kind == 2); }
                    uint32_t v[4];
#pragma unroll
                    for (int i = 0; i < 4; i++)
                        v[i] = (__float_as_uint(fmaf((c[0][i] + c[1][i]) + (c[2][i] + c[3][i]), i & 1 ? sg1 : sg0, 12582912.f)) << 6) + (i < 2);
                    red_add64((u64*)p, v[0], v[2]);
                    red_add64((u64*)(p + 2048), v[1], v[3]);
                };
                tile(lo + 16384, rp, IC<0>{});
                if (w == 0) PROFT(7);
                tile(lo + 32768, rp + 49152, IC<0>{});
                if (kind == 2) tile(lo + 49152, rp + 98304, IC<0>{});
                tile(0, rp + (kind == 2 ? 28 * 4096 : 98304), IC<1>{});
                if (w == 0) PROFT(8);
                sts32(sb + OFF_MX + 16, __float_as_uint(isig));
                mbar_expect_elect(arm ^ (8 * pb), armb - (w == 2 && s == NSEG - 2 ? 40960 : 0));
                u64 y[20];
                uint32_t b[20];
                bool done[5] = {false, false, false, false, false};
                float z = isig;
                mbar_spin(bar + 8 * B_GO, pb);
                if (w == 0) PROFT(9);
                do {
#pragma unroll
                    for (int i = 0; i < 10; i++) {
                        if (STAG && (i == 2 || i == 5 || i == 8)) {
#pragma unroll
                            for (int k = 0; k < (i == 2 ? STAG / 100 : i == 5 ? STAG / 10 % 10 : STAG % 10); k++) asm volatile("ex2.approx.ftz.f32 %0,%0;" : "+f"(z));
                            asm volatile("{.reg .pred p; setp.ne.u32 p,%1,0; @p mov.b32 %0,%2;}" : "+r"(sfd) : "r"((uint32_t)never), "f"(z));
                            SFENCE();
                        }
                        ld_acc0(y[2 * i], y[2 * i + 1], lp + (i >> 1) * 32768 + (i & 1) * 4096);
                        if (STAG && (i == 1 || i == 4 || i == 7)) SFENCE();
                    }
                    uint32_t ok = 32u, late = 32u;
                    static_for<5>([&](auto IT) {
                        constexpr int it = IT.value;
                        if (it == 1) late = and3((uint32_t)y[4], (uint32_t)y[6], (uint32_t)y[8]);
                        else if (it == 2) late &= and3((uint32_t)y[10], (uint32_t)y[12], (uint32_t)y[14]);
                        else if (it == 3) ok &= late;
                        else ok = and3(ok, (uint32_t)y[4 * it], (uint32_t)y[4 * it + 2]);
                        if (it != 3) SFENCE();
                        if (it == 1 || it == 2) ok = and3(ok, (uint32_t)y[4 * it], (uint32_t)y[4 * it + 2]);
                        ok = and3(ok, (uint32_t)y[4 * it + 1], (uint32_t)y[4 * it + 3]);
                        const bool all = __all_sync(~0u, ok);
#pragma unroll
                        for (int j = 0; j < 4; j++) {
                            const u64 v = y[4 * it + j];
                            b[4 * it + j] = pack2((float)(int)(uint32_t)v, (float)(int)(uint32_t)(v >> 32));
                        }
                        sts128(lw + OFF_MEMB + it * 2048, b[4 * it], b[4 * it + 1], b[4 * it + 2], b[4 * it + 3]);
                        mbar_arrive_elect_if(bar + 8 * (B_MEM + it), all && !done[it]);
                        done[it] = all;
                        SFENCE();
                        if (it == 0 && w == 0) PROFT(10);
                    });
                } while (!done[4]);
                if (w == 0) PROFT(11);
                amax = b[0];
#pragma unroll
                for (int i = 1; i < 19; i += 2) amax = absmax2(amax, absmax2(b[i], b[i + 1]));
                amax = absmax2(amax, b[19]);
                const int adv = (s & 7) == 7 ? 163840 - 896 : 128;
                rp += adv; lp += adv;
            }
        }
        asm volatile("prefetch.tensormap [%0];" ::"l"(w & 1 ? &maps.wo1 : &maps.o2) : "memory");
        bar_sync(NB_KX, 384);
        bar_sync(NB_QK, 384);
        if (rank < 2) { bar_arrive(NB_W1, 512); bar_arrive(NB_WIN, 256); } else bar_arrive(NB_W1, 480);
    } else {
        asm volatile("setmaxnreg.dec.sync.aligned.u32 %0;" ::"n"(48));
        const uint32_t rank = cta_rank();
        const int w = warp - 12;
        pdl_wait();
        if (blockIdx.x == 2 && w == 3) asm volatile("st.release.gpu.global.u32 [%0],1;" ::"l"(g_started + layer) : "memory");
        uint32_t* sy = g_sync + layer * SYNC_LAYER;
        if (w == 1) TLI(690 + blockIdx.x, 1, gtime());
        if (w == 1) {
            mbar_expect_elect(bar + 8 * B_XT, 40960);
            bulk_g2s_elect(sb + OFF_X, g_xn, 40960, bar + 8 * B_XT);
            bar_sync(NB_PRO, 288);
            TLI(690 + blockIdx.x, 2, gtime());
            if (rank == 2) mbar_spin(bar + 8 * B_ST, 0);
            else mbar_arrive_remote_elect(mapa(bar + 8 * B_ST, 2));
            mbar_spin(bar + 8 * B_XT, 0);
            bar_arrive(NB_LD, 288);
            mbar_expect_elect(bar + 8 * (B_XT + 1), rank < 2 ? 45056 : 40960);
        }
        uint32_t* hp = sy + 1024;
        auto hint = [&](uint32_t t) {
            asm volatile("{.reg .pred p; elect.sync _|p, 0xffffffff; @p red.relaxed.gpu.global.max.u32 [%0+4],%1; @p red.relaxed.gpu.global.add.u32 [%0],1;}"
                         ::"l"(hp), "r"(t) : "memory");
        };
        if (rank == 2) {
            if (w == 0) {
                for (int s = -1; s < NSEG - 1; s++) {
                    const uint32_t pb = s & 1, va = sb + OFF_VX + (pb ^ 1) * 8192 + 4096, vb = bar + 8 * (B_VX + (pb ^ 1));
                    bar_sync(NB_KF, 288);
                    fence_async();
                    bulk_s2s_elect(mapa(va, 0), va, 4096, mapa(vb, 0));
                    bulk_s2s_elect(mapa(va, 1), va, 4096, mapa(vb, 1));
                    if (s >= 0) mbar_spin(bar + 8 * (B_XD + pb), (s >> 1) & 1);
                    bar_sync(NB_W1, 480);
                }
            } else if (w == 1) {
                const unsigned char *pn = g_p + h * 12288, *px = g_xn + 40960;
                const uint32_t* pf = sy + wk::SY_P + h;
                for (int s = -1, nb = -1; s < NSEG - 1; s++, pn += H_ * 12288, px += 40960) {
                    const uint32_t pb = s & 1, xt = bar + 8 * (B_XT + pb), qa = sb + OFF_Q + (pb ^ 1) * 5120 + 1024;
                    if (s >= 0) mbar_spin(bar + 8 * (B_X1 + pb), (s >> 1) & 1);
                    if (s + 2 < NSEG) bulk_g2s_all3_elect(sb + OFF_X + pb * 40960, px, 40960, xt);
                    if (s == nb) {
                        while (__any_sync(~0u, ld_acquire(pf) < 3)) {}
                        pf += H_;
                        nb += s < 0 ? 4 : 6;
                    }
                    bulk_g2s_all3_elect(sb + OFF_VX + (pb ^ 1) * 8192, pn + 8192, 4096, bar + 8 * (B_VX + (pb ^ 1)));
                    bulk_g2s_elect(mapa(qa, 0), pn, 4096, mapa(xt, 0));
                    bulk_g2s_elect(mapa(qa, 1), pn + 4096, 4096, mapa(xt, 1));
                    mbar_spin(xt, ((s + 2) >> 1) & 1);
                    bar_sync(NB_W1, 480);
                }
                mbar_spin(bar + 8 * (B_VX + 1), 1);
            } else if (w == 2) {
                const char* pf = lane < 5 ? (const char*)(g_acc + layer * ACC_LAYER) + (5 * h + lane) * 1024 : (const char*)hp;
                const int pfa = lane < 5 ? 163840 : 1024;
                if (lane < 6) for (int i = 0; i < 8; i++) prefetch_l2(pf + i * 128);
                __syncwarp();
                const uint32_t go = mapa(bar + 8 * B_GO, min(lane, 2));
                for (int s = 0; s < NSEG - 1; s++, hp += 32) {
                    bar_sync(NB_W1, 480);
                    sts32(sb + OFF_MX + 32, 0);
                    uint32_t t = gtime32(), t0 = clk(), c, tm;
                    hint(t);
                    if (h == 0) TLI(940 + s, 0, t);
                    if (lane < 6 && s < NSEG - 8) prefetch_l2(pf + ((s >> 3) + 1) * pfa + (s & 7) * 128);
                    __syncwarp();
                    while (clk() - t0 < (uint32_t)delay2) {}
                    do asm volatile("ld.relaxed.gpu.global.v2.u32 {%0,%1},[%2];" : "=r"(c), "=r"(tm) : "l"(hp) : "memory"); while (__any_sync(~0u, c != 3 * H_));
                    const uint32_t wait = min(tm - t, 10000u) * 7 / 4 + delay;
                    while (clk() - t0 < wait) {}
                    if (lane < 3) mbar_arrive_remote(go);
                    __syncwarp();
                }
                bar_sync(NB_W1, 480);
            }
        } else {
            if (w < 2) sts32(sb + OFF_PT + w * 768 + 640 + lane * 4, 0u);
            const uint32_t px = opaque(sb + OFF_PX + (w & 1) * 1280 + lane * 8);
            const uint32_t pt = opaque(sb + OFF_PT + (w & 1) * 768 + lane * 4);
            uint32_t os = opaque(sb + OFF_OST + (lane >> 4) * 1024 + w * 256 + (lane & 15) * 16);
            uint32_t& sfd = os;
            const int lim = opaque(8 * w + g + 8 - 2 * q);
            unsigned char* op = g_o + h * 8192 + rank * 2048;
            uint32_t* oc = sy + wk::SY_O;
            auto report = [&]() {
                bulk_wait<0>();
                __syncwarp();
                asm volatile("{.reg .pred p; elect.sync _|p, 0xffffffff; @p red.relaxed.gpu.global.add.u32 [%0],1;}" ::"l"(oc) : "memory");
                oc++;
            };
            auto store_o = [&](int n) {
                bulk_s2g_elect(op, sb + OFF_OST + (n & 1) * 4096, 2048);
                bulk_s2g_elect(op + 4096, sb + OFF_OST + (n & 1) * 4096 + 2048, 2048);
                bulk_commit();
                op += H_ * 8192;
            };
            for (int s = 0; s < NSEG; s++) {
                const uint32_t pb = s & 1, ph = (s >> 1) & 1;
                if ((w >> 1) != rank) { if (s >= 1) mbar_spin(bar + 8 * B_PXE, pb ^ 1); }
                else if (w & 1) mbar_spin(bar + 8 * (B_XT + (pb ^ 1)), ((s + 1) >> 1) & 1);
                else mbar_expect_elect(bar + 8 * B_PXF, rank ? 2560 : 1536);
                const u64 dq = mkdesc(sb + OFF_Q + pb * 5120 + 1024, 128, 512), dk = mkdesc(sb + OFF_K + pb * 5120, 128, 1024);
                SFENCE();
                bar_sync(NB_W1, 512);
                float c[20];
                wg_fence();
                wgmma_n40_ss<0>(c, dq, dk);
#pragma unroll
                for (int ks = 1; ks < 4; ks++) wgmma_n40_ss<1>(c, dq + ks * 16, dk + ks * 16);
                wg_commit();
                bar_arrive(NB_X, 384);
                if (w == 2 * rank) { hint(gtime32()); hp += 32; }
                wg_wait<0>();
                if ((w >> 1) != rank) {
                    const uint32_t pa = mapa(px, rank ^ 1), pf = mapa(bar + 8 * B_PXF, rank ^ 1);
#pragma unroll
                    for (int nt = 0; nt < 5; nt++)
                        if (nt < 3 || rank == 0) st_async2(pa + nt * 256, __float_as_uint(c[4 * nt]), __float_as_uint(c[4 * nt + 1]), pf);
                    if ((w & 1) && s) store_o(s - 1);
                    mbar_spin(bar + 8 * (w & 1 ? B_VX : B_VM) + 8 * pb, ph);
                } else {
                    mbar_spin(bar + 8 * B_PXF, pb);
                    float u[10];
#pragma unroll
                    for (int nt = 0; nt < 5; nt++) lds64f(u[2 * nt], u[2 * nt + 1], px + nt * 256);
#pragma unroll
                    for (int i = 0; i < 10; i++) u[i] = 8 * (i >> 1) + (i & 1) <= lim ? u[i] + c[4 * (i >> 1) + (i & 1)] : -INFINITY;
                    float mx = fmaxf(fmaxf(fmaxf(fmaxf(u[0], u[1]), fmaxf(u[2], u[3])), fmaxf(fmaxf(u[4], u[5]), fmaxf(u[6], u[7]))), fmaxf(u[8], u[9]));
                    const float m1 = __shfl_xor_sync(~0u, mx, 1), m2 = __shfl_xor_sync(~0u, mx, 2), m3 = __shfl_xor_sync(~0u, mx, 3);
                    mx = fmaxf(fmaxf(mx, m1), fmaxf(m2, m3)) * SM_SCALE;
#pragma unroll
                    for (int i = 0; i < 10; i++) u[i] = ex2(fmaf(u[i], SM_SCALE, -mx));
                    float sum = (((u[0] + u[1]) + (u[2] + u[3])) + ((u[4] + u[5]) + (u[6] + u[7]))) + (u[8] + u[9]);
                    const float s1 = __shfl_xor_sync(~0u, sum, 1), s2 = __shfl_xor_sync(~0u, sum, 2), s3 = __shfl_xor_sync(~0u, sum, 3);
                    sum = rcp((sum + s1) + (s2 + s3));
#pragma unroll
                    for (int nt = 0; nt < 5; nt++) sts32(pt + (nt ? nt - 1 : 4) * 128, pack2(u[2 * nt] * sum, u[2 * nt + 1] * sum));
                }
                float acc[2][8];
                const u64 dv = mkdesc(sb + OFF_VX + pb * 8192, 128, 512), dp = mkdesc(sb + OFF_PT, 128, 768);
                const u64 dm = mkdesc(sb + OFF_VM + pb * 2048, 0, 128);
                fence_async();
                bar_sync(NB_WIN, 256);
                wg_fence();
#pragma unroll
                for (int m = 0; m < 2; m++) {
                    wgmma_n16_ss<0>(acc[m], dv + m * 256, dp);
                    wgmma_n16_ss<1>(acc[m], dv + m * 256 + 16, dp + 16);
                    wgmma_n16_ss<1>(acc[m], dm + m * 64, dp + 32);
                }
                wg_commit();
                bar_arrive_if<NB_W2, 384>(s < NSEG - 1);
                wg_wait<0>();
#pragma unroll
                for (int m = 0; m < 2; m++)
                    stsm4t(os + pb * 4096 + m * 2048, pack2(acc[m][0], acc[m][1]), pack2(acc[m][2], acc[m][3]), pack2(acc[m][4], acc[m][5]), pack2(acc[m][6], acc[m][7]));
                fence_async();
                mbar_arrive_remote_elect(mapa(bar + 8 * (B_XD + pb), 2));
                if ((w >> 1) == rank) mbar_arrive_remote_elect(mapa(bar + 8 * B_PXE, rank ^ 1));
                else if ((w & 1) && s) report();
            }
            bar_sync(NB_W2, 128);
            if (w == 3 - 2 * rank) {
                store_o(NSEG - 1);
                report();
            }
        }
    }
    __syncwarp();
    if (lane < 3) mbar_arrive_remote(mapa(bar + 8 * B_FIN, lane));
    mbar_wait(bar + 8 * B_FIN, 0);
    TLE(2 + 5 * layer);
    fence_async();
    if (warp < 8) asm volatile("setmaxnreg.dec.sync.aligned.u32 128;"); else asm volatile("setmaxnreg.inc.sync.aligned.u32 128;");
    }
    const int b = blockIdx.x;
    worker<false>(sb, maps, x, x1, layer, b >= 3 * H_ ? b - 3 * H_ : b < 10 * SPLIT_B ? wk::I_SB + b : -1, gridDim.x - 3 * H_);
}

int g_delay = 5001350, g_layers = 2;

void make_map(CUtensorMap* m, CUtensorMapDataType dt, const void* p, const cuuint64_t* dim, const cuuint64_t* str, const cuuint32_t* box, CUtensorMapSwizzle sw) {
    typedef CUresult (*Fn)(CUtensorMap*, CUtensorMapDataType, cuuint32_t, void*, const cuuint64_t*, const cuuint64_t*, const cuuint32_t*,
                           const cuuint32_t*, CUtensorMapInterleave, CUtensorMapSwizzle, CUtensorMapL2promotion, CUtensorMapFloatOOBfill);
    static Fn fn = nullptr;
    if (!fn) {
        cudaDriverEntryPointQueryResult qr;
        cudaGetDriverEntryPoint("cuTensorMapEncodeTiled", (void**)&fn, cudaEnableDefault, &qr);
    }
    const cuuint32_t es[3] = {1, 1, 1};
    fn(m, dt, 3, (void*)p, dim, str, box, es, CU_TENSOR_MAP_INTERLEAVE_NONE, sw, CU_TENSOR_MAP_L2_PROMOTION_L2_128B, CU_TENSOR_MAP_FLOAT_OOB_FILL_NONE);
}
void map_weight(CUtensorMap* m, const bf16* p, int rows, int cols, int ng, int br = 64) {
    const cuuint64_t dim[3] = {64, (cuuint64_t)rows, (cuuint64_t)cols / 64}, str[2] = {(cuuint64_t)cols * 2, 128};
    const cuuint32_t box[3] = {64, (cuuint32_t)br, (cuuint32_t)ng};
    make_map(m, CU_TENSOR_MAP_DATA_TYPE_BFLOAT16, p, dim, str, box, CU_TENSOR_MAP_SWIZZLE_128B);
}
void map_pieces(CUtensorMap* m, const void* p, int np, int ns) {
    const cuuint64_t dim[3] = {256, (cuuint64_t)np * 2, NSEG}, str[2] = {2048, (cuuint64_t)np * 4096};
    const cuuint32_t box[3] = {256, 2, (cuuint32_t)ns};
    make_map(m, CU_TENSOR_MAP_DATA_TYPE_UINT64, p, dim, str, box, CU_TENSOR_MAP_SWIZZLE_NONE);
}

template <class... P, class... A> void launch(void (*k)(P...), int grid, int block, int smem, int cluster, bool pdl, A... args) {
    cudaLaunchConfig_t c = {};
    c.gridDim = dim3(grid); c.blockDim = dim3(block); c.dynamicSmemBytes = smem; c.stream = cudaStreamPerThread;
    cudaLaunchAttribute at[2];
    int n = 0;
    if (cluster > 1) { at[n].id = cudaLaunchAttributeClusterDimension; at[n].val.clusterDim.x = cluster; at[n].val.clusterDim.y = 1; at[n].val.clusterDim.z = 1; n++; }
    if (pdl) { at[n].id = cudaLaunchAttributeProgrammaticStreamSerialization; at[n].val.programmaticStreamSerializationAllowed = 1; n++; }
    c.attrs = at; c.numAttrs = n;
    cudaLaunchKernelEx(&c, k, args...);
}

int max_clusters() {
    cudaLaunchConfig_t c = {};
    c.gridDim = dim3(3 * H_); c.blockDim = dim3(512); c.dynamicSmemBytes = rec::SMEM;
    cudaLaunchAttribute at[1];
    at[0].id = cudaLaunchAttributeClusterDimension; at[0].val.clusterDim.x = 3; at[0].val.clusterDim.y = 1; at[0].val.clusterDim.z = 1;
    c.attrs = at; c.numAttrs = 1;
    int n = 0;
    cudaOccupancyMaxActiveClusters(&n, rec_kernel, &c);
    return n;
}

}

extern "C" void kernel_launch(void* const* d_in, const int* in_sizes, int n_in, void* d_out, int out_size) {
    const bf16* x = (const bf16*)d_in[0];
    const bf16* mem0 = (const bf16*)d_in[1];
    const bf16* Wq = (const bf16*)d_in[2];
    const bf16* Wk = (const bf16*)d_in[3];
    const bf16* Wv = (const bf16*)d_in[4];
    const bf16* Wo = (const bf16*)d_in[5];
    const bf16* wr = (const bf16*)d_in[8];
    const bf16* wi = (const bf16*)d_in[9];
    cudaFuncSetAttribute(rec_kernel, cudaFuncAttributeMaxDynamicSharedMemorySize, rec::SMEM);
    cudaFuncSetAttribute(side_kernel, cudaFuncAttributeMaxDynamicSharedMemorySize, wk::SMEM);
    cudaFuncSetAttribute(colfft_kernel, cudaFuncAttributeMaxDynamicSharedMemorySize, CF_SMEM);
    Maps maps;
    void *pxn, *po;
    cudaGetSymbolAddress(&pxn, g_xn);
    cudaGetSymbolAddress(&po, g_o);
    map_weight(&maps.wq2, Wq, D_, 4096, 2); map_weight(&maps.wv1, Wv, D_, 4096, 1);
    map_weight(&maps.wo2, Wo, 4096, D_, 2); map_weight(&maps.wo1, Wo, 4096, D_, 1, 192);
    map_pieces(&maps.x6, pxn, 10, 6); map_pieces(&maps.x4, pxn, 10, 4);
    map_pieces(&maps.o6, po, 64, 6); map_pieces(&maps.o2, po, 64, 2);
    bf16 *x1, *x2;
    cudaGetSymbolAddress((void**)&x1, g_x1);
    cudaGetSymbolAddress((void**)&x2, g_x2);
    constexpr int ONE_PER_SM = 116 * 1024;
    cudaFuncSetAttribute(rowfft_kernel, cudaFuncAttributeMaxDynamicSharedMemorySize, ONE_PER_SM);
    cudaFuncSetAttribute(rowifft_kernel, cudaFuncAttributeMaxDynamicSharedMemorySize, ONE_PER_SM);
    static int ncl = 0, nsm = 0;
    if (!ncl) { ncl = max_clusters(); cudaDeviceGetAttribute(&nsm, cudaDevAttrMultiProcessorCount, 0); }
    maps.wr = wr; maps.wi = wi;
    launch(prep_kernel, 128, 512, 0, 1, false, x, Wq, Wk, Wv, Wo);
    for (int layer = 0; layer < g_layers; layer++) {
        const bf16* xin = layer ? x2 : x;
        launch(rec_kernel, 3 * ncl, 512, rec::SMEM, 3, true, maps, xin, x1, mem0, Wq, Wk, Wv, Wo, layer, g_delay % 10000, g_delay / 10000);
        launch(side_kernel, max(nsm - 3 * ncl, 1), 512, wk::SMEM, 1, true, maps, xin, x1, layer, 3 * (ncl - H_));
        launch(rowfft_kernel, 128, 256, ONE_PER_SM, 1, true, xin, x1, Wq, Wk, Wv, layer);
        launch(colfft_kernel, 107, 384, CF_SMEM, 1, true, layer);
        launch(rowifft_kernel, 128, 256, ONE_PER_SM, 1, true, (const bf16*)x1, layer ? (bf16*)d_out : x2, layer);
    }
}
```

```cpp
#include <cuda_runtime.h>
#include <cuda_bf16.h>
#include <cuda.h>
#include <stdint.h>

#define DEV __device__ __forceinline__
typedef unsigned long long u64;
typedef __nv_bfloat16 bf16;

namespace {

constexpr int S_ = 2048, D_ = 640, H_ = 32, E_ = 128, NSEG = 64;

__device__ __align__(1024) unsigned char g_xn[S_ * D_ * 2];
__device__ __align__(1024) unsigned char g_o[S_ * H_ * E_ * 2];
constexpr int ACC_LAYER = 32 * 5120;
__device__ __align__(4096) u64 g_acc[2 * ACC_LAYER];
__device__ __align__(16) float g_nrm[256];
__device__ __align__(1024) unsigned char g_p[NSEG * H_ * 3 * 4096];
constexpr int SYNC_LAYER = 1024 + 64 * 32;
__device__ __align__(128) uint32_t g_sync[2 * SYNC_LAYER];
__device__ uint32_t g_started[2];
__device__ __align__(1024) bf16 g_x1[S_ * D_];
__device__ __align__(1024) bf16 g_x2[S_ * D_];
constexpr int YT_ROWS = 128;
__device__ __align__(1024) float g_yt[2 * YT_ROWS * D_];
constexpr int NCOL = 321;
__device__ __align__(1024) unsigned char g_z[NCOL * 8192];
__device__ __align__(1024) unsigned char g_wt[NCOL * 8192];
__device__ __align__(1024) uint4 g_f128[2 * 8 * 256];
__device__ __align__(1024) uint4 g_f64[2 * 4 * 128];
__device__ __align__(1024) bf16 g_g32[2 * 4096];
#define TLI(id, k, v)
#define TLS(i)
#define TLE(i)

DEV uint32_t s2u(const void* p) { return (uint32_t)__cvta_generic_to_shared(p); }
DEV uint32_t clk() { uint32_t c; asm volatile("mov.u32 %0,%%clock;" : "=r"(c)::"memory"); return c; }
DEV uint32_t gtime32() { uint32_t t; asm volatile("mov.u32 %0,%%globaltimer_lo;" : "=r"(t)::"memory"); return t; }
DEV uint32_t cta_rank() { uint32_t r; asm volatile("mov.u32 %0,%%cluster_ctarank;" : "=r"(r)); return __shfl_sync(~0u, r, 0); }
DEV uint32_t mapa(uint32_t a, uint32_t r) { uint32_t o; asm("mapa.shared::cluster.u32 %0,%1,%2;" : "=r"(o) : "r"(a), "r"(r)); return o; }
DEV void mbar_init(uint32_t b, uint32_t n) { asm volatile("mbarrier.init.shared::cta.b64 [%0],%1;" ::"r"(b), "r"(n) : "memory"); }
DEV bool mbar_try(uint32_t b, uint32_t par, int) {
    uint32_t ok;
    asm volatile("{.reg .pred p; mbarrier.test_wait.parity.shared::cta.b64 p,[%1],%2; selp.u32 %0,1,0,p;}" : "=r"(ok) : "r"(b), "r"(par) : "memory");
    return ok;
}
DEV bool mbar_try(uint32_t b, uint32_t par) {
    uint32_t ok;
    asm volatile("{.reg .pred p; mbarrier.try_wait.parity.shared::cta.b64 p,[%1],%2; selp.u32 %0,1,0,p;}" : "=r"(ok) : "r"(b), "r"(par) : "memory");
    return ok;
}
constexpr uint32_t SPIN_LIMIT = 1u << 18;
DEV void die() { __trap(); }
DEV void mbar_wait(uint32_t b, uint32_t par) {
    uint32_t n = 0;
    while (!mbar_try(b, par)) if (++n > SPIN_LIMIT) die();
}
DEV void mbar_spin(uint32_t b, uint32_t par) { while (!mbar_try(b, par)) {} }
DEV uint32_t opaque(uint32_t x) { return __shfl_xor_sync(~0u, x, 0); }
#define SFENCE() asm volatile("{.reg .pred p; setp.ne.u32 p,%1,0; @p mov.u32 %0,%%clock;}" : "+r"(sfd) : "r"((uint32_t)never) : "memory")
DEV void mbar_arrive(uint32_t b) { asm volatile("mbarrier.arrive.shared::cta.b64 _,[%0];" ::"r"(b) : "memory"); }
DEV void mbar_arrive_elect(uint32_t b) { asm volatile("{.reg .pred p; elect.sync _|p, 0xffffffff; @p mbarrier.arrive.shared::cta.b64 _,[%0];}" ::"r"(b) : "memory"); }
DEV void mbar_arrive_elect_if(uint32_t b, bool c) {
    asm volatile("{.reg .pred p, q; setp.ne.u32 q,%1,0; elect.sync _|p, 0xffffffff; and.pred p,p,q; @p mbarrier.arrive.shared::cta.b64 _,[%0];}" ::"r"(b), "r"((uint32_t)c) : "memory");
}
DEV void mbar_expect_elect(uint32_t b, uint32_t tx) {
    asm volatile("{.reg .pred p; elect.sync _|p, 0xffffffff; @p mbarrier.arrive.expect_tx.shared::cta.b64 _,[%0],%1;}" ::"r"(b), "r"(tx) : "memory");
}
DEV void mbar_arrive_remote_elect(uint32_t b) { asm volatile("{.reg .pred p; elect.sync _|p, 0xffffffff; @p mbarrier.arrive.shared::cluster.b64 _,[%0];}" ::"r"(b) : "memory"); }
DEV bool elect() { uint32_t r; asm volatile("{.reg .pred p; elect.sync _|p, 0xffffffff; selp.u32 %0,1,0,p;}" : "=r"(r)); return r; }
DEV void mbar_arrive_remote(uint32_t b) { asm volatile("mbarrier.arrive.shared::cluster.b64 _,[%0];" ::"r"(b) : "memory"); }
DEV void mbar_expect(uint32_t b, uint32_t tx) { asm volatile("mbarrier.arrive.expect_tx.shared::cta.b64 _,[%0],%1;" ::"r"(b), "r"(tx) : "memory"); }
DEV void bar_sync(int id, int n) { asm volatile("bar.sync %0,%1;" ::"r"(id), "r"(n) : "memory"); }
DEV void bar_arrive(int id, int n) { asm volatile("bar.arrive %0,%1;" ::"r"(id), "r"(n) : "memory"); }
template <int ID, int N> DEV void bar_arrive_if(bool p) {
    asm volatile("{.reg .pred p; setp.ne.u32 p,%0,0; @p bar.arrive %1,%2;}" ::"r"((uint32_t)p), "n"(ID), "n"(N) : "memory");
}
DEV void prefetch_bulk(const void* p, uint32_t bytes) { asm volatile("cp.async.bulk.prefetch.L2.global [%0],%1;" ::"l"(p), "r"(bytes) : "memory"); }
DEV void prefetch_l2(const void* p) { asm volatile("prefetch.global.L2 [%0];" ::"l"(p) : "memory"); }
template <int ID, int N> DEV void bar_sync_if(bool p) {
    asm volatile("{.reg .pred p; setp.ne.u32 p,%0,0; @p bar.sync %1,%2;}" ::"r"((uint32_t)p), "n"(ID), "n"(N) : "memory");
}
DEV void st_remote(uint32_t a, uint32_t x) { asm volatile("st.relaxed.cluster.shared::cluster.u32 [%0],%1;" ::"r"(a), "r"(x) : "memory"); }
DEV void st_async1(uint32_t a, uint32_t x, uint32_t b) {
    asm volatile("st.async.shared::cluster.mbarrier::complete_tx::bytes.u32 [%0],%1,[%2];" ::"r"(a), "r"(x), "r"(b) : "memory");
}
DEV void st_async2(uint32_t a, uint32_t x, uint32_t y, uint32_t b) {
    asm volatile("st.async.shared::cluster.mbarrier::complete_tx::bytes.v2.u32 [%0],{%1,%2},[%3];" ::"r"(a), "r"(x), "r"(y), "r"(b) : "memory");
}
DEV void st_async4(uint32_t a, uint32_t x, uint32_t y, uint32_t z, uint32_t w, uint32_t b) {
    asm volatile("st.async.shared::cluster.mbarrier::complete_tx::bytes.v4.u32 [%0],{%1,%2,%3,%4},[%5];" ::"r"(a), "r"(x), "r"(y), "r"(z), "r"(w), "r"(b) : "memory");
}
DEV void bulk_g2s(uint32_t dst, const void* src, uint32_t bytes, uint32_t b) {
    asm volatile("cp.async.bulk.shared::cluster.global.mbarrier::complete_tx::bytes [%0],[%1],%2,[%3];" ::"r"(dst), "l"(src), "r"(bytes), "r"(b) : "memory");
}
DEV void bulk_g2s_elect(uint32_t dst, const void* src, uint32_t bytes, uint32_t b) {
    asm volatile("{.reg .pred p; elect.sync _|p, 0xffffffff; @p cp.async.bulk.shared::cluster.global.mbarrier::complete_tx::bytes [%0],[%1],%2,[%3];}"
                 ::"r"(dst), "l"(src), "r"(bytes), "r"(b) : "memory");
}
DEV void bulk_g2s_all3_elect(uint32_t dst, const void* src, uint32_t bytes, uint32_t b) {
    asm volatile("{.reg .pred p; elect.sync _|p, 0xffffffff; @p cp.async.bulk.shared::cluster.global.mbarrier::complete_tx::bytes.multicast::cluster [%0],[%1],%2,[%3],%4;}"
                 ::"r"(dst), "l"(src), "r"(bytes), "r"(b), "h"((unsigned short)7) : "memory");
}
DEV void bulk_s2s_elect(uint32_t dst, uint32_t src, uint32_t bytes, uint32_t b) {
    asm volatile("{.reg .pred p; elect.sync _|p, 0xffffffff; @p cp.async.bulk.shared::cluster.shared::cta.mbarrier::complete_tx::bytes [%0],[%1],%2,[%3];}"
                 ::"r"(dst), "r"(src), "r"(bytes), "r"(b) : "memory");
}
DEV void bulk_s2g_elect(void* dst, uint32_t src, uint32_t bytes) {
    asm volatile("{.reg .pred p; elect.sync _|p, 0xffffffff; @p cp.async.bulk.global.shared::cta.bulk_group [%0],[%1],%2;}" ::"l"(dst), "r"(src), "r"(bytes) : "memory");
}
DEV void bulk_s2s(uint32_t dst, uint32_t src, uint32_t bytes, uint32_t b) {
    asm volatile("cp.async.bulk.shared::cluster.shared::cta.mbarrier::complete_tx::bytes [%0],[%1],%2,[%3];" ::"r"(dst), "r"(src), "r"(bytes), "r"(b) : "memory");
}
DEV void bulk_s2g(void* dst, uint32_t src, uint32_t bytes) {
    asm volatile("cp.async.bulk.global.shared::cta.bulk_group [%0],[%1],%2;" ::"l"(dst), "r"(src), "r"(bytes) : "memory");
}
DEV void tma3d(uint32_t dst, const CUtensorMap* m, int c0, int c1, int c2, uint32_t b) {
    asm volatile("cp.async.bulk.tensor.3d.shared::cluster.global.mbarrier::complete_tx::bytes [%0],[%1,{%3,%4,%5}],[%2];"
                 ::"r"(dst), "l"(m), "r"(b), "r"(c0), "r"(c1), "r"(c2) : "memory");
}
DEV void bulk_commit() { asm volatile("cp.async.bulk.commit_group;" ::: "memory"); }
template <int N> DEV void bulk_wait() { asm volatile("cp.async.bulk.wait_group %0;" ::"n"(N) : "memory"); }
template <int N> DEV void bulk_wait_read() { asm volatile("cp.async.bulk.wait_group.read %0;" ::"n"(N) : "memory"); }
DEV void flag_add(uint32_t* p) { asm volatile("red.relaxed.gpu.global.add.u32 [%0],1;" ::"l"(p) : "memory"); }
DEV uint32_t ld_acquire(const uint32_t* p) { uint32_t v; asm volatile("ld.acquire.gpu.global.u32 %0,[%1];" : "=r"(v) : "l"(p) : "memory"); return v; }
DEV void flag_wait(const uint32_t* p, uint32_t n) {
    for (uint32_t it = 0; ld_acquire(p) < n; __nanosleep(40)) if (++it > (SPIN_LIMIT << 3)) die();
}
DEV void cp16(uint32_t dst, const void* src) { asm volatile("cp.async.cg.shared.global [%0],[%1],16;" ::"r"(dst), "l"(src) : "memory"); }
DEV void cp_commit() { asm volatile("cp.async.commit_group;" ::: "memory"); }
template <int N> DEV void cp_wait() { asm volatile("cp.async.wait_group %0;" ::"n"(N) : "memory"); }
DEV uint32_t lds32(uint32_t a) { uint32_t x; asm volatile("ld.shared.u32 %0,[%1];" : "=r"(x) : "r"(a) : "memory"); return x; }
DEV void fence_async() { asm volatile("fence.proxy.async.shared::cta;" ::: "memory"); }
DEV uint32_t pack2(float lo, float hi) { uint32_t r; asm("cvt.rn.bf16x2.f32 %0,%1,%2;" : "=r"(r) : "f"(hi), "f"(lo)); return r; }
DEV uint32_t prmt(uint32_t a, uint32_t b, uint32_t s) { uint32_t r; asm("prmt.b32 %0,%1,%2,%3;" : "=r"(r) : "r"(a), "r"(b), "r"(s)); return r; }
DEV float ex2(float x) { float r; asm("ex2.approx.ftz.f32 %0,%1;" : "=f"(r) : "f"(x)); return r; }
DEV float sqrt_approx(float x) { float r; asm("sqrt.approx.ftz.f32 %0,%1;" : "=f"(r) : "f"(x)); return r; }
DEV float rcp(float x) { float r; asm("rcp.approx.ftz.f32 %0,%1;" : "=f"(r) : "f"(x)); return r; }
DEV void lds128(uint32_t* r, uint32_t a) { asm volatile("ld.shared.v4.u32 {%0,%1,%2,%3},[%4];" : "=r"(r[0]), "=r"(r[1]), "=r"(r[2]), "=r"(r[3]) : "r"(a) : "memory"); }
DEV void lds64(uint32_t* r, uint32_t a) { asm volatile("ld.shared.v2.u32 {%0,%1},[%2];" : "=r"(r[0]), "=r"(r[1]) : "r"(a) : "memory"); }
DEV void lds64f(float& x, float& y, uint32_t a) { asm volatile("ld.shared.v2.f32 {%0,%1},[%2];" : "=f"(x), "=f"(y) : "r"(a) : "memory"); }
DEV void lds128f(float* r, uint32_t a) { asm volatile("ld.shared.v4.f32 {%0,%1,%2,%3},[%4];" : "=f"(r[0]), "=f"(r[1]), "=f"(r[2]), "=f"(r[3]) : "r"(a) : "memory"); }
DEV void sts128(uint32_t a, uint32_t x, uint32_t y, uint32_t z, uint32_t w) { asm volatile("st.shared.v4.u32 [%0],{%1,%2,%3,%4};" ::"r"(a), "r"(x), "r"(y), "r"(z), "r"(w) : "memory"); }
DEV void sts64(uint32_t a, uint32_t x, uint32_t y) { asm volatile("st.shared.v2.u32 [%0],{%1,%2};" ::"r"(a), "r"(x), "r"(y) : "memory"); }
DEV void sts32(uint32_t a, uint32_t x) { asm volatile("st.shared.u32 [%0],%1;" ::"r"(a), "r"(x) : "memory"); }
DEV void ldsm4(uint32_t* r, uint32_t a) { asm volatile("ldmatrix.sync.aligned.m8n8.x4.shared.b16 {%0,%1,%2,%3},[%4];" : "=r"(r[0]), "=r"(r[1]), "=r"(r[2]), "=r"(r[3]) : "r"(a) : "memory"); }
DEV void ldsm4t(uint32_t* r, uint32_t a) { asm volatile("ldmatrix.sync.aligned.m8n8.x4.trans.shared.b16 {%0,%1,%2,%3},[%4];" : "=r"(r[0]), "=r"(r[1]), "=r"(r[2]), "=r"(r[3]) : "r"(a) : "memory"); }
DEV void ldsm2(uint32_t* r, uint32_t a) { asm volatile("ldmatrix.sync.aligned.m8n8.x2.shared.b16 {%0,%1},[%2];" : "=r"(r[0]), "=r"(r[1]) : "r"(a) : "memory"); }
DEV void stsm4t(uint32_t a, uint32_t x, uint32_t y, uint32_t z, uint32_t w) { asm volatile("stmatrix.sync.aligned.m8n8.x4.trans.shared.b16 [%0],{%1,%2,%3,%4};" ::"r"(a), "r"(x), "r"(y), "r"(z), "r"(w) : "memory"); }
DEV void stsm4(uint32_t a, uint32_t x, uint32_t y, uint32_t z, uint32_t w) { asm volatile("stmatrix.sync.aligned.m8n8.x4.shared.b16 [%0],{%1,%2,%3,%4};" ::"r"(a), "r"(x), "r"(y), "r"(z), "r"(w) : "memory"); }
DEV void stsm2(uint32_t a, uint32_t x, uint32_t y) { asm volatile("stmatrix.sync.aligned.m8n8.x2.shared.b16 [%0],{%1,%2};" ::"r"(a), "r"(x), "r"(y) : "memory"); }
DEV void sts128f_if(uint32_t a, const float* v, bool p) {
    asm volatile("{.reg .pred p; setp.ne.u32 p,%5,0; @p st.shared.v4.f32 [%0],{%1,%2,%3,%4};}" ::"r"(a), "f"(v[0]), "f"(v[1]), "f"(v[2]), "f"(v[3]), "r"((uint32_t)p) : "memory");
}
DEV void lds128f_if(float* v, uint32_t a, bool p) {
    asm volatile("{.reg .pred p; setp.ne.u32 p,%5,0; @p ld.shared.v4.f32 {%0,%1,%2,%3},[%4];}"
                 : "+f"(v[0]), "+f"(v[1]), "+f"(v[2]), "+f"(v[3]) : "r"(a), "r"((uint32_t)p) : "memory");
}
DEV void stsm2t_if(uint32_t a, uint32_t x, uint32_t y, bool p) {
    asm volatile("{.reg .pred p; setp.ne.u32 p,%3,0; @p stmatrix.sync.aligned.m8n8.x2.trans.shared.b16 [%0],{%1,%2};}" ::"r"(a), "r"(x), "r"(y), "r"((uint32_t)p) : "memory");
}
DEV void stsm2t(uint32_t a, uint32_t x, uint32_t y) { asm volatile("stmatrix.sync.aligned.m8n8.x2.trans.shared.b16 [%0],{%1,%2};" ::"r"(a), "r"(x), "r"(y) : "memory"); }
DEV void mma16(float* d, uint32_t a0, uint32_t a1, uint32_t a2, uint32_t a3, uint32_t b0, uint32_t b1) {
    asm volatile("mma.sync.aligned.m16n8k16.row.col.f32.bf16.bf16.f32 {%0,%1,%2,%3},{%4,%5,%6,%7},{%8,%9},{%0,%1,%2,%3};"
                 : "+f"(d[0]), "+f"(d[1]), "+f"(d[2]), "+f"(d[3]) : "r"(a0), "r"(a1), "r"(a2), "r"(a3), "r"(b0), "r"(b1));
}
DEV void mma8(float* d, uint32_t a0, uint32_t a1, uint32_t b0) {
    asm volatile("mma.sync.aligned.m16n8k8.row.col.f32.bf16.bf16.f32 {%0,%1,%2,%3},{%4,%5},{%6},{%0,%1,%2,%3};"
                 : "+f"(d[0]), "+f"(d[1]), "+f"(d[2]), "+f"(d[3]) : "r"(a0), "r"(a1), "r"(b0));
}
DEV u64 mkdesc(uint32_t a, uint32_t lbo, uint32_t sbo) { return (u64)((a & 0x3ffff) >> 4) | ((u64)(lbo >> 4) << 16) | ((u64)(sbo >> 4) << 32); }
constexpr u64 SW128 = 1ull << 62;
DEV void wg_fence() { asm volatile("wgmma.fence.sync.aligned;" ::: "memory"); }
DEV void wg_commit() { asm volatile("wgmma.commit_group.sync.aligned;" ::: "memory"); }
template <int N> DEV void wg_wait() { asm volatile("wgmma.wait_group.sync.aligned %0;" ::"n"(N) : "memory"); }
template <int ACC> DEV void wgmma_n32_rs(float* d, const uint32_t* a, u64 desc) {
    asm volatile("wgmma.mma_async.sync.aligned.m64n32k16.f32.bf16.bf16 {%0,%1,%2,%3,%4,%5,%6,%7,%8,%9,%10,%11,%12,%13,%14,%15},{%16,%17,%18,%19},%20,%21,1,1,0;"
                 : "+f"(d[0]), "+f"(d[1]), "+f"(d[2]), "+f"(d[3]), "+f"(d[4]), "+f"(d[5]), "+f"(d[6]), "+f"(d[7]),
                   "+f"(d[8]), "+f"(d[9]), "+f"(d[10]), "+f"(d[11]), "+f"(d[12]), "+f"(d[13]), "+f"(d[14]), "+f"(d[15])
                 : "r"(a[0]), "r"(a[1]), "r"(a[2]), "r"(a[3]), "l"(desc), "n"(ACC));
}
template <int ACC> DEV void wgmma_n32_ss(float* d, u64 da, u64 desc) {
    asm volatile("wgmma.mma_async.sync.aligned.m64n32k16.f32.bf16.bf16 {%0,%1,%2,%3,%4,%5,%6,%7,%8,%9,%10,%11,%12,%13,%14,%15},%16,%17,%18,1,1,1,0;"
                 : "+f"(d[0]), "+f"(d[1]), "+f"(d[2]), "+f"(d[3]), "+f"(d[4]), "+f"(d[5]), "+f"(d[6]), "+f"(d[7]),
                   "+f"(d[8]), "+f"(d[9]), "+f"(d[10]), "+f"(d[11]), "+f"(d[12]), "+f"(d[13]), "+f"(d[14]), "+f"(d[15])
                 : "l"(da), "l"(desc), "n"(ACC));
}
template <int ACC> DEV void wgmma_n16_ss(float* d, u64 da, u64 desc) {
    asm volatile("wgmma.mma_async.sync.aligned.m64n16k16.f32.bf16.bf16 {%0,%1,%2,%3,%4,%5,%6,%7},%8,%9,%10,1,1,0,0;"
                 : "+f"(d[0]), "+f"(d[1]), "+f"(d[2]), "+f"(d[3]), "+f"(d[4]), "+f"(d[5]), "+f"(d[6]), "+f"(d[7])
                 : "l"(da), "l"(desc), "n"(ACC));
}
#define ACC8(o) "+f"(d[o]), "+f"(d[o + 1]), "+f"(d[o + 2]), "+f"(d[o + 3]), "+f"(d[o + 4]), "+f"(d[o + 5]), "+f"(d[o + 6]), "+f"(d[o + 7])
template <int ACC, int TB> DEV void wgmma_n64_rs(float* d, const uint32_t* a, u64 desc) {
    asm volatile("wgmma.mma_async.sync.aligned.m64n64k16.f32.bf16.bf16 {%0,%1,%2,%3,%4,%5,%6,%7,%8,%9,%10,%11,%12,%13,%14,%15,"
                 "%16,%17,%18,%19,%20,%21,%22,%23,%24,%25,%26,%27,%28,%29,%30,%31},{%32,%33,%34,%35},%36,%37,1,1,%38;"
                 : ACC8(0), ACC8(8), ACC8(16), ACC8(24) : "r"(a[0]), "r"(a[1]), "r"(a[2]), "r"(a[3]), "l"(desc), "n"(ACC), "n"(TB));
}
template <int ACC, int TB> DEV void wgmma_n80_rs(float* d, const uint32_t* a, u64 desc) {
    asm volatile("wgmma.mma_async.sync.aligned.m64n80k16.f32.bf16.bf16 {%0,%1,%2,%3,%4,%5,%6,%7,%8,%9,%10,%11,%12,%13,%14,%15,"
                 "%16,%17,%18,%19,%20,%21,%22,%23,%24,%25,%26,%27,%28,%29,%30,%31,%32,%33,%34,%35,%36,%37,%38,%39},{%40,%41,%42,%43},%44,%45,1,1,%46;"
                 : ACC8(0), ACC8(8), ACC8(16), ACC8(24), ACC8(32) : "r"(a[0]), "r"(a[1]), "r"(a[2]), "r"(a[3]), "l"(desc), "n"(ACC), "n"(TB));
}
template <int TA, int TB> DEV void wgmma_n64_ss(float* d, u64 da, u64 db, int acc) {
    asm volatile("{.reg .pred p; setp.ne.b32 p,%34,0; wgmma.mma_async.sync.aligned.m64n64k16.f32.bf16.bf16 {%0,%1,%2,%3,%4,%5,%6,%7,%8,%9,%10,%11,%12,%13,%14,%15,%16,%17,%18,%19,%20,%21,%22,%23,%24,%25,%26,%27,%28,%29,%30,%31},%32,%33,p,1,1,%35,%36;}"
                 : ACC8(0), ACC8(8), ACC8(16), ACC8(24) : "l"(da), "l"(db), "r"(acc), "n"(TA), "n"(TB));
}
template <int TA, int TB> DEV void wgmma_n128_ss(float* d, u64 da, u64 db, int acc) {
    asm volatile("{.reg .pred p; setp.ne.b32 p,%66,0; wgmma.mma_async.sync.aligned.m64n128k16.f32.bf16.bf16 {%0,%1,%2,%3,%4,%5,%6,%7,%8,%9,%10,%11,%12,%13,%14,%15,%16,%17,%18,%19,%20,%21,%22,%23,%24,%25,%26,%27,%28,%29,%30,%31,%32,%33,%34,%35,%36,%37,%38,%39,%40,%41,%42,%43,%44,%45,%46,%47,%48,%49,%50,%51,%52,%53,%54,%55,%56,%57,%58,%59,%60,%61,%62,%63},%64,%65,p,1,1,%67,%68;}"
                 : ACC8(0), ACC8(8), ACC8(16), ACC8(24), ACC8(32), ACC8(40), ACC8(48), ACC8(56) : "l"(da), "l"(db), "r"(acc), "n"(TA), "n"(TB));
}
template <int TA, int TB> DEV void wgmma_n192_ss(float* d, u64 da, u64 db, int acc) {
    asm volatile("{.reg .pred p; setp.ne.b32 p,%98,0; wgmma.mma_async.sync.aligned.m64n192k16.f32.bf16.bf16 {%0,%1,%2,%3,%4,%5,%6,%7,%8,%9,%10,%11,%12,%13,%14,%15,%16,%17,%18,%19,%20,%21,%22,%23,%24,%25,%26,%27,%28,%29,%30,%31,%32,%33,%34,%35,%36,%37,%38,%39,%40,%41,%42,%43,%44,%45,%46,%47,%48,%49,%50,%51,%52,%53,%54,%55,%56,%57,%58,%59,%60,%61,%62,%63,%64,%65,%66,%67,%68,%69,%70,%71,%72,%73,%74,%75,%76,%77,%78,%79,%80,%81,%82,%83,%84,%85,%86,%87,%88,%89,%90,%91,%92,%93,%94,%95},%96,%97,p,1,1,%99,%100;}"
                 : ACC8(0), ACC8(8), ACC8(16), ACC8(24), ACC8(32), ACC8(40), ACC8(48), ACC8(56), ACC8(64), ACC8(72), ACC8(80), ACC8(88) : "l"(da), "l"(db), "r"(acc), "n"(TA), "n"(TB));
}
template <int ACC> DEV void wgmma_n40_ss(float* d, u64 da, u64 desc) {
    asm volatile("wgmma.mma_async.sync.aligned.m64n40k16.f32.bf16.bf16 {%0,%1,%2,%3,%4,%5,%6,%7,%8,%9,%10,%11,%12,%13,%14,%15,%16,%17,%18,%19},%20,%21,%22,1,1,0,0;"
                 : ACC8(0), ACC8(8), "+f"(d[16]), "+f"(d[17]), "+f"(d[18]), "+f"(d[19]) : "l"(da), "l"(desc), "n"(ACC));
}
DEV void pdl_wait() { asm volatile("griddepcontrol.wait;" ::: "memory"); }
DEV void pdl_launch() { asm volatile("griddepcontrol.launch_dependents;" ::: "memory"); }
DEV uint32_t ldg32(const void* p) { uint32_t v; asm volatile("ld.global.nc.u32 %0,[%1];" : "=r"(v) : "l"(p)); return v; }
DEV void ld_acc(u64& a, u64& b, const void* p) {
    const uint32_t done = (uint32_t)a & (uint32_t)b & 32u;
    asm volatile("{.reg .pred p; setp.eq.u32 p,%3,0;\n"
                 "@p ld.relaxed.gpu.global.v2.u64 {%0,%1},[%2];}" : "+l"(a), "+l"(b) : "l"(p), "r"(done) : "memory");
}
DEV void ld_acc0(u64& a, u64& b, const void* p) {
    asm volatile("ld.relaxed.gpu.global.v2.u64 {%0,%1},[%2];" : "=l"(a), "=l"(b) : "l"(p) : "memory");
}
DEV uint32_t and3(uint32_t a, uint32_t b, uint32_t c) { uint32_t r; asm volatile("lop3.b32 %0,%1,%2,%3,0x80;" : "=r"(r) : "r"(a), "r"(b), "r"(c)); return r; }
DEV uint32_t absmax2(uint32_t a, uint32_t b) { uint32_t r; asm("max.xorsign.abs.bf16x2 %0,%1,%2;" : "=r"(r) : "r"(a), "r"(b)); return r; }
DEV float lds32f(uint32_t a) { float x; asm volatile("ld.shared.f32 %0,[%1];" : "=f"(x) : "r"(a) : "memory"); return x; }
DEV void red_add64(u64* p, uint32_t lo, uint32_t hi) {
    asm volatile("{.reg .b64 v; mov.b64 v,{%1,%2}; red.relaxed.gpu.global.add.u64 [%0],v;}" ::"l"(p), "r"(lo), "r"(hi) : "memory");
}
DEV float bf_round(float x) { return __bfloat162float(__float2bfloat16_rn(x)); }
DEV float bf_lo(uint32_t u) { return __uint_as_float(u << 16); }
DEV float bf_hi(uint32_t u) { return __uint_as_float(u & 0xffff0000u); }

#define GPROF(i, n)
#define PROFT(i)
#define STAMP(i)

DEV void unpack8(float* v, uint4 u) {
    v[0] = bf_lo(u.x); v[1] = bf_hi(u.x); v[2] = bf_lo(u.y); v[3] = bf_hi(u.y);
    v[4] = bf_lo(u.z); v[5] = bf_hi(u.z); v[6] = bf_lo(u.w); v[7] = bf_hi(u.w);
}
DEV int xn_off(int row, int chunk) { return (row >> 5) * 40960 + (chunk >> 3) * 4096 + (row & 31) * 128 + (((chunk ^ row) & 7) << 4); }

DEV void ln_row(float (&v)[3][8], int lane) {
    float s = 0.f;
#pragma unroll
    for (int c = 0; c < 3; c++)
#pragma unroll
        for (int j = 0; j < 8; j++) s += v[c][j];
#pragma unroll
    for (int o = 16; o; o >>= 1) s += __shfl_xor_sync(~0u, s, o);
    float mean = s * (1.f / D_), q = 0.f;
#pragma unroll
    for (int c = 0; c < 3; c++)
        if (c < 2 || lane < 16)
#pragma unroll
            for (int j = 0; j < 8; j++) { float d = v[c][j] - mean; q += d * d; }
#pragma unroll
    for (int o = 16; o; o >>= 1) q += __shfl_xor_sync(~0u, q, o);
    float mb = bf_round(mean);
    float inv = 1.f / bf_round(sqrtf(bf_round(bf_round(q * (1.f / D_)) + 1e-5f)));
#pragma unroll
    for (int c = 0; c < 3; c++)
#pragma unroll
        for (int j = 0; j < 8; j++) v[c][j] = bf_round(v[c][j] - mb) * inv;
}

__host__ __device__ constexpr int col_freq(int c) {
    return c == 320 ? 320 : c < 192 ? (c >> 6) * 128 + (c & 63) : c == 192 ? 192 : c < 256 ? 448 - c : c == 256 ? 64 : 384 - c;
}
DEV float rdft(int n, int k, int sn, int N) {
    float s, c;
    sincospif((float)((n * k) & (N - 1)) * (2.f / N), &s, &c);
    return !sn ? c : k ? s : (n & 1 ? -1.f : 1.f);
}

__global__ void __launch_bounds__(512) prep_kernel(const bf16* __restrict__ x, const bf16* __restrict__ Wq, const bf16* __restrict__ Wk,
                                                   const bf16* __restrict__ Wv, const bf16* __restrict__ Wo) {
    __shared__ float red[32], col[4][640];
    const int tid = threadIdx.x, lane = tid & 31, warp = tid >> 5, b = blockIdx.x, row = b * 16 + warp;
    TLS(0);
    pdl_launch();
    uint4 ux[3], uv[5], uo[8];
#pragma unroll
    for (int c = 0; c < 3; c++) ux[c] = c < 2 || lane < 16 ? *(const uint4*)(x + row * D_ + (c * 32 + lane) * 8) : make_uint4(0, 0, 0, 0);
#pragma unroll
    for (int i = 0; i < 5; i++) uv[i] = *(const uint4*)(Wv + (size_t)((b & 3) * 160 + i * 32 + (tid >> 4)) * 4096 + (b >> 2) * E_ + (tid & 15) * 8);
    if (tid < 320) {
#pragma unroll
        for (int r = 0; r < 8; r++) uo[r] = *(const uint4*)(Wo + (size_t)(b * 32 + tid / 80 * 8 + r) * D_ + tid % 80 * 8);
    }
    if (tid >= 504) prefetch_bulk((const char*)(tid & 4 ? Wk : Wq) + (b * 4 + (tid & 3)) * 10240, 10240);
    if (b < 3) ((uint4*)g_sync)[b * 512 + tid] = make_uint4(0, 0, 0, 0);
    for (int i = b * 512 + tid; i < ACC_LAYER; i += 128 * 512) ((uint4*)g_acc)[i] = make_uint4(0, 0, 0, 0);
    if (tid < 2 * YT_ROWS * D_ / 4 / 128) ((uint4*)g_yt)[b * (2 * YT_ROWS * D_ / 4 / 128) + tid] = make_uint4(0, 0, 0, 0);
    const int gid = tid < 104 ? b * 104 + tid : 1 << 20;
    if (gid < 4096) {
        const int inv = gid >> 11, ks = (gid >> 8) & 7, t = gid & 255, g = (t & 31) >> 2, q = t & 3, tile = t >> 5;
        uint32_t v[4];
#pragma unroll
        for (int j = 0; j < 4; j++) {
            float x[2];
#pragma unroll
            for (int u = 0; u < 2; u++) {
                const int m = inv ? 16 * tile + 2 * g + (j & 1) : 16 * ks + 8 * (j >> 1) + 2 * q + u;
                const int k2 = inv ? 8 * ks + 2 * q + u : 8 * tile + g, sn = inv ? j >> 1 : j & 1;
                x[u] = rdft(m, k2, sn, 128);
                if (sn && k2) x[u] = -x[u];
            }
            v[j] = pack2(x[0], x[1]);
        }
        g_f128[gid] = make_uint4(v[0], v[1], v[2], v[3]);
    } else if (gid < 5120) {
        const int id = gid - 4096, inv = id >> 9, ks = (id >> 7) & 3, t = id & 127, g = (t & 31) >> 2, q = t & 3, tile = t >> 5;
        uint32_t v[4];
#pragma unroll
        for (int j = 0; j < 4; j++) {
            float x[2];
#pragma unroll
            for (int u = 0; u < 2; u++) {
                const int a = inv ? 16 * tile + g + 8 * (j & 1) : 16 * ks + 8 * (j >> 1) + 2 * q + u;
                const int ka = inv ? 8 * ks + 2 * q + u : 8 * tile + g, sn = inv ? j >> 1 : j & 1;
                x[u] = rdft(a, ka, sn, 64);
            }
            v[j] = pack2(x[0], x[1]);
        }
        g_f64[id] = make_uint4(v[0], v[1], v[2], v[3]);
    } else if (gid < 5120 + 8192) {
        const int id = gid - 5120, inv = id >> 12, n = ((id >> 9) & 7) * 8 + ((id >> 3) & 7), k = ((id >> 6) & 7) * 8 + (id & 7);
        float s, c;
        sincospif((float)(((n >> 1) * (k >> 1)) & 31) * (1.f / 16), &s, &c);
        if (inv) s = -s;
        g_g32[id] = __float2bfloat16_rn((n & 1) == (k & 1) ? c : (k & 1) ? s : -s);
    }
    {
        float v[3][8];
#pragma unroll
        for (int c = 0; c < 3; c++) unpack8(v[c], ux[c]);
        ln_row(v, lane);
#pragma unroll
        for (int c = 0; c < 3; c++)
            if (c < 2 || lane < 16)
                *(uint4*)(g_xn + xn_off(row, c * 32 + lane)) =
                    make_uint4(pack2(v[c][0], v[c][1]), pack2(v[c][2], v[c][3]), pack2(v[c][4], v[c][5]), pack2(v[c][6], v[c][7]));
    }
    float sv = 0.f;
#pragma unroll
    for (int i = 0; i < 5; i++) {
        float w[8];
        unpack8(w, uv[i]);
#pragma unroll
        for (int j = 0; j < 8; j++) sv += w[j] * w[j];
    }
    if (tid < 320) {
        float a[8] = {0.f, 0.f, 0.f, 0.f, 0.f, 0.f, 0.f, 0.f};
#pragma unroll
        for (int r = 0; r < 8; r++) {
            float w[8];
            unpack8(w, uo[r]);
#pragma unroll
            for (int j = 0; j < 8; j++) a[j] += w[j] * w[j];
        }
#pragma unroll
        for (int j = 0; j < 8; j++) col[tid / 80][tid % 80 * 8 + j] = a[j];
    }
    __syncthreads();
    float so = (col[0][tid] + col[1][tid]) + (col[2][tid] + col[3][tid]);
    if (tid < 128) so = fmaxf(so, (col[0][512 + tid] + col[1][512 + tid]) + (col[2][512 + tid] + col[3][512 + tid]));
#pragma unroll
    for (int o = 16; o; o >>= 1) { sv += __shfl_xor_sync(~0u, sv, o); so = fmaxf(so, __shfl_xor_sync(~0u, so, o)); }
    if (lane == 0) { red[warp] = sv; red[16 + warp] = so; }
    __syncthreads();
    if (tid == 0) {
        float a = 0.f, c = 0.f;
        for (int i = 0; i < 16; i++) { a += red[i]; c = fmaxf(c, red[16 + i]); }
        g_nrm[b] = a; g_nrm[128 + b] = c;
    }
    TLE(0);
}

DEV void filter_tile(const bf16* __restrict__ wr, const bf16* __restrict__ wi, int ka, int c) {
    const int kn = ka ? 2048 - ka : 32, kc = col_freq(c);
    const unsigned short* pr = (const unsigned short*)wr + kc;
    const unsigned short* pi = (const unsigned short*)wi + kc;
#pragma unroll 1
    for (int i = 0; i < 4; i += 2) {
        unsigned short a[32], b[32];
#pragma unroll
        for (int n = 0; n < 32; n++) {
            const int k = ((n & 1 ? kn : ka) + 64 * (4 * (2 * (i + (n >> 4)) + ((n >> 1) & 1)) + ((n >> 2) & 3))) & 2047;
            a[n] = __ldg(pr + k * NCOL); b[n] = __ldg(pi + k * NCOL);
        }
#pragma unroll
        for (int n = 0; n < 32; n += 4)
            *(uint4*)(g_wt + c * 8192 + (i + (n >> 4)) * 2048 + (ka * 4 + ((n >> 2) & 3)) * 16) =
                make_uint4(a[n] | ((uint32_t)b[n] << 16), a[n + 1] | ((uint32_t)b[n + 1] << 16), a[n + 2] | ((uint32_t)b[n + 2] << 16), a[n + 3] | ((uint32_t)b[n + 3] << 16));
    }
}

namespace wk {
constexpr int STAGE = 49152, NST = 4, OFF_OUT = 3 * STAGE, OFF_RED = 4 * STAGE, OFF_BAR = OFF_RED + 32768, SMEM = OFF_BAR + 128;
constexpr int NPB = 11;
__host__ __device__ constexpr int pb_start(int b) { return b == 0 ? 2 : b < NPB ? 6 * b : 64; }
#define NOB 7
#define SPLIT_A 2
#define SPLIT_B 9
constexpr int N_P = NPB * H_, I_F = N_P, I_OB = I_F + 32, I_OT = I_OB + NOB * 5, I_SA = I_OT + (30 - 3 * NOB) * 10;
constexpr int I_SB = I_SA + 10 * SPLIT_A, N_ITEMS = I_SB + 10 * SPLIT_B;
DEV void ot_decode(int id, int& b, int& nt, int& k0, int& k1) {
    const int base = id < I_SA ? I_OT : id < I_SB ? I_SA : I_SB, j = (id - base) / 10;
    nt = (id - base) % 10;
    if (id < I_SA) { b = 3 * NOB + j; k0 = 0; k1 = 22; }
    else if (id < I_SB) { b = 30; k0 = 22 * j / SPLIT_A; k1 = 22 * (j + 1) / SPLIT_A; }
    else { b = 31; k0 = 22 * j / SPLIT_B; k1 = 22 * (j + 1) / SPLIT_B; }
}
enum { SY_TICKET = 0, SY_O = 32, SY_P = 128 };
}
struct Ring {
    int st; uint32_t ph;
    DEV uint32_t par() const { return (ph >> st) & 1; }
    DEV void next(int n) { ph ^= 1u << st; st = st + 1 >= n ? 0 : st + 1; }
};
struct Maps { CUtensorMap wq2, wv1, wo2, wo1, x6, x4, o6, o2; const bf16 *wr, *wi; };

template <int NSG> DEV void proj_tile(uint32_t sb, uint32_t bar, Ring& rg, int wg, int id) {
    using namespace wk;
    float acc[NSG * 16];
#pragma unroll
    for (int i = 0; i < NSG * 16; i++) acc[i] = 0.f;
    const int lane = threadIdx.x & 31, ww = (threadIdx.x >> 5) & 3;
    for (int kb = 0; kb < 10; kb++, rg.next(3)) {
        const int st = rg.st;
        if (kb) mbar_wait(bar + 8 * st, rg.par());
        const u64 da = mkdesc(sb + st * STAGE + wg * 8192, 0, 1024) | SW128, db = mkdesc(sb + st * STAGE + 24576, 0, 1024) | SW128;
        wg_fence();
#pragma unroll
        for (int ks = 0; ks < 4; ks++) {
            if (NSG == 4) wgmma_n128_ss<1, 0>(acc, da + ks * 128, db + ks * 2, 1);
            if (NSG == 6) wgmma_n192_ss<1, 0>(acc, da + ks * 128, db + ks * 2, 1);
        }
        wg_commit();
        wg_wait<0>();
        mbar_arrive_elect(bar + 8 * (NST + st));
    }
    const uint32_t out = sb + OFF_OUT + wg * 24576;
    bar_sync(5 + wg, 160);
    const uint32_t la = out + (wg < 2 ? (lane >> 4) * 1024 + ww * 256 + (lane & 15) * 16 : ww * 1024 + ((lane >> 3) & 1) * 512 + (lane >> 4) * 128 + (lane & 7) * 16);
#pragma unroll
    for (int j = 0; j < 2 * NSG; j++) {
        const float* c = acc + 8 * j;
        const uint32_t p0 = pack2(c[0], c[1]), p1 = pack2(c[2], c[3]), p2 = pack2(c[4], c[5]), p3 = pack2(c[6], c[7]);
        if (wg < 2) stsm4t(la + j * 2048, p0, p1, p2, p3);
        else stsm4(la + (j >> 1) * 4096 + (j & 1) * 256, p0, p1, p2, p3);
    }
    if ((threadIdx.x & 127) == 0) sts32(bar + 80 + 4 * wg, id);
    fence_async();
    bar_arrive(1 + wg, 160);
}

DEV uint32_t resid(uint32_t u, float a, float b) { return pack2(bf_lo(u) + bf_round(a), bf_hi(u) + bf_round(b)); }

template <bool SIDE>
DEV void worker(uint32_t sb, const Maps& maps, const bf16* __restrict__ x, bf16* __restrict__ x1, int layer, int fix, int nfix) {
    using namespace wk;
    const uint32_t bar = sb + OFF_BAR, slot = bar + 64;
    const int tid = threadIdx.x, lane = tid & 31, warp = __shfl_sync(~0u, tid >> 5, 0);
    uint32_t* sy = g_sync + layer * SYNC_LAYER;
    if (tid == 0) {
        for (int i = 0; i < NST; i++) { mbar_init(bar + 8 * i, 1); mbar_init(bar + 8 * (NST + i), 12); }
        asm volatile("fence.mbarrier_init.release.cluster;" ::: "memory");
    }
    __syncthreads();
    if (warp > 12) {
        const int wg = warp - 13;
        bar_arrive(5 + wg, 160);
        for (;;) {
            bar_sync(1 + wg, 160);
            const int id = (int)lds32(bar + 80 + 4 * wg);
            if (id < 0) break;
            const int s0 = pb_start(id >> 5), ns = pb_start((id >> 5) + 1) - s0;
            if (lane == 0) {
                for (int j = 0; j < ns; j++)
                    bulk_s2g(g_p + (size_t)(((s0 + j) * H_ + (id & 31)) * 3 + wg) * 4096, sb + OFF_OUT + wg * 24576 + j * 4096, 4096);
                bulk_commit();
                bulk_wait<0>();
                flag_add(sy + SY_P + id);
            }
            __syncwarp();
            bar_arrive(5 + wg, 160);
        }
    } else if (warp == 12) {
        if (lane == 0) {
            Ring rg = {0, 7u};
            auto acquire = [&]() { mbar_wait(bar + 8 * (NST + rg.st), rg.par()); return sb + rg.st * STAGE; };
            if (fix >= 0 && fix < N_P) {
                for (int kb = 0; kb < 3; kb++) {
                    tma3d(sb + kb * STAGE, &maps.wq2, 0, kb * 64, 2 * (fix & 31), bar + 8 * kb);
                    tma3d(sb + kb * STAGE + 16384, &maps.wv1, 0, kb * 64, 2 * (fix & 31), bar + 8 * kb);
                }
                asm volatile("prefetch.tensormap [%0];" ::"l"(&maps.x4) : "memory");
            }
            if (SIDE) flag_wait(g_started + layer, 1); else pdl_wait();
            for (;;) {
                int id = fix;
                if (id < 0) {
                    id = nfix + (int)atomicAdd(sy + SY_TICKET, 1u);
                    if (layer && id >= I_F) id += I_OB - I_F;
                    if (id >= I_SB) id = -1;
                }
                if (id >= 0) { TLI(id, 0, gtime()); TLI(id, 3, blockIdx.x + (SIDE ? 1000 : 0)); }
                uint32_t d = acquire();
                sts32(slot + 4 * rg.st, id);
                if (id < 0) { mbar_arrive(bar + 8 * rg.st); if (SIDE) pdl_launch(); break; }
                if (id < N_P) {
                    const int b = id >> 5, h = id & 31;
                    const bool six = b && b < NPB - 1;
                    for (int kb = 0; kb < 10; kb++, rg.next(3)) {
                        if (kb) d = acquire();
                        const uint32_t fb = bar + 8 * rg.st;
                        mbar_expect(fb, six ? 49152 : 40960);
                        tma3d(d + 24576, six ? &maps.x6 : &maps.x4, 0, 2 * kb, pb_start(b), fb);
                        if (fix < 0 || kb >= 3) {
                            tma3d(d, &maps.wq2, 0, kb * 64, 2 * h, fb);
                            tma3d(d + 16384, &maps.wv1, 0, kb * 64, 2 * h, fb);
                        }
                    }
                } else if (id < I_OB) {
                    mbar_arrive(bar + 8 * rg.st);
                    mbar_wait(bar + 8 * (NST + rg.st), rg.par() ^ 1);
                    rg.next(NST);
                } else if (id < I_OT) {
                    const int b = (id - I_OB) / 5, nt = (id - I_OB) % 5;
                    for (int j = 0; j < 6; j++) flag_wait(sy + SY_O + 6 * b + j, 64);
                    for (int kb = 0; kb < 64; kb++, rg.next(NST)) {
                        if (kb) d = acquire();
                        const uint32_t fb = bar + 8 * rg.st;
                        mbar_expect(fb, 40960);
                        tma3d(d, &maps.o6, 0, 2 * kb, 6 * b, fb);
                        tma3d(d + 24576, &maps.wo2, 0, kb * 64, 2 * nt, fb);
                    }
                } else {
                    int b, nt, k0, k1;
                    ot_decode(id, b, nt, k0, k1);
                    for (int kb = k0; kb < k1; kb++, rg.next(NST)) {
                        if (kb > k0) d = acquire();
                        const uint32_t fb = bar + 8 * rg.st;
                        mbar_expect(fb, 49152);
                        tma3d(d + 24576, &maps.wo1, 0, 3 * kb * 64, nt, fb);
                        if (kb == k0) for (int j = 0; j < 2; j++) flag_wait(sy + SY_O + 2 * b + j, 64);
                        for (int u = 0; u < 3; u++) tma3d(d + u * 8192, &maps.o2, 0, 2 * (3 * kb + u), 2 * b, fb);
                    }
                }
                fix = -1;
            }
        }
    } else {
        const int wg = warp >> 2, g = lane >> 2, q = lane & 3;
        Ring rg = {0, 0u};
        bool stores_done = false;
        for (;;) {
            mbar_wait(bar + 8 * rg.st, rg.par());
            const int id = (int)lds32(slot + 4 * rg.st);
            if ((id < 0 || id >= N_P) && !stores_done) {
                bar_sync(5 + wg, 160);
                if ((tid & 127) == 0) sts32(bar + 80 + 4 * wg, ~0u);
                bar_arrive(1 + wg, 160);
                stores_done = true;
                bar_sync(4, 384);
                mbar_arrive_elect(bar + 8 * (NST + 3));
            }
            if (id < 0) break;
            if (tid == 0) TLI(id, 1, gtime());
            if (id < N_P) {
                const int b = id >> 5;
                if (b == 0 || b == NPB - 1) proj_tile<4>(sb, bar, rg, wg, id);
                else proj_tile<6>(sb, bar, rg, wg, id);
            } else if (id < I_OB) {
                if (tid < NCOL) filter_tile(maps.wr, maps.wi, id - I_F, tid);
                __syncwarp();
                mbar_arrive_elect(bar + 8 * (NST + rg.st));
                rg.next(NST);
            } else if (id < I_OT) {
                const int b = (id - I_OB) / 5, nt = (id - I_OB) % 5;
                const size_t o = (size_t)(192 * b + 16 * warp + g) * D_ + nt * 128 + 2 * q;
                float acc[64];
#pragma unroll
                for (int i = 0; i < 64; i++) acc[i] = 0.f;
                for (int kb = 0; kb < 64; kb++, rg.next(NST)) {
                    const int st = rg.st;
                    if (kb) mbar_wait(bar + 8 * st, rg.par());
                    const u64 da = mkdesc(sb + st * STAGE + wg * 8192, 128, 1024), db = mkdesc(sb + st * STAGE + 24576, 8192, 1024) | SW128;
                    wg_fence();
#pragma unroll
                    for (int ks = 0; ks < 4; ks++) wgmma_n128_ss<0, 1>(acc, da + ks * 16, db + ks * 128, 1);
                    wg_commit();
                    wg_wait<0>();
                    mbar_arrive_elect(bar + 8 * (NST + st));
                }
                uint32_t xr[32];
#pragma unroll
                for (int t = 0; t < 32; t++) xr[t] = ldg32(x + o + 8 * (t >> 1) + (t & 1) * 8 * D_);
#pragma unroll
                for (int t = 0; t < 32; t++) *(uint32_t*)(x1 + o + 8 * (t >> 1) + (t & 1) * 8 * D_) = resid(xr[t], acc[2 * t], acc[2 * t + 1]);
            } else {
                int b, nt, k0, k1;
                ot_decode(id, b, nt, k0, k1);
                const size_t o = (size_t)(64 * b + 16 * (warp & 3) + g) * D_ + nt * 64 + 2 * q;
                float acc[32];
                uint32_t xr[16];
#pragma unroll
                for (int t = 0; t < 16; t++) xr[t] = wg == 0 && id < I_SA ? ldg32(x + o + 8 * (t >> 1) + (t & 1) * 8 * D_) : 0;
#pragma unroll
                for (int i = 0; i < 32; i++) acc[i] = 0.f;
                for (int kb = k0; kb < k1; kb++, rg.next(NST)) {
                    const int st = rg.st;
                    if (kb > k0) mbar_wait(bar + 8 * st, rg.par());
                    const u64 da = mkdesc(sb + st * STAGE + wg * 8192, 128, 1024), db = mkdesc(sb + st * STAGE + 24576 + wg * 8192, 0, 1024) | SW128;
                    wg_fence();
#pragma unroll
                    for (int ks = 0; ks < 4; ks++) wgmma_n64_ss<0, 1>(acc, da + ks * 16, db + ks * 128, 1);
                    wg_commit();
                    wg_wait<0>();
                    mbar_arrive_elect(bar + 8 * (NST + st));
                }
                const uint32_t ra = sb + OFF_RED + (tid & 127) * 16;
                if (wg) {
#pragma unroll
                    for (int t = 0; t < 8; t++)
                        sts128(ra + (wg - 1) * 16384 + t * 2048, __float_as_uint(acc[4 * t]), __float_as_uint(acc[4 * t + 1]), __float_as_uint(acc[4 * t + 2]), __float_as_uint(acc[4 * t + 3]));
                }
                bar_sync(4, 384);
                if (wg == 0) {
#pragma unroll
                    for (int t = 0; t < 8; t++) {
                        float u[4], v[4];
                        lds128f(u, ra + t * 2048); lds128f(v, ra + 16384 + t * 2048);
#pragma unroll
                        for (int i = 0; i < 4; i++) acc[4 * t + i] += u[i] + v[i];
                    }
                }
                bar_sync(4, 384);
                if (wg == 0) {
                    if (id < I_SA) {
#pragma unroll
                        for (int t = 0; t < 16; t++) *(uint32_t*)(x1 + o + 8 * (t >> 1) + (t & 1) * 8 * D_) = resid(xr[t], acc[2 * t], acc[2 * t + 1]);
                    } else {
                        float* y = g_yt + (layer * YT_ROWS - (S_ - YT_ROWS)) * D_ + o;
#pragma unroll
                        for (int t = 0; t < 16; t++)
                            asm volatile("red.relaxed.gpu.global.add.v2.f32 [%0],{%1,%2};" ::"l"(y + 8 * (t >> 1) + (t & 1) * 8 * D_), "f"(acc[2 * t]), "f"(acc[2 * t + 1]) : "memory");
                    }
                }
            }
            if (tid == 0) TLI(id, 2, gtime());
        }
    }
}

__global__ void __launch_bounds__(512, 1) side_kernel(const __grid_constant__ Maps maps, const bf16* __restrict__ x, bf16* __restrict__ x1, int layer, int nfix) {
    extern __shared__ __align__(1024) unsigned char smem[];
    TLS(3 + 5 * layer);
    worker<true>(s2u(smem), maps, x, x1, layer, -1, nfix);
    __syncwarp();
    if (blockIdx.x == 0) pdl_wait();
    TLE(3 + 5 * layer);
}

constexpr float C5A = 0.30901699437494742f, C5B = -0.80901699437494742f, S5A = 0.95105651629515357f, S5B = 0.58778525229247313f;
template <int SGN> DEV void dft5(const float (&tr)[5], const float (&ti)[5], float (&zr)[5], float (&zi)[5]) {
    const float ar = tr[1] + tr[4], ai = ti[1] + ti[4], br = tr[2] + tr[3], bi = ti[2] + ti[3];
    const float cr = tr[1] - tr[4], ci = ti[1] - ti[4], dr = tr[2] - tr[3], di = ti[2] - ti[3];
    zr[0] = tr[0] + ar + br; zi[0] = ti[0] + ai + bi;
    const float m1r = tr[0] + C5A * ar + C5B * br, m1i = ti[0] + C5A * ai + C5B * bi;
    const float m2r = tr[0] + C5B * ar + C5A * br, m2i = ti[0] + C5B * ai + C5A * bi;
    const float n1r = SGN * (S5A * cr + S5B * dr), n1i = SGN * (S5A * ci + S5B * di);
    const float n2r = SGN * (S5B * cr - S5A * dr), n2i = SGN * (S5B * ci - S5A * di);
    zr[1] = m1r + n1i; zi[1] = m1i - n1r; zr[4] = m1r - n1i; zi[4] = m1i + n1r;
    zr[2] = m2r + n2i; zi[2] = m2i - n2r; zr[3] = m2r - n2i; zi[3] = m2i + n2r;
}
DEV void ln40(float (&v)[40]) {
    float s = 0.f;
#pragma unroll
    for (int i = 0; i < 40; i++) s += v[i];
#pragma unroll
    for (int o = 8; o; o >>= 1) s += __shfl_xor_sync(~0u, s, o);
    const float mean = s * (1.f / D_);
    float q = 0.f;
#pragma unroll
    for (int i = 0; i < 40; i++) { const float d = v[i] - mean; q += d * d; }
#pragma unroll
    for (int o = 8; o; o >>= 1) q += __shfl_xor_sync(~0u, q, o);
    const float mb = bf_round(mean);
    const float inv = 1.f / bf_round(sqrtf(bf_round(bf_round(q * (1.f / D_)) + 1e-5f)));
#pragma unroll
    for (int i = 0; i < 40; i++) v[i] = bf_round(v[i] - mb) * inv;
}
__global__ void __maxnreg__(120) rowfft_kernel(const bf16* __restrict__ x0, bf16* __restrict__ x, const bf16* __restrict__ Wq,
                                                     const bf16* __restrict__ Wk, const bf16* __restrict__ Wv, int layer) {
    extern __shared__ __align__(1024) unsigned char smem[];
    const uint32_t sb = s2u(smem), sx = sb + 23552, sy = sx + 20480, bar = sy + 40960;
    const int tid = threadIdx.x, lane = tid & 31, q = lane & 3, blk = 127 - blockIdx.x, k2 = tid >> 2;
    if (tid == 0) TLI(800 + blk, 0, gtime());
    float twr[5], twi[5];
#pragma unroll
    for (int r = 1; r < 5; r++) { sincospif((float)(r * k2) * (-1.f / 320), &twi[r], &twr[r]); }
    uint32_t f[8][4];
#pragma unroll
    for (int ks = 0; ks < 8; ks++) { const uint4 u = g_f128[ks * 256 + tid]; f[ks][0] = u.x; f[ks][1] = u.y; f[ks][2] = u.z; f[ks][3] = u.w; }
    const bool split = blk * 16 >= S_ - YT_ROWS;
    if (tid == 0) {
        mbar_init(bar, 1);
        asm volatile("fence.mbarrier_init.release.cluster;" ::: "memory");
        mbar_expect(bar, split ? 61440 : 20480);
        if (split) bulk_g2s(sx, x0 + (size_t)blk * 16 * D_, 20480, bar);
    }
    __syncthreads();
    pdl_wait();
    pdl_launch();
    TLS(4 + 5 * layer);
    if (tid == 0) TLI(800 + blk, 1, gtime());
    if (tid == 0 && blk == 0) g_started[layer] = 0;
    if (tid == 0) {
        if (split) bulk_g2s(sy, g_yt + (layer * YT_ROWS + blk * 16 - (S_ - YT_ROWS)) * D_, 40960, bar);
        else bulk_g2s(sx, x + (size_t)blk * 16 * D_, 20480, bar);
    }
    mbar_wait(bar, 0);
    {
        const int rho = tid >> 4, j = tid & 15;
        float v[40];
#pragma unroll
        for (int i = 0; i < 5; i++) {
            uint32_t u[4];
            lds128(u, sx + tid * 80 + i * 16);
            if (split) {
                float p[8];
                lds128f(p, sy + tid * 160 + i * 32); lds128f(p + 4, sy + tid * 160 + i * 32 + 16);
#pragma unroll
                for (int k = 0; k < 4; k++) u[k] = resid(u[k], p[2 * k], p[2 * k + 1]);
                sts128(sx + tid * 80 + i * 16, u[0], u[1], u[2], u[3]);
            }
            unpack8(v + 8 * i, make_uint4(u[0], u[1], u[2], u[3]));
        }
        if (layer == 0 && tid < 12) prefetch_bulk((const char*)(tid < 4 ? Wk : tid < 8 ? Wq : Wv) + (blk * 4 + (tid & 3)) * 10240, 10240);
        ln40(v);
        const uint32_t a = sb + ((rho >> 1) & 1) * 2304 + j * 144 + (2 * (rho >> 2) + (rho & 1)) * 16;
#pragma unroll
        for (int r = 0; r < 5; r++)
            sts128(a + r * 4608, pack2(v[r], v[5 + r]), pack2(v[10 + r], v[15 + r]), pack2(v[20 + r], v[25 + r]), pack2(v[30 + r], v[35 + r]));
    }
    fence_async();
    __syncthreads();
    if (tid == 0) TLI(800 + blk, 2, gtime());
    if (tid == 0 && split) { bulk_s2g(x + (size_t)blk * 16 * D_, sx, 20480); bulk_commit(); }
    float acc[40];
    const u64 db = mkdesc(sb, 144, 2304);
    wg_fence();
    wgmma_n80_rs<0, 0>(acc, f[0], db);
#pragma unroll
    for (int ks = 1; ks < 8; ks++) wgmma_n80_rs<1, 0>(acc, f[ks], db + ks * 18);
    wg_commit();
    wg_wait<0>();
    unsigned char* zp = g_z + (blk >> 1) * 128 + ((((blk & 1) * 4 + q) ^ ((blk >> 1) & 7)) << 4);
    uint32_t o[5][4];
#pragma unroll
    for (int u = 0; u < 4; u++) {
        float tr[5], ti[5], zr[5], zi[5];
#pragma unroll
        for (int r = 0; r < 5; r++) {
            const float yr = acc[8 * r + 4 * (u >> 1) + (u & 1)], yi = k2 ? acc[8 * r + 4 * (u >> 1) + 2 + (u & 1)] : 0.f;
            tr[r] = r ? yr * twr[r] - yi * twi[r] : yr;
            ti[r] = r ? yr * twi[r] + yi * twr[r] : yi;
        }
        dft5<1>(tr, ti, zr, zi);
#pragma unroll
        for (int j = 0; j < 5; j++) o[j][u] = pack2(zr[j], j < 3 ? zi[j] : -zi[j]);
    }
#pragma unroll
    for (int j = 0; j < 5; j++)
        if (j < 3 || k2) *(uint4*)(zp + (64 * j + k2) * 8192) = make_uint4(o[j][0], o[j][1], o[j][2], o[j][3]);
    if (k2 == 0) {
#pragma unroll
        for (int u = 0; u < 4; u++) {
            float tr[5], ti[5], zr[5], zi[5];
            const float cr[5] = {1.f, -C5B, C5A, -C5A, C5B}, ci[5] = {0.f, -S5B, -S5A, -S5A, -S5B};
#pragma unroll
            for (int r = 0; r < 5; r++) { const float y = acc[8 * r + 4 * (u >> 1) + 2 + (u & 1)]; tr[r] = y * cr[r]; ti[r] = y * ci[r]; }
            dft5<1>(tr, ti, zr, zi);
            o[0][u] = pack2(zr[0], zi[0]); o[1][u] = pack2(zr[1], zi[1]); o[2][u] = pack2(zr[2], 0.f);
        }
        *(uint4*)(zp + 256 * 8192) = make_uint4(o[0][0], o[0][1], o[0][2], o[0][3]);
        *(uint4*)(zp + 192 * 8192) = make_uint4(o[1][0], o[1][1], o[1][2], o[1][3]);
        *(uint4*)(zp + 320 * 8192) = make_uint4(o[2][0], o[2][1], o[2][2], o[2][3]);
    }
    if (tid == 0) bulk_wait_read<0>();
    TLE(4 + 5 * layer);
    if (tid == 0) TLI(800 + blk, 3, gtime());
}

constexpr int CF_SMEM = 16384 + 8192 + 3 * 24576 + 64;
__global__ void __maxnreg__(88) colfft_kernel(int layer) {
    extern __shared__ __align__(1024) unsigned char smem[];
    const uint32_t sb = s2u(smem), bar = sb + 98304;
    const int tid = threadIdx.x, lane = tid & 31, q = lane & 3, wg = __shfl_sync(~0u, tid >> 7, 0), t = tid & 127, ka = t >> 2;
    asm volatile("setmaxnreg.inc.sync.aligned.u32 88;");
    const int col = blockIdx.x * 3 + wg;
    const uint32_t d0 = sb + 24576 + wg * 24576, d1 = d0 + 8192;
    if (tid == 0) {
        for (int i = 0; i < 4; i++) mbar_init(bar + 8 * i, 1);
        asm volatile("fence.mbarrier_init.release.cluster;" ::: "memory");
        mbar_expect(bar + 24, 49152);
        for (int i = 0; i < 3; i++) bulk_g2s(d0 + i * 24576 + 16384, g_wt + (col + i) * 8192, 8192, bar + 24);
        bulk_g2s(sb, g_g32, 16384, bar + 24);
        bulk_g2s(sb + 16384, g_f64 + 512, 8192, bar + 24);
    }
    uint32_t a[4][4];
#pragma unroll
    for (int ks = 0; ks < 4; ks++) { const uint4 u = g_f64[ks * 128 + t]; a[ks][0] = u.x; a[ks][1] = u.y; a[ks][2] = u.z; a[ks][3] = u.w; }
    float twr[8], twi[8];
#pragma unroll
    for (int i = 0; i < 8; i++) sincospif((float)((4 * i + q) * (ka ? ka : -32)) * (1.f / 1024), &twi[i], &twr[i]);
    __syncthreads();
    pdl_wait();
    pdl_launch();
    TLS(5 + 5 * layer);
    if (t == 0) {
        mbar_expect(bar + 8 * wg, 8192);
        bulk_g2s(d0, g_z + col * 8192, 8192, bar + 8 * wg);
    }
    float acc[32];
    mbar_wait(bar + 8 * wg, 0);
    {
        const u64 db = mkdesc(d0, 0, 1024) | SW128;
        wg_fence();
        wgmma_n64_rs<0, 1>(acc, a[0], db);
#pragma unroll
        for (int ks = 1; ks < 4; ks++) wgmma_n64_rs<1, 1>(acc, a[ks], db + ks * 128);
        wg_commit();
        wg_wait<0>();
    }
#pragma unroll
    for (int i = 0; i < 8; i++) {
        const float c0 = acc[4 * i], c1 = acc[4 * i + 1], c2 = acc[4 * i + 2], c3 = acc[4 * i + 3];
        const float pr = c0 + c3, pi = c1 - c2, nr = ka ? c0 - c3 : c2, ni = ka ? c1 + c2 : c3;
        a[i >> 1][2 * (i & 1)] = ka ? pack2(pr * twr[i] + pi * twi[i], pi * twr[i] - pr * twi[i]) : pack2(c0, c1);
        a[i >> 1][2 * (i & 1) + 1] = pack2(nr * twr[i] - ni * twi[i], ni * twr[i] + nr * twi[i]);
    }
    mbar_wait(bar + 24, 0);
    {
        const u64 db = mkdesc(sb, 128, 1024);
        wg_fence();
        wgmma_n64_rs<0, 0>(acc, a[0], db);
#pragma unroll
        for (int ks = 1; ks < 4; ks++) wgmma_n64_rs<1, 0>(acc, a[ks], db + ks * 16);
        wg_commit();
        wg_wait<0>();
    }
    constexpr float NORM = 1.f / (2048.f * 640.f);
#pragma unroll
    for (int i = 0; i < 4; i++) lds128(a[i], d0 + 16384 + i * 2048 + t * 16);
#pragma unroll
    for (int i = 0; i < 16; i++) {
        const float zr = acc[2 * i] * NORM, zi = acc[2 * i + 1] * NORM, wr = bf_lo(a[i >> 2][i & 3]), wi = bf_hi(a[i >> 2][i & 3]);
        a[i >> 2][i & 3] = pack2(zr * wr - zi * wi, zr * wi + zi * wr);
    }
    {
        const u64 db = mkdesc(sb + 8192, 128, 1024);
        wg_fence();
        wgmma_n64_rs<0, 0>(acc, a[0], db);
#pragma unroll
        for (int ks = 1; ks < 4; ks++) wgmma_n64_rs<1, 0>(acc, a[ks], db + ks * 16);
        wg_commit();
        wg_wait<0>();
    }
    const uint32_t row = (t >> 5) * 2048 + (lane & 15) * 128;
#pragma unroll
    for (int i = 0; i < 8; i++) {
        const float c0 = acc[4 * i], c1 = acc[4 * i + 1], c2 = acc[4 * i + 2], c3 = acc[4 * i + 3];
        const float pr = c0 * twr[i] - c1 * twi[i], pi = c1 * twr[i] + c0 * twi[i];
        const float nr = c2 * twr[i] + c3 * twi[i], ni = c3 * twr[i] - c2 * twi[i];
        a[i >> 1][2 * (i & 1)] = ka ? pack2(pr + nr, pi + ni) : pack2(c0, c1);
        a[i >> 1][2 * (i & 1) + 1] = ka ? pack2(ni - pi, pr - nr) : pack2(nr, ni);
    }
#pragma unroll
    for (int i = 0; i < 4; i++) stsm4(d1 + row + (((2 * i + (lane >> 4)) ^ (lane & 7)) << 4), a[i][0], a[i][1], a[i][2], a[i][3]);
#pragma unroll
    for (int i = 0; i < 4; i++) lds128(a[i], sb + 16384 + i * 2048 + t * 16);
    fence_async();
    bar_sync(1 + wg, 128);
    {
        const u64 db = mkdesc(d1, 0, 1024) | SW128;
        wg_fence();
        wgmma_n64_rs<0, 1>(acc, a[0], db);
#pragma unroll
        for (int ks = 1; ks < 4; ks++) wgmma_n64_rs<1, 1>(acc, a[ks], db + ks * 128);
        wg_commit();
        wg_wait<0>();
    }
#pragma unroll
    for (int i = 0; i < 4; i++)
        stsm4(d0 + row + (((2 * i + (lane >> 4)) ^ (lane & 7)) << 4), pack2(acc[8 * i], acc[8 * i + 1]), pack2(acc[8 * i + 2], acc[8 * i + 3]),
              pack2(acc[8 * i + 4], acc[8 * i + 5]), pack2(acc[8 * i + 6], acc[8 * i + 7]));
    fence_async();
    bar_sync(1 + wg, 128);
    if (t == 0) {
        bulk_s2g(g_z + col * 8192, d0, 8192);
        asm volatile("cp.async.bulk.commit_group;" ::: "memory");
        bulk_wait_read<0>();
    }
    TLE(5 + 5 * layer);
}

__global__ void __maxnreg__(120) rowifft_kernel(const bf16* __restrict__ x, bf16* __restrict__ out, int last) {
    extern __shared__ __align__(1024) unsigned char smem[];
    const uint32_t sb = s2u(smem), sx = sb + 20480, sy = sx + 20480, bar = sy + 16 * 1296;
    const int tid = threadIdx.x, lane = tid & 31, q = lane & 3, blk = blockIdx.x, k2 = tid >> 2, warp = tid >> 5;
    float twr[5], twi[5];
#pragma unroll
    for (int r = 1; r < 5; r++) { sincospif((float)(r * k2) * (1.f / 320), &twi[r], &twr[r]); twr[r] *= 2.f; twi[r] *= 2.f; }
    uint32_t f[8][4];
#pragma unroll
    for (int ks = 0; ks < 8; ks++) { const uint4 u = g_f128[2048 + ks * 256 + tid]; f[ks][0] = u.x; f[ks][1] = u.y; f[ks][2] = u.z; f[ks][3] = u.w; }
    if (tid == 0) {
        mbar_init(bar, 1);
        asm volatile("fence.mbarrier_init.release.cluster;" ::: "memory");
        mbar_expect(bar, 20480);
        bulk_g2s(sx, x + (size_t)blk * 16 * D_, 20480, bar);
    }
    pdl_wait();
    pdl_launch();
    TLS(6 + 5 * last);
    const unsigned char* zp = g_z + (blk >> 1) * 128 + ((((blk & 1) * 4 + q) ^ ((blk >> 1) & 7)) << 4);
    uint4 z[6];
#pragma unroll
    for (int j = 0; j < 5; j++) z[j] = *(const uint4*)(zp + (64 * j + k2) * 8192);
    z[5] = k2 ? make_uint4(0, 0, 0, 0) : *(const uint4*)(zp + 320 * 8192);
    float acc[40];
#pragma unroll
    for (int u = 0; u < 4; u++) {
        float yr[6], yi[6], tr[5], ti[5], zr[5], zi[5];
#pragma unroll
        for (int j = 0; j < 6; j++) { const uint32_t v = u == 0 ? z[j].x : u == 1 ? z[j].y : u == 2 ? z[j].z : z[j].w; yr[j] = bf_lo(v); yi[j] = bf_hi(v); }
#pragma unroll
        for (int j = 0; j < 5; j++) { tr[j] = yr[j]; ti[j] = j < 3 ? yi[j] : -yi[j]; }
        dft5<-1>(tr, ti, zr, zi);
        const float c1[5] = {1.f, C5A, C5B, C5B, C5A}, s1[5] = {0.f, S5A, S5B, -S5B, -S5A};
        const float c2[5] = {1.f, C5B, C5A, C5A, C5B}, s2[5] = {0.f, S5B, -S5A, S5A, -S5B};
        const float c3[5] = {1.f, -C5B, C5A, -C5A, C5B}, s3[5] = {0.f, S5B, S5A, S5A, S5B};
        const float c4[5] = {1.f, -C5A, C5B, -C5B, C5A}, s4[5] = {0.f, S5A, -S5B, -S5B, S5A};
#pragma unroll
        for (int r = 0; r < 5; r++) {
            float er = r ? zr[r] * twr[r] - zi[r] * twi[r] : 2.f * zr[0], ei = r ? zr[r] * twi[r] + zi[r] * twr[r] : 2.f * zi[0];
            if (k2 == 0) {
                er = yr[0] + 2.f * (yr[1] * c1[r] - yi[1] * s1[r] + yr[2] * c2[r] - yi[2] * s2[r]);
                ei = (r & 1 ? -yr[5] : yr[5]) + 2.f * (yr[4] * c3[r] - yi[4] * s3[r] + yr[3] * c4[r] - yi[3] * s4[r]);
            }
            acc[8 * r + 4 * (u >> 1) + (u & 1)] = er;
            acc[8 * r + 4 * (u >> 1) + 2 + (u & 1)] = ei;
        }
    }
#pragma unroll
    for (int r = 0; r < 5; r++)
        stsm4(sb + (2 * warp + ((lane >> 3) & 1)) * 1280 + (2 * r + (lane >> 4)) * 128 + (lane & 7) * 16, pack2(acc[8 * r], acc[8 * r + 1]),
              pack2(acc[8 * r + 2], acc[8 * r + 3]), pack2(acc[8 * r + 4], acc[8 * r + 5]), pack2(acc[8 * r + 6], acc[8 * r + 7]));
    fence_async();
    __syncthreads();
    const u64 db = mkdesc(sb, 1280, 128);
    wg_fence();
    wgmma_n80_rs<0, 1>(acc, f[0], db);
#pragma unroll
    for (int ks = 1; ks < 8; ks++) wgmma_n80_rs<1, 1>(acc, f[ks], db + ks * 160);
    wg_commit();
    wg_wait<0>();
#pragma unroll
    for (int u = 0; u < 4; u++) {
        float e[10];
#pragma unroll
        for (int r = 0; r < 5; r++) { e[r] = acc[8 * r + 4 * (u >> 1) + (u & 1)]; e[5 + r] = acc[8 * r + 4 * (u >> 1) + 2 + (u & 1)]; }
#pragma unroll
        for (int i = 0; i < 5; i++) sts32(sy + (4 * q + u) * 1296 + k2 * 20 + i * 4, pack2(e[2 * i], e[2 * i + 1]));
    }
    __syncthreads();
    const int rho = tid >> 4, j = tid & 15;
    float v[40];
    mbar_wait(bar, 0);
#pragma unroll
    for (int i = 0; i < 5; i++) {
        uint32_t y[4], u[4];
        lds128(y, sy + rho * 1296 + j * 80 + i * 16);
        lds128(u, sx + tid * 80 + i * 16);
#pragma unroll
        for (int k = 0; k < 4; k++) u[k] = pack2(bf_lo(u[k]) + bf_lo(y[k]), bf_hi(u[k]) + bf_hi(y[k]));
        sts128(sx + tid * 80 + i * 16, u[0], u[1], u[2], u[3]);
        unpack8(v + 8 * i, make_uint4(u[0], u[1], u[2], u[3]));
    }
    if (!last) {
        ln40(v);
#pragma unroll
        for (int i = 0; i < 5; i++) {
            const int c = j * 5 + i;
            sts128(sb + (c >> 3) * 2048 + rho * 128 + (((c ^ rho) & 7) << 4), pack2(v[8 * i], v[8 * i + 1]), pack2(v[8 * i + 2], v[8 * i + 3]),
                   pack2(v[8 * i + 4], v[8 * i + 5]), pack2(v[8 * i + 6], v[8 * i + 7]));
        }
    }
    fence_async();
    __syncthreads();
    if (lane == 0) {
        if (warp == 7) bulk_s2g(out + (size_t)blk * 16 * D_, sx, 20480);
        else if (!last && warp < 5) {
            unsigned char* p = g_xn + (blk >> 1) * 40960 + warp * 8192 + (blk & 1) * 2048;
            bulk_s2g(p, sb + warp * 4096, 2048);
            bulk_s2g(p + 4096, sb + warp * 4096 + 2048, 2048);
        }
        bulk_commit();
        bulk_wait_read<0>();
    }
    TLE(6 + 5 * last);
}

namespace rec {
#define NS 3
constexpr int OFF_X = 0;
constexpr int OFF_WO = 81920;
constexpr int OFF_WS = OFF_WO + 65536;
constexpr int OFF_XCH = OFF_WS + NS * 4096;
constexpr int OFF_MEMB = OFF_XCH + 12288;
constexpr int OFF_VX = OFF_MEMB + 10240;
constexpr int OFF_VM = OFF_VX + 16384;
constexpr int OFF_Q = OFF_VM + 4096;
constexpr int OFF_K = OFF_Q + 10240;
constexpr int OFF_OST = OFF_WO + 49152;
constexpr int OFF_PX = OFF_OST + 8192;
constexpr int OFF_PT = OFF_PX + 2560;
constexpr int OFF_PS = OFF_K + 10240;
constexpr int OFF_OB = OFF_PS + 1280;
constexpr int OFF_MX = OFF_OB + 2048;
constexpr int OFF_BAR = OFF_MX + 64;
constexpr int OFF_PROF = OFF_BAR + 256;
constexpr int SMEM = OFF_PROF + 4096 > wk::SMEM ? OFF_PROF + 4096 : wk::SMEM;
enum { B_XT = 0, B_VM = 2, B_VX = 4, B_XD = 6, B_X1 = 8, B_GO = 10, B_PXF = 12, B_PXE = 13, B_FIN = 14, B_ST = 15, B_MEM = 16   };
enum { NB_W2 = 0, NB_XCH = 1, NB_QK = 2, NB_WIN = 3, NB_ATT = 4, NB_X = 5, NB_PRO = 6, NB_W1 = 7, NB_PAIR = 8  , NB_KF = 12, NB_LD = 13, NB_KX = 15 };
#define TPOS 1
#define LATE 1
#define STAG 585
#define NOX 0
#define NW1 4
#define NW1B 0
template <int N> struct IC { static constexpr int value = N; };
template <int N, int I = 0, class F> DEV void static_for(F&& f) { if constexpr (I < N) { f(IC<I>{}); static_for<N, I + 1>(f); } }
constexpr float SM_SCALE = 0.08838834764831845f * 1.4426950408889634f;
}

__global__ void __launch_bounds__(512, 1) rec_kernel(const __grid_constant__ Maps maps, const bf16* __restrict__ x, bf16* __restrict__ x1, const bf16* __restrict__ mem0, const bf16* __restrict__ Wq, const bf16* __restrict__ Wk,
                                                     const bf16* __restrict__ Wv, const bf16* __restrict__ Wo, int layer, int delay, int delay2) {
    using namespace rec;
    extern __shared__ __align__(1024) unsigned char smem[];
    const uint32_t sb = s2u(smem);
    pdl_launch();
    if (blockIdx.x < 3 * H_) {
    const int tid = threadIdx.x, lane = tid & 31, warp = __shfl_sync(~0u, tid >> 5, 0);
    const int g = lane >> 2, q = lane & 3;
    const int h = blockIdx.x / 3;
    const uint32_t bar = sb + OFF_BAR;
    STAMP(2 * layer);
    TLS(2 + 5 * layer);
    if (tid == 0) TLI(690 + blockIdx.x, 0, gtime());
    if (tid == 0) {
        for (int i = 0; i < 2; i++) {
            mbar_init(bar + 8 * (B_XT + i), 1); mbar_init(bar + 8 * (B_VX + i), 1);
            mbar_init(bar + 8 * (B_XD + i), 8); mbar_init(bar + 8 * (B_X1 + i), 1); mbar_init(bar + 8 * (B_VM + i), 1);
        }
        mbar_init(bar + 8 * B_PXF, 1); mbar_init(bar + 8 * B_PXE, 2); mbar_init(bar + 8 * B_ST, 2); mbar_init(bar + 8 * B_GO, 1);
        for (int i = 0; i < 5; i++) mbar_init(bar + 8 * (B_MEM + i), 4);
        mbar_init(bar + 8 * B_FIN, 48);
        asm volatile("fence.mbarrier_init.release.cluster;" ::: "memory");
    }
    asm volatile("barrier.cluster.arrive.aligned; barrier.cluster.wait.aligned;" ::: "memory");
    const bool never = delay < 0;

    if (warp < 8) {
        asm volatile("setmaxnreg.inc.sync.aligned.u32 184;");
        const uint32_t rank = cta_rank();
        const int wg = warp >> 2;
        uint32_t fa[20 - NS][4], fb[20][4];
        const uint32_t l16 = opaque(sb + lane * 16);
        uint32_t dst = opaque(rank < 2 ? sb + OFF_Q + wg * 10240 + (warp & 3) * 256 + (lane & 15) * 16 + (lane >> 4) * 1024
                                       : sb + OFF_VM + warp * 256 + lane * 4);
        int dstep = rank < 2 ? 5120 : 2048;
        uint32_t& sfd = dst;
        const uint32_t ws = OFF_WS + warp * 512, xo = OFF_XCH + warp * 512, xi = OFF_XCH + (warp ^ 4) * 512, mb = OFF_MEMB + wg * 512;
        {
            static_assert(NS <= 4 && OFF_WS + 32768 <= OFF_VX, "staging space");
            const int t = tid & 127;
            const bf16* src = (rank == 2 ? Wv + wg * 64 : (wg ? Wk : Wq) + rank * 64) + h * E_ + (size_t)(512 + (t >> 3)) * 4096 + (t & 7) * 8;
            constexpr int SA = OFF_WS, SB = OFF_VX;
            const uint32_t sdst = sb + (wg ? SB : SA) + (t >> 3) * 128 + (((t & 7) ^ ((t >> 3) & 7)) << 4);
            const uint32_t ra = sb + wg * 4096 + ((lane >> 4) * 8 + (lane & 7)) * 128 + (((2 * (warp & 3) + ((lane >> 3) & 1)) ^ (lane & 7)) << 4);
            auto issue = [&](int rd) {
#pragma unroll 1
                for (int i = 0; i < 8; i++, src += 16 * 4096) cp16(sdst + (~rd & 1) * 16384 + i * 2048, src);
                src -= 256 * 4096;
                cp_commit();
            };
            issue(4); issue(3);
            float acc[16];
            const u64 da = mkdesc(sb + SA, 0, 1024) | SW128, db = mkdesc(sb + OFF_X + wg * 40960, 0, 1024) | SW128;
            mbar_spin(bar + 8 * (B_XT + wg), 0);
#pragma unroll
            for (int rd = 4; rd >= 0; rd--) {
                if (rd) cp_wait<1>(); else cp_wait<0>();
                fence_async();
                bar_sync(NB_XCH, 256);
                wg_fence();
#pragma unroll
                for (int ks = 0; ks < 8; ks++) {
                    const u64 a = da + (~rd & 1) * 1024 + ks * 128, b = db + (2 * rd + (ks >> 2)) * 256 + (ks & 3) * 2;
                    if (rd == 4 && ks == 0) wgmma_n32_ss<0>(acc, a, b); else wgmma_n32_ss<1>(acc, a, b);
                }
                wg_commit();
                wg_wait<0>();
#pragma unroll
                for (int i = 0; i < 4; i++) {
                    const int n = rd * 4 + i, o = (~rd & 1) * 16384 + (i >> 1) * 8192 + (i & 1) * 2048;
                    if (n < NS) {
                        uint32_t f[4];
                        ldsm4t(f, ra + SA + o);
                        sts128(l16 + ws + n * 4096, f[0], f[1], f[2], f[3]);
                    } else ldsm4t(fa[n - NS], ra + SA + o);
                    ldsm4t(fb[n], ra + SB + o);
                }
                if (rd > 1) { bar_sync(NB_XCH, 256); issue(rd - 2); }
            }
            fence_async();
            bar_sync(NB_PRO, 416);
            uint32_t pk[8];
#pragma unroll
            for (int i = 0; i < 8; i++) pk[i] = pack2(acc[2 * i], acc[2 * i + 1]);
            if (rank < 2) {
                stsm4t(dst - wg * 5120 + 1024, pk[0], pk[1], pk[2], pk[3]);
                stsm4t(dst - wg * 5120 + 3072, pk[4], pk[5], pk[6], pk[7]);
            } else {
                const uint32_t la = l16 + (l16 & 256) + OFF_VX + wg * 8192 + (warp & 3) * 1024;
                stsm4(la, pk[0], pk[2], pk[1], pk[3]);
                stsm4(la + 256, pk[4], pk[6], pk[5], pk[7]);
            }
        }
        uint32_t xlo = (uint32_t)mkdesc(sb + OFF_X + wg * 64, 0, 0);
        const uint32_t xtog = xlo ^ (uint32_t)mkdesc(sb + OFF_X + 40960 + wg * 64, 0, 0);
        uint32_t p8 = 0;
        bar_sync(NB_LD, 288);
        for (int s = -1;; s++) {
            uint32_t t[NS ? NS : 1][4];
            {
                float acc[16];
                auto xproj = [&](auto I0, auto I1) {
                    const u64 desc = (u64)xlo | (64ull << 32) | SW128;
                    wg_fence();
#pragma unroll
                    for (int i = I0.value; i < I1.value; i++) {
                        const u64 db = desc + (i >> 1) * 256 + (i & 1) * 2;
                        if (i == 0) wgmma_n32_rs<0>(acc, fb[i], db);
                        else if (!NOX) wgmma_n32_rs<1>(acc, fb[i], db);
                    }
                    wg_commit();
                    if (TPOS == 0 ? I0.value == 0 : I1.value == 20) {
#pragma unroll
                        for (int i = 0; i < NS; i++) lds128(t[i], l16 + ws + i * 4096);
                    }
                    wg_wait<0>();
                };
                if (s >= 0 && rank < 2) { fence_async(); bar_arrive(NB_W1, 512); bar_sync(NB_X, 384); }
                bar_sync_if<NB_W1, 480>(s >= 0 && rank == 2);
                if (s == NSEG - 1) break;
                xproj(IC<0>{}, IC<NW1>{});
                if (warp == 4 && s >= 0) PROFT(15);
                bar_sync_if<NB_W2, 384>(s >= 0 && rank < 2);
                if (NW1B > 0) xproj(IC<NW1>{}, IC<NW1 + NW1B>{});
                bar_sync_if<NB_WIN, 384>(s >= 0 && rank == 2);
                xproj(IC<NW1 + NW1B>{}, IC<20>{});
                if (warp == 4 && s >= 0) PROFT(12);
                sts128f_if(l16 + xo, acc + 8, !wg); sts128f_if(l16 + xo + 4096, acc + 12, !wg);
                sts128f_if(l16 + xo, acc, wg); sts128f_if(l16 + xo + 4096, acc + 4, wg);
                bar_sync(NB_PAIR + (warp & 3), 64);
                lds128f_if(acc + 8, l16 + xi, !wg); lds128f_if(acc + 12, l16 + xi + 4096, !wg);
                lds128f_if(acc, l16 + xi, wg); lds128f_if(acc + 4, l16 + xi + 4096, wg);
                float u[8];
#pragma unroll
                for (int i = 0; i < 8; i++) u[i] = acc[i] + acc[8 + i];
                if (rank < 2) {
                    stsm4t(dst + (wg ? 3072 : 11264), pack2(u[0], u[1]), pack2(u[2], u[3]), pack2(u[4], u[5]), pack2(u[6], u[7]));
                } else {
                    stsm4(l16 + (l16 & 256) + OFF_VX + 4096 + (warp & 3) * 1024 + wg * 256 + p8 * 1024,
                          pack2(u[0], u[1]), pack2(u[4], u[5]), pack2(u[2], u[3]), pack2(u[6], u[7]));
                    bar_arrive(NB_KF, 288);
                }
                bar_arrive(NB_KX, 384);
                xlo ^= xtog;
                if (warp == 4 && s >= 0) PROFT(3);
            }
            float da[4] = {0.f, 0.f, 0.f, 0.f}, db[4] = {0.f, 0.f, 0.f, 0.f}, ea[4] = {0.f, 0.f, 0.f, 0.f}, eb[4] = {0.f, 0.f, 0.f, 0.f};
            uint32_t b[10][4];
            const uint32_t mp = p8 >> 3;
            while (!mbar_try(bar + 8 * B_MEM, mp)) {}
            lds128(b[0], l16 + mb); lds128(b[1], l16 + mb + 1024);
            bool rdy;
            const uint32_t xb0 = mapa(bar + 8 * B_VM + p8, 0), xb1 = mapa(bar + 8 * B_VM + p8, 1);
            SFENCE();
            float is;
#pragma unroll
            for (int j = 0; j < 10; j++) {
#pragma unroll
                for (int x = 0; x < 2; x++) {
                    const int i = 2 * j + x;
                    const uint32_t* f = i < NS ? t[i] : fa[i - NS];
                    mma16(NS > 2 && x && j ? ea : da, f[0], f[1], f[2], f[3], b[j][2 * x], b[j][2 * x + 1]);
                    mma16(NS > 2 && x && j ? eb : db, fb[i][0], fb[i][1], fb[i][2], fb[i][3], b[j][2 * x], b[j][2 * x + 1]);
                    SFENCE();
                    if (x == 0 && j < 8 && !(j & 1)) rdy = mbar_try(bar + 8 * (B_MEM + 1 + (j >> 1)), mp, 1);
                    if (x == LATE && j < 8 && (j & 1) == 1 - LATE) {
                        if (__builtin_expect(!rdy, 0)) while (!mbar_try(bar + 8 * (B_MEM + 1 + (j >> 1)), mp)) {}
                        lds128(b[(j | 1) + 1], l16 + mb + ((j | 1) + 1) * 1024);
                        lds128(b[(j | 1) + 2], l16 + mb + ((j | 1) + 2) * 1024);
                    }
                    if (x == 0 && j == 8) is = lds32f(sb + OFF_MX + 16);
                }
                if (j == 0 && warp == 4) PROFT(16);
            }
            if (warp == 4) PROFT(20);
            if (NS > 2) {
#pragma unroll
                for (int i = 0; i < 4; i++) { da[i] += ea[i]; db[i] += eb[i]; }
            }
            sts128f_if(l16 + xo + 8192, db, !wg); sts128f_if(l16 + xo + 8192, da, wg);
            bar_sync(NB_PAIR + (warp & 3), 64);
            lds128f_if(db, l16 + xi + 8192, !wg); lds128f_if(da, l16 + xi + 8192, wg);
            const uint32_t p0 = pack2((da[0] + db[0]) * is, (da[1] + db[1]) * is), p1 = pack2((da[2] + db[2]) * is, (da[3] + db[3]) * is);
            stsm2t_if(dst, p0, p1, rank < 2);
            bar_arrive_if<NB_QK, 384>(rank < 2);
            if (rank == 2) {
                st_async1(mapa(dst, 0), p0, xb0); st_async1(mapa(dst, 1), p0, xb1);
                st_async1(mapa(dst + 128, 0), p1, xb0); st_async1(mapa(dst + 128, 1), p1, xb1);
                sts32(dst, p0); sts32(dst + 128, p1);
                bar_arrive(NB_QK, 384);
            }
            if (warp == 4) PROFT(17);
            dst += dstep; dstep = -dstep; p8 ^= 8;
        }
    } else if (warp < 12) {
        asm volatile("setmaxnreg.dec.sync.aligned.u32 96;");
        const uint32_t rank = cta_rank();
        const int w = warp - 8;
        uint32_t amax = 0;
        {
            const int t = tid & 127, nr = rank == 2 ? 4 : 3;
            for (int r = 0; r < nr; r++) {
                const bf16* src = Wo + (size_t)(h * E_) * D_ + (r < 3 ? 192 * r + 64 * rank : 576);
#pragma unroll 1
                for (int i = 0; i < 8; i++) {
                    const int e = i * 16 + (t >> 3);
                    cp16(sb + OFF_WO + r * 16384 + e * 128 + (((t & 7) ^ (e & 6)) << 4), src + e * D_ + (t & 7) * 8);
                }
            }
            cp_commit();
            cp_wait<0>();
            bar_sync(NB_ATT, 128);
            for (int r = 0; r < nr; r++) {
                uint32_t u[8][4];
                const uint32_t p = sb + OFF_WO + r * 16384 + 2 * q * 128 + (((2 * w + (g & 1)) ^ (2 * q)) << 4) + (g >> 1) * 4;
#pragma unroll
                for (int ks = 0; ks < 8; ks++)
#pragma unroll
                    for (int j = 0; j < 4; j++) u[ks][j] = lds32(p + (16 * ks + (j & 1) * 8 + (j >> 1)) * 128);
                bar_sync(NB_ATT, 128);
#pragma unroll
                for (int ks = 0; ks < 8; ks++)
                    sts128(sb + OFF_WO + (r * 4 + w) * 4096 + ks * 512 + lane * 16, prmt(u[ks][0], u[ks][2], 0x5410), prmt(u[ks][0], u[ks][2], 0x7632),
                           prmt(u[ks][1], u[ks][3], 0x5410), prmt(u[ks][1], u[ks][3], 0x7632));
            }
        }
        {
            uint32_t m0[5][4];
#pragma unroll
            for (int it = 0; it < 5; it++)
#pragma unroll
                for (int j = 0; j < 4; j++) m0[it][j] = ldg32(mem0 + g * D_ + (it * 4 + w) * 32 + 2 * q + 8 * j);
            bar_sync(NB_PRO, 416);
#pragma unroll
            for (int it = 0; it < 5; it++) {
                sts128(sb + OFF_MEMB + (it * 4 + w) * 512 + lane * 16, m0[it][0], m0[it][1], m0[it][2], m0[it][3]);
                amax = absmax2(amax, absmax2(absmax2(m0[it][0], m0[it][1]), absmax2(m0[it][2], m0[it][3])));
            }
            if (tid == 256) { sts32(sb + OFF_MX + 16, 0x3f800000u); sts128(sb + OFF_MX + 48, 0x3f803f80u, 0x3f803f80u, 0x3f803f80u, 0x3f803f80u); }
            __syncwarp();
            if (lane < 5) mbar_arrive(bar + 8 * (B_MEM + lane));
            __syncwarp();
        }
        if (w == 0) TLI(690 + blockIdx.x, 3, gtime());
        pdl_wait();
        float cw;
        {
            const float4 a = ((const float4*)g_nrm)[lane], c = ((const float4*)g_nrm)[32 + lane];
            float sm = sqrt_approx((a.x + a.y) + (a.z + a.w)) * sqrt_approx((c.x + c.y) + (c.z + c.w)), mxv = sm;
#pragma unroll 1
            for (int o = 16; o; o >>= 1) { sm += __shfl_xor_sync(~0u, sm, o); mxv = fmaxf(mxv, __shfl_xor_sync(~0u, mxv, o)); }
            cw = 26.5f * fmaxf(sm, 8.f * mxv);
        }
        if (w == 0) {
            mbar_expect_elect(bar + 8 * B_X1, 1280);
            mbar_expect_elect(bar + 8 * B_VM, rank < 2 ? 2048 : 0);
            mbar_expect_elect(bar + 8 * B_VX, rank < 2 ? 8192 : 0);
        }
        {
            const int kind = rank;
            const uint32_t l16 = opaque(sb + lane * 16), lw = opaque(sb + lane * 16 + w * 512);
            const uint32_t pa = opaque(sb + OFF_PS + rank * 512 + lane * 4 + w * 128);
            uint32_t lq = opaque(sb + OFF_Q + (lane & 7) * 16 + ((lane >> 3) & 1) * 256 + (lane >> 4) * 128);
            const uint32_t lv = opaque(sb + OFF_VX + w * 2048 + (lane & 7) * 16 + ((lane >> 3) & 1) * 512 + (lane >> 4) * 128);
            const uint32_t lo = opaque(sb + OFF_WO + w * 4096 + lane * 16);
            uint32_t& sfd = lq;
            const char* rp = (const char*)(g_acc + layer * ACC_LAYER) + (4 * rank + w) * 4096 + opaque((q >> 1) * 1024 + ((q & 1) * 8 + g) * 8);
            const char* lp = (const char*)(g_acc + layer * ACC_LAYER) + opaque(w * 8192 + (lane >> 3) * 1024 + (lane & 7) * 16);
            const uint32_t arm = bar + 8 * (w == 0 ? B_X1 + 1 : w == 1 ? B_VX + 1 : w == 2 ? B_XT : B_VM + 1);
            const uint32_t armb = w == 0 ? 1280 : (w == 1 ? 4096 : w == 2 ? 40960 : 0) + (rank == 2 ? 0 : w == 3 ? 2048 : 4096);
            float isig = 1.f;
            for (int s = 0; s < NSEG - 1; s++) {
                const uint32_t pb = s & 1, ph = (s >> 1) & 1, x1 = bar + 8 * (B_X1 + pb);
                uint32_t kf[8];
                bar_sync(NB_KX, 384);
                ldsm4(kf, lw + OFF_K + 1024 + w * 512 + pb * 5120); ldsm4(kf + 4, lw + OFF_K + 1536 + w * 512 + pb * 5120);
                sts32(sb + OFF_MX + w * 4, __reduce_max_sync(~0u, max(amax & 0x7fff0000u, (amax << 16) & 0x7fff0000u)));
                const uint32_t va = lv + pb * 8192, vma = lw + OFF_VM + pb * 2048;
                uint32_t wf[8][4], vf[2][2][4], vm[4], one[4];
                mbar_spin(bar + 8 * (B_VX + pb), ph);
#pragma unroll
                for (int t = 0; t < 2; t++)
#pragma unroll
                    for (int j = 0; j < 2; j++) ldsm4(vf[t][j], va + t * 1024 + j * 256);
                lds128(one, sb + OFF_MX + 48);
                auto scores = [&](auto MM) {
                    constexpr int mm = MM.value;
                    uint32_t qf[8], mf[8];
                    const uint32_t qa = lq + pb * 5120, ka = l16 + OFF_K + pb * 5120;
                    const uint32_t pa0 = mapa(pa, rank ^ 1), pa1 = mapa(pa, 2), pa2 = mapa(pa, rank);
                    const uint32_t xb0 = mapa(x1, rank ^ 1), xb1 = mapa(x1, 2), xb2 = mapa(x1, rank);
                    const uint32_t pm = 640 - rank * 384;
                    SFENCE();
                    if (w == 0) PROFT(2);
                    bar_sync(NB_QK, 384);
                    ldsm4(qf, qa); ldsm4(qf + 4, qa + 512);
                    if (mm) { ldsm4(mf, ka); ldsm4(mf + 4, ka + 512); }
                    SFENCE();
                    float c[4][4];
#pragma unroll
                    for (int i = 0; i < 4; i++) c[i][0] = c[i][1] = c[i][2] = c[i][3] = 0.f;
#pragma unroll
                    for (int i = 0; i < (mm ? 8 : 4); i++) {
                        const int hf = mm ? i >> 2 : i >> 1;
                        const uint32_t* f = (mm && (i & 2) ? mf : kf) + 4 * hf + 2 * (i & 1);
                        mma16(c[i & 3], qf[4 * hf], qf[4 * hf + 1], qf[4 * hf + 2], qf[4 * hf + 3], f[0], f[1]);
                    }
                    SFENCE();
                    bar_arrive(NB_W1, 512);
                    const uint32_t y = mm ? pack2(c[0][0] + c[1][2], c[0][1] + c[1][3])
                                          : pack2((c[0][0] + c[1][2]) + (c[2][0] + c[3][2]), (c[0][1] + c[1][3]) + (c[2][1] + c[3][3]));
                    st_async1(pa0, y, xb0); st_async1(pa1, y, xb1);
                    if (mm) {
                        const uint32_t z = pack2(c[2][0] + c[3][2], c[2][1] + c[3][3]);
                        st_async1(pa0 + pm, z, xb0); st_async1(pa1 + pm, z, xb1); st_async1(pa2 + pm, z, xb2);
                    }
                    st_async1(pa2, y, xb2);
                    if (w == 0) PROFT(5);
                };
                if (kind == 2) bar_sync(NB_QK, 384);
                else if (w == 3) scores(IC<1>{});
                else scores(IC<0>{});
                float m4[4];
                lds128f(m4, sb + OFF_MX);
                bar_arrive_if<NB_W1, 480>(kind == 2);
                mbar_spin(x1, ph);
                if (w == 0) PROFT(6);
                float sc[10];
                {
                    uint32_t u[4], v[4], m[2];
                    ldsm4(u, l16 + OFF_PS); ldsm4(v, l16 + OFF_PS + 512); ldsm2(m, l16 + OFF_PS + 1024);
                    SFENCE();
                    m4[0] = fmaxf(fmaxf(m4[0], m4[1]), fmaxf(m4[2], m4[3])) * isig;
                    SFENCE();
#pragma unroll
                    for (int i = 0; i < 4; i++) { sc[2 * i] = bf_lo(u[i]) + bf_lo(v[i]); sc[2 * i + 1] = bf_hi(u[i]) + bf_hi(v[i]); }
                    sc[8] = bf_lo(m[0]) + bf_lo(m[1]); sc[9] = bf_hi(m[0]) + bf_hi(m[1]);
                }
                float mx = fmaxf(fmaxf(fmaxf(fmaxf(sc[0], sc[1]), fmaxf(sc[2], sc[3])), fmaxf(fmaxf(sc[4], sc[5]), fmaxf(sc[6], sc[7]))), fmaxf(sc[8], sc[9]));
                auto fetch = [&](int i) { lds128(wf[i], lo + i * 512); };
                {
                    float m1 = __shfl_xor_sync(~0u, mx, 1), m2 = __shfl_xor_sync(~0u, mx, 2), m3 = __shfl_xor_sync(~0u, mx, 3);
                    mbar_spin(bar + 8 * (B_VM + pb), ph);
                    ldsm4(vm, vma);
                    mx = fmaxf(fmaxf(mx, m1), fmaxf(m2, m3)) * SM_SCALE;
                }
#pragma unroll
                for (int i = 0; i < 10; i++) sc[i] = fmaf(sc[i], SM_SCALE, -mx);
                float o0[4] = {0.f, 0.f, 0.f, 0.f}, o1[4] = {0.f, 0.f, 0.f, 0.f}, rs[4] = {0.f, 0.f, 0.f, 0.f};
                sc[8] = ex2(sc[8]); fetch(0); fetch(1); sc[9] = ex2(sc[9]);
                SFENCE();
                fetch(2); sc[0] = ex2(sc[0]); fetch(3); fetch(4); sc[1] = ex2(sc[1]); fetch(5); fetch(6); sc[2] = ex2(sc[2]);
                SFENCE();
                {
                    const uint32_t p = pack2(sc[8], sc[9]);
                    sc[3] = ex2(sc[3]); fetch(7);
                    mma8(o0, vm[0], vm[1], p);
                    mma8(o1, vm[2], vm[3], p);
                    sc[4] = ex2(sc[4]);
                    mma8(rs, one[0], one[1], p);
                    sc[5] = ex2(sc[5]);
                }
                SFENCE();
                {
                    const uint32_t p0 = pack2(sc[0], sc[1]), p1 = pack2(sc[2], sc[3]);
                    sc[6] = ex2(sc[6]);
                    mma16(o0, vf[0][0][0], vf[0][0][1], vf[0][0][2], vf[0][0][3], p0, p1);
                    SFENCE();
                    sc[7] = ex2(sc[7]);
                    mma16(o1, vf[1][0][0], vf[1][0][1], vf[1][0][2], vf[1][0][3], p0, p1);
                    SFENCE();
                    mma16(rs, one[0], one[1], one[2], one[3], p0, p1);
                    SFENCE();
                }
                {
                    const uint32_t p0 = pack2(sc[4], sc[5]), p1 = pack2(sc[6], sc[7]);
                    mma16(o0, vf[0][1][0], vf[0][1][1], vf[0][1][2], vf[0][1][3], p0, p1);
                    mma16(o1, vf[1][1][0], vf[1][1][1], vf[1][1][2], vf[1][1][3], p0, p1);
                    SFENCE();
                    mma16(rs, one[0], one[1], one[2], one[3], p0, p1);
                }
                const uint32_t e = max((__float_as_uint(cw * fmaxf(m4[0], 1.f)) >> 23) & 255u, 31u);
                SFENCE();
                stsm4t(lw + OFF_OB, pack2(o0[0], o0[1]), pack2(o0[2], o0[3]), pack2(o1[0], o1[1]), pack2(o1[2], o1[3]));
                if (w == 0) PROFT(13);
                bar_sync(NB_ATT, 128);
                uint32_t ob[16];
#pragma unroll
                for (int j = 0; j < 4; j++) ldsm4(ob + 4 * j, l16 + OFF_OB + j * 512);
                SFENCE();
                const float sig = __uint_as_float((278u - e) << 23);
                isig = __uint_as_float((e - 30u) << 23);
                const float sg0 = rcp(rs[0]) * sig, sg1 = rcp(rs[1]) * sig;
                SFENCE();
                auto tile = [&](uint32_t next, const char* p, auto LAST) {
                    float c[4][4];
#pragma unroll
                    for (int i = 0; i < 4; i++) c[i][0] = c[i][1] = c[i][2] = c[i][3] = 0.f;
#pragma unroll
                    for (int ks = 0; ks < 8; ks++) {
                        mma16(c[ks & 3], wf[ks][0], wf[ks][1], wf[ks][2], wf[ks][3], ob[2 * ks], ob[2 * ks + 1]);
                        if ((ks & 3) == 0) SFENCE();
                        if ((ks & 3) == 3 && !LAST.value) {
                            SFENCE();
#pragma unroll
                            for (int i = ks; i >= ks - 3; i--) { lds128(wf[i], next + i * 512); if (i == ks - 2) SFENCE(); }
                            if (ks == 3) SFENCE();
                        }
                    }
                    SFENCE();
                    if (LAST.value) { bar_arrive_if<NB_WIN, 256>(kind < 2); bar_arrive_if<NB_WIN, 384>(kind == 2); }
                    uint32_t v[4];
#pragma unroll
                    for (int i = 0; i < 4; i++)
                        v[i] = (__float_as_uint(fmaf((c[0][i] + c[1][i]) + (c[2][i] + c[3][i]), i & 1 ? sg1 : sg0, 12582912.f)) << 6) + (i < 2);
                    red_add64((u64*)p, v[0], v[2]);
                    red_add64((u64*)(p + 2048), v[1], v[3]);
                };
                tile(lo + 16384, rp, IC<0>{});
                if (w == 0) PROFT(7);
                tile(lo + 32768, rp + 49152, IC<0>{});
                if (kind == 2) tile(lo + 49152, rp + 98304, IC<0>{});
                tile(0, rp + (kind == 2 ? 28 * 4096 : 98304), IC<1>{});
                if (w == 0) PROFT(8);
                sts32(sb + OFF_MX + 16, __float_as_uint(isig));
                mbar_expect_elect(arm ^ (8 * pb), armb - (w == 2 && s == NSEG - 2 ? 40960 : 0) - (s == 0 && w == (rank < 2 ? 2 : 1) ? 4096 : 0));
                u64 y[20];
                uint32_t b[20];
                bool done[5] = {false, false, false, false, false};
                float z = isig;
                mbar_spin(bar + 8 * B_GO, pb);
                if (w == 0) PROFT(9);
                do {
#pragma unroll
                    for (int i = 0; i < 10; i++) {
                        if (STAG && (i == 2 || i == 5 || i == 8)) {
#pragma unroll
                            for (int k = 0; k < (i == 2 ? STAG / 100 : i == 5 ? STAG / 10 % 10 : STAG % 10); k++) asm volatile("ex2.approx.ftz.f32 %0,%0;" : "+f"(z));
                            asm volatile("{.reg .pred p; setp.ne.u32 p,%1,0; @p mov.b32 %0,%2;}" : "+r"(sfd) : "r"((uint32_t)never), "f"(z));
                            SFENCE();
                        }
                        ld_acc0(y[2 * i], y[2 * i + 1], lp + (i >> 1) * 32768 + (i & 1) * 4096);
                        if (STAG && (i == 1 || i == 4 || i == 7)) SFENCE();
                    }
                    uint32_t ok = 32u, late = 32u;
                    static_for<5>([&](auto IT) {
                        constexpr int it = IT.value;
                        if (it == 1) late = and3((uint32_t)y[4], (uint32_t)y[6], (uint32_t)y[8]);
                        else if (it == 2) late &= and3((uint32_t)y[10], (uint32_t)y[12], (uint32_t)y[14]);
                        else if (it == 3) ok &= late;
                        else ok = and3(ok, (uint32_t)y[4 * it], (uint32_t)y[4 * it + 2]);
                        if (it != 3) SFENCE();
                        if (it == 1 || it == 2) ok = and3(ok, (uint32_t)y[4 * it], (uint32_t)y[4 * it + 2]);
                        ok = and3(ok, (uint32_t)y[4 * it + 1], (uint32_t)y[4 * it + 3]);
                        const bool all = __all_sync(~0u, ok);
#pragma unroll
                        for (int j = 0; j < 4; j++) {
                            const u64 v = y[4 * it + j];
                            b[4 * it + j] = pack2((float)(int)(uint32_t)v, (float)(int)(uint32_t)(v >> 32));
                        }
                        sts128(lw + OFF_MEMB + it * 2048, b[4 * it], b[4 * it + 1], b[4 * it + 2], b[4 * it + 3]);
                        mbar_arrive_elect_if(bar + 8 * (B_MEM + it), all && !done[it]);
                        done[it] = all;
                        SFENCE();
                        if (it == 0 && w == 0) PROFT(10);
                    });
                } while (!done[4]);
                if (w == 0) PROFT(11);
                amax = b[0];
#pragma unroll
                for (int i = 1; i < 19; i += 2) amax = absmax2(amax, absmax2(b[i], b[i + 1]));
                amax = absmax2(amax, b[19]);
                const int adv = (s & 7) == 7 ? 163840 - 896 : 128;
                rp += adv; lp += adv;
            }
        }
        asm volatile("prefetch.tensormap [%0];" ::"l"(w & 1 ? &maps.wo1 : &maps.o2) : "memory");
        bar_sync(NB_KX, 384);
        bar_sync(NB_QK, 384);
        if (rank < 2) { bar_arrive(NB_W1, 512); bar_arrive(NB_WIN, 256); } else bar_arrive(NB_W1, 480);
    } else {
        asm volatile("setmaxnreg.dec.sync.aligned.u32 %0;" ::"n"(48));
        const uint32_t rank = cta_rank();
        const int w = warp - 12;
        pdl_wait();
        if (blockIdx.x == 2 && w == 3) asm volatile("st.release.gpu.global.u32 [%0],1;" ::"l"(g_started + layer) : "memory");
        uint32_t* sy = g_sync + layer * SYNC_LAYER;
        if (w == 1) TLI(690 + blockIdx.x, 1, gtime());
        if (w == 1) {
            mbar_expect_elect(bar + 8 * B_XT, 40960);
            mbar_expect_elect(bar + 8 * (B_XT + 1), 40960);
            if (rank < 2) bulk_g2s_all3_elect(sb + OFF_X + rank * 40960, g_xn + rank * 40960, 40960, bar + 8 * (B_XT + rank));
            bar_sync(NB_PRO, 416);
            if (rank == 2) mbar_spin(bar + 8 * B_ST, 0);
            else mbar_arrive_remote_elect(mapa(bar + 8 * B_ST, 2));
            TLI(690 + blockIdx.x, 2, gtime());
            bar_arrive(NB_LD, 288);
        }
        uint32_t* hp = sy + 1024;
        auto hint = [&](uint32_t t) {
            asm volatile("{.reg .pred p; elect.sync _|p, 0xffffffff; @p red.relaxed.gpu.global.max.u32 [%0+4],%1; @p red.relaxed.gpu.global.add.u32 [%0],1;}"
                         ::"l"(hp), "r"(t) : "memory");
        };
        if (rank == 2) {
            if (w == 0) {
                for (int s = -1; s < NSEG - 1; s++) {
                    const uint32_t pb = s & 1, nby = s < 1 ? 8192 : 4096, va = sb + OFF_VX + (pb ^ 1) * 8192 + 8192 - nby, vb = bar + 8 * (B_VX + (pb ^ 1));
                    bar_sync(NB_KF, 288);
                    fence_async();
                    bulk_s2s_elect(mapa(va, 0), va, nby, mapa(vb, 0));
                    bulk_s2s_elect(mapa(va, 1), va, nby, mapa(vb, 1));
                    if (s >= 0) mbar_spin(bar + 8 * (B_XD + pb), (s >> 1) & 1);
                    bar_sync(NB_W1, 480);
                }
            } else if (w == 1) {
                const unsigned char *pn = g_p + (H_ + h) * 12288, *px = g_xn + 2 * 40960;
                const uint32_t* pf = sy + wk::SY_P + h;
                bar_sync(NB_W1, 480);
                for (int s = 0, nb = 1; s < NSEG - 1; s++, pn += H_ * 12288, px += 40960) {
                    const uint32_t pb = s & 1, xt = bar + 8 * (B_XT + pb), qa = sb + OFF_Q + (pb ^ 1) * 5120 + 1024;
                    mbar_spin(bar + 8 * (B_X1 + pb), (s >> 1) & 1);
                    if (s + 2 < NSEG) bulk_g2s_all3_elect(sb + OFF_X + pb * 40960, px, 40960, xt);
                    if (s == nb) {
                        while (__any_sync(~0u, ld_acquire(pf) < 3)) {}
                        pf += H_;
                        nb += s == 1 ? 4 : 6;
                    }
                    if (s) {
                        bulk_g2s_all3_elect(sb + OFF_VX + (pb ^ 1) * 8192, pn + 8192, 4096, bar + 8 * (B_VX + (pb ^ 1)));
                        bulk_g2s_elect(mapa(qa, 0), pn, 4096, mapa(xt, 0));
                        bulk_g2s_elect(mapa(qa, 1), pn + 4096, 4096, mapa(xt, 1));
                    }
                    mbar_spin(xt, ((s + 2) >> 1) & 1);
                    bar_sync(NB_W1, 480);
                }
                mbar_spin(bar + 8 * (B_VX + 1), 1);
            } else if (w == 2) {
                const char* pf = lane < 5 ? (const char*)(g_acc + layer * ACC_LAYER) + (5 * h + lane) * 1024 : (const char*)hp;
                const int pfa = lane < 5 ? 163840 : 1024;
                if (lane < 6) for (int i = 0; i < 8; i++) prefetch_l2(pf + i * 128);
                __syncwarp();
                const uint32_t go = mapa(bar + 8 * B_GO, min(lane, 2));
                for (int s = 0; s < NSEG - 1; s++, hp += 32) {
                    bar_sync(NB_W1, 480);
                    sts32(sb + OFF_MX + 32, 0);
                    uint32_t t = gtime32(), t0 = clk(), c, tm;
                    hint(t);
                    if (h == 0) TLI(940 + s, 0, t);
                    if (lane < 6 && s < NSEG - 8) prefetch_l2(pf + ((s >> 3) + 1) * pfa + (s & 7) * 128);
                    __syncwarp();
                    while (clk() - t0 < (uint32_t)delay2) {}
                    do asm volatile("ld.relaxed.gpu.global.v2.u32 {%0,%1},[%2];" : "=r"(c), "=r"(tm) : "l"(hp) : "memory"); while (__any_sync(~0u, c != 3 * H_));
                    const uint32_t wait = min(tm - t, 10000u) * 7 / 4 + delay;
                    while (clk() - t0 < wait) {}
                    if (lane < 3) mbar_arrive_remote(go);
                    __syncwarp();
                }
                bar_sync(NB_W1, 480);
            }
        } else {
            if (w < 2) sts32(sb + OFF_PT + w * 768 + 640 + lane * 4, 0u);
            const uint32_t px = opaque(sb + OFF_PX + (w & 1) * 1280 + lane * 8);
            const uint32_t pt = opaque(sb + OFF_PT + (w & 1) * 768 + lane * 4);
            uint32_t os = opaque(sb + OFF_OST + (lane >> 4) * 1024 + w * 256 + (lane & 15) * 16);
            uint32_t& sfd = os;
            const int lim = opaque(8 * w + g + 8 - 2 * q);
            unsigned char* op = g_o + h * 8192 + rank * 2048;
            uint32_t* oc = sy + wk::SY_O;
            auto report = [&]() {
                bulk_wait<0>();
                __syncwarp();
                asm volatile("{.reg .pred p; elect.sync _|p, 0xffffffff; @p red.relaxed.gpu.global.add.u32 [%0],1;}" ::"l"(oc) : "memory");
                oc++;
            };
            auto store_o = [&](int n) {
                bulk_s2g_elect(op, sb + OFF_OST + (n & 1) * 4096, 2048);
                bulk_s2g_elect(op + 4096, sb + OFF_OST + (n & 1) * 4096 + 2048, 2048);
                bulk_commit();
                op += H_ * 8192;
            };
            for (int s = 0; s < NSEG; s++) {
                const uint32_t pb = s & 1, ph = (s >> 1) & 1;
                if ((w >> 1) != rank) { if (s >= 1) mbar_spin(bar + 8 * B_PXE, pb ^ 1); }
                else if (w & 1) mbar_spin(bar + 8 * (B_XT + (pb ^ 1)), ((s + 1) >> 1) & 1);
                else mbar_expect_elect(bar + 8 * B_PXF, rank ? 2560 : 1536);
                const u64 dq = mkdesc(sb + OFF_Q + pb * 5120 + 1024, 128, 512), dk = mkdesc(sb + OFF_K + pb * 5120, 128, 1024);
                SFENCE();
                bar_sync(NB_W1, 512);
                float c[20];
                wg_fence();
                wgmma_n40_ss<0>(c, dq, dk);
#pragma unroll
                for (int ks = 1; ks < 4; ks++) wgmma_n40_ss<1>(c, dq + ks * 16, dk + ks * 16);
                wg_commit();
                bar_arrive(NB_X, 384);
                if (w == 2 * rank) { hint(gtime32()); hp += 32; }
                wg_wait<0>();
                if ((w >> 1) != rank) {
                    const uint32_t pa = mapa(px, rank ^ 1), pf = mapa(bar + 8 * B_PXF, rank ^ 1);
#pragma unroll
                    for (int nt = 0; nt < 5; nt++)
                        if (nt < 3 || rank == 0) st_async2(pa + nt * 256, __float_as_uint(c[4 * nt]), __float_as_uint(c[4 * nt + 1]), pf);
                    if ((w & 1) && s) store_o(s - 1);
                    mbar_spin(bar + 8 * (w & 1 ? B_VX : B_VM) + 8 * pb, ph);
                } else {
                    mbar_spin(bar + 8 * B_PXF, pb);
                    float u[10];
#pragma unroll
                    for (int nt = 0; nt < 5; nt++) lds64f(u[2 * nt], u[2 * nt + 1], px + nt * 256);
#pragma unroll
                    for (int i = 0; i < 10; i++) u[i] = 8 * (i >> 1) + (i & 1) <= lim ? u[i] + c[4 * (i >> 1) + (i & 1)] : -INFINITY;
                    float mx = fmaxf(fmaxf(fmaxf(fmaxf(u[0], u[1]), fmaxf(u[2], u[3])), fmaxf(fmaxf(u[4], u[5]), fmaxf(u[6], u[7]))), fmaxf(u[8], u[9]));
                    const float m1 = __shfl_xor_sync(~0u, mx, 1), m2 = __shfl_xor_sync(~0u, mx, 2), m3 = __shfl_xor_sync(~0u, mx, 3);
                    mx = fmaxf(fmaxf(mx, m1), fmaxf(m2, m3)) * SM_SCALE;
#pragma unroll
                    for (int i = 0; i < 10; i++) u[i] = ex2(fmaf(u[i], SM_SCALE, -mx));
                    float sum = (((u[0] + u[1]) + (u[2] + u[3])) + ((u[4] + u[5]) + (u[6] + u[7]))) + (u[8] + u[9]);
                    const float s1 = __shfl_xor_sync(~0u, sum, 1), s2 = __shfl_xor_sync(~0u, sum, 2), s3 = __shfl_xor_sync(~0u, sum, 3);
                    sum = rcp((sum + s1) + (s2 + s3));
#pragma unroll
                    for (int nt = 0; nt < 5; nt++) sts32(pt + (nt ? nt - 1 : 4) * 128, pack2(u[2 * nt] * sum, u[2 * nt + 1] * sum));
                }
                float acc[2][8];
                const u64 dv = mkdesc(sb + OFF_VX + pb * 8192, 128, 512), dp = mkdesc(sb + OFF_PT, 128, 768);
                const u64 dm = mkdesc(sb + OFF_VM + pb * 2048, 0, 128);
                fence_async();
                bar_sync(NB_WIN, 256);
                wg_fence();
#pragma unroll
                for (int m = 0; m < 2; m++) {
                    wgmma_n16_ss<0>(acc[m], dv + m * 256, dp);
                    wgmma_n16_ss<1>(acc[m], dv + m * 256 + 16, dp + 16);
                    wgmma_n16_ss<1>(acc[m], dm + m * 64, dp + 32);
                }
                wg_commit();
                bar_arrive_if<NB_W2, 384>(s < NSEG - 1);
                wg_wait<0>();
#pragma unroll
                for (int m = 0; m < 2; m++)
                    stsm4t(os + pb * 4096 + m * 2048, pack2(acc[m][0], acc[m][1]), pack2(acc[m][2], acc[m][3]), pack2(acc[m][4], acc[m][5]), pack2(acc[m][6], acc[m][7]));
                fence_async();
                mbar_arrive_remote_elect(mapa(bar + 8 * (B_XD + pb), 2));
                if ((w >> 1) == rank) mbar_arrive_remote_elect(mapa(bar + 8 * B_PXE, rank ^ 1));
                else if ((w & 1) && s) report();
            }
            bar_sync(NB_W2, 128);
            if (w == 3 - 2 * rank) {
                store_o(NSEG - 1);
                report();
            }
        }
    }
    __syncwarp();
    if (lane < 3) mbar_arrive_remote(mapa(bar + 8 * B_FIN, lane));
    mbar_wait(bar + 8 * B_FIN, 0);
    TLE(2 + 5 * layer);
    fence_async();
    if (warp < 8) asm volatile("setmaxnreg.dec.sync.aligned.u32 128;"); else asm volatile("setmaxnreg.inc.sync.aligned.u32 128;");
    }
    const int b = blockIdx.x;
    worker<false>(sb, maps, x, x1, layer, b >= 3 * H_ ? b - 3 * H_ : b < 10 * SPLIT_B ? wk::I_SB + b : -1, gridDim.x - 3 * H_);
}

int g_delay = 5001350, g_layers = 2;

void make_map(CUtensorMap* m, CUtensorMapDataType dt, const void* p, const cuuint64_t* dim, const cuuint64_t* str, const cuuint32_t* box, CUtensorMapSwizzle sw) {
    typedef CUresult (*Fn)(CUtensorMap*, CUtensorMapDataType, cuuint32_t, void*, const cuuint64_t*, const cuuint64_t*, const cuuint32_t*,
                           const cuuint32_t*, CUtensorMapInterleave, CUtensorMapSwizzle, CUtensorMapL2promotion, CUtensorMapFloatOOBfill);
    static Fn fn = nullptr;
    if (!fn) {
        cudaDriverEntryPointQueryResult qr;
        cudaGetDriverEntryPoint("cuTensorMapEncodeTiled", (void**)&fn, cudaEnableDefault, &qr);
    }
    const cuuint32_t es[3] = {1, 1, 1};
    fn(m, dt, 3, (void*)p, dim, str, box, es, CU_TENSOR_MAP_INTERLEAVE_NONE, sw, CU_TENSOR_MAP_L2_PROMOTION_L2_128B, CU_TENSOR_MAP_FLOAT_OOB_FILL_NONE);
}
void map_weight(CUtensorMap* m, const bf16* p, int rows, int cols, int ng, int br = 64) {
    const cuuint64_t dim[3] = {64, (cuuint64_t)rows, (cuuint64_t)cols / 64}, str[2] = {(cuuint64_t)cols * 2, 128};
    const cuuint32_t box[3] = {64, (cuuint32_t)br, (cuuint32_t)ng};
    make_map(m, CU_TENSOR_MAP_DATA_TYPE_BFLOAT16, p, dim, str, box, CU_TENSOR_MAP_SWIZZLE_128B);
}
void map_pieces(CUtensorMap* m, const void* p, int np, int ns) {
    const cuuint64_t dim[3] = {256, (cuuint64_t)np * 2, NSEG}, str[2] = {2048, (cuuint64_t)np * 4096};
    const cuuint32_t box[3] = {256, 2, (cuuint32_t)ns};
    make_map(m, CU_TENSOR_MAP_DATA_TYPE_UINT64, p, dim, str, box, CU_TENSOR_MAP_SWIZZLE_NONE);
}

template <class... P, class... A> void launch(void (*k)(P...), int grid, int block, int smem, int cluster, bool pdl, A... args) {
    cudaLaunchConfig_t c = {};
    c.gridDim = dim3(grid); c.blockDim = dim3(block); c.dynamicSmemBytes = smem; c.stream = cudaStreamPerThread;
    cudaLaunchAttribute at[2];
    int n = 0;
    if (cluster > 1) { at[n].id = cudaLaunchAttributeClusterDimension; at[n].val.clusterDim.x = cluster; at[n].val.clusterDim.y = 1; at[n].val.clusterDim.z = 1; n++; }
    if (pdl) { at[n].id = cudaLaunchAttributeProgrammaticStreamSerialization; at[n].val.programmaticStreamSerializationAllowed = 1; n++; }
    c.attrs = at; c.numAttrs = n;
    cudaLaunchKernelEx(&c, k, args...);
}

int max_clusters() {
    cudaLaunchConfig_t c = {};
    c.gridDim = dim3(3 * H_); c.blockDim = dim3(512); c.dynamicSmemBytes = rec::SMEM;
    cudaLaunchAttribute at[1];
    at[0].id = cudaLaunchAttributeClusterDimension; at[0].val.clusterDim.x = 3; at[0].val.clusterDim.y = 1; at[0].val.clusterDim.z = 1;
    c.attrs = at; c.numAttrs = 1;
    int n = 0;
    cudaOccupancyMaxActiveClusters(&n, rec_kernel, &c);
    return n;
}

}

extern "C" void kernel_launch(void* const* d_in, const int* in_sizes, int n_in, void* d_out, int out_size) {
    const bf16* x = (const bf16*)d_in[0];
    const bf16* mem0 = (const bf16*)d_in[1];
    const bf16* Wq = (const bf16*)d_in[2];
    const bf16* Wk = (const bf16*)d_in[3];
    const bf16* Wv = (const bf16*)d_in[4];
    const bf16* Wo = (const bf16*)d_in[5];
    const bf16* wr = (const bf16*)d_in[8];
    const bf16* wi = (const bf16*)d_in[9];
    cudaFuncSetAttribute(rec_kernel, cudaFuncAttributeMaxDynamicSharedMemorySize, rec::SMEM);
    cudaFuncSetAttribute(side_kernel, cudaFuncAttributeMaxDynamicSharedMemorySize, wk::SMEM);
    cudaFuncSetAttribute(colfft_kernel, cudaFuncAttributeMaxDynamicSharedMemorySize, CF_SMEM);
    Maps maps;
    void *pxn, *po;
    cudaGetSymbolAddress(&pxn, g_xn);
    cudaGetSymbolAddress(&po, g_o);
    map_weight(&maps.wq2, Wq, D_, 4096, 2); map_weight(&maps.wv1, Wv, D_, 4096, 1);
    map_weight(&maps.wo2, Wo, 4096, D_, 2); map_weight(&maps.wo1, Wo, 4096, D_, 1, 192);
    map_pieces(&maps.x6, pxn, 10, 6); map_pieces(&maps.x4, pxn, 10, 4);
    map_pieces(&maps.o6, po, 64, 6); map_pieces(&maps.o2, po, 64, 2);
    bf16 *x1, *x2;
    cudaGetSymbolAddress((void**)&x1, g_x1);
    cudaGetSymbolAddress((void**)&x2, g_x2);
    constexpr int ONE_PER_SM = 116 * 1024;
    cudaFuncSetAttribute(rowfft_kernel, cudaFuncAttributeMaxDynamicSharedMemorySize, ONE_PER_SM);
    cudaFuncSetAttribute(rowifft_kernel, cudaFuncAttributeMaxDynamicSharedMemorySize, ONE_PER_SM);
    static int ncl = 0, nsm = 0;
    if (!ncl) { ncl = max_clusters(); cudaDeviceGetAttribute(&nsm, cudaDevAttrMultiProcessorCount, 0); }
    maps.wr = wr; maps.wi = wi;
    launch(prep_kernel, 128, 512, 0, 1, false, x, Wq, Wk, Wv, Wo);
    for (int layer = 0; layer < g_layers; layer++) {
        const bf16* xin = layer ? x2 : x;
        launch(rec_kernel, 3 * ncl, 512, rec::SMEM, 3, true, maps, xin, x1, mem0, Wq, Wk, Wv, Wo, layer, g_delay % 10000, g_delay / 10000);
        launch(side_kernel, max(nsm - 3 * ncl, 1), 512, wk::SMEM, 1, true, maps, xin, x1, layer, 3 * (ncl - H_));
        launch(rowfft_kernel, 128, 256, ONE_PER_SM, 1, true, xin, x1, Wq, Wk, Wv, layer);
        launch(colfft_kernel, 107, 384, CF_SMEM, 1, true, layer);
        launch(rowifft_kernel, 128, 256, ONE_PER_SM, 1, true, (const bf16*)x1, layer ? (bf16*)d_out : x2, layer);
    }
}
```

```cpp
#include <cuda_runtime.h>
#include <cuda_bf16.h>
#include <cuda.h>
#include <stdint.h>

#define DEV __device__ __forceinline__
typedef unsigned long long u64;
typedef __nv_bfloat16 bf16;

namespace {

constexpr int S_ = 2048, D_ = 640, H_ = 32, E_ = 128, NSEG = 64;

__device__ __align__(1024) unsigned char g_xn[S_ * D_ * 2];
__device__ __align__(1024) unsigned char g_o[S_ * H_ * E_ * 2];
constexpr int ACC_LAYER = 32 * 5120;
__device__ __align__(4096) u64 g_acc[2 * ACC_LAYER];
__device__ __align__(16) float g_nrm[256];
__device__ __align__(1024) unsigned char g_p[NSEG * H_ * 3 * 4096];
constexpr int SYNC_LAYER = 1024 + 64 * 32;
__device__ __align__(128) uint32_t g_sync[2 * SYNC_LAYER];
__device__ uint32_t g_started[2];
__device__ __align__(1024) bf16 g_x1[S_ * D_];
__device__ __align__(1024) bf16 g_x2[S_ * D_];
constexpr int YT_ROWS = 128;
__device__ __align__(1024) float g_yt[2 * YT_ROWS * D_];
constexpr int NCOL = 321;
__device__ __align__(1024) unsigned char g_z[NCOL * 8192];
__device__ __align__(1024) unsigned char g_wt[NCOL * 8192];
__device__ __align__(1024) uint4 g_f128[2 * 8 * 256];
__device__ __align__(1024) uint4 g_f64[2 * 4 * 128];
__device__ __align__(1024) bf16 g_g32[2 * 4096];
#define TLI(id, k, v)
#define TLS(i)
#define TLE(i)

DEV uint32_t s2u(const void* p) { return (uint32_t)__cvta_generic_to_shared(p); }
DEV uint32_t clk() { uint32_t c; asm volatile("mov.u32 %0,%%clock;" : "=r"(c)::"memory"); return c; }
DEV uint32_t gtime32() { uint32_t t; asm volatile("mov.u32 %0,%%globaltimer_lo;" : "=r"(t)::"memory"); return t; }
DEV uint32_t cta_rank() { uint32_t r; asm volatile("mov.u32 %0,%%cluster_ctarank;" : "=r"(r)); return __shfl_sync(~0u, r, 0); }
DEV uint32_t mapa(uint32_t a, uint32_t r) { uint32_t o; asm("mapa.shared::cluster.u32 %0,%1,%2;" : "=r"(o) : "r"(a), "r"(r)); return o; }
DEV void mbar_init(uint32_t b, uint32_t n) { asm volatile("mbarrier.init.shared::cta.b64 [%0],%1;" ::"r"(b), "r"(n) : "memory"); }
DEV bool mbar_try(uint32_t b, uint32_t par, int) {
    uint32_t ok;
    asm volatile("{.reg .pred p; mbarrier.test_wait.parity.shared::cta.b64 p,[%1],%2; selp.u32 %0,1,0,p;}" : "=r"(ok) : "r"(b), "r"(par) : "memory");
    return ok;
}
DEV bool mbar_try(uint32_t b, uint32_t par) {
    uint32_t ok;
    asm volatile("{.reg .pred p; mbarrier.try_wait.parity.shared::cta.b64 p,[%1],%2; selp.u32 %0,1,0,p;}" : "=r"(ok) : "r"(b), "r"(par) : "memory");
    return ok;
}
constexpr uint32_t SPIN_LIMIT = 1u << 18;
DEV void die() { __trap(); }
DEV void mbar_wait(uint32_t b, uint32_t par) {
    uint32_t n = 0;
    while (!mbar_try(b, par)) if (++n > SPIN_LIMIT) die();
}
DEV void mbar_spin(uint32_t b, uint32_t par) { while (!mbar_try(b, par)) {} }
DEV uint32_t opaque(uint32_t x) { return __shfl_xor_sync(~0u, x, 0); }
#define SFENCE() asm volatile("{.reg .pred p; setp.ne.u32 p,%1,0; @p mov.u32 %0,%%clock;}" : "+r"(sfd) : "r"((uint32_t)never) : "memory")
DEV void mbar_arrive(uint32_t b) { asm volatile("mbarrier.arrive.shared::cta.b64 _,[%0];" ::"r"(b) : "memory"); }
DEV void mbar_arrive_elect(uint32_t b) { asm volatile("{.reg .pred p; elect.sync _|p, 0xffffffff; @p mbarrier.arrive.shared::cta.b64 _,[%0];}" ::"r"(b) : "memory"); }
DEV void mbar_arrive_elect_if(uint32_t b, bool c) {
    asm volatile("{.reg .pred p, q; setp.ne.u32 q,%1,0; elect.sync _|p, 0xffffffff; and.pred p,p,q; @p mbarrier.arrive.shared::cta.b64 _,[%0];}" ::"r"(b), "r"((uint32_t)c) : "memory");
}
DEV void mbar_expect_elect(uint32_t b, uint32_t tx) {
    asm volatile("{.reg .pred p; elect.sync _|p, 0xffffffff; @p mbarrier.arrive.expect_tx.shared::cta.b64 _,[%0],%1;}" ::"r"(b), "r"(tx) : "memory");
}
DEV void mbar_arrive_remote_elect(uint32_t b) { asm volatile("{.reg .pred p; elect.sync _|p, 0xffffffff; @p mbarrier.arrive.shared::cluster.b64 _,[%0];}" ::"r"(b) : "memory"); }
DEV bool elect() { uint32_t r; asm volatile("{.reg .pred p; elect.sync _|p, 0xffffffff; selp.u32 %0,1,0,p;}" : "=r"(r)); return r; }
DEV void mbar_arrive_remote(uint32_t b) { asm volatile("mbarrier.arrive.shared::cluster.b64 _,[%0];" ::"r"(b) : "memory"); }
DEV void mbar_expect(uint32_t b, uint32_t tx) { asm volatile("mbarrier.arrive.expect_tx.shared::cta.b64 _,[%0],%1;" ::"r"(b), "r"(tx) : "memory"); }
DEV void bar_sync(int id, int n) { asm volatile("bar.sync %0,%1;" ::"r"(id), "r"(n) : "memory"); }
DEV void bar_arrive(int id, int n) { asm volatile("bar.arrive %0,%1;" ::"r"(id), "r"(n) : "memory"); }
template <int ID, int N> DEV void bar_arrive_if(bool p) {
    asm volatile("{.reg .pred p; setp.ne.u32 p,%0,0; @p bar.arrive %1,%2;}" ::"r"((uint32_t)p), "n"(ID), "n"(N) : "memory");
}
DEV void prefetch_l2(const void* p) { asm volatile("prefetch.global.L2 [%0];" ::"l"(p) : "memory"); }
template <int ID, int N> DEV void bar_sync_if(bool p) {
    asm volatile("{.reg .pred p; setp.ne.u32 p,%0,0; @p bar.sync %1,%2;}" ::"r"((uint32_t)p), "n"(ID), "n"(N) : "memory");
}
DEV void st_remote(uint32_t a, uint32_t x) { asm volatile("st.relaxed.cluster.shared::cluster.u32 [%0],%1;" ::"r"(a), "r"(x) : "memory"); }
DEV void st_async1(uint32_t a, uint32_t x, uint32_t b) {
    asm volatile("st.async.shared::cluster.mbarrier::complete_tx::bytes.u32 [%0],%1,[%2];" ::"r"(a), "r"(x), "r"(b) : "memory");
}
DEV void st_async2(uint32_t a, uint32_t x, uint32_t y, uint32_t b) {
    asm volatile("st.async.shared::cluster.mbarrier::complete_tx::bytes.v2.u32 [%0],{%1,%2},[%3];" ::"r"(a), "r"(x), "r"(y), "r"(b) : "memory");
}
DEV void st_async4(uint32_t a, uint32_t x, uint32_t y, uint32_t z, uint32_t w, uint32_t b) {
    asm volatile("st.async.shared::cluster.mbarrier::complete_tx::bytes.v4.u32 [%0],{%1,%2,%3,%4},[%5];" ::"r"(a), "r"(x), "r"(y), "r"(z), "r"(w), "r"(b) : "memory");
}
DEV void bulk_g2s(uint32_t dst, const void* src, uint32_t bytes, uint32_t b) {
    asm volatile("cp.async.bulk.shared::cluster.global.mbarrier::complete_tx::bytes [%0],[%1],%2,[%3];" ::"r"(dst), "l"(src), "r"(bytes), "r"(b) : "memory");
}
DEV void bulk_g2s_elect(uint32_t dst, const void* src, uint32_t bytes, uint32_t b) {
    asm volatile("{.reg .pred p; elect.sync _|p, 0xffffffff; @p cp.async.bulk.shared::cluster.global.mbarrier::complete_tx::bytes [%0],[%1],%2,[%3];}"
                 ::"r"(dst), "l"(src), "r"(bytes), "r"(b) : "memory");
}
DEV void bulk_g2s_all3_elect(uint32_t dst, const void* src, uint32_t bytes, uint32_t b) {
    asm volatile("{.reg .pred p; elect.sync _|p, 0xffffffff; @p cp.async.bulk.shared::cluster.global.mbarrier::complete_tx::bytes.multicast::cluster [%0],[%1],%2,[%3],%4;}"
                 ::"r"(dst), "l"(src), "r"(bytes), "r"(b), "h"((unsigned short)7) : "memory");
}
DEV void bulk_s2s_elect(uint32_t dst, uint32_t src, uint32_t bytes, uint32_t b) {
    asm volatile("{.reg .pred p; elect.sync _|p, 0xffffffff; @p cp.async.bulk.shared::cluster.shared::cta.mbarrier::complete_tx::bytes [%0],[%1],%2,[%3];}"
                 ::"r"(dst), "r"(src), "r"(bytes), "r"(b) : "memory");
}
DEV void bulk_s2g_elect(void* dst, uint32_t src, uint32_t bytes) {
    asm volatile("{.reg .pred p; elect.sync _|p, 0xffffffff; @p cp.async.bulk.global.shared::cta.bulk_group [%0],[%1],%2;}" ::"l"(dst), "r"(src), "r"(bytes) : "memory");
}
DEV void bulk_s2s(uint32_t dst, uint32_t src, uint32_t bytes, uint32_t b) {
    asm volatile("cp.async.bulk.shared::cluster.shared::cta.mbarrier::complete_tx::bytes [%0],[%1],%2,[%3];" ::"r"(dst), "r"(src), "r"(bytes), "r"(b) : "memory");
}
DEV void bulk_s2g(void* dst, uint32_t src, uint32_t bytes) {
    asm volatile("cp.async.bulk.global.shared::cta.bulk_group [%0],[%1],%2;" ::"l"(dst), "r"(src), "r"(bytes) : "memory");
}
DEV void tma3d(uint32_t dst, const CUtensorMap* m, int c0, int c1, int c2, uint32_t b) {
    asm volatile("cp.async.bulk.tensor.3d.shared::cluster.global.mbarrier::complete_tx::bytes [%0],[%1,{%3,%4,%5}],[%2];"
                 ::"r"(dst), "l"(m), "r"(b), "r"(c0), "r"(c1), "r"(c2) : "memory");
}
DEV void bulk_commit() { asm volatile("cp.async.bulk.commit_group;" ::: "memory"); }
template <int N> DEV void bulk_wait() { asm volatile("cp.async.bulk.wait_group %0;" ::"n"(N) : "memory"); }
template <int N> DEV void bulk_wait_read() { asm volatile("cp.async.bulk.wait_group.read %0;" ::"n"(N) : "memory"); }
DEV void flag_add(uint32_t* p) { asm volatile("red.relaxed.gpu.global.add.u32 [%0],1;" ::"l"(p) : "memory"); }
DEV uint32_t ld_acquire(const uint32_t* p) { uint32_t v; asm volatile("ld.acquire.gpu.global.u32 %0,[%1];" : "=r"(v) : "l"(p) : "memory"); return v; }
DEV void flag_wait(const uint32_t* p, uint32_t n) {
    for (uint32_t it = 0; ld_acquire(p) < n; __nanosleep(40)) if (++it > (SPIN_LIMIT << 3)) die();
}
DEV void cp16(uint32_t dst, const void* src) { asm volatile("cp.async.cg.shared.global [%0],[%1],16;" ::"r"(dst), "l"(src) : "memory"); }
DEV void cp_commit() { asm volatile("cp.async.commit_group;" ::: "memory"); }
template <int N> DEV void cp_wait() { asm volatile("cp.async.wait_group %0;" ::"n"(N) : "memory"); }
DEV uint32_t lds32(uint32_t a) { uint32_t x; asm volatile("ld.shared.u32 %0,[%1];" : "=r"(x) : "r"(a) : "memory"); return x; }
DEV void fence_async() { asm volatile("fence.proxy.async.shared::cta;" ::: "memory"); }
DEV uint32_t pack2(float lo, float hi) { uint32_t r; asm("cvt.rn.bf16x2.f32 %0,%1,%2;" : "=r"(r) : "f"(hi), "f"(lo)); return r; }
DEV uint32_t prmt(uint32_t a, uint32_t b, uint32_t s) { uint32_t r; asm("prmt.b32 %0,%1,%2,%3;" : "=r"(r) : "r"(a), "r"(b), "r"(s)); return r; }
DEV float ex2(float x) { float r; asm("ex2.approx.ftz.f32 %0,%1;" : "=f"(r) : "f"(x)); return r; }
DEV float sqrt_approx(float x) { float r; asm("sqrt.approx.ftz.f32 %0,%1;" : "=f"(r) : "f"(x)); return r; }
DEV float rcp(float x) { float r; asm("rcp.approx.ftz.f32 %0,%1;" : "=f"(r) : "f"(x)); return r; }
DEV void lds128(uint32_t* r, uint32_t a) { asm volatile("ld.shared.v4.u32 {%0,%1,%2,%3},[%4];" : "=r"(r[0]), "=r"(r[1]), "=r"(r[2]), "=r"(r[3]) : "r"(a) : "memory"); }
DEV void lds64(uint32_t* r, uint32_t a) { asm volatile("ld.shared.v2.u32 {%0,%1},[%2];" : "=r"(r[0]), "=r"(r[1]) : "r"(a) : "memory"); }
DEV void lds64f(float& x, float& y, uint32_t a) { asm volatile("ld.shared.v2.f32 {%0,%1},[%2];" : "=f"(x), "=f"(y) : "r"(a) : "memory"); }
DEV void lds128f(float* r, uint32_t a) { asm volatile("ld.shared.v4.f32 {%0,%1,%2,%3},[%4];" : "=f"(r[0]), "=f"(r[1]), "=f"(r[2]), "=f"(r[3]) : "r"(a) : "memory"); }
DEV void sts128(uint32_t a, uint32_t x, uint32_t y, uint32_t z, uint32_t w) { asm volatile("st.shared.v4.u32 [%0],{%1,%2,%3,%4};" ::"r"(a), "r"(x), "r"(y), "r"(z), "r"(w) : "memory"); }
DEV void sts64(uint32_t a, uint32_t x, uint32_t y) { asm volatile("st.shared.v2.u32 [%0],{%1,%2};" ::"r"(a), "r"(x), "r"(y) : "memory"); }
DEV void sts32(uint32_t a, uint32_t x) { asm volatile("st.shared.u32 [%0],%1;" ::"r"(a), "r"(x) : "memory"); }
DEV void ldsm4(uint32_t* r, uint32_t a) { asm volatile("ldmatrix.sync.aligned.m8n8.x4.shared.b16 {%0,%1,%2,%3},[%4];" : "=r"(r[0]), "=r"(r[1]), "=r"(r[2]), "=r"(r[3]) : "r"(a) : "memory"); }
DEV void ldsm4t(uint32_t* r, uint32_t a) { asm volatile("ldmatrix.sync.aligned.m8n8.x4.trans.shared.b16 {%0,%1,%2,%3},[%4];" : "=r"(r[0]), "=r"(r[1]), "=r"(r[2]), "=r"(r[3]) : "r"(a) : "memory"); }
DEV void ldsm2(uint32_t* r, uint32_t a) { asm volatile("ldmatrix.sync.aligned.m8n8.x2.shared.b16 {%0,%1},[%2];" : "=r"(r[0]), "=r"(r[1]) : "r"(a) : "memory"); }
DEV void stsm4t(uint32_t a, uint32_t x, uint32_t y, uint32_t z, uint32_t w) { asm volatile("stmatrix.sync.aligned.m8n8.x4.trans.shared.b16 [%0],{%1,%2,%3,%4};" ::"r"(a), "r"(x), "r"(y), "r"(z), "r"(w) : "memory"); }
DEV void stsm4(uint32_t a, uint32_t x, uint32_t y, uint32_t z, uint32_t w) { asm volatile("stmatrix.sync.aligned.m8n8.x4.shared.b16 [%0],{%1,%2,%3,%4};" ::"r"(a), "r"(x), "r"(y), "r"(z), "r"(w) : "memory"); }
DEV void stsm2(uint32_t a, uint32_t x, uint32_t y) { asm volatile("stmatrix.sync.aligned.m8n8.x2.shared.b16 [%0],{%1,%2};" ::"r"(a), "r"(x), "r"(y) : "memory"); }
DEV void sts128f_if(uint32_t a, const float* v, bool p) {
    asm volatile("{.reg .pred p; setp.ne.u32 p,%5,0; @p st.shared.v4.f32 [%0],{%1,%2,%3,%4};}" ::"r"(a), "f"(v[0]), "f"(v[1]), "f"(v[2]), "f"(v[3]), "r"((uint32_t)p) : "memory");
}
DEV void lds128f_if(float* v, uint32_t a, bool p) {
    asm volatile("{.reg .pred p; setp.ne.u32 p,%5,0; @p ld.shared.v4.f32 {%0,%1,%2,%3},[%4];}"
                 : "+f"(v[0]), "+f"(v[1]), "+f"(v[2]), "+f"(v[3]) : "r"(a), "r"((uint32_t)p) : "memory");
}
DEV void stsm2t_if(uint32_t a, uint32_t x, uint32_t y, bool p) {
    asm volatile("{.reg .pred p; setp.ne.u32 p,%3,0; @p stmatrix.sync.aligned.m8n8.x2.trans.shared.b16 [%0],{%1,%2};}" ::"r"(a), "r"(x), "r"(y), "r"((uint32_t)p) : "memory");
}
DEV void stsm2t(uint32_t a, uint32_t x, uint32_t y) { asm volatile("stmatrix.sync.aligned.m8n8.x2.trans.shared.b16 [%0],{%1,%2};" ::"r"(a), "r"(x), "r"(y) : "memory"); }
DEV void mma16(float* d, uint32_t a0, uint32_t a1, uint32_t a2, uint32_t a3, uint32_t b0, uint32_t b1) {
    asm volatile("mma.sync.aligned.m16n8k16.row.col.f32.bf16.bf16.f32 {%0,%1,%2,%3},{%4,%5,%6,%7},{%8,%9},{%0,%1,%2,%3};"
                 : "+f"(d[0]), "+f"(d[1]), "+f"(d[2]), "+f"(d[3]) : "r"(a0), "r"(a1), "r"(a2), "r"(a3), "r"(b0), "r"(b1));
}
DEV void mma8(float* d, uint32_t a0, uint32_t a1, uint32_t b0) {
    asm volatile("mma.sync.aligned.m16n8k8.row.col.f32.bf16.bf16.f32 {%0,%1,%2,%3},{%4,%5},{%6},{%0,%1,%2,%3};"
                 : "+f"(d[0]), "+f"(d[1]), "+f"(d[2]), "+f"(d[3]) : "r"(a0), "r"(a1), "r"(b0));
}
DEV u64 mkdesc(uint32_t a, uint32_t lbo, uint32_t sbo) { return (u64)((a & 0x3ffff) >> 4) | ((u64)(lbo >> 4) << 16) | ((u64)(sbo >> 4) << 32); }
constexpr u64 SW128 = 1ull << 62;
DEV void wg_fence() { asm volatile("wgmma.fence.sync.aligned;" ::: "memory"); }
DEV void wg_commit() { asm volatile("wgmma.commit_group.sync.aligned;" ::: "memory"); }
template <int N> DEV void wg_wait() { asm volatile("wgmma.wait_group.sync.aligned %0;" ::"n"(N) : "memory"); }
template <int ACC> DEV void wgmma_n32_rs(float* d, const uint32_t* a, u64 desc) {
    asm volatile("wgmma.mma_async.sync.aligned.m64n32k16.f32.bf16.bf16 {%0,%1,%2,%3,%4,%5,%6,%7,%8,%9,%10,%11,%12,%13,%14,%15},{%16,%17,%18,%19},%20,%21,1,1,0;"
                 : "+f"(d[0]), "+f"(d[1]), "+f"(d[2]), "+f"(d[3]), "+f"(d[4]), "+f"(d[5]), "+f"(d[6]), "+f"(d[7]),
                   "+f"(d[8]), "+f"(d[9]), "+f"(d[10]), "+f"(d[11]), "+f"(d[12]), "+f"(d[13]), "+f"(d[14]), "+f"(d[15])
                 : "r"(a[0]), "r"(a[1]), "r"(a[2]), "r"(a[3]), "l"(desc), "n"(ACC));
}
template <int ACC> DEV void wgmma_n32_ss(float* d, u64 da, u64 desc) {
    asm volatile("wgmma.mma_async.sync.aligned.m64n32k16.f32.bf16.bf16 {%0,%1,%2,%3,%4,%5,%6,%7,%8,%9,%10,%11,%12,%13,%14,%15},%16,%17,%18,1,1,1,0;"
                 : "+f"(d[0]), "+f"(d[1]), "+f"(d[2]), "+f"(d[3]), "+f"(d[4]), "+f"(d[5]), "+f"(d[6]), "+f"(d[7]),
                   "+f"(d[8]), "+f"(d[9]), "+f"(d[10]), "+f"(d[11]), "+f"(d[12]), "+f"(d[13]), "+f"(d[14]), "+f"(d[15])
                 : "l"(da), "l"(desc), "n"(ACC));
}
template <int ACC> DEV void wgmma_n16_ss(float* d, u64 da, u64 desc) {
    asm volatile("wgmma.mma_async.sync.aligned.m64n16k16.f32.bf16.bf16 {%0,%1,%2,%3,%4,%5,%6,%7},%8,%9,%10,1,1,0,0;"
                 : "+f"(d[0]), "+f"(d[1]), "+f"(d[2]), "+f"(d[3]), "+f"(d[4]), "+f"(d[5]), "+f"(d[6]), "+f"(d[7])
                 : "l"(da), "l"(desc), "n"(ACC));
}
#define ACC8(o) "+f"(d[o]), "+f"(d[o + 1]), "+f"(d[o + 2]), "+f"(d[o + 3]), "+f"(d[o + 4]), "+f"(d[o + 5]), "+f"(d[o + 6]), "+f"(d[o + 7])
template <int ACC, int TB> DEV void wgmma_n64_rs(float* d, const uint32_t* a, u64 desc) {
    asm volatile("wgmma.mma_async.sync.aligned.m64n64k16.f32.bf16.bf16 {%0,%1,%2,%3,%4,%5,%6,%7,%8,%9,%10,%11,%12,%13,%14,%15,"
                 "%16,%17,%18,%19,%20,%21,%22,%23,%24,%25,%26,%27,%28,%29,%30,%31},{%32,%33,%34,%35},%36,%37,1,1,%38;"
                 : ACC8(0), ACC8(8), ACC8(16), ACC8(24) : "r"(a[0]), "r"(a[1]), "r"(a[2]), "r"(a[3]), "l"(desc), "n"(ACC), "n"(TB));
}
template <int ACC, int TB> DEV void wgmma_n80_rs(float* d, const uint32_t* a, u64 desc) {
    asm volatile("wgmma.mma_async.sync.aligned.m64n80k16.f32.bf16.bf16 {%0,%1,%2,%3,%4,%5,%6,%7,%8,%9,%10,%11,%12,%13,%14,%15,"
                 "%16,%17,%18,%19,%20,%21,%22,%23,%24,%25,%26,%27,%28,%29,%30,%31,%32,%33,%34,%35,%36,%37,%38,%39},{%40,%41,%42,%43},%44,%45,1,1,%46;"
                 : ACC8(0), ACC8(8), ACC8(16), ACC8(24), ACC8(32) : "r"(a[0]), "r"(a[1]), "r"(a[2]), "r"(a[3]), "l"(desc), "n"(ACC), "n"(TB));
}
template <int TA, int TB> DEV void wgmma_n64_ss(float* d, u64 da, u64 db, int acc) {
    asm volatile("{.reg .pred p; setp.ne.b32 p,%34,0; wgmma.mma_async.sync.aligned.m64n64k16.f32.bf16.bf16 {%0,%1,%2,%3,%4,%5,%6,%7,%8,%9,%10,%11,%12,%13,%14,%15,%16,%17,%18,%19,%20,%21,%22,%23,%24,%25,%26,%27,%28,%29,%30,%31},%32,%33,p,1,1,%35,%36;}"
                 : ACC8(0), ACC8(8), ACC8(16), ACC8(24) : "l"(da), "l"(db), "r"(acc), "n"(TA), "n"(TB));
}
template <int TA, int TB> DEV void wgmma_n128_ss(float* d, u64 da, u64 db, int acc) {
    asm volatile("{.reg .pred p; setp.ne.b32 p,%66,0; wgmma.mma_async.sync.aligned.m64n128k16.f32.bf16.bf16 {%0,%1,%2,%3,%4,%5,%6,%7,%8,%9,%10,%11,%12,%13,%14,%15,%16,%17,%18,%19,%20,%21,%22,%23,%24,%25,%26,%27,%28,%29,%30,%31,%32,%33,%34,%35,%36,%37,%38,%39,%40,%41,%42,%43,%44,%45,%46,%47,%48,%49,%50,%51,%52,%53,%54,%55,%56,%57,%58,%59,%60,%61,%62,%63},%64,%65,p,1,1,%67,%68;}"
                 : ACC8(0), ACC8(8), ACC8(16), ACC8(24), ACC8(32), ACC8(40), ACC8(48), ACC8(56) : "l"(da), "l"(db), "r"(acc), "n"(TA), "n"(TB));
}
template <int TA, int TB> DEV void wgmma_n192_ss(float* d, u64 da, u64 db, int acc) {
    asm volatile("{.reg .pred p; setp.ne.b32 p,%98,0; wgmma.mma_async.sync.aligned.m64n192k16.f32.bf16.bf16 {%0,%1,%2,%3,%4,%5,%6,%7,%8,%9,%10,%11,%12,%13,%14,%15,%16,%17,%18,%19,%20,%21,%22,%23,%24,%25,%26,%27,%28,%29,%30,%31,%32,%33,%34,%35,%36,%37,%38,%39,%40,%41,%42,%43,%44,%45,%46,%47,%48,%49,%50,%51,%52,%53,%54,%55,%56,%57,%58,%59,%60,%61,%62,%63,%64,%65,%66,%67,%68,%69,%70,%71,%72,%73,%74,%75,%76,%77,%78,%79,%80,%81,%82,%83,%84,%85,%86,%87,%88,%89,%90,%91,%92,%93,%94,%95},%96,%97,p,1,1,%99,%100;}"
                 : ACC8(0), ACC8(8), ACC8(16), ACC8(24), ACC8(32), ACC8(40), ACC8(48), ACC8(56), ACC8(64), ACC8(72), ACC8(80), ACC8(88) : "l"(da), "l"(db), "r"(acc), "n"(TA), "n"(TB));
}
template <int ACC> DEV void wgmma_n40_ss(float* d, u64 da, u64 desc) {
    asm volatile("wgmma.mma_async.sync.aligned.m64n40k16.f32.bf16.bf16 {%0,%1,%2,%3,%4,%5,%6,%7,%8,%9,%10,%11,%12,%13,%14,%15,%16,%17,%18,%19},%20,%21,%22,1,1,0,0;"
                 : ACC8(0), ACC8(8), "+f"(d[16]), "+f"(d[17]), "+f"(d[18]), "+f"(d[19]) : "l"(da), "l"(desc), "n"(ACC));
}
DEV void pdl_wait() { asm volatile("griddepcontrol.wait;" ::: "memory"); }
DEV void pdl_launch() { asm volatile("griddepcontrol.launch_dependents;" ::: "memory"); }
DEV uint32_t ldg32(const void* p) { uint32_t v; asm volatile("ld.global.nc.u32 %0,[%1];" : "=r"(v) : "l"(p)); return v; }
DEV void ld_acc(u64& a, u64& b, const void* p) {
    const uint32_t done = (uint32_t)a & (uint32_t)b & 32u;
    asm volatile("{.reg .pred p; setp.eq.u32 p,%3,0;\n"
                 "@p ld.relaxed.gpu.global.v2.u64 {%0,%1},[%2];}" : "+l"(a), "+l"(b) : "l"(p), "r"(done) : "memory");
}
DEV void ld_acc0(u64& a, u64& b, const void* p) {
    asm volatile("ld.relaxed.gpu.global.v2.u64 {%0,%1},[%2];" : "=l"(a), "=l"(b) : "l"(p) : "memory");
}
DEV uint32_t and3(uint32_t a, uint32_t b, uint32_t c) { uint32_t r; asm volatile("lop3.b32 %0,%1,%2,%3,0x80;" : "=r"(r) : "r"(a), "r"(b), "r"(c)); return r; }
DEV uint32_t absmax2(uint32_t a, uint32_t b) { uint32_t r; asm("max.xorsign.abs.bf16x2 %0,%1,%2;" : "=r"(r) : "r"(a), "r"(b)); return r; }
DEV float lds32f(uint32_t a) { float x; asm volatile("ld.shared.f32 %0,[%1];" : "=f"(x) : "r"(a) : "memory"); return x; }
DEV void red_add64(u64* p, uint32_t lo, uint32_t hi) {
    asm volatile("{.reg .b64 v; mov.b64 v,{%1,%2}; red.relaxed.gpu.global.add.u64 [%0],v;}" ::"l"(p), "r"(lo), "r"(hi) : "memory");
}
DEV float bf_round(float x) { return __bfloat162float(__float2bfloat16_rn(x)); }
DEV float bf_lo(uint32_t u) { return __uint_as_float(u << 16); }
DEV float bf_hi(uint32_t u) { return __uint_as_float(u & 0xffff0000u); }

#define GPROF(i, n)
#define PROFT(i)
#define STAMP(i)

DEV void unpack8(float* v, uint4 u) {
    v[0] = bf_lo(u.x); v[1] = bf_hi(u.x); v[2] = bf_lo(u.y); v[3] = bf_hi(u.y);
    v[4] = bf_lo(u.z); v[5] = bf_hi(u.z); v[6] = bf_lo(u.w); v[7] = bf_hi(u.w);
}
DEV int xn_off(int row, int chunk) { return (row >> 5) * 40960 + (chunk >> 3) * 4096 + (row & 31) * 128 + (((chunk ^ row) & 7) << 4); }

DEV void ln_row(float (&v)[3][8], int lane) {
    float s = 0.f;
#pragma unroll
    for (int c = 0; c < 3; c++)
#pragma unroll
        for (int j = 0; j < 8; j++) s += v[c][j];
#pragma unroll
    for (int o = 16; o; o >>= 1) s += __shfl_xor_sync(~0u, s, o);
    float mean = s * (1.f / D_), q = 0.f;
#pragma unroll
    for (int c = 0; c < 3; c++)
        if (c < 2 || lane < 16)
#pragma unroll
            for (int j = 0; j < 8; j++) { float d = v[c][j] - mean; q += d * d; }
#pragma unroll
    for (int o = 16; o; o >>= 1) q += __shfl_xor_sync(~0u, q, o);
    float mb = bf_round(mean);
    float inv = 1.f / bf_round(sqrtf(bf_round(bf_round(q * (1.f / D_)) + 1e-5f)));
#pragma unroll
    for (int c = 0; c < 3; c++)
#pragma unroll
        for (int j = 0; j < 8; j++) v[c][j] = bf_round(v[c][j] - mb) * inv;
}

__host__ __device__ constexpr int col_freq(int c) {
    return c == 320 ? 320 : c < 192 ? (c >> 6) * 128 + (c & 63) : c == 192 ? 192 : c < 256 ? 448 - c : c == 256 ? 64 : 384 - c;
}
DEV float rdft(int n, int k, int sn, int N) {
    float s, c;
    sincospif((float)((n * k) & (N - 1)) * (2.f / N), &s, &c);
    return !sn ? c : k ? s : (n & 1 ? -1.f : 1.f);
}

__global__ void __launch_bounds__(512) prep_kernel(const bf16* __restrict__ x, const bf16* __restrict__ Wv, const bf16* __restrict__ Wo) {
    __shared__ float red[32], col[4][640];
    const int tid = threadIdx.x, lane = tid & 31, warp = tid >> 5, b = blockIdx.x, row = b * 16 + warp;
    TLS(0);
    pdl_launch();
    uint4 ux[3], uv[5], uo[8];
#pragma unroll
    for (int c = 0; c < 3; c++) ux[c] = c < 2 || lane < 16 ? *(const uint4*)(x + row * D_ + (c * 32 + lane) * 8) : make_uint4(0, 0, 0, 0);
#pragma unroll
    for (int i = 0; i < 5; i++) uv[i] = *(const uint4*)(Wv + (size_t)((b & 3) * 160 + i * 32 + (tid >> 4)) * 4096 + (b >> 2) * E_ + (tid & 15) * 8);
    if (tid < 320) {
#pragma unroll
        for (int r = 0; r < 8; r++) uo[r] = *(const uint4*)(Wo + (size_t)(b * 32 + tid / 80 * 8 + r) * D_ + tid % 80 * 8);
    }
    if (b < 3) ((uint4*)g_sync)[b * 512 + tid] = make_uint4(0, 0, 0, 0);
    for (int i = b * 512 + tid; i < ACC_LAYER; i += 128 * 512) ((uint4*)g_acc)[i] = make_uint4(0, 0, 0, 0);
    if (tid < 2 * YT_ROWS * D_ / 4 / 128) ((uint4*)g_yt)[b * (2 * YT_ROWS * D_ / 4 / 128) + tid] = make_uint4(0, 0, 0, 0);
    const int gid = tid < 104 ? b * 104 + tid : 1 << 20;
    if (gid < 4096) {
        const int inv = gid >> 11, ks = (gid >> 8) & 7, t = gid & 255, g = (t & 31) >> 2, q = t & 3, tile = t >> 5;
        uint32_t v[4];
#pragma unroll
        for (int j = 0; j < 4; j++) {
            float x[2];
#pragma unroll
            for (int u = 0; u < 2; u++) {
                const int m = inv ? 16 * tile + 2 * g + (j & 1) : 16 * ks + 8 * (j >> 1) + 2 * q + u;
                const int k2 = inv ? 8 * ks + 2 * q + u : 8 * tile + g, sn = inv ? j >> 1 : j & 1;
                x[u] = rdft(m, k2, sn, 128);
                if (sn && k2) x[u] = -x[u];
            }
            v[j] = pack2(x[0], x[1]);
        }
        g_f128[gid] = make_uint4(v[0], v[1], v[2], v[3]);
    } else if (gid < 5120) {
        const int id = gid - 4096, inv = id >> 9, ks = (id >> 7) & 3, t = id & 127, g = (t & 31) >> 2, q = t & 3, tile = t >> 5;
        uint32_t v[4];
#pragma unroll
        for (int j = 0; j < 4; j++) {
            float x[2];
#pragma unroll
            for (int u = 0; u < 2; u++) {
                const int a = inv ? 16 * tile + g + 8 * (j & 1) : 16 * ks + 8 * (j >> 1) + 2 * q + u;
                const int ka = inv ? 8 * ks + 2 * q + u : 8 * tile + g, sn = inv ? j >> 1 : j & 1;
                x[u] = rdft(a, ka, sn, 64);
            }
            v[j] = pack2(x[0], x[1]);
        }
        g_f64[id] = make_uint4(v[0], v[1], v[2], v[3]);
    } else if (gid < 5120 + 8192) {
        const int id = gid - 5120, inv = id >> 12, n = ((id >> 9) & 7) * 8 + ((id >> 3) & 7), k = ((id >> 6) & 7) * 8 + (id & 7);
        float s, c;
        sincospif((float)(((n >> 1) * (k >> 1)) & 31) * (1.f / 16), &s, &c);
        if (inv) s = -s;
        g_g32[id] = __float2bfloat16_rn((n & 1) == (k & 1) ? c : (k & 1) ? s : -s);
    }
    {
        float v[3][8];
#pragma unroll
        for (int c = 0; c < 3; c++) unpack8(v[c], ux[c]);
        ln_row(v, lane);
#pragma unroll
        for (int c = 0; c < 3; c++)
            if (c < 2 || lane < 16)
                *(uint4*)(g_xn + xn_off(row, c * 32 + lane)) =
                    make_uint4(pack2(v[c][0], v[c][1]), pack2(v[c][2], v[c][3]), pack2(v[c][4], v[c][5]), pack2(v[c][6], v[c][7]));
    }
    float sv = 0.f;
#pragma unroll
    for (int i = 0; i < 5; i++) {
        float w[8];
        unpack8(w, uv[i]);
#pragma unroll
        for (int j = 0; j < 8; j++) sv += w[j] * w[j];
    }
    if (tid < 320) {
        float a[8] = {0.f, 0.f, 0.f, 0.f, 0.f, 0.f, 0.f, 0.f};
#pragma unroll
        for (int r = 0; r < 8; r++) {
            float w[8];
            unpack8(w, uo[r]);
#pragma unroll
            for (int j = 0; j < 8; j++) a[j] += w[j] * w[j];
        }
#pragma unroll
        for (int j = 0; j < 8; j++) col[tid / 80][tid % 80 * 8 + j] = a[j];
    }
    __syncthreads();
    float so = (col[0][tid] + col[1][tid]) + (col[2][tid] + col[3][tid]);
    if (tid < 128) so = fmaxf(so, (col[0][512 + tid] + col[1][512 + tid]) + (col[2][512 + tid] + col[3][512 + tid]));
#pragma unroll
    for (int o = 16; o; o >>= 1) { sv += __shfl_xor_sync(~0u, sv, o); so = fmaxf(so, __shfl_xor_sync(~0u, so, o)); }
    if (lane == 0) { red[warp] = sv; red[16 + warp] = so; }
    __syncthreads();
    if (tid == 0) {
        float a = 0.f, c = 0.f;
        for (int i = 0; i < 16; i++) { a += red[i]; c = fmaxf(c, red[16 + i]); }
        g_nrm[b] = a; g_nrm[128 + b] = c;
    }
    TLE(0);
}

constexpr int FT_BYTES = 64 * NCOL * 2;
DEV uint32_t lds16(uint32_t a) { unsigned short x; asm volatile("ld.shared.u16 %0,[%1];" : "=h"(x) : "r"(a) : "memory"); return x; }
DEV void filter_tile(uint32_t sr, uint32_t si, int kb, int warp, int lane) {
#pragma unroll 3
    for (int c = warp; c < NCOL; c += 12) {
        const uint32_t o = lane * (4 * NCOL) + col_freq(c) * 2;
        *(uint2*)(g_wt + c * 8192 + kb * 256 + ((lane ^ ((kb & 3) << 2)) << 3)) =
            make_uint2(lds16(sr + o) | (lds16(si + o) << 16), lds16(sr + o + 2 * NCOL) | (lds16(si + o + 2 * NCOL) << 16));
    }
}

namespace wk {
constexpr int STAGE = 49152, NST = 4, OFF_OUT = 3 * STAGE, OFF_RED = 4 * STAGE, OFF_BAR = OFF_RED + 32768, SMEM = OFF_BAR + 128;
constexpr int NPB = 11;
__host__ __device__ constexpr int pb_start(int b) { return b == 0 ? 2 : b < NPB ? 6 * b : 64; }
#define NOB 7
#define SPLIT_A 2
#define SPLIT_B 9
constexpr int N_P = NPB * H_, I_F = N_P, I_OB = I_F + 32, I_OT = I_OB + NOB * 5, I_SA = I_OT + (30 - 3 * NOB) * 10;
constexpr int I_SB = I_SA + 10 * SPLIT_A, N_ITEMS = I_SB + 10 * SPLIT_B;
DEV void ot_decode(int id, int& b, int& nt, int& k0, int& k1) {
    const int base = id < I_SA ? I_OT : id < I_SB ? I_SA : I_SB, j = (id - base) / 10;
    nt = (id - base) % 10;
    if (id < I_SA) { b = 3 * NOB + j; k0 = 0; k1 = 22; }
    else if (id < I_SB) { b = 30; k0 = 22 * j / SPLIT_A; k1 = 22 * (j + 1) / SPLIT_A; }
    else { b = 31; k0 = 22 * j / SPLIT_B; k1 = 22 * (j + 1) / SPLIT_B; }
}
enum { SY_TICKET = 0, SY_O = 32, SY_P = 128 };
}
struct Ring {
    int st; uint32_t ph;
    DEV uint32_t par() const { return (ph >> st) & 1; }
    DEV void next(int n) { ph ^= 1u << st; st = st + 1 >= n ? 0 : st + 1; }
};
struct Maps { CUtensorMap wq2, wv1, wo2, wo1, x6, x4, o6, o2; const bf16 *wr, *wi; };

template <int NSG> DEV void proj_tile(uint32_t sb, uint32_t bar, Ring& rg, int wg, int id) {
    using namespace wk;
    float acc[NSG * 16];
#pragma unroll
    for (int i = 0; i < NSG * 16; i++) acc[i] = 0.f;
    const int lane = threadIdx.x & 31, ww = (threadIdx.x >> 5) & 3;
    for (int kb = 0; kb < 10; kb++, rg.next(3)) {
        const int st = rg.st;
        if (kb) mbar_wait(bar + 8 * st, rg.par());
        const u64 da = mkdesc(sb + st * STAGE + wg * 8192, 0, 1024) | SW128, db = mkdesc(sb + st * STAGE + 24576, 0, 1024) | SW128;
        wg_fence();
#pragma unroll
        for (int ks = 0; ks < 4; ks++) {
            if (NSG == 4) wgmma_n128_ss<1, 0>(acc, da + ks * 128, db + ks * 2, 1);
            if (NSG == 6) wgmma_n192_ss<1, 0>(acc, da + ks * 128, db + ks * 2, 1);
        }
        wg_commit();
        wg_wait<0>();
        mbar_arrive_elect(bar + 8 * (NST + st));
    }
    const uint32_t out = sb + OFF_OUT + wg * 24576;
    bar_sync(5 + wg, 160);
    const uint32_t la = out + (wg < 2 ? (lane >> 4) * 1024 + ww * 256 + (lane & 15) * 16 : ww * 1024 + ((lane >> 3) & 1) * 512 + (lane >> 4) * 128 + (lane & 7) * 16);
#pragma unroll
    for (int j = 0; j < 2 * NSG; j++) {
        const float* c = acc + 8 * j;
        const uint32_t p0 = pack2(c[0], c[1]), p1 = pack2(c[2], c[3]), p2 = pack2(c[4], c[5]), p3 = pack2(c[6], c[7]);
        if (wg < 2) stsm4t(la + j * 2048, p0, p1, p2, p3);
        else stsm4(la + (j >> 1) * 4096 + (j & 1) * 256, p0, p1, p2, p3);
    }
    if ((threadIdx.x & 127) == 0) sts32(bar + 80 + 4 * wg, id);
    fence_async();
    bar_arrive(1 + wg, 160);
}

DEV uint32_t resid(uint32_t u, float a, float b) { return pack2(bf_lo(u) + bf_round(a), bf_hi(u) + bf_round(b)); }

template <bool SIDE>
DEV void worker(uint32_t sb, const Maps& maps, const bf16* __restrict__ x, bf16* __restrict__ x1, int layer, int fix, int nfix) {
    using namespace wk;
    const uint32_t bar = sb + OFF_BAR, slot = bar + 64;
    const int tid = threadIdx.x, lane = tid & 31, warp = __shfl_sync(~0u, tid >> 5, 0);
    uint32_t* sy = g_sync + layer * SYNC_LAYER;
    if (tid == 0) {
        for (int i = 0; i < NST; i++) { mbar_init(bar + 8 * i, 1); mbar_init(bar + 8 * (NST + i), 12); }
        asm volatile("fence.mbarrier_init.release.cluster;" ::: "memory");
    }
    __syncthreads();
    if (warp > 12) {
        const int wg = warp - 13;
        bar_arrive(5 + wg, 160);
        for (;;) {
            bar_sync(1 + wg, 160);
            const int id = (int)lds32(bar + 80 + 4 * wg);
            if (id < 0) break;
            const int s0 = pb_start(id >> 5), ns = pb_start((id >> 5) + 1) - s0;
            if (lane == 0) {
                for (int j = 0; j < ns; j++)
                    bulk_s2g(g_p + (size_t)(((s0 + j) * H_ + (id & 31)) * 3 + wg) * 4096, sb + OFF_OUT + wg * 24576 + j * 4096, 4096);
                bulk_commit();
                bulk_wait<0>();
                flag_add(sy + SY_P + id);
            }
            __syncwarp();
            bar_arrive(5 + wg, 160);
        }
    } else if (warp == 12) {
        if (lane == 0) {
            Ring rg = {0, 7u};
            auto acquire = [&]() { mbar_wait(bar + 8 * (NST + rg.st), rg.par()); return sb + rg.st * STAGE; };
            if (fix >= 0 && fix < N_P) {
                for (int kb = 0; kb < 3; kb++) {
                    tma3d(sb + kb * STAGE, &maps.wq2, 0, kb * 64, 2 * (fix & 31), bar + 8 * kb);
                    tma3d(sb + kb * STAGE + 16384, &maps.wv1, 0, kb * 64, 2 * (fix & 31), bar + 8 * kb);
                }
                asm volatile("prefetch.tensormap [%0];" ::"l"(&maps.x4) : "memory");
            }
            if (SIDE) flag_wait(g_started + layer, 1); else pdl_wait();
            for (;;) {
                int id = fix;
                if (id < 0) {
                    id = nfix + (int)atomicAdd(sy + SY_TICKET, 1u);
                    if (layer && id >= I_F) id += I_OB - I_F;
                    if (id >= I_SB) id = -1;
                }
                if (id >= 0) { TLI(id, 0, gtime()); TLI(id, 3, blockIdx.x + (SIDE ? 1000 : 0)); }
                uint32_t d = acquire();
                sts32(slot + 4 * rg.st, id);
                if (id < 0) { mbar_arrive(bar + 8 * rg.st); if (SIDE) pdl_launch(); break; }
                if (id < N_P) {
                    const int b = id >> 5, h = id & 31;
                    const bool six = b && b < NPB - 1;
                    for (int kb = 0; kb < 10; kb++, rg.next(3)) {
                        if (kb) d = acquire();
                        const uint32_t fb = bar + 8 * rg.st;
                        mbar_expect(fb, six ? 49152 : 40960);
                        tma3d(d + 24576, six ? &maps.x6 : &maps.x4, 0, 2 * kb, pb_start(b), fb);
                        if (fix < 0 || kb >= 3) {
                            tma3d(d, &maps.wq2, 0, kb * 64, 2 * h, fb);
                            tma3d(d + 16384, &maps.wv1, 0, kb * 64, 2 * h, fb);
                        }
                    }
                } else if (id < I_OB) {
                    for (int i = 0; i < 2; i++, rg.next(NST)) {
                        if (i) d = acquire();
                        mbar_expect(bar + 8 * rg.st, FT_BYTES);
                        bulk_g2s(d, (const char*)(i ? maps.wi : maps.wr) + (id - I_F) * FT_BYTES, FT_BYTES, bar + 8 * rg.st);
                    }
                } else if (id < I_OT) {
                    const int b = (id - I_OB) / 5, nt = (id - I_OB) % 5;
                    flag_wait(sy + SY_O + 6 * b + 5, 64);
                    for (int kb = 0; kb < 64; kb++, rg.next(NST)) {
                        if (kb) d = acquire();
                        const uint32_t fb = bar + 8 * rg.st;
                        mbar_expect(fb, 40960);
                        tma3d(d, &maps.o6, 0, 2 * kb, 6 * b, fb);
                        tma3d(d + 24576, &maps.wo2, 0, kb * 64, 2 * nt, fb);
                    }
                } else {
                    int b, nt, k0, k1;
                    ot_decode(id, b, nt, k0, k1);
                    for (int kb = k0; kb < k1; kb++, rg.next(NST)) {
                        if (kb > k0) d = acquire();
                        const uint32_t fb = bar + 8 * rg.st;
                        mbar_expect(fb, 49152);
                        tma3d(d + 24576, &maps.wo1, 0, 3 * kb * 64, nt, fb);
                        if (kb == k0) flag_wait(sy + SY_O + 2 * b + 1, 64);
                        for (int u = 0; u < 3; u++) tma3d(d + u * 8192, &maps.o2, 0, 2 * (3 * kb + u), 2 * b, fb);
                    }
                }
                fix = -1;
            }
        }
    } else {
        const int wg = warp >> 2, g = lane >> 2, q = lane & 3;
        Ring rg = {0, 0u};
        bool stores_done = false;
        for (;;) {
            mbar_wait(bar + 8 * rg.st, rg.par());
            const int id = (int)lds32(slot + 4 * rg.st);
            if ((id < 0 || id >= N_P) && !stores_done) {
                bar_sync(5 + wg, 160);
                if ((tid & 127) == 0) sts32(bar + 80 + 4 * wg, ~0u);
                bar_arrive(1 + wg, 160);
                stores_done = true;
                bar_sync(4, 384);
                mbar_arrive_elect(bar + 8 * (NST + 3));
            }
            if (id < 0) break;
            if (tid == 0) TLI(id, 1, gtime());
            if (id < N_P) {
                const int b = id >> 5;
                if (b == 0 || b == NPB - 1) proj_tile<4>(sb, bar, rg, wg, id);
                else proj_tile<6>(sb, bar, rg, wg, id);
            } else if (id < I_OB) {
                const int s0 = rg.st;
                rg.next(NST);
                mbar_wait(bar + 8 * rg.st, rg.par());
                filter_tile(sb + s0 * STAGE, sb + rg.st * STAGE, id - I_F, warp, lane);
                mbar_arrive_elect(bar + 8 * (NST + s0));
                mbar_arrive_elect(bar + 8 * (NST + rg.st));
                rg.next(NST);
            } else if (id < I_OT) {
                const int b = (id - I_OB) / 5, nt = (id - I_OB) % 5;
                const size_t o = (size_t)(192 * b + 16 * warp + g) * D_ + nt * 128 + 2 * q;
                float acc[64];
#pragma unroll
                for (int i = 0; i < 64; i++) acc[i] = 0.f;
                for (int kb = 0; kb < 64; kb++, rg.next(NST)) {
                    const int st = rg.st;
                    if (kb) mbar_wait(bar + 8 * st, rg.par());
                    const u64 da = mkdesc(sb + st * STAGE + wg * 8192, 128, 1024), db = mkdesc(sb + st * STAGE + 24576, 8192, 1024) | SW128;
                    wg_fence();
#pragma unroll
                    for (int ks = 0; ks < 4; ks++) wgmma_n128_ss<0, 1>(acc, da + ks * 16, db + ks * 128, 1);
                    wg_commit();
                    wg_wait<0>();
                    mbar_arrive_elect(bar + 8 * (NST + st));
                }
                uint32_t xr[32];
#pragma unroll
                for (int t = 0; t < 32; t++) xr[t] = ldg32(x + o + 8 * (t >> 1) + (t & 1) * 8 * D_);
#pragma unroll
                for (int t = 0; t < 32; t++) *(uint32_t*)(x1 + o + 8 * (t >> 1) + (t & 1) * 8 * D_) = resid(xr[t], acc[2 * t], acc[2 * t + 1]);
            } else {
                int b, nt, k0, k1;
                ot_decode(id, b, nt, k0, k1);
                const size_t o = (size_t)(64 * b + 16 * (warp & 3) + g) * D_ + nt * 64 + 2 * q;
                float acc[32];
                uint32_t xr[16];
#pragma unroll
                for (int t = 0; t < 16; t++) xr[t] = wg == 0 && id < I_SA ? ldg32(x + o + 8 * (t >> 1) + (t & 1) * 8 * D_) : 0;
#pragma unroll
                for (int i = 0; i < 32; i++) acc[i] = 0.f;
                for (int kb = k0; kb < k1; kb++, rg.next(NST)) {
                    const int st = rg.st;
                    if (kb > k0) mbar_wait(bar + 8 * st, rg.par());
                    const u64 da = mkdesc(sb + st * STAGE + wg * 8192, 128, 1024), db = mkdesc(sb + st * STAGE + 24576 + wg * 8192, 0, 1024) | SW128;
                    wg_fence();
#pragma unroll
                    for (int ks = 0; ks < 4; ks++) wgmma_n64_ss<0, 1>(acc, da + ks * 16, db + ks * 128, 1);
                    wg_commit();
                    wg_wait<0>();
                    mbar_arrive_elect(bar + 8 * (NST + st));
                }
                const uint32_t ra = sb + OFF_RED + (tid & 127) * 16;
                if (wg) {
#pragma unroll
                    for (int t = 0; t < 8; t++)
                        sts128(ra + (wg - 1) * 16384 + t * 2048, __float_as_uint(acc[4 * t]), __float_as_uint(acc[4 * t + 1]), __float_as_uint(acc[4 * t + 2]), __float_as_uint(acc[4 * t + 3]));
                }
                bar_sync(4, 384);
                if (wg == 0) {
#pragma unroll
                    for (int t = 0; t < 8; t++) {
                        float u[4], v[4];
                        lds128f(u, ra + t * 2048); lds128f(v, ra + 16384 + t * 2048);
#pragma unroll
                        for (int i = 0; i < 4; i++) acc[4 * t + i] += u[i] + v[i];
                    }
                }
                bar_sync(4, 384);
                if (wg == 0) {
                    if (id < I_SA) {
#pragma unroll
                        for (int t = 0; t < 16; t++) *(uint32_t*)(x1 + o + 8 * (t >> 1) + (t & 1) * 8 * D_) = resid(xr[t], acc[2 * t], acc[2 * t + 1]);
                    } else {
                        float* y = g_yt + (layer * YT_ROWS - (S_ - YT_ROWS)) * D_ + o;
#pragma unroll
                        for (int t = 0; t < 16; t++)
                            asm volatile("red.relaxed.gpu.global.add.v2.f32 [%0],{%1,%2};" ::"l"(y + 8 * (t >> 1) + (t & 1) * 8 * D_), "f"(acc[2 * t]), "f"(acc[2 * t + 1]) : "memory");
                    }
                }
            }
            if (tid == 0) TLI(id, 2, gtime());
        }
    }
}

__global__ void __launch_bounds__(512, 1) side_kernel(const __grid_constant__ Maps maps, const bf16* __restrict__ x, bf16* __restrict__ x1, int layer, int nfix) {
    extern __shared__ __align__(1024) unsigned char smem[];
    TLS(3 + 5 * layer);
    worker<true>(s2u(smem), maps, x, x1, layer, -1, nfix);
    __syncwarp();
    if (blockIdx.x == 0) pdl_wait();
    TLE(3 + 5 * layer);
}

constexpr float C5A = 0.30901699437494742f, C5B = -0.80901699437494742f, S5A = 0.95105651629515357f, S5B = 0.58778525229247313f;
template <int SGN> DEV void dft5(const float (&tr)[5], const float (&ti)[5], float (&zr)[5], float (&zi)[5]) {
    const float ar = tr[1] + tr[4], ai = ti[1] + ti[4], br = tr[2] + tr[3], bi = ti[2] + ti[3];
    const float cr = tr[1] - tr[4], ci = ti[1] - ti[4], dr = tr[2] - tr[3], di = ti[2] - ti[3];
    zr[0] = tr[0] + ar + br; zi[0] = ti[0] + ai + bi;
    const float m1r = tr[0] + C5A * ar + C5B * br, m1i = ti[0] + C5A * ai + C5B * bi;
    const float m2r = tr[0] + C5B * ar + C5A * br, m2i = ti[0] + C5B * ai + C5A * bi;
    const float n1r = SGN * (S5A * cr + S5B * dr), n1i = SGN * (S5A * ci + S5B * di);
    const float n2r = SGN * (S5B * cr - S5A * dr), n2i = SGN * (S5B * ci - S5A * di);
    zr[1] = m1r + n1i; zi[1] = m1i - n1r; zr[4] = m1r - n1i; zi[4] = m1i + n1r;
    zr[2] = m2r + n2i; zi[2] = m2i - n2r; zr[3] = m2r - n2i; zi[3] = m2i + n2r;
}
DEV void ln40(float (&v)[40]) {
    float s = 0.f;
#pragma unroll
    for (int i = 0; i < 40; i++) s += v[i];
#pragma unroll
    for (int o = 8; o; o >>= 1) s += __shfl_xor_sync(~0u, s, o);
    const float mean = s * (1.f / D_);
    float q = 0.f;
#pragma unroll
    for (int i = 0; i < 40; i++) { const float d = v[i] - mean; q += d * d; }
#pragma unroll
    for (int o = 8; o; o >>= 1) q += __shfl_xor_sync(~0u, q, o);
    const float mb = bf_round(mean);
    const float inv = 1.f / bf_round(sqrtf(bf_round(bf_round(q * (1.f / D_)) + 1e-5f)));
#pragma unroll
    for (int i = 0; i < 40; i++) v[i] = bf_round(v[i] - mb) * inv;
}
__global__ void __maxnreg__(120) rowfft_kernel(const bf16* __restrict__ x0, bf16* __restrict__ x, int layer) {
    extern __shared__ __align__(1024) unsigned char smem[];
    const uint32_t sb = s2u(smem), sx = sb + 23552, sy = sx + 20480, bar = sy + 40960;
    const int tid = threadIdx.x, lane = tid & 31, q = lane & 3, blk = 127 - blockIdx.x, k2 = tid >> 2;
    if (tid == 0) TLI(800 + blk, 0, gtime());
    float twr[5], twi[5];
#pragma unroll
    for (int r = 1; r < 5; r++) { sincospif((float)(r * k2) * (-1.f / 320), &twi[r], &twr[r]); }
    uint32_t f[8][4];
#pragma unroll
    for (int ks = 0; ks < 8; ks++) { const uint4 u = g_f128[ks * 256 + tid]; f[ks][0] = u.x; f[ks][1] = u.y; f[ks][2] = u.z; f[ks][3] = u.w; }
    const bool split = blk * 16 >= S_ - YT_ROWS;
    if (tid == 0) {
        mbar_init(bar, 1);
        asm volatile("fence.mbarrier_init.release.cluster;" ::: "memory");
        mbar_expect(bar, split ? 61440 : 20480);
        if (split) bulk_g2s(sx, x0 + (size_t)blk * 16 * D_, 20480, bar);
    }
    __syncthreads();
    pdl_wait();
    pdl_launch();
    TLS(4 + 5 * layer);
    if (tid == 0) TLI(800 + blk, 1, gtime());
    if (tid == 0 && blk == 0) g_started[layer] = 0;
    if (tid == 0) {
        if (split) bulk_g2s(sy, g_yt + (layer * YT_ROWS + blk * 16 - (S_ - YT_ROWS)) * D_, 40960, bar);
        else bulk_g2s(sx, x + (size_t)blk * 16 * D_, 20480, bar);
    }
    mbar_wait(bar, 0);
    {
        const int rho = tid >> 4, j = tid & 15;
        float v[40];
#pragma unroll
        for (int i = 0; i < 5; i++) {
            uint32_t u[4];
            lds128(u, sx + tid * 80 + i * 16);
            if (split) {
                float p[8];
                lds128f(p, sy + tid * 160 + i * 32); lds128f(p + 4, sy + tid * 160 + i * 32 + 16);
#pragma unroll
                for (int k = 0; k < 4; k++) u[k] = resid(u[k], p[2 * k], p[2 * k + 1]);
                sts128(sx + tid * 80 + i * 16, u[0], u[1], u[2], u[3]);
            }
            unpack8(v + 8 * i, make_uint4(u[0], u[1], u[2], u[3]));
        }
        ln40(v);
        const uint32_t a = sb + ((rho >> 1) & 1) * 2304 + j * 144 + (2 * (rho >> 2) + (rho & 1)) * 16;
#pragma unroll
        for (int r = 0; r < 5; r++)
            sts128(a + r * 4608, pack2(v[r], v[5 + r]), pack2(v[10 + r], v[15 + r]), pack2(v[20 + r], v[25 + r]), pack2(v[30 + r], v[35 + r]));
    }
    fence_async();
    __syncthreads();
    if (tid == 0) TLI(800 + blk, 2, gtime());
    if (tid == 0 && split) { bulk_s2g(x + (size_t)blk * 16 * D_, sx, 20480); bulk_commit(); }
    float acc[40];
    const u64 db = mkdesc(sb, 144, 2304);
    wg_fence();
    wgmma_n80_rs<0, 0>(acc, f[0], db);
#pragma unroll
    for (int ks = 1; ks < 8; ks++) wgmma_n80_rs<1, 0>(acc, f[ks], db + ks * 18);
    wg_commit();
    wg_wait<0>();
    unsigned char* zp = g_z + (blk >> 1) * 128 + ((((blk & 1) * 4 + q) ^ ((blk >> 1) & 7)) << 4);
    uint32_t o[5][4];
#pragma unroll
    for (int u = 0; u < 4; u++) {
        float tr[5], ti[5], zr[5], zi[5];
#pragma unroll
        for (int r = 0; r < 5; r++) {
            const float yr = acc[8 * r + 4 * (u >> 1) + (u & 1)], yi = k2 ? acc[8 * r + 4 * (u >> 1) + 2 + (u & 1)] : 0.f;
            tr[r] = r ? yr * twr[r] - yi * twi[r] : yr;
            ti[r] = r ? yr * twi[r] + yi * twr[r] : yi;
        }
        dft5<1>(tr, ti, zr, zi);
#pragma unroll
        for (int j = 0; j < 5; j++) o[j][u] = pack2(zr[j], j < 3 ? zi[j] : -zi[j]);
    }
#pragma unroll
    for (int j = 0; j < 5; j++)
        if (j < 3 || k2) *(uint4*)(zp + (64 * j + k2) * 8192) = make_uint4(o[j][0], o[j][1], o[j][2], o[j][3]);
    if (k2 == 0) {
#pragma unroll
        for (int u = 0; u < 4; u++) {
            float tr[5], ti[5], zr[5], zi[5];
            const float cr[5] = {1.f, -C5B, C5A, -C5A, C5B}, ci[5] = {0.f, -S5B, -S5A, -S5A, -S5B};
#pragma unroll
            for (int r = 0; r < 5; r++) { const float y = acc[8 * r + 4 * (u >> 1) + 2 + (u & 1)]; tr[r] = y * cr[r]; ti[r] = y * ci[r]; }
            dft5<1>(tr, ti, zr, zi);
            o[0][u] = pack2(zr[0], zi[0]); o[1][u] = pack2(zr[1], zi[1]); o[2][u] = pack2(zr[2], 0.f);
        }
        *(uint4*)(zp + 256 * 8192) = make_uint4(o[0][0], o[0][1], o[0][2], o[0][3]);
        *(uint4*)(zp + 192 * 8192) = make_uint4(o[1][0], o[1][1], o[1][2], o[1][3]);
        *(uint4*)(zp + 320 * 8192) = make_uint4(o[2][0], o[2][1], o[2][2], o[2][3]);
    }
    if (tid == 0) bulk_wait_read<0>();
    TLE(4 + 5 * layer);
    if (tid == 0) TLI(800 + blk, 3, gtime());
}

constexpr int CF_SMEM = 16384 + 8192 + 3 * 24576 + 64;
__global__ void __maxnreg__(88) colfft_kernel(int layer) {
    extern __shared__ __align__(1024) unsigned char smem[];
    const uint32_t sb = s2u(smem), bar = sb + 98304;
    const int tid = threadIdx.x, lane = tid & 31, q = lane & 3, wg = __shfl_sync(~0u, tid >> 7, 0), t = tid & 127, ka = t >> 2;
    asm volatile("setmaxnreg.inc.sync.aligned.u32 88;");
    const int col = blockIdx.x * 3 + wg;
    const uint32_t d0 = sb + 24576 + wg * 24576, d1 = d0 + 8192;
    if (tid == 0) {
        for (int i = 0; i < 4; i++) mbar_init(bar + 8 * i, 1);
        asm volatile("fence.mbarrier_init.release.cluster;" ::: "memory");
        mbar_expect(bar + 24, 49152);
        for (int i = 0; i < 3; i++) bulk_g2s(d0 + i * 24576 + 16384, g_wt + (col + i) * 8192, 8192, bar + 24);
        bulk_g2s(sb, g_g32, 16384, bar + 24);
        bulk_g2s(sb + 16384, g_f64 + 512, 8192, bar + 24);
    }
    uint32_t a[4][4];
#pragma unroll
    for (int ks = 0; ks < 4; ks++) { const uint4 u = g_f64[ks * 128 + t]; a[ks][0] = u.x; a[ks][1] = u.y; a[ks][2] = u.z; a[ks][3] = u.w; }
    float twr[8], twi[8];
#pragma unroll
    for (int i = 0; i < 8; i++) sincospif((float)((4 * i + q) * (ka ? ka : -32)) * (1.f / 1024), &twi[i], &twr[i]);
    __syncthreads();
    pdl_wait();
    pdl_launch();
    TLS(5 + 5 * layer);
    if (t == 0) {
        mbar_expect(bar + 8 * wg, 8192);
        bulk_g2s(d0, g_z + col * 8192, 8192, bar + 8 * wg);
    }
    float acc[32];
    mbar_wait(bar + 8 * wg, 0);
    {
        const u64 db = mkdesc(d0, 0, 1024) | SW128;
        wg_fence();
        wgmma_n64_rs<0, 1>(acc, a[0], db);
#pragma unroll
        for (int ks = 1; ks < 4; ks++) wgmma_n64_rs<1, 1>(acc, a[ks], db + ks * 128);
        wg_commit();
        wg_wait<0>();
    }
#pragma unroll
    for (int i = 0; i < 8; i++) {
        const float c0 = acc[4 * i], c1 = acc[4 * i + 1], c2 = acc[4 * i + 2], c3 = acc[4 * i + 3];
        const float pr = c0 + c3, pi = c1 - c2, nr = ka ? c0 - c3 : c2, ni = ka ? c1 + c2 : c3;
        a[i >> 1][2 * (i & 1)] = ka ? pack2(pr * twr[i] + pi * twi[i], pi * twr[i] - pr * twi[i]) : pack2(c0, c1);
        a[i >> 1][2 * (i & 1) + 1] = pack2(nr * twr[i] - ni * twi[i], ni * twr[i] + nr * twi[i]);
    }
    mbar_wait(bar + 24, 0);
    {
        const u64 db = mkdesc(sb, 128, 1024);
        wg_fence();
        wgmma_n64_rs<0, 0>(acc, a[0], db);
#pragma unroll
        for (int ks = 1; ks < 4; ks++) wgmma_n64_rs<1, 0>(acc, a[ks], db + ks * 16);
        wg_commit();
        wg_wait<0>();
    }
    constexpr float NORM = 1.f / (2048.f * 640.f);
#pragma unroll
    for (int i = 0; i < 16; i++) {
        const int k = ((i & 1 ? (ka ? -ka : 32) : ka) + 64 * q + 256 * (i >> 1)) & 2047;
        a[i >> 2][i & 3] = lds32(d0 + 16384 + 4 * (k ^ ((k >> 3) & 24)));
    }
#pragma unroll
    for (int i = 0; i < 16; i++) {
        const float zr = acc[2 * i] * NORM, zi = acc[2 * i + 1] * NORM, wr = bf_lo(a[i >> 2][i & 3]), wi = bf_hi(a[i >> 2][i & 3]);
        a[i >> 2][i & 3] = pack2(zr * wr - zi * wi, zr * wi + zi * wr);
    }
    {
        const u64 db = mkdesc(sb + 8192, 128, 1024);
        wg_fence();
        wgmma_n64_rs<0, 0>(acc, a[0], db);
#pragma unroll
        for (int ks = 1; ks < 4; ks++) wgmma_n64_rs<1, 0>(acc, a[ks], db + ks * 16);
        wg_commit();
        wg_wait<0>();
    }
    const uint32_t row = (t >> 5) * 2048 + (lane & 15) * 128;
#pragma unroll
    for (int i = 0; i < 8; i++) {
        const float c0 = acc[4 * i], c1 = acc[4 * i + 1], c2 = acc[4 * i + 2], c3 = acc[4 * i + 3];
        const float pr = c0 * twr[i] - c1 * twi[i], pi = c1 * twr[i] + c0 * twi[i];
        const float nr = c2 * twr[i] + c3 * twi[i], ni = c3 * twr[i] - c2 * twi[i];
        a[i >> 1][2 * (i & 1)] = ka ? pack2(pr + nr, pi + ni) : pack2(c0, c1);
        a[i >> 1][2 * (i & 1) + 1] = ka ? pack2(ni - pi, pr - nr) : pack2(nr, ni);
    }
#pragma unroll
    for (int i = 0; i < 4; i++) stsm4(d1 + row + (((2 * i + (lane >> 4)) ^ (lane & 7)) << 4), a[i][0], a[i][1], a[i][2], a[i][3]);
#pragma unroll
    for (int i = 0; i < 4; i++) lds128(a[i], sb + 16384 + i * 2048 + t * 16);
    fence_async();
    bar_sync(1 + wg, 128);
    {
        const u64 db = mkdesc(d1, 0, 1024) | SW128;
        wg_fence();
        wgmma_n64_rs<0, 1>(acc, a[0], db);
#pragma unroll
        for (int ks = 1; ks < 4; ks++) wgmma_n64_rs<1, 1>(acc, a[ks], db + ks * 128);
        wg_commit();
        wg_wait<0>();
    }
#pragma unroll
    for (int i = 0; i < 4; i++)
        stsm4(d0 + row + (((2 * i + (lane >> 4)) ^ (lane & 7)) << 4), pack2(acc[8 * i], acc[8 * i + 1]), pack2(acc[8 * i + 2], acc[8 * i + 3]),
              pack2(acc[8 * i + 4], acc[8 * i + 5]), pack2(acc[8 * i + 6], acc[8 * i + 7]));
    fence_async();
    bar_sync(1 + wg, 128);
    if (t == 0) {
        bulk_s2g(g_z + col * 8192, d0, 8192);
        asm volatile("cp.async.bulk.commit_group;" ::: "memory");
        bulk_wait_read<0>();
    }
    TLE(5 + 5 * layer);
}

__global__ void __maxnreg__(120) rowifft_kernel(const bf16* __restrict__ x, bf16* __restrict__ out, int last) {
    extern __shared__ __align__(1024) unsigned char smem[];
    const uint32_t sb = s2u(smem), sx = sb + 20480, sy = sx + 20480, bar = sy + 16 * 1296;
    const int tid = threadIdx.x, lane = tid & 31, q = lane & 3, blk = blockIdx.x, k2 = tid >> 2, warp = tid >> 5;
    float twr[5], twi[5];
#pragma unroll
    for (int r = 1; r < 5; r++) { sincospif((float)(r * k2) * (1.f / 320), &twi[r], &twr[r]); twr[r] *= 2.f; twi[r] *= 2.f; }
    uint32_t f[8][4];
#pragma unroll
    for (int ks = 0; ks < 8; ks++) { const uint4 u = g_f128[2048 + ks * 256 + tid]; f[ks][0] = u.x; f[ks][1] = u.y; f[ks][2] = u.z; f[ks][3] = u.w; }
    if (tid == 0) {
        mbar_init(bar, 1);
        asm volatile("fence.mbarrier_init.release.cluster;" ::: "memory");
        mbar_expect(bar, 20480);
        bulk_g2s(sx, x + (size_t)blk * 16 * D_, 20480, bar);
    }
    pdl_wait();
    pdl_launch();
    TLS(6 + 5 * last);
    const unsigned char* zp = g_z + (blk >> 1) * 128 + ((((blk & 1) * 4 + q) ^ ((blk >> 1) & 7)) << 4);
    uint4 z[6];
#pragma unroll
    for (int j = 0; j < 5; j++) z[j] = *(const uint4*)(zp + (64 * j + k2) * 8192);
    z[5] = k2 ? make_uint4(0, 0, 0, 0) : *(const uint4*)(zp + 320 * 8192);
    float acc[40];
#pragma unroll
    for (int u = 0; u < 4; u++) {
        float yr[6], yi[6], tr[5], ti[5], zr[5], zi[5];
#pragma unroll
        for (int j = 0; j < 6; j++) { const uint32_t v = u == 0 ? z[j].x : u == 1 ? z[j].y : u == 2 ? z[j].z : z[j].w; yr[j] = bf_lo(v); yi[j] = bf_hi(v); }
#pragma unroll
        for (int j = 0; j < 5; j++) { tr[j] = yr[j]; ti[j] = j < 3 ? yi[j] : -yi[j]; }
        dft5<-1>(tr, ti, zr, zi);
        const float c1[5] = {1.f, C5A, C5B, C5B, C5A}, s1[5] = {0.f, S5A, S5B, -S5B, -S5A};
        const float c2[5] = {1.f, C5B, C5A, C5A, C5B}, s2[5] = {0.f, S5B, -S5A, S5A, -S5B};
        const float c3[5] = {1.f, -C5B, C5A, -C5A, C5B}, s3[5] = {0.f, S5B, S5A, S5A, S5B};
        const float c4[5] = {1.f, -C5A, C5B, -C5B, C5A}, s4[5] = {0.f, S5A, -S5B, -S5B, S5A};
#pragma unroll
        for (int r = 0; r < 5; r++) {
            float er = r ? zr[r] * twr[r] - zi[r] * twi[r] : 2.f * zr[0], ei = r ? zr[r] * twi[r] + zi[r] * twr[r] : 2.f * zi[0];
            if (k2 == 0) {
                er = yr[0] + 2.f * (yr[1] * c1[r] - yi[1] * s1[r] + yr[2] * c2[r] - yi[2] * s2[r]);
                ei = (r & 1 ? -yr[5] : yr[5]) + 2.f * (yr[4] * c3[r] - yi[4] * s3[r] + yr[3] * c4[r] - yi[3] * s4[r]);
            }
            acc[8 * r + 4 * (u >> 1) + (u & 1)] = er;
            acc[8 * r + 4 * (u >> 1) + 2 + (u & 1)] = ei;
        }
    }
#pragma unroll
    for (int r = 0; r < 5; r++)
        stsm4(sb + (2 * warp + ((lane >> 3) & 1)) * 1280 + (2 * r + (lane >> 4)) * 128 + (lane & 7) * 16, pack2(acc[8 * r], acc[8 * r + 1]),
              pack2(acc[8 * r + 2], acc[8 * r + 3]), pack2(acc[8 * r + 4], acc[8 * r + 5]), pack2(acc[8 * r + 6], acc[8 * r + 7]));
    fence_async();
    __syncthreads();
    const u64 db = mkdesc(sb, 1280, 128);
    wg_fence();
    wgmma_n80_rs<0, 1>(acc, f[0], db);
#pragma unroll
    for (int ks = 1; ks < 8; ks++) wgmma_n80_rs<1, 1>(acc, f[ks], db + ks * 160);
    wg_commit();
    wg_wait<0>();
#pragma unroll
    for (int u = 0; u < 4; u++) {
        float e[10];
#pragma unroll
        for (int r = 0; r < 5; r++) { e[r] = acc[8 * r + 4 * (u >> 1) + (u & 1)]; e[5 + r] = acc[8 * r + 4 * (u >> 1) + 2 + (u & 1)]; }
#pragma unroll
        for (int i = 0; i < 5; i++) sts32(sy + (4 * q + u) * 1296 + k2 * 20 + i * 4, pack2(e[2 * i], e[2 * i + 1]));
    }
    __syncthreads();
    const int rho = tid >> 4, j = tid & 15;
    float v[40];
    mbar_wait(bar, 0);
#pragma unroll
    for (int i = 0; i < 5; i++) {
        uint32_t y[4], u[4];
        lds128(y, sy + rho * 1296 + j * 80 + i * 16);
        lds128(u, sx + tid * 80 + i * 16);
#pragma unroll
        for (int k = 0; k < 4; k++) u[k] = pack2(bf_lo(u[k]) + bf_lo(y[k]), bf_hi(u[k]) + bf_hi(y[k]));
        sts128(sx + tid * 80 + i * 16, u[0], u[1], u[2], u[3]);
        unpack8(v + 8 * i, make_uint4(u[0], u[1], u[2], u[3]));
    }
    if (!last) {
        ln40(v);
#pragma unroll
        for (int i = 0; i < 5; i++) {
            const int c = j * 5 + i;
            sts128(sb + (c >> 3) * 2048 + rho * 128 + (((c ^ rho) & 7) << 4), pack2(v[8 * i], v[8 * i + 1]), pack2(v[8 * i + 2], v[8 * i + 3]),
                   pack2(v[8 * i + 4], v[8 * i + 5]), pack2(v[8 * i + 6], v[8 * i + 7]));
        }
    }
    fence_async();
    __syncthreads();
    if (lane == 0) {
        if (warp == 7) bulk_s2g(out + (size_t)blk * 16 * D_, sx, 20480);
        else if (!last && warp < 5) {
            unsigned char* p = g_xn + (blk >> 1) * 40960 + warp * 8192 + (blk & 1) * 2048;
            bulk_s2g(p, sb + warp * 4096, 2048);
            bulk_s2g(p + 4096, sb + warp * 4096 + 2048, 2048);
        }
        bulk_commit();
        bulk_wait_read<0>();
    }
    TLE(6 + 5 * last);
}

namespace rec {
#define NS 3
constexpr int OFF_X = 0;
constexpr int OFF_WO = 81920;
constexpr int OFF_WS = OFF_WO + 65536;
constexpr int OFF_XCH = OFF_WS + NS * 4096;
constexpr int OFF_MEMB = OFF_XCH + 12288;
constexpr int OFF_VX = OFF_MEMB + 10240;
constexpr int OFF_VM = OFF_VX + 16384;
constexpr int OFF_Q = OFF_VM + 4096;
constexpr int OFF_K = OFF_Q + 10240;
constexpr int OFF_OST = OFF_WO + 49152;
constexpr int OFF_PX = OFF_OST + 8192;
constexpr int OFF_PT = OFF_PX + 2560;
constexpr int OFF_PS = OFF_K + 10240;
constexpr int OFF_OB = OFF_PS + 1280;
constexpr int OFF_MX = OFF_OB + 2048;
constexpr int OFF_BAR = OFF_MX + 64;
constexpr int OFF_PROF = OFF_BAR + 256;
constexpr int SMEM = OFF_PROF + 4096 > wk::SMEM ? OFF_PROF + 4096 : wk::SMEM;
enum { B_XT = 0, B_VM = 2, B_VX = 4, B_XD = 6, B_X1 = 8, B_GO = 10, B_PXF = 12, B_PXE = 13, B_FIN = 14, B_ST = 15, B_MEM = 16   };
enum { NB_W2 = 0, NB_XCH = 1, NB_QK = 2, NB_WIN = 3, NB_ATT = 4, NB_X = 5, NB_PRO = 6, NB_W1 = 7, NB_PAIR = 8  , NB_KF = 12, NB_LD = 13, NB_KX = 15 };
#define TPOS 1
#define LATE 1
#define STAG 585
#define NOX 0
#define NW1 4
#define NW1B 0
template <int N> struct IC { static constexpr int value = N; };
template <int N, int I = 0, class F> DEV void static_for(F&& f) { if constexpr (I < N) { f(IC<I>{}); static_for<N, I + 1>(f); } }
constexpr float SM_SCALE = 0.08838834764831845f * 1.4426950408889634f;
}

__global__ void __launch_bounds__(512, 1) rec_kernel(const __grid_constant__ Maps maps, const bf16* __restrict__ x, bf16* __restrict__ x1, const bf16* __restrict__ mem0, const bf16* __restrict__ Wq, const bf16* __restrict__ Wk,
                                                     const bf16* __restrict__ Wv, const bf16* __restrict__ Wo, int layer, int delay, int delay2) {
    using namespace rec;
    extern __shared__ __align__(1024) unsigned char smem[];
    const uint32_t sb = s2u(smem);
    pdl_launch();
    if (blockIdx.x < 3 * H_) {
    const int tid = threadIdx.x, lane = tid & 31, warp = __shfl_sync(~0u, tid >> 5, 0);
    const int g = lane >> 2, q = lane & 3;
    const int h = blockIdx.x / 3;
    const uint32_t bar = sb + OFF_BAR;
    STAMP(2 * layer);
    TLS(2 + 5 * layer);
    if (tid == 0) TLI(690 + blockIdx.x, 0, gtime());
    if (tid == 0) {
        for (int i = 0; i < 2; i++) {
            mbar_init(bar + 8 * (B_XT + i), 1); mbar_init(bar + 8 * (B_VX + i), 1);
            mbar_init(bar + 8 * (B_XD + i), 8); mbar_init(bar + 8 * (B_X1 + i), 1); mbar_init(bar + 8 * (B_VM + i), 1);
        }
        mbar_init(bar + 8 * B_PXF, 1); mbar_init(bar + 8 * B_PXE, 2); mbar_init(bar + 8 * B_ST, 2); mbar_init(bar + 8 * B_GO, 1);
        for (int i = 0; i < 5; i++) mbar_init(bar + 8 * (B_MEM + i), 4);
        mbar_init(bar + 8 * B_FIN, 48);
        asm volatile("fence.mbarrier_init.release.cluster;" ::: "memory");
    }
    asm volatile("barrier.cluster.arrive.aligned; barrier.cluster.wait.aligned;" ::: "memory");
    const bool never = delay < 0;

    if (warp < 8) {
        asm volatile("setmaxnreg.inc.sync.aligned.u32 184;");
        const uint32_t rank = cta_rank();
        const int wg = warp >> 2;
        uint32_t fa[20 - NS][4], fb[20][4];
        const uint32_t l16 = opaque(sb + lane * 16);
        uint32_t dst = opaque(rank < 2 ? sb + OFF_Q + wg * 10240 + (warp & 3) * 256 + (lane & 15) * 16 + (lane >> 4) * 1024
                                       : sb + OFF_VM + warp * 256 + lane * 4);
        int dstep = rank < 2 ? 5120 : 2048;
        uint32_t& sfd = dst;
        const uint32_t ws = OFF_WS + warp * 512, xo = OFF_XCH + warp * 512, xi = OFF_XCH + (warp ^ 4) * 512, mb = OFF_MEMB + wg * 512;
        {
            static_assert(NS <= 4 && OFF_WS + 32768 <= OFF_VX, "staging space");
            const int t = tid & 127;
            const bf16* src = (rank == 2 ? Wv + wg * 64 : (wg ? Wk : Wq) + rank * 64) + h * E_ + (size_t)(512 + (t >> 3)) * 4096 + (t & 7) * 8;
            constexpr int SA = OFF_WS, SB = OFF_VX;
            const uint32_t sdst = sb + (wg ? SB : SA) + (t >> 3) * 128 + (((t & 7) ^ ((t >> 3) & 7)) << 4);
            const uint32_t ra = sb + wg * 4096 + ((lane >> 4) * 8 + (lane & 7)) * 128 + (((2 * (warp & 3) + ((lane >> 3) & 1)) ^ (lane & 7)) << 4);
            auto issue = [&](int rd) {
#pragma unroll 1
                for (int i = 0; i < 8; i++, src += 16 * 4096) cp16(sdst + (~rd & 1) * 16384 + i * 2048, src);
                src -= 256 * 4096;
                cp_commit();
            };
            issue(4); issue(3);
            float acc[16];
            const u64 da = mkdesc(sb + SA, 0, 1024) | SW128, db = mkdesc(sb + OFF_X + wg * 40960, 0, 1024) | SW128;
            mbar_spin(bar + 8 * (B_XT + wg), 0);
#pragma unroll
            for (int rd = 4; rd >= 0; rd--) {
                if (rd) cp_wait<1>(); else cp_wait<0>();
                fence_async();
                bar_sync(NB_XCH, 256);
                wg_fence();
#pragma unroll
                for (int ks = 0; ks < 8; ks++) {
                    const u64 a = da + (~rd & 1) * 1024 + ks * 128, b = db + (2 * rd + (ks >> 2)) * 256 + (ks & 3) * 2;
                    if (rd == 4 && ks == 0) wgmma_n32_ss<0>(acc, a, b); else wgmma_n32_ss<1>(acc, a, b);
                }
                wg_commit();
                wg_wait<0>();
#pragma unroll
                for (int i = 0; i < 4; i++) {
                    const int n = rd * 4 + i, o = (~rd & 1) * 16384 + (i >> 1) * 8192 + (i & 1) * 2048;
                    if (n < NS) {
                        uint32_t f[4];
                        ldsm4t(f, ra + SA + o);
                        sts128(l16 + ws + n * 4096, f[0], f[1], f[2], f[3]);
                    } else ldsm4t(fa[n - NS], ra + SA + o);
                    ldsm4t(fb[n], ra + SB + o);
                }
                if (rd > 1) { bar_sync(NB_XCH, 256); issue(rd - 2); }
            }
            fence_async();
            bar_sync(NB_PRO, 416);
            uint32_t pk[8];
#pragma unroll
            for (int i = 0; i < 8; i++) pk[i] = pack2(acc[2 * i], acc[2 * i + 1]);
            if (rank < 2) {
                stsm4t(dst - wg * 5120 + 1024, pk[0], pk[1], pk[2], pk[3]);
                stsm4t(dst - wg * 5120 + 3072, pk[4], pk[5], pk[6], pk[7]);
            } else {
                const uint32_t la = l16 + (l16 & 256) + OFF_VX + wg * 8192 + (warp & 3) * 1024;
                stsm4(la, pk[0], pk[2], pk[1], pk[3]);
                stsm4(la + 256, pk[4], pk[6], pk[5], pk[7]);
            }
        }
        uint32_t xlo = (uint32_t)mkdesc(sb + OFF_X + wg * 64, 0, 0);
        const uint32_t xtog = xlo ^ (uint32_t)mkdesc(sb + OFF_X + 40960 + wg * 64, 0, 0);
        uint32_t p8 = 0;
        bar_sync(NB_LD, 288);
        for (int s = -1;; s++) {
            uint32_t t[NS ? NS : 1][4];
            {
                float acc[16];
                auto xproj = [&](auto I0, auto I1) {
                    const u64 desc = (u64)xlo | (64ull << 32) | SW128;
                    wg_fence();
#pragma unroll
                    for (int i = I0.value; i < I1.value; i++) {
                        const u64 db = desc + (i >> 1) * 256 + (i & 1) * 2;
                        if (i == 0) wgmma_n32_rs<0>(acc, fb[i], db);
                        else if (!NOX) wgmma_n32_rs<1>(acc, fb[i], db);
                    }
                    wg_commit();
                    if (TPOS == 0 ? I0.value == 0 : I1.value == 20) {
#pragma unroll
                        for (int i = 0; i < NS; i++) lds128(t[i], l16 + ws + i * 4096);
                    }
                    wg_wait<0>();
                };
                if (s >= 0 && rank < 2) { fence_async(); bar_arrive(NB_W1, 512); bar_sync(NB_X, 384); }
                bar_sync_if<NB_W1, 480>(s >= 0 && rank == 2);
                if (s == NSEG - 1) break;
                xproj(IC<0>{}, IC<NW1>{});
                if (warp == 4 && s >= 0) PROFT(15);
                bar_sync_if<NB_W2, 384>(s >= 0 && rank < 2);
                if (NW1B > 0) xproj(IC<NW1>{}, IC<NW1 + NW1B>{});
                bar_sync_if<NB_WIN, 384>(s >= 0 && rank == 2);
                xproj(IC<NW1 + NW1B>{}, IC<20>{});
                if (warp == 4 && s >= 0) PROFT(12);
                sts128f_if(l16 + xo, acc + 8, !wg); sts128f_if(l16 + xo + 4096, acc + 12, !wg);
                sts128f_if(l16 + xo, acc, wg); sts128f_if(l16 + xo + 4096, acc + 4, wg);
                bar_sync(NB_PAIR + (warp & 3), 64);
                lds128f_if(acc + 8, l16 + xi, !wg); lds128f_if(acc + 12, l16 + xi + 4096, !wg);
                lds128f_if(acc, l16 + xi, wg); lds128f_if(acc + 4, l16 + xi + 4096, wg);
                float u[8];
#pragma unroll
                for (int i = 0; i < 8; i++) u[i] = acc[i] + acc[8 + i];
                if (rank < 2) {
                    stsm4t(dst + (wg ? 3072 : 11264), pack2(u[0], u[1]), pack2(u[2], u[3]), pack2(u[4], u[5]), pack2(u[6], u[7]));
                } else {
                    stsm4(l16 + (l16 & 256) + OFF_VX + 4096 + (warp & 3) * 1024 + wg * 256 + p8 * 1024,
                          pack2(u[0], u[1]), pack2(u[4], u[5]), pack2(u[2], u[3]), pack2(u[6], u[7]));
                    bar_arrive(NB_KF, 288);
                }
                bar_arrive(NB_KX, 384);
                xlo ^= xtog;
                if (warp == 4 && s >= 0) PROFT(3);
            }
            float da[4] = {0.f, 0.f, 0.f, 0.f}, db[4] = {0.f, 0.f, 0.f, 0.f}, ea[4] = {0.f, 0.f, 0.f, 0.f}, eb[4] = {0.f, 0.f, 0.f, 0.f};
            uint32_t b[10][4];
            const uint32_t mp = p8 >> 3;
            while (!mbar_try(bar + 8 * B_MEM, mp)) {}
            lds128(b[0], l16 + mb); lds128(b[1], l16 + mb + 1024);
            bool rdy;
            const uint32_t xb0 = mapa(bar + 8 * B_VM + p8, 0), xb1 = mapa(bar + 8 * B_VM + p8, 1);
            SFENCE();
            float is;
#pragma unroll
            for (int j = 0; j < 10; j++) {
#pragma unroll
                for (int x = 0; x < 2; x++) {
                    const int i = 2 * j + x;
                    const uint32_t* f = i < NS ? t[i] : fa[i - NS];
                    mma16(NS > 2 && x && j ? ea : da, f[0], f[1], f[2], f[3], b[j][2 * x], b[j][2 * x + 1]);
                    mma16(NS > 2 && x && j ? eb : db, fb[i][0], fb[i][1], fb[i][2], fb[i][3], b[j][2 * x], b[j][2 * x + 1]);
                    SFENCE();
                    if (x == 0 && j < 8 && !(j & 1)) rdy = mbar_try(bar + 8 * (B_MEM + 1 + (j >> 1)), mp, 1);
                    if (x == LATE && j < 8 && (j & 1) == 1 - LATE) {
                        if (__builtin_expect(!rdy, 0)) while (!mbar_try(bar + 8 * (B_MEM + 1 + (j >> 1)), mp)) {}
                        lds128(b[(j | 1) + 1], l16 + mb + ((j | 1) + 1) * 1024);
                        lds128(b[(j | 1) + 2], l16 + mb + ((j | 1) + 2) * 1024);
                    }
                    if (x == 0 && j == 8) is = lds32f(sb + OFF_MX + 16);
                }
                if (j == 0 && warp == 4) PROFT(16);
            }
            if (warp == 4) PROFT(20);
            if (NS > 2) {
#pragma unroll
                for (int i = 0; i < 4; i++) { da[i] += ea[i]; db[i] += eb[i]; }
            }
            sts128f_if(l16 + xo + 8192, db, !wg); sts128f_if(l16 + xo + 8192, da, wg);
            bar_sync(NB_PAIR + (warp & 3), 64);
            lds128f_if(db, l16 + xi + 8192, !wg); lds128f_if(da, l16 + xi + 8192, wg);
            const uint32_t p0 = pack2((da[0] + db[0]) * is, (da[1] + db[1]) * is), p1 = pack2((da[2] + db[2]) * is, (da[3] + db[3]) * is);
            stsm2t_if(dst, p0, p1, rank < 2);
            bar_arrive_if<NB_QK, 384>(rank < 2);
            if (rank == 2) {
                st_async1(mapa(dst, 0), p0, xb0); st_async1(mapa(dst, 1), p0, xb1);
                st_async1(mapa(dst + 128, 0), p1, xb0); st_async1(mapa(dst + 128, 1), p1, xb1);
                sts32(dst, p0); sts32(dst + 128, p1);
                bar_arrive(NB_QK, 384);
            }
            if (warp == 4) PROFT(17);
            dst += dstep; dstep = -dstep; p8 ^= 8;
        }
    } else if (warp < 12) {
        asm volatile("setmaxnreg.dec.sync.aligned.u32 96;");
        const uint32_t rank = cta_rank();
        const int w = warp - 8;
        uint32_t amax = 0;
        {
            const int t = tid & 127, nr = rank == 2 ? 4 : 3;
            for (int r = 0; r < nr; r++) {
                const bf16* src = Wo + (size_t)(h * E_) * D_ + (r < 3 ? 192 * r + 64 * rank : 576);
#pragma unroll 1
                for (int i = 0; i < 8; i++) {
                    const int e = i * 16 + (t >> 3);
                    cp16(sb + OFF_WO + r * 16384 + e * 128 + (((t & 7) ^ (e & 6)) << 4), src + e * D_ + (t & 7) * 8);
                }
            }
            cp_commit();
            cp_wait<0>();
            bar_sync(NB_ATT, 128);
            for (int r = 0; r < nr; r++) {
                uint32_t u[8][4];
                const uint32_t p = sb + OFF_WO + r * 16384 + 2 * q * 128 + (((2 * w + (g & 1)) ^ (2 * q)) << 4) + (g >> 1) * 4;
#pragma unroll
                for (int ks = 0; ks < 8; ks++)
#pragma unroll
                    for (int j = 0; j < 4; j++) u[ks][j] = lds32(p + (16 * ks + (j & 1) * 8 + (j >> 1)) * 128);
                bar_sync(NB_ATT, 128);
#pragma unroll
                for (int ks = 0; ks < 8; ks++)
                    sts128(sb + OFF_WO + (r * 4 + w) * 4096 + ks * 512 + lane * 16, prmt(u[ks][0], u[ks][2], 0x5410), prmt(u[ks][0], u[ks][2], 0x7632),
                           prmt(u[ks][1], u[ks][3], 0x5410), prmt(u[ks][1], u[ks][3], 0x7632));
            }
        }
        {
            uint32_t m0[5][4];
#pragma unroll
            for (int it = 0; it < 5; it++)
#pragma unroll
                for (int j = 0; j < 4; j++) m0[it][j] = ldg32(mem0 + g * D_ + (it * 4 + w) * 32 + 2 * q + 8 * j);
            bar_sync(NB_PRO, 416);
#pragma unroll
            for (int it = 0; it < 5; it++) {
                sts128(sb + OFF_MEMB + (it * 4 + w) * 512 + lane * 16, m0[it][0], m0[it][1], m0[it][2], m0[it][3]);
                amax = absmax2(amax, absmax2(absmax2(m0[it][0], m0[it][1]), absmax2(m0[it][2], m0[it][3])));
            }
            if (tid == 256) { sts32(sb + OFF_MX + 16, 0x3f800000u); sts128(sb + OFF_MX + 48, 0x3f803f80u, 0x3f803f80u, 0x3f803f80u, 0x3f803f80u); }
            __syncwarp();
            if (lane < 5) mbar_arrive(bar + 8 * (B_MEM + lane));
            __syncwarp();
        }
        if (w == 0) TLI(690 + blockIdx.x, 3, gtime());
        pdl_wait();
        float cw;
        {
            const float4 a = ((const float4*)g_nrm)[lane], c = ((const float4*)g_nrm)[32 + lane];
            float sm = sqrt_approx((a.x + a.y) + (a.z + a.w)) * sqrt_approx((c.x + c.y) + (c.z + c.w)), mxv = sm;
#pragma unroll 1
            for (int o = 16; o; o >>= 1) { sm += __shfl_xor_sync(~0u, sm, o); mxv = fmaxf(mxv, __shfl_xor_sync(~0u, mxv, o)); }
            cw = 26.5f * fmaxf(sm, 8.f * mxv);
        }
        if (w == 0) {
            mbar_expect_elect(bar + 8 * B_X1, 1280);
            mbar_expect_elect(bar + 8 * B_VM, rank < 2 ? 2048 : 0);
            mbar_expect_elect(bar + 8 * B_VX, rank < 2 ? 8192 : 0);
        }
        {
            const int kind = rank;
            const uint32_t l16 = opaque(sb + lane * 16), lw = opaque(sb + lane * 16 + w * 512);
            const uint32_t pa = opaque(sb + OFF_PS + rank * 512 + lane * 4 + w * 128);
            uint32_t lq = opaque(sb + OFF_Q + (lane & 7) * 16 + ((lane >> 3) & 1) * 256 + (lane >> 4) * 128);
            const uint32_t lv = opaque(sb + OFF_VX + w * 2048 + (lane & 7) * 16 + ((lane >> 3) & 1) * 512 + (lane >> 4) * 128);
            const uint32_t lo = opaque(sb + OFF_WO + w * 4096 + lane * 16);
            uint32_t& sfd = lq;
            const char* rp = (const char*)(g_acc + layer * ACC_LAYER) + (4 * rank + w) * 4096 + opaque((q >> 1) * 1024 + ((q & 1) * 8 + g) * 8);
            const char* lp = (const char*)(g_acc + layer * ACC_LAYER) + opaque(w * 8192 + (lane >> 3) * 1024 + (lane & 7) * 16);
            const uint32_t arm = bar + 8 * (w == 0 ? B_X1 + 1 : w == 1 ? B_VX + 1 : w == 2 ? B_XT : B_VM + 1);
            const uint32_t armb = w == 0 ? 1280 : (w == 1 ? 4096 : w == 2 ? 40960 : 0) + (rank == 2 ? 0 : w == 3 ? 2048 : 4096);
            float isig = 1.f;
            for (int s = 0; s < NSEG - 1; s++) {
                const uint32_t pb = s & 1, ph = (s >> 1) & 1, x1 = bar + 8 * (B_X1 + pb);
                uint32_t kf[8];
                bar_sync(NB_KX, 384);
                ldsm4(kf, lw + OFF_K + 1024 + w * 512 + pb * 5120); ldsm4(kf + 4, lw + OFF_K + 1536 + w * 512 + pb * 5120);
                sts32(sb + OFF_MX + w * 4, __reduce_max_sync(~0u, max(amax & 0x7fff0000u, (amax << 16) & 0x7fff0000u)));
                const uint32_t va = lv + pb * 8192, vma = lw + OFF_VM + pb * 2048;
                uint32_t wf[8][4], vf[2][2][4], vm[4], one[4];
                mbar_spin(bar + 8 * (B_VX + pb), ph);
#pragma unroll
                for (int t = 0; t < 2; t++)
#pragma unroll
                    for (int j = 0; j < 2; j++) ldsm4(vf[t][j], va + t * 1024 + j * 256);
                lds128(one, sb + OFF_MX + 48);
                auto scores = [&](auto MM) {
                    constexpr int mm = MM.value;
                    uint32_t qf[8], mf[8];
                    const uint32_t qa = lq + pb * 5120, ka = l16 + OFF_K + pb * 5120;
                    const uint32_t pa0 = mapa(pa, rank ^ 1), pa1 = mapa(pa, 2), pa2 = mapa(pa, rank);
                    const uint32_t xb0 = mapa(x1, rank ^ 1), xb1 = mapa(x1, 2), xb2 = mapa(x1, rank);
                    const uint32_t pm = 640 - rank * 384;
                    SFENCE();
                    if (w == 0) PROFT(2);
                    bar_sync(NB_QK, 384);
                    ldsm4(qf, qa); ldsm4(qf + 4, qa + 512);
                    if (mm) { ldsm4(mf, ka); ldsm4(mf + 4, ka + 512); }
                    SFENCE();
                    float c[4][4];
#pragma unroll
                    for (int i = 0; i < 4; i++) c[i][0] = c[i][1] = c[i][2] = c[i][3] = 0.f;
#pragma unroll
                    for (int i = 0; i < (mm ? 8 : 4); i++) {
                        const int hf = mm ? i >> 2 : i >> 1;
                        const uint32_t* f = (mm && (i & 2) ? mf : kf) + 4 * hf + 2 * (i & 1);
                        mma16(c[i & 3], qf[4 * hf], qf[4 * hf + 1], qf[4 * hf + 2], qf[4 * hf + 3], f[0], f[1]);
                    }
                    SFENCE();
                    bar_arrive(NB_W1, 512);
                    const uint32_t y = mm ? pack2(c[0][0] + c[1][2], c[0][1] + c[1][3])
                                          : pack2((c[0][0] + c[1][2]) + (c[2][0] + c[3][2]), (c[0][1] + c[1][3]) + (c[2][1] + c[3][3]));
                    st_async1(pa0, y, xb0); st_async1(pa1, y, xb1);
                    if (mm) {
                        const uint32_t z = pack2(c[2][0] + c[3][2], c[2][1] + c[3][3]);
                        st_async1(pa0 + pm, z, xb0); st_async1(pa1 + pm, z, xb1); st_async1(pa2 + pm, z, xb2);
                    }
                    st_async1(pa2, y, xb2);
                    if (w == 0) PROFT(5);
                };
                if (kind == 2) bar_sync(NB_QK, 384);
                else if (w == 3) scores(IC<1>{});
                else scores(IC<0>{});
                float m4[4];
                lds128f(m4, sb + OFF_MX);
                bar_arrive_if<NB_W1, 480>(kind == 2);
                mbar_spin(x1, ph);
                if (w == 0) PROFT(6);
                float sc[10];
                {
                    uint32_t u[4], v[4], m[2];
                    ldsm4(u, l16 + OFF_PS); ldsm4(v, l16 + OFF_PS + 512); ldsm2(m, l16 + OFF_PS + 1024);
                    SFENCE();
                    m4[0] = fmaxf(fmaxf(m4[0], m4[1]), fmaxf(m4[2], m4[3])) * isig;
                    SFENCE();
#pragma unroll
                    for (int i = 0; i < 4; i++) { sc[2 * i] = bf_lo(u[i]) + bf_lo(v[i]); sc[2 * i + 1] = bf_hi(u[i]) + bf_hi(v[i]); }
                    sc[8] = bf_lo(m[0]) + bf_lo(m[1]); sc[9] = bf_hi(m[0]) + bf_hi(m[1]);
                }
                float mx = fmaxf(fmaxf(fmaxf(fmaxf(sc[0], sc[1]), fmaxf(sc[2], sc[3])), fmaxf(fmaxf(sc[4], sc[5]), fmaxf(sc[6], sc[7]))), fmaxf(sc[8], sc[9]));
                auto fetch = [&](int i) { lds128(wf[i], lo + i * 512); };
                {
                    float m1 = __shfl_xor_sync(~0u, mx, 1), m2 = __shfl_xor_sync(~0u, mx, 2), m3 = __shfl_xor_sync(~0u, mx, 3);
                    mbar_spin(bar + 8 * (B_VM + pb), ph);
                    ldsm4(vm, vma);
                    mx = fmaxf(fmaxf(mx, m1), fmaxf(m2, m3)) * SM_SCALE;
                }
#pragma unroll
                for (int i = 0; i < 10; i++) sc[i] = fmaf(sc[i], SM_SCALE, -mx);
                float o0[4] = {0.f, 0.f, 0.f, 0.f}, o1[4] = {0.f, 0.f, 0.f, 0.f}, rs[4] = {0.f, 0.f, 0.f, 0.f};
                sc[8] = ex2(sc[8]); fetch(0); fetch(1); sc[9] = ex2(sc[9]);
                SFENCE();
                fetch(2); sc[0] = ex2(sc[0]); fetch(3); fetch(4); sc[1] = ex2(sc[1]); fetch(5); fetch(6); sc[2] = ex2(sc[2]);
                SFENCE();
                {
                    const uint32_t p = pack2(sc[8], sc[9]);
                    sc[3] = ex2(sc[3]); fetch(7);
                    mma8(o0, vm[0], vm[1], p);
                    mma8(o1, vm[2], vm[3], p);
                    sc[4] = ex2(sc[4]);
                    mma8(rs, one[0], one[1], p);
                    sc[5] = ex2(sc[5]);
                }
                SFENCE();
                {
                    const uint32_t p0 = pack2(sc[0], sc[1]), p1 = pack2(sc[2], sc[3]);
                    sc[6] = ex2(sc[6]);
                    mma16(o0, vf[0][0][0], vf[0][0][1], vf[0][0][2], vf[0][0][3], p0, p1);
                    SFENCE();
                    sc[7] = ex2(sc[7]);
                    mma16(o1, vf[1][0][0], vf[1][0][1], vf[1][0][2], vf[1][0][3], p0, p1);
                    SFENCE();
                    mma16(rs, one[0], one[1], one[2], one[3], p0, p1);
                    SFENCE();
                }
                {
                    const uint32_t p0 = pack2(sc[4], sc[5]), p1 = pack2(sc[6], sc[7]);
                    mma16(o0, vf[0][1][0], vf[0][1][1], vf[0][1][2], vf[0][1][3], p0, p1);
                    mma16(o1, vf[1][1][0], vf[1][1][1], vf[1][1][2], vf[1][1][3], p0, p1);
                    SFENCE();
                    mma16(rs, one[0], one[1], one[2], one[3], p0, p1);
                }
                const uint32_t e = max((__float_as_uint(cw * fmaxf(m4[0], 1.f)) >> 23) & 255u, 31u);
                SFENCE();
                stsm4t(lw + OFF_OB, pack2(o0[0], o0[1]), pack2(o0[2], o0[3]), pack2(o1[0], o1[1]), pack2(o1[2], o1[3]));
                if (w == 0) PROFT(13);
                bar_sync(NB_ATT, 128);
                uint32_t ob[16];
#pragma unroll
                for (int j = 0; j < 4; j++) ldsm4(ob + 4 * j, l16 + OFF_OB + j * 512);
                SFENCE();
                const float sig = __uint_as_float((278u - e) << 23);
                isig = __uint_as_float((e - 30u) << 23);
                const float sg0 = rcp(rs[0]) * sig, sg1 = rcp(rs[1]) * sig;
                SFENCE();
                auto tile = [&](uint32_t next, const char* p, auto LAST) {
                    float c[4][4];
#pragma unroll
                    for (int i = 0; i < 4; i++) c[i][0] = c[i][1] = c[i][2] = c[i][3] = 0.f;
#pragma unroll
                    for (int ks = 0; ks < 8; ks++) {
                        mma16(c[ks & 3], wf[ks][0], wf[ks][1], wf[ks][2], wf[ks][3], ob[2 * ks], ob[2 * ks + 1]);
                        if ((ks & 3) == 0) SFENCE();
                        if ((ks & 3) == 3 && !LAST.value) {
                            SFENCE();
#pragma unroll
                            for (int i = ks; i >= ks - 3; i--) { lds128(wf[i], next + i * 512); if (i == ks - 2) SFENCE(); }
                            if (ks == 3) SFENCE();
                        }
                    }
                    SFENCE();
                    if (LAST.value) { bar_arrive_if<NB_WIN, 256>(kind < 2); bar_arrive_if<NB_WIN, 384>(kind == 2); }
                    uint32_t v[4];
#pragma unroll
                    for (int i = 0; i < 4; i++)
                        v[i] = (__float_as_uint(fmaf((c[0][i] + c[1][i]) + (c[2][i] + c[3][i]), i & 1 ? sg1 : sg0, 12582912.f)) << 6) + (i < 2);
                    red_add64((u64*)p, v[0], v[2]);
                    red_add64((u64*)(p + 2048), v[1], v[3]);
                };
                tile(lo + 16384, rp, IC<0>{});
                if (w == 0) PROFT(7);
                tile(lo + 32768, rp + 49152, IC<0>{});
                if (kind == 2) tile(lo + 49152, rp + 98304, IC<0>{});
                tile(0, rp + (kind == 2 ? 28 * 4096 : 98304), IC<1>{});
                if (w == 0) PROFT(8);
                sts32(sb + OFF_MX + 16, __float_as_uint(isig));
                mbar_expect_elect(arm ^ (8 * pb), armb - (w == 2 && s == NSEG - 2 ? 40960 : 0) - (s == 0 && w == (rank < 2 ? 2 : 1) ? 4096 : 0));
                u64 y[20];
                uint32_t b[20];
                bool done[5] = {false, false, false, false, false};
                float z = isig;
                mbar_spin(bar + 8 * B_GO, pb);
                if (w == 0) PROFT(9);
                do {
#pragma unroll
                    for (int i = 0; i < 10; i++) {
                        if (STAG && (i == 2 || i == 5 || i == 8)) {
#pragma unroll
                            for (int k = 0; k < (i == 2 ? STAG / 100 : i == 5 ? STAG / 10 % 10 : STAG % 10); k++) asm volatile("ex2.approx.ftz.f32 %0,%0;" : "+f"(z));
                            asm volatile("{.reg .pred p; setp.ne.u32 p,%1,0; @p mov.b32 %0,%2;}" : "+r"(sfd) : "r"((uint32_t)never), "f"(z));
                            SFENCE();
                        }
                        ld_acc0(y[2 * i], y[2 * i + 1], lp + (i >> 1) * 32768 + (i & 1) * 4096);
                        if (STAG && (i == 1 || i == 4 || i == 7)) SFENCE();
                    }
                    uint32_t ok = 32u, late = 32u;
                    static_for<5>([&](auto IT) {
                        constexpr int it = IT.value;
                        if (it == 1) late = and3((uint32_t)y[4], (uint32_t)y[6], (uint32_t)y[8]);
                        else if (it == 2) late &= and3((uint32_t)y[10], (uint32_t)y[12], (uint32_t)y[14]);
                        else if (it == 3) ok &= late;
                        else ok = and3(ok, (uint32_t)y[4 * it], (uint32_t)y[4 * it + 2]);
                        if (it != 3) SFENCE();
                        if (it == 1 || it == 2) ok = and3(ok, (uint32_t)y[4 * it], (uint32_t)y[4 * it + 2]);
                        ok = and3(ok, (uint32_t)y[4 * it + 1], (uint32_t)y[4 * it + 3]);
                        const bool all = __all_sync(~0u, ok);
#pragma unroll
                        for (int j = 0; j < 4; j++) {
                            const u64 v = y[4 * it + j];
                            b[4 * it + j] = pack2((float)(int)(uint32_t)v, (float)(int)(uint32_t)(v >> 32));
                        }
                        sts128(lw + OFF_MEMB + it * 2048, b[4 * it], b[4 * it + 1], b[4 * it + 2], b[4 * it + 3]);
                        mbar_arrive_elect_if(bar + 8 * (B_MEM + it), all && !done[it]);
                        done[it] = all;
                        SFENCE();
                        if (it == 0 && w == 0) PROFT(10);
                    });
                } while (!done[4]);
                if (w == 0) PROFT(11);
                amax = b[0];
#pragma unroll
                for (int i = 1; i < 19; i += 2) amax = absmax2(amax, absmax2(b[i], b[i + 1]));
                amax = absmax2(amax, b[19]);
                const int adv = (s & 7) == 7 ? 163840 - 896 : 128;
                rp += adv; lp += adv;
            }
        }
        asm volatile("prefetch.tensormap [%0];" ::"l"(w & 1 ? &maps.wo1 : &maps.o2) : "memory");
        bar_sync(NB_KX, 384);
        bar_sync(NB_QK, 384);
        if (rank < 2) { bar_arrive(NB_W1, 512); bar_arrive(NB_WIN, 256); } else bar_arrive(NB_W1, 480);
    } else {
        asm volatile("setmaxnreg.dec.sync.aligned.u32 %0;" ::"n"(48));
        const uint32_t rank = cta_rank();
        const int w = warp - 12;
        pdl_wait();
        if (blockIdx.x == 2 && w == 3) asm volatile("st.release.gpu.global.u32 [%0],1;" ::"l"(g_started + layer) : "memory");
        uint32_t* sy = g_sync + layer * SYNC_LAYER;
        if (w == 1) TLI(690 + blockIdx.x, 1, gtime());
        if (w == 1) {
            mbar_expect_elect(bar + 8 * B_XT, 40960);
            mbar_expect_elect(bar + 8 * (B_XT + 1), 40960);
            if (rank < 2) bulk_g2s_all3_elect(sb + OFF_X + rank * 40960, g_xn + rank * 40960, 40960, bar + 8 * (B_XT + rank));
            bar_sync(NB_PRO, 416);
            if (rank == 2) mbar_spin(bar + 8 * B_ST, 0);
            else mbar_arrive_remote_elect(mapa(bar + 8 * B_ST, 2));
            TLI(690 + blockIdx.x, 2, gtime());
            bar_arrive(NB_LD, 288);
        }
        uint32_t* hp = sy + 1024;
        auto hint = [&](uint32_t t) {
            asm volatile("{.reg .pred p; elect.sync _|p, 0xffffffff; @p red.relaxed.gpu.global.max.u32 [%0+4],%1; @p red.relaxed.gpu.global.add.u32 [%0],1;}"
                         ::"l"(hp), "r"(t) : "memory");
        };
        if (rank == 2) {
            if (w == 0) {
                for (int s = -1; s < NSEG - 1; s++) {
                    const uint32_t pb = s & 1, nby = s < 1 ? 8192 : 4096, va = sb + OFF_VX + (pb ^ 1) * 8192 + 8192 - nby, vb = bar + 8 * (B_VX + (pb ^ 1));
                    bar_sync(NB_KF, 288);
                    fence_async();
                    bulk_s2s_elect(mapa(va, 0), va, nby, mapa(vb, 0));
                    bulk_s2s_elect(mapa(va, 1), va, nby, mapa(vb, 1));
                    if (s >= 0) mbar_spin(bar + 8 * (B_XD + pb), (s >> 1) & 1);
                    bar_sync(NB_W1, 480);
                }
            } else if (w == 1) {
                const unsigned char *pn = g_p + (H_ + h) * 12288, *px = g_xn + 2 * 40960;
                const uint32_t* pf = sy + wk::SY_P + h;
                bar_sync(NB_W1, 480);
                for (int s = 0, nb = 1; s < NSEG - 1; s++, pn += H_ * 12288, px += 40960) {
                    const uint32_t pb = s & 1, xt = bar + 8 * (B_XT + pb), qa = sb + OFF_Q + (pb ^ 1) * 5120 + 1024;
                    mbar_spin(bar + 8 * (B_X1 + pb), (s >> 1) & 1);
                    if (s + 2 < NSEG) bulk_g2s_all3_elect(sb + OFF_X + pb * 40960, px, 40960, xt);
                    if (s == nb) {
                        while (__any_sync(~0u, ld_acquire(pf) < 3)) {}
                        pf += H_;
                        nb += s == 1 ? 4 : 6;
                    }
                    if (s) {
                        bulk_g2s_all3_elect(sb + OFF_VX + (pb ^ 1) * 8192, pn + 8192, 4096, bar + 8 * (B_VX + (pb ^ 1)));
                        bulk_g2s_elect(mapa(qa, 0), pn, 4096, mapa(xt, 0));
                        bulk_g2s_elect(mapa(qa, 1), pn + 4096, 4096, mapa(xt, 1));
                    }
                    mbar_spin(xt, ((s + 2) >> 1) & 1);
                    bar_sync(NB_W1, 480);
                }
                mbar_spin(bar + 8 * (B_VX + 1), 1);
            } else if (w == 2) {
                const char* pf = lane < 5 ? (const char*)(g_acc + layer * ACC_LAYER) + (5 * h + lane) * 1024 : (const char*)hp;
                const int pfa = lane < 5 ? 163840 : 1024;
                if (lane < 6) for (int i = 0; i < 8; i++) prefetch_l2(pf + i * 128);
                __syncwarp();
                const uint32_t go = mapa(bar + 8 * B_GO, min(lane, 2));
                for (int s = 0; s < NSEG - 1; s++, hp += 32) {
                    bar_sync(NB_W1, 480);
                    sts32(sb + OFF_MX + 32, 0);
                    uint32_t t = gtime32(), t0 = clk(), c, tm;
                    hint(t);
                    if (h == 0) TLI(940 + s, 0, t);
                    if (lane < 6 && s < NSEG - 8) prefetch_l2(pf + ((s >> 3) + 1) * pfa + (s & 7) * 128);
                    __syncwarp();
                    while (clk() - t0 < (uint32_t)delay2) {}
                    do asm volatile("ld.relaxed.gpu.global.v2.u32 {%0,%1},[%2];" : "=r"(c), "=r"(tm) : "l"(hp) : "memory"); while (__any_sync(~0u, c != 3 * H_));
                    const uint32_t wait = min(tm - t, 10000u) * 7 / 4 + delay;
                    while (clk() - t0 < wait) {}
                    if (lane < 3) mbar_arrive_remote(go);
                    __syncwarp();
                }
                bar_sync(NB_W1, 480);
            }
        } else {
            if (w < 2) sts32(sb + OFF_PT + w * 768 + 640 + lane * 4, 0u);
            const uint32_t px = opaque(sb + OFF_PX + (w & 1) * 1280 + lane * 8);
            const uint32_t pt = opaque(sb + OFF_PT + (w & 1) * 768 + lane * 4);
            uint32_t os = opaque(sb + OFF_OST + (lane >> 4) * 1024 + w * 256 + (lane & 15) * 16);
            uint32_t& sfd = os;
            const int lim = opaque(8 * w + g + 8 - 2 * q);
            unsigned char* op = g_o + h * 8192 + rank * 2048;
            uint32_t* oc = sy + wk::SY_O;
            auto report = [&]() {
                bulk_wait<0>();
                __syncwarp();
                asm volatile("{.reg .pred p; elect.sync _|p, 0xffffffff; @p red.relaxed.gpu.global.add.u32 [%0],1;}" ::"l"(oc) : "memory");
                oc++;
            };
            auto store_o = [&](int n) {
                bulk_s2g_elect(op, sb + OFF_OST + (n & 1) * 4096, 2048);
                bulk_s2g_elect(op + 4096, sb + OFF_OST + (n & 1) * 4096 + 2048, 2048);
                bulk_commit();
                op += H_ * 8192;
            };
            for (int s = 0; s < NSEG; s++) {
                const uint32_t pb = s & 1, ph = (s >> 1) & 1;
                if ((w >> 1) != rank) { if (s >= 1) mbar_spin(bar + 8 * B_PXE, pb ^ 1); }
                else if (w & 1) mbar_spin(bar + 8 * (B_XT + (pb ^ 1)), ((s + 1) >> 1) & 1);
                else mbar_expect_elect(bar + 8 * B_PXF, rank ? 2560 : 1536);
                const u64 dq = mkdesc(sb + OFF_Q + pb * 5120 + 1024, 128, 512), dk = mkdesc(sb + OFF_K + pb * 5120, 128, 1024);
                SFENCE();
                bar_sync(NB_W1, 512);
                float c[20];
                wg_fence();
                wgmma_n40_ss<0>(c, dq, dk);
#pragma unroll
                for (int ks = 1; ks < 4; ks++) wgmma_n40_ss<1>(c, dq + ks * 16, dk + ks * 16);
                wg_commit();
                bar_arrive(NB_X, 384);
                if (w == 2 * rank) { hint(gtime32()); hp += 32; }
                wg_wait<0>();
                if ((w >> 1) != rank) {
                    const uint32_t pa = mapa(px, rank ^ 1), pf = mapa(bar + 8 * B_PXF, rank ^ 1);
#pragma unroll
                    for (int nt = 0; nt < 5; nt++)
                        if (nt < 3 || rank == 0) st_async2(pa + nt * 256, __float_as_uint(c[4 * nt]), __float_as_uint(c[4 * nt + 1]), pf);
                    if ((w & 1) && s) store_o(s - 1);
                    mbar_spin(bar + 8 * (w & 1 ? B_VX : B_VM) + 8 * pb, ph);
                } else {
                    mbar_spin(bar + 8 * B_PXF, pb);
                    float u[10];
#pragma unroll
                    for (int nt = 0; nt < 5; nt++) lds64f(u[2 * nt], u[2 * nt + 1], px + nt * 256);
#pragma unroll
                    for (int i = 0; i < 10; i++) u[i] = 8 * (i >> 1) + (i & 1) <= lim ? u[i] + c[4 * (i >> 1) + (i & 1)] : -INFINITY;
                    float mx = fmaxf(fmaxf(fmaxf(fmaxf(u[0], u[1]), fmaxf(u[2], u[3])), fmaxf(fmaxf(u[4], u[5]), fmaxf(u[6], u[7]))), fmaxf(u[8], u[9]));
                    const float m1 = __shfl_xor_sync(~0u, mx, 1), m2 = __shfl_xor_sync(~0u, mx, 2), m3 = __shfl_xor_sync(~0u, mx, 3);
                    mx = fmaxf(fmaxf(mx, m1), fmaxf(m2, m3)) * SM_SCALE;
#pragma unroll
                    for (int i = 0; i < 10; i++) u[i] = ex2(fmaf(u[i], SM_SCALE, -mx));
                    float sum = (((u[0] + u[1]) + (u[2] + u[3])) + ((u[4] + u[5]) + (u[6] + u[7]))) + (u[8] + u[9]);
                    const float s1 = __shfl_xor_sync(~0u, sum, 1), s2 = __shfl_xor_sync(~0u, sum, 2), s3 = __shfl_xor_sync(~0u, sum, 3);
                    sum = rcp((sum + s1) + (s2 + s3));
#pragma unroll
                    for (int nt = 0; nt < 5; nt++) sts32(pt + (nt ? nt - 1 : 4) * 128, pack2(u[2 * nt] * sum, u[2 * nt + 1] * sum));
                }
                float acc[2][8];
                const u64 dv = mkdesc(sb + OFF_VX + pb * 8192, 128, 512), dp = mkdesc(sb + OFF_PT, 128, 768);
                const u64 dm = mkdesc(sb + OFF_VM + pb * 2048, 0, 128);
                fence_async();
                bar_sync(NB_WIN, 256);
                wg_fence();
#pragma unroll
                for (int m = 0; m < 2; m++) {
                    wgmma_n16_ss<0>(acc[m], dv + m * 256, dp);
                    wgmma_n16_ss<1>(acc[m], dv + m * 256 + 16, dp + 16);
                    wgmma_n16_ss<1>(acc[m], dm + m * 64, dp + 32);
                }
                wg_commit();
                bar_arrive_if<NB_W2, 384>(s < NSEG - 1);
                wg_wait<0>();
#pragma unroll
                for (int m = 0; m < 2; m++)
                    stsm4t(os + pb * 4096 + m * 2048, pack2(acc[m][0], acc[m][1]), pack2(acc[m][2], acc[m][3]), pack2(acc[m][4], acc[m][5]), pack2(acc[m][6], acc[m][7]));
                fence_async();
                mbar_arrive_remote_elect(mapa(bar + 8 * (B_XD + pb), 2));
                if ((w >> 1) == rank) mbar_arrive_remote_elect(mapa(bar + 8 * B_PXE, rank ^ 1));
                else if ((w & 1) && s) report();
            }
            bar_sync(NB_W2, 128);
            if (w == 3 - 2 * rank) {
                store_o(NSEG - 1);
                report();
            }
        }
    }
    __syncwarp();
    if (lane < 3) mbar_arrive_remote(mapa(bar + 8 * B_FIN, lane));
    mbar_wait(bar + 8 * B_FIN, 0);
    TLE(2 + 5 * layer);
    fence_async();
    if (warp < 8) asm volatile("setmaxnreg.dec.sync.aligned.u32 128;"); else asm volatile("setmaxnreg.inc.sync.aligned.u32 128;");
    }
    const int b = blockIdx.x;
    worker<false>(sb, maps, x, x1, layer, b >= 3 * H_ ? b - 3 * H_ : b < 10 * SPLIT_B ? wk::I_SB + b : -1, gridDim.x - 3 * H_);
}

int g_delay = 5001350, g_layers = 2;

void make_map(CUtensorMap* m, CUtensorMapDataType dt, const void* p, const cuuint64_t* dim, const cuuint64_t* str, const cuuint32_t* box, CUtensorMapSwizzle sw) {
    typedef CUresult (*Fn)(CUtensorMap*, CUtensorMapDataType, cuuint32_t, void*, const cuuint64_t*, const cuuint64_t*, const cuuint32_t*,
                           const cuuint32_t*, CUtensorMapInterleave, CUtensorMapSwizzle, CUtensorMapL2promotion, CUtensorMapFloatOOBfill);
    static Fn fn = nullptr;
    if (!fn) {
        cudaDriverEntryPointQueryResult qr;
        cudaGetDriverEntryPoint("cuTensorMapEncodeTiled", (void**)&fn, cudaEnableDefault, &qr);
    }
    const cuuint32_t es[3] = {1, 1, 1};
    fn(m, dt, 3, (void*)p, dim, str, box, es, CU_TENSOR_MAP_INTERLEAVE_NONE, sw, CU_TENSOR_MAP_L2_PROMOTION_L2_128B, CU_TENSOR_MAP_FLOAT_OOB_FILL_NONE);
}
void map_weight(CUtensorMap* m, const bf16* p, int rows, int cols, int ng, int br = 64) {
    const cuuint64_t dim[3] = {64, (cuuint64_t)rows, (cuuint64_t)cols / 64}, str[2] = {(cuuint64_t)cols * 2, 128};
    const cuuint32_t box[3] = {64, (cuuint32_t)br, (cuuint32_t)ng};
    make_map(m, CU_TENSOR_MAP_DATA_TYPE_BFLOAT16, p, dim, str, box, CU_TENSOR_MAP_SWIZZLE_128B);
}
void map_pieces(CUtensorMap* m, const void* p, int np, int ns) {
    const cuuint64_t dim[3] = {256, (cuuint64_t)np * 2, NSEG}, str[2] = {2048, (cuuint64_t)np * 4096};
    const cuuint32_t box[3] = {256, 2, (cuuint32_t)ns};
    make_map(m, CU_TENSOR_MAP_DATA_TYPE_UINT64, p, dim, str, box, CU_TENSOR_MAP_SWIZZLE_NONE);
}

template <class... P, class... A> void launch(void (*k)(P...), int grid, int block, int smem, int cluster, bool pdl, A... args) {
    cudaLaunchConfig_t c = {};
    c.gridDim = dim3(grid); c.blockDim = dim3(block); c.dynamicSmemBytes = smem; c.stream = cudaStreamPerThread;
    cudaLaunchAttribute at[2];
    int n = 0;
    if (cluster > 1) { at[n].id = cudaLaunchAttributeClusterDimension; at[n].val.clusterDim.x = cluster; at[n].val.clusterDim.y = 1; at[n].val.clusterDim.z = 1; n++; }
    if (pdl) { at[n].id = cudaLaunchAttributeProgrammaticStreamSerialization; at[n].val.programmaticStreamSerializationAllowed = 1; n++; }
    c.attrs = at; c.numAttrs = n;
    cudaLaunchKernelEx(&c, k, args...);
}

int max_clusters() {
    cudaLaunchConfig_t c = {};
    c.gridDim = dim3(3 * H_); c.blockDim = dim3(512); c.dynamicSmemBytes = rec::SMEM;
    cudaLaunchAttribute at[1];
    at[0].id = cudaLaunchAttributeClusterDimension; at[0].val.clusterDim.x = 3; at[0].val.clusterDim.y = 1; at[0].val.clusterDim.z = 1;
    c.attrs = at; c.numAttrs = 1;
    int n = 0;
    cudaOccupancyMaxActiveClusters(&n, rec_kernel, &c);
    return n;
}

}

extern "C" void kernel_launch(void* const* d_in, const int* in_sizes, int n_in, void* d_out, int out_size) {
    const bf16* x = (const bf16*)d_in[0];
    const bf16* mem0 = (const bf16*)d_in[1];
    const bf16* Wq = (const bf16*)d_in[2];
    const bf16* Wk = (const bf16*)d_in[3];
    const bf16* Wv = (const bf16*)d_in[4];
    const bf16* Wo = (const bf16*)d_in[5];
    const bf16* wr = (const bf16*)d_in[8];
    const bf16* wi = (const bf16*)d_in[9];
    cudaFuncSetAttribute(rec_kernel, cudaFuncAttributeMaxDynamicSharedMemorySize, rec::SMEM);
    cudaFuncSetAttribute(side_kernel, cudaFuncAttributeMaxDynamicSharedMemorySize, wk::SMEM);
    cudaFuncSetAttribute(colfft_kernel, cudaFuncAttributeMaxDynamicSharedMemorySize, CF_SMEM);
    Maps maps;
    void *pxn, *po;
    cudaGetSymbolAddress(&pxn, g_xn);
    cudaGetSymbolAddress(&po, g_o);
    map_weight(&maps.wq2, Wq, D_, 4096, 2); map_weight(&maps.wv1, Wv, D_, 4096, 1);
    map_weight(&maps.wo2, Wo, 4096, D_, 2); map_weight(&maps.wo1, Wo, 4096, D_, 1, 192);
    map_pieces(&maps.x6, pxn, 10, 6); map_pieces(&maps.x4, pxn, 10, 4);
    map_pieces(&maps.o6, po, 64, 6); map_pieces(&maps.o2, po, 64, 2);
    bf16 *x1, *x2;
    cudaGetSymbolAddress((void**)&x1, g_x1);
    cudaGetSymbolAddress((void**)&x2, g_x2);
    constexpr int ONE_PER_SM = 116 * 1024;
    cudaFuncSetAttribute(rowfft_kernel, cudaFuncAttributeMaxDynamicSharedMemorySize, ONE_PER_SM);
    cudaFuncSetAttribute(rowifft_kernel, cudaFuncAttributeMaxDynamicSharedMemorySize, ONE_PER_SM);
    static int ncl = 0, nsm = 0;
    if (!ncl) { ncl = max_clusters(); cudaDeviceGetAttribute(&nsm, cudaDevAttrMultiProcessorCount, 0); }
    maps.wr = wr; maps.wi = wi;
    launch(prep_kernel, 128, 512, 0, 1, false, x, Wv, Wo);
    for (int layer = 0; layer < g_layers; layer++) {
        const bf16* xin = layer ? x2 : x;
        launch(rec_kernel, 3 * ncl, 512, rec::SMEM, 3, true, maps, xin, x1, mem0, Wq, Wk, Wv, Wo, layer, g_delay % 10000, g_delay / 10000);
        launch(side_kernel, max(nsm - 3 * ncl, 1), 512, wk::SMEM, 1, true, maps, xin, x1, layer, 3 * (ncl - H_));
        launch(rowfft_kernel, 128, 256, ONE_PER_SM, 1, true, xin, x1, layer);
        launch(colfft_kernel, 107, 384, CF_SMEM, 1, true, layer);
        launch(rowifft_kernel, 128, 256, ONE_PER_SM, 1, true, (const bf16*)x1, layer ? (bf16*)d_out : x2, layer);
    }
}
```

```cpp
#include <cuda_runtime.h>
#include <cuda_bf16.h>
#include <cuda.h>
#include <stdint.h>

#define DEV __device__ __forceinline__
typedef unsigned long long u64;
typedef __nv_bfloat16 bf16;

namespace {

constexpr int S_ = 2048, D_ = 640, H_ = 32, E_ = 128, NSEG = 64;

__device__ __align__(1024) unsigned char g_xn[S_ * D_ * 2];
__device__ __align__(1024) unsigned char g_o[S_ * H_ * E_ * 2];
constexpr int ACC_LAYER = 32 * 5120;
__device__ __align__(4096) u64 g_acc[2 * ACC_LAYER];
__device__ __align__(16) float g_nrm[256];
__device__ __align__(1024) unsigned char g_p[NSEG * H_ * 3 * 4096];
constexpr int SYNC_LAYER = 1024 + 64 * 32;
__device__ __align__(128) uint32_t g_sync[2 * SYNC_LAYER];
__device__ uint32_t g_started[2];
__device__ __align__(1024) bf16 g_x1[S_ * D_];
__device__ __align__(1024) bf16 g_x2[S_ * D_];
constexpr int YT_ROWS = 192;
__device__ __align__(1024) float g_yt[2 * YT_ROWS * D_];
constexpr int NCOL = 321;
__device__ __align__(1024) unsigned char g_z[NCOL * 8192];
__device__ __align__(1024) unsigned char g_wt[NCOL * 8192];
__device__ __align__(1024) uint4 g_f128[2 * 8 * 256];
__device__ __align__(1024) uint4 g_f64[2 * 4 * 128];
__device__ __align__(1024) bf16 g_g32[2 * 4096];
#define TLI(id, k, v)
#define TLS(i)
#define TLE(i)

DEV uint32_t s2u(const void* p) { return (uint32_t)__cvta_generic_to_shared(p); }
DEV uint32_t clk() { uint32_t c; asm volatile("mov.u32 %0,%%clock;" : "=r"(c)::"memory"); return c; }
DEV uint32_t gtime32() { uint32_t t; asm volatile("mov.u32 %0,%%globaltimer_lo;" : "=r"(t)::"memory"); return t; }
DEV uint32_t cta_rank() { uint32_t r; asm volatile("mov.u32 %0,%%cluster_ctarank;" : "=r"(r)); return __shfl_sync(~0u, r, 0); }
DEV uint32_t mapa(uint32_t a, uint32_t r) { uint32_t o; asm("mapa.shared::cluster.u32 %0,%1,%2;" : "=r"(o) : "r"(a), "r"(r)); return o; }
DEV void mbar_init(uint32_t b, uint32_t n) { asm volatile("mbarrier.init.shared::cta.b64 [%0],%1;" ::"r"(b), "r"(n) : "memory"); }
DEV bool mbar_try(uint32_t b, uint32_t par, int) {
    uint32_t ok;
    asm volatile("{.reg .pred p; mbarrier.test_wait.parity.shared::cta.b64 p,[%1],%2; selp.u32 %0,1,0,p;}" : "=r"(ok) : "r"(b), "r"(par) : "memory");
    return ok;
}
DEV bool mbar_try(uint32_t b, uint32_t par) {
    uint32_t ok;
    asm volatile("{.reg .pred p; mbarrier.try_wait.parity.shared::cta.b64 p,[%1],%2; selp.u32 %0,1,0,p;}" : "=r"(ok) : "r"(b), "r"(par) : "memory");
    return ok;
}
constexpr uint32_t SPIN_LIMIT = 1u << 18;
DEV void die() { __trap(); }
DEV void mbar_wait(uint32_t b, uint32_t par) {
    uint32_t n = 0;
    while (!mbar_try(b, par)) if (++n > SPIN_LIMIT) die();
}
DEV void mbar_spin(uint32_t b, uint32_t par) { while (!mbar_try(b, par)) {} }
DEV uint32_t opaque(uint32_t x) { return __shfl_xor_sync(~0u, x, 0); }
#define SFENCE() asm volatile("{.reg .pred p; setp.ne.u32 p,%1,0; @p mov.u32 %0,%%clock;}" : "+r"(sfd) : "r"((uint32_t)never) : "memory")
DEV void mbar_arrive(uint32_t b) { asm volatile("mbarrier.arrive.shared::cta.b64 _,[%0];" ::"r"(b) : "memory"); }
DEV void mbar_arrive_elect(uint32_t b) { asm volatile("{.reg .pred p; elect.sync _|p, 0xffffffff; @p mbarrier.arrive.shared::cta.b64 _,[%0];}" ::"r"(b) : "memory"); }
DEV void mbar_arrive_elect_if(uint32_t b, bool c) {
    asm volatile("{.reg .pred p, q; setp.ne.u32 q,%1,0; elect.sync _|p, 0xffffffff; and.pred p,p,q; @p mbarrier.arrive.shared::cta.b64 _,[%0];}" ::"r"(b), "r"((uint32_t)c) : "memory");
}
DEV void mbar_expect_elect(uint32_t b, uint32_t tx) {
    asm volatile("{.reg .pred p; elect.sync _|p, 0xffffffff; @p mbarrier.arrive.expect_tx.shared::cta.b64 _,[%0],%1;}" ::"r"(b), "r"(tx) : "memory");
}
DEV void mbar_arrive_remote_elect(uint32_t b) { asm volatile("{.reg .pred p; elect.sync _|p, 0xffffffff; @p mbarrier.arrive.shared::cluster.b64 _,[%0];}" ::"r"(b) : "memory"); }
DEV bool elect() { uint32_t r; asm volatile("{.reg .pred p; elect.sync _|p, 0xffffffff; selp.u32 %0,1,0,p;}" : "=r"(r)); return r; }
DEV void mbar_arrive_remote(uint32_t b) { asm volatile("mbarrier.arrive.shared::cluster.b64 _,[%0];" ::"r"(b) : "memory"); }
DEV void mbar_expect(uint32_t b, uint32_t tx) { asm volatile("mbarrier.arrive.expect_tx.shared::cta.b64 _,[%0],%1;" ::"r"(b), "r"(tx) : "memory"); }
DEV void bar_sync(int id, int n) { asm volatile("bar.sync %0,%1;" ::"r"(id), "r"(n) : "memory"); }
DEV void bar_arrive(int id, int n) { asm volatile("bar.arrive %0,%1;" ::"r"(id), "r"(n) : "memory"); }
template <int ID, int N> DEV void bar_arrive_if(bool p) {
    asm volatile("{.reg .pred p; setp.ne.u32 p,%0,0; @p bar.arrive %1,%2;}" ::"r"((uint32_t)p), "n"(ID), "n"(N) : "memory");
}
DEV void prefetch_l2(const void* p) { asm volatile("prefetch.global.L2 [%0];" ::"l"(p) : "memory"); }
template <int ID, int N> DEV void bar_sync_if(bool p) {
    asm volatile("{.reg .pred p; setp.ne.u32 p,%0,0; @p bar.sync %1,%2;}" ::"r"((uint32_t)p), "n"(ID), "n"(N) : "memory");
}
DEV void st_remote(uint32_t a, uint32_t x) { asm volatile("st.relaxed.cluster.shared::cluster.u32 [%0],%1;" ::"r"(a), "r"(x) : "memory"); }
DEV void st_async1(uint32_t a, uint32_t x, uint32_t b) {
    asm volatile("st.async.shared::cluster.mbarrier::complete_tx::bytes.u32 [%0],%1,[%2];" ::"r"(a), "r"(x), "r"(b) : "memory");
}
DEV void st_async2(uint32_t a, uint32_t x, uint32_t y, uint32_t b) {
    asm volatile("st.async.shared::cluster.mbarrier::complete_tx::bytes.v2.u32 [%0],{%1,%2},[%3];" ::"r"(a), "r"(x), "r"(y), "r"(b) : "memory");
}
DEV void st_async4(uint32_t a, uint32_t x, uint32_t y, uint32_t z, uint32_t w, uint32_t b) {
    asm volatile("st.async.shared::cluster.mbarrier::complete_tx::bytes.v4.u32 [%0],{%1,%2,%3,%4},[%5];" ::"r"(a), "r"(x), "r"(y), "r"(z), "r"(w), "r"(b) : "memory");
}
DEV void bulk_g2s(uint32_t dst, const void* src, uint32_t bytes, uint32_t b) {
    asm volatile("cp.async.bulk.shared::cluster.global.mbarrier::complete_tx::bytes [%0],[%1],%2,[%3];" ::"r"(dst), "l"(src), "r"(bytes), "r"(b) : "memory");
}
DEV void bulk_g2s_elect(uint32_t dst, const void* src, uint32_t bytes, uint32_t b) {
    asm volatile("{.reg .pred p; elect.sync _|p, 0xffffffff; @p cp.async.bulk.shared::cluster.global.mbarrier::complete_tx::bytes [%0],[%1],%2,[%3];}"
                 ::"r"(dst), "l"(src), "r"(bytes), "r"(b) : "memory");
}
DEV void bulk_g2s_all3_elect(uint32_t dst, const void* src, uint32_t bytes, uint32_t b) {
    asm volatile("{.reg .pred p; elect.sync _|p, 0xffffffff; @p cp.async.bulk.shared::cluster.global.mbarrier::complete_tx::bytes.multicast::cluster [%0],[%1],%2,[%3],%4;}"
                 ::"r"(dst), "l"(src), "r"(bytes), "r"(b), "h"((unsigned short)7) : "memory");
}
DEV void bulk_s2s_elect(uint32_t dst, uint32_t src, uint32_t bytes, uint32_t b) {
    asm volatile("{.reg .pred p; elect.sync _|p, 0xffffffff; @p cp.async.bulk.shared::cluster.shared::cta.mbarrier::complete_tx::bytes [%0],[%1],%2,[%3];}"
                 ::"r"(dst), "r"(src), "r"(bytes), "r"(b) : "memory");
}
DEV void bulk_s2g_elect(void* dst, uint32_t src, uint32_t bytes) {
    asm volatile("{.reg .pred p; elect.sync _|p, 0xffffffff; @p cp.async.bulk.global.shared::cta.bulk_group [%0],[%1],%2;}" ::"l"(dst), "r"(src), "r"(bytes) : "memory");
}
DEV void bulk_s2s(uint32_t dst, uint32_t src, uint32_t bytes, uint32_t b) {
    asm volatile("cp.async.bulk.shared::cluster.shared::cta.mbarrier::complete_tx::bytes [%0],[%1],%2,[%3];" ::"r"(dst), "r"(src), "r"(bytes), "r"(b) : "memory");
}
DEV void bulk_s2g(void* dst, uint32_t src, uint32_t bytes) {
    asm volatile("cp.async.bulk.global.shared::cta.bulk_group [%0],[%1],%2;" ::"l"(dst), "r"(src), "r"(bytes) : "memory");
}
DEV void tma3d(uint32_t dst, const CUtensorMap* m, int c0, int c1, int c2, uint32_t b) {
    asm volatile("cp.async.bulk.tensor.3d.shared::cluster.global.mbarrier::complete_tx::bytes [%0],[%1,{%3,%4,%5}],[%2];"
                 ::"r"(dst), "l"(m), "r"(b), "r"(c0), "r"(c1), "r"(c2) : "memory");
}
DEV void bulk_commit() { asm volatile("cp.async.bulk.commit_group;" ::: "memory"); }
template <int N> DEV void bulk_wait() { asm volatile("cp.async.bulk.wait_group %0;" ::"n"(N) : "memory"); }
template <int N> DEV void bulk_wait_read() { asm volatile("cp.async.bulk.wait_group.read %0;" ::"n"(N) : "memory"); }
DEV void flag_add(uint32_t* p) { asm volatile("red.relaxed.gpu.global.add.u32 [%0],1;" ::"l"(p) : "memory"); }
DEV uint32_t ld_acquire(const uint32_t* p) { uint32_t v; asm volatile("ld.acquire.gpu.global.u32 %0,[%1];" : "=r"(v) : "l"(p) : "memory"); return v; }
DEV void flag_wait(const uint32_t* p, uint32_t n) {
    for (uint32_t it = 0; ld_acquire(p) < n; __nanosleep(40)) if (++it > (SPIN_LIMIT << 3)) die();
}
DEV void cp16(uint32_t dst, const void* src) { asm volatile("cp.async.cg.shared.global [%0],[%1],16;" ::"r"(dst), "l"(src) : "memory"); }
DEV void cp_commit() { asm volatile("cp.async.commit_group;" ::: "memory"); }
template <int N> DEV void cp_wait() { asm volatile("cp.async.wait_group %0;" ::"n"(N) : "memory"); }
DEV uint32_t lds32(uint32_t a) { uint32_t x; asm volatile("ld.shared.u32 %0,[%1];" : "=r"(x) : "r"(a) : "memory"); return x; }
DEV void fence_async() { asm volatile("fence.proxy.async.shared::cta;" ::: "memory"); }
DEV uint32_t pack2(float lo, float hi) { uint32_t r; asm("cvt.rn.bf16x2.f32 %0,%1,%2;" : "=r"(r) : "f"(hi), "f"(lo)); return r; }
DEV uint32_t prmt(uint32_t a, uint32_t b, uint32_t s) { uint32_t r; asm("prmt.b32 %0,%1,%2,%3;" : "=r"(r) : "r"(a), "r"(b), "r"(s)); return r; }
DEV float ex2(float x) { float r; asm("ex2.approx.ftz.f32 %0,%1;" : "=f"(r) : "f"(x)); return r; }
DEV float sqrt_approx(float x) { float r; asm("sqrt.approx.ftz.f32 %0,%1;" : "=f"(r) : "f"(x)); return r; }
DEV float rcp(float x) { float r; asm("rcp.approx.ftz.f32 %0,%1;" : "=f"(r) : "f"(x)); return r; }
DEV void lds128(uint32_t* r, uint32_t a) { asm volatile("ld.shared.v4.u32 {%0,%1,%2,%3},[%4];" : "=r"(r[0]), "=r"(r[1]), "=r"(r[2]), "=r"(r[3]) : "r"(a) : "memory"); }
DEV void lds64(uint32_t* r, uint32_t a) { asm volatile("ld.shared.v2.u32 {%0,%1},[%2];" : "=r"(r[0]), "=r"(r[1]) : "r"(a) : "memory"); }
DEV void lds64f(float& x, float& y, uint32_t a) { asm volatile("ld.shared.v2.f32 {%0,%1},[%2];" : "=f"(x), "=f"(y) : "r"(a) : "memory"); }
DEV void lds128f(float* r, uint32_t a) { asm volatile("ld.shared.v4.f32 {%0,%1,%2,%3},[%4];" : "=f"(r[0]), "=f"(r[1]), "=f"(r[2]), "=f"(r[3]) : "r"(a) : "memory"); }
DEV void sts128(uint32_t a, uint32_t x, uint32_t y, uint32_t z, uint32_t w) { asm volatile("st.shared.v4.u32 [%0],{%1,%2,%3,%4};" ::"r"(a), "r"(x), "r"(y), "r"(z), "r"(w) : "memory"); }
DEV void sts64(uint32_t a, uint32_t x, uint32_t y) { asm volatile("st.shared.v2.u32 [%0],{%1,%2};" ::"r"(a), "r"(x), "r"(y) : "memory"); }
DEV void sts32(uint32_t a, uint32_t x) { asm volatile("st.shared.u32 [%0],%1;" ::"r"(a), "r"(x) : "memory"); }
DEV void ldsm4(uint32_t* r, uint32_t a) { asm volatile("ldmatrix.sync.aligned.m8n8.x4.shared.b16 {%0,%1,%2,%3},[%4];" : "=r"(r[0]), "=r"(r[1]), "=r"(r[2]), "=r"(r[3]) : "r"(a) : "memory"); }
DEV void ldsm4t(uint32_t* r, uint32_t a) { asm volatile("ldmatrix.sync.aligned.m8n8.x4.trans.shared.b16 {%0,%1,%2,%3},[%4];" : "=r"(r[0]), "=r"(r[1]), "=r"(r[2]), "=r"(r[3]) : "r"(a) : "memory"); }
DEV void ldsm2(uint32_t* r, uint32_t a) { asm volatile("ldmatrix.sync.aligned.m8n8.x2.shared.b16 {%0,%1},[%2];" : "=r"(r[0]), "=r"(r[1]) : "r"(a) : "memory"); }
DEV void stsm4t(uint32_t a, uint32_t x, uint32_t y, uint32_t z, uint32_t w) { asm volatile("stmatrix.sync.aligned.m8n8.x4.trans.shared.b16 [%0],{%1,%2,%3,%4};" ::"r"(a), "r"(x), "r"(y), "r"(z), "r"(w) : "memory"); }
DEV void stsm4(uint32_t a, uint32_t x, uint32_t y, uint32_t z, uint32_t w) { asm volatile("stmatrix.sync.aligned.m8n8.x4.shared.b16 [%0],{%1,%2,%3,%4};" ::"r"(a), "r"(x), "r"(y), "r"(z), "r"(w) : "memory"); }
DEV void stsm2(uint32_t a, uint32_t x, uint32_t y) { asm volatile("stmatrix.sync.aligned.m8n8.x2.shared.b16 [%0],{%1,%2};" ::"r"(a), "r"(x), "r"(y) : "memory"); }
DEV void sts128f_if(uint32_t a, const float* v, bool p) {
    asm volatile("{.reg .pred p; setp.ne.u32 p,%5,0; @p st.shared.v4.f32 [%0],{%1,%2,%3,%4};}" ::"r"(a), "f"(v[0]), "f"(v[1]), "f"(v[2]), "f"(v[3]), "r"((uint32_t)p) : "memory");
}
DEV void lds128f_if(float* v, uint32_t a, bool p) {
    asm volatile("{.reg .pred p; setp.ne.u32 p,%5,0; @p ld.shared.v4.f32 {%0,%1,%2,%3},[%4];}"
                 : "+f"(v[0]), "+f"(v[1]), "+f"(v[2]), "+f"(v[3]) : "r"(a), "r"((uint32_t)p) : "memory");
}
DEV void stsm2t_if(uint32_t a, uint32_t x, uint32_t y, bool p) {
    asm volatile("{.reg .pred p; setp.ne.u32 p,%3,0; @p stmatrix.sync.aligned.m8n8.x2.trans.shared.b16 [%0],{%1,%2};}" ::"r"(a), "r"(x), "r"(y), "r"((uint32_t)p) : "memory");
}
DEV void stsm2t(uint32_t a, uint32_t x, uint32_t y) { asm volatile("stmatrix.sync.aligned.m8n8.x2.trans.shared.b16 [%0],{%1,%2};" ::"r"(a), "r"(x), "r"(y) : "memory"); }
DEV void mma16(float* d, uint32_t a0, uint32_t a1, uint32_t a2, uint32_t a3, uint32_t b0, uint32_t b1) {
    asm volatile("mma.sync.aligned.m16n8k16.row.col.f32.bf16.bf16.f32 {%0,%1,%2,%3},{%4,%5,%6,%7},{%8,%9},{%0,%1,%2,%3};"
                 : "+f"(d[0]), "+f"(d[1]), "+f"(d[2]), "+f"(d[3]) : "r"(a0), "r"(a1), "r"(a2), "r"(a3), "r"(b0), "r"(b1));
}
DEV void mma8(float* d, uint32_t a0, uint32_t a1, uint32_t b0) {
    asm volatile("mma.sync.aligned.m16n8k8.row.col.f32.bf16.bf16.f32 {%0,%1,%2,%3},{%4,%5},{%6},{%0,%1,%2,%3};"
                 : "+f"(d[0]), "+f"(d[1]), "+f"(d[2]), "+f"(d[3]) : "r"(a0), "r"(a1), "r"(b0));
}
DEV u64 mkdesc(uint32_t a, uint32_t lbo, uint32_t sbo) { return (u64)((a & 0x3ffff) >> 4) | ((u64)(lbo >> 4) << 16) | ((u64)(sbo >> 4) << 32); }
constexpr u64 SW128 = 1ull << 62;
DEV void wg_fence() { asm volatile("wgmma.fence.sync.aligned;" ::: "memory"); }
DEV void wg_commit() { asm volatile("wgmma.commit_group.sync.aligned;" ::: "memory"); }
template <int N> DEV void wg_wait() { asm volatile("wgmma.wait_group.sync.aligned %0;" ::"n"(N) : "memory"); }
template <int ACC> DEV void wgmma_n32_rs(float* d, const uint32_t* a, u64 desc) {
    asm volatile("wgmma.mma_async.sync.aligned.m64n32k16.f32.bf16.bf16 {%0,%1,%2,%3,%4,%5,%6,%7,%8,%9,%10,%11,%12,%13,%14,%15},{%16,%17,%18,%19},%20,%21,1,1,0;"
                 : "+f"(d[0]), "+f"(d[1]), "+f"(d[2]), "+f"(d[3]), "+f"(d[4]), "+f"(d[5]), "+f"(d[6]), "+f"(d[7]),
                   "+f"(d[8]), "+f"(d[9]), "+f"(d[10]), "+f"(d[11]), "+f"(d[12]), "+f"(d[13]), "+f"(d[14]), "+f"(d[15])
                 : "r"(a[0]), "r"(a[1]), "r"(a[2]), "r"(a[3]), "l"(desc), "n"(ACC));
}
template <int ACC> DEV void wgmma_n32_ss(float* d, u64 da, u64 desc) {
    asm volatile("wgmma.mma_async.sync.aligned.m64n32k16.f32.bf16.bf16 {%0,%1,%2,%3,%4,%5,%6,%7,%8,%9,%10,%11,%12,%13,%14,%15},%16,%17,%18,1,1,1,0;"
                 : "+f"(d[0]), "+f"(d[1]), "+f"(d[2]), "+f"(d[3]), "+f"(d[4]), "+f"(d[5]), "+f"(d[6]), "+f"(d[7]),
                   "+f"(d[8]), "+f"(d[9]), "+f"(d[10]), "+f"(d[11]), "+f"(d[12]), "+f"(d[13]), "+f"(d[14]), "+f"(d[15])
                 : "l"(da), "l"(desc), "n"(ACC));
}
template <int ACC> DEV void wgmma_n16_ss(float* d, u64 da, u64 desc) {
    asm volatile("wgmma.mma_async.sync.aligned.m64n16k16.f32.bf16.bf16 {%0,%1,%2,%3,%4,%5,%6,%7},%8,%9,%10,1,1,0,0;"
                 : "+f"(d[0]), "+f"(d[1]), "+f"(d[2]), "+f"(d[3]), "+f"(d[4]), "+f"(d[5]), "+f"(d[6]), "+f"(d[7])
                 : "l"(da), "l"(desc), "n"(ACC));
}
#define ACC8(o) "+f"(d[o]), "+f"(d[o + 1]), "+f"(d[o + 2]), "+f"(d[o + 3]), "+f"(d[o + 4]), "+f"(d[o + 5]), "+f"(d[o + 6]), "+f"(d[o + 7])
template <int ACC, int TB> DEV void wgmma_n64_rs(float* d, const uint32_t* a, u64 desc) {
    asm volatile("wgmma.mma_async.sync.aligned.m64n64k16.f32.bf16.bf16 {%0,%1,%2,%3,%4,%5,%6,%7,%8,%9,%10,%11,%12,%13,%14,%15,"
                 "%16,%17,%18,%19,%20,%21,%22,%23,%24,%25,%26,%27,%28,%29,%30,%31},{%32,%33,%34,%35},%36,%37,1,1,%38;"
                 : ACC8(0), ACC8(8), ACC8(16), ACC8(24) : "r"(a[0]), "r"(a[1]), "r"(a[2]), "r"(a[3]), "l"(desc), "n"(ACC), "n"(TB));
}
template <int ACC, int TB> DEV void wgmma_n80_rs(float* d, const uint32_t* a, u64 desc) {
    asm volatile("wgmma.mma_async.sync.aligned.m64n80k16.f32.bf16.bf16 {%0,%1,%2,%3,%4,%5,%6,%7,%8,%9,%10,%11,%12,%13,%14,%15,"
                 "%16,%17,%18,%19,%20,%21,%22,%23,%24,%25,%26,%27,%28,%29,%30,%31,%32,%33,%34,%35,%36,%37,%38,%39},{%40,%41,%42,%43},%44,%45,1,1,%46;"
                 : ACC8(0), ACC8(8), ACC8(16), ACC8(24), ACC8(32) : "r"(a[0]), "r"(a[1]), "r"(a[2]), "r"(a[3]), "l"(desc), "n"(ACC), "n"(TB));
}
template <int TA, int TB> DEV void wgmma_n64_ss(float* d, u64 da, u64 db, int acc) {
    asm volatile("{.reg .pred p; setp.ne.b32 p,%34,0; wgmma.mma_async.sync.aligned.m64n64k16.f32.bf16.bf16 {%0,%1,%2,%3,%4,%5,%6,%7,%8,%9,%10,%11,%12,%13,%14,%15,%16,%17,%18,%19,%20,%21,%22,%23,%24,%25,%26,%27,%28,%29,%30,%31},%32,%33,p,1,1,%35,%36;}"
                 : ACC8(0), ACC8(8), ACC8(16), ACC8(24) : "l"(da), "l"(db), "r"(acc), "n"(TA), "n"(TB));
}
template <int TA, int TB> DEV void wgmma_n128_ss(float* d, u64 da, u64 db, int acc) {
    asm volatile("{.reg .pred p; setp.ne.b32 p,%66,0; wgmma.mma_async.sync.aligned.m64n128k16.f32.bf16.bf16 {%0,%1,%2,%3,%4,%5,%6,%7,%8,%9,%10,%11,%12,%13,%14,%15,%16,%17,%18,%19,%20,%21,%22,%23,%24,%25,%26,%27,%28,%29,%30,%31,%32,%33,%34,%35,%36,%37,%38,%39,%40,%41,%42,%43,%44,%45,%46,%47,%48,%49,%50,%51,%52,%53,%54,%55,%56,%57,%58,%59,%60,%61,%62,%63},%64,%65,p,1,1,%67,%68;}"
                 : ACC8(0), ACC8(8), ACC8(16), ACC8(24), ACC8(32), ACC8(40), ACC8(48), ACC8(56) : "l"(da), "l"(db), "r"(acc), "n"(TA), "n"(TB));
}
template <int TA, int TB> DEV void wgmma_n192_ss(float* d, u64 da, u64 db, int acc) {
    asm volatile("{.reg .pred p; setp.ne.b32 p,%98,0; wgmma.mma_async.sync.aligned.m64n192k16.f32.bf16.bf16 {%0,%1,%2,%3,%4,%5,%6,%7,%8,%9,%10,%11,%12,%13,%14,%15,%16,%17,%18,%19,%20,%21,%22,%23,%24,%25,%26,%27,%28,%29,%30,%31,%32,%33,%34,%35,%36,%37,%38,%39,%40,%41,%42,%43,%44,%45,%46,%47,%48,%49,%50,%51,%52,%53,%54,%55,%56,%57,%58,%59,%60,%61,%62,%63,%64,%65,%66,%67,%68,%69,%70,%71,%72,%73,%74,%75,%76,%77,%78,%79,%80,%81,%82,%83,%84,%85,%86,%87,%88,%89,%90,%91,%92,%93,%94,%95},%96,%97,p,1,1,%99,%100;}"
                 : ACC8(0), ACC8(8), ACC8(16), ACC8(24), ACC8(32), ACC8(40), ACC8(48), ACC8(56), ACC8(64), ACC8(72), ACC8(80), ACC8(88) : "l"(da), "l"(db), "r"(acc), "n"(TA), "n"(TB));
}
template <int ACC> DEV void wgmma_n40_ss(float* d, u64 da, u64 desc) {
    asm volatile("wgmma.mma_async.sync.aligned.m64n40k16.f32.bf16.bf16 {%0,%1,%2,%3,%4,%5,%6,%7,%8,%9,%10,%11,%12,%13,%14,%15,%16,%17,%18,%19},%20,%21,%22,1,1,0,0;"
                 : ACC8(0), ACC8(8), "+f"(d[16]), "+f"(d[17]), "+f"(d[18]), "+f"(d[19]) : "l"(da), "l"(desc), "n"(ACC));
}
DEV void pdl_wait() { asm volatile("griddepcontrol.wait;" ::: "memory"); }
DEV void pdl_launch() { asm volatile("griddepcontrol.launch_dependents;" ::: "memory"); }
DEV uint32_t ldg32(const void* p) { uint32_t v; asm volatile("ld.global.nc.u32 %0,[%1];" : "=r"(v) : "l"(p)); return v; }
DEV void ld_acc(u64& a, u64& b, const void* p) {
    const uint32_t done = (uint32_t)a & (uint32_t)b & 32u;
    asm volatile("{.reg .pred p; setp.eq.u32 p,%3,0;\n"
                 "@p ld.relaxed.gpu.global.v2.u64 {%0,%1},[%2];}" : "+l"(a), "+l"(b) : "l"(p), "r"(done) : "memory");
}
DEV void ld_acc0(u64& a, u64& b, const void* p) {
    asm volatile("ld.relaxed.gpu.global.v2.u64 {%0,%1},[%2];" : "=l"(a), "=l"(b) : "l"(p) : "memory");
}
DEV uint32_t and3(uint32_t a, uint32_t b, uint32_t c) { uint32_t r; asm volatile("lop3.b32 %0,%1,%2,%3,0x80;" : "=r"(r) : "r"(a), "r"(b), "r"(c)); return r; }
DEV uint32_t absmax2(uint32_t a, uint32_t b) { uint32_t r; asm("max.xorsign.abs.bf16x2 %0,%1,%2;" : "=r"(r) : "r"(a), "r"(b)); return r; }
DEV float lds32f(uint32_t a) { float x; asm volatile("ld.shared.f32 %0,[%1];" : "=f"(x) : "r"(a) : "memory"); return x; }
DEV void red_add64(u64* p, uint32_t lo, uint32_t hi) {
    asm volatile("{.reg .b64 v; mov.b64 v,{%1,%2}; red.relaxed.gpu.global.add.u64 [%0],v;}" ::"l"(p), "r"(lo), "r"(hi) : "memory");
}
DEV float bf_round(float x) { return __bfloat162float(__float2bfloat16_rn(x)); }
DEV float bf_lo(uint32_t u) { return __uint_as_float(u << 16); }
DEV float bf_hi(uint32_t u) { return __uint_as_float(u & 0xffff0000u); }

#define GPROF(i, n)
#define PROFT(i)
#define STAMP(i)

DEV void unpack8(float* v, uint4 u) {
    v[0] = bf_lo(u.x); v[1] = bf_hi(u.x); v[2] = bf_lo(u.y); v[3] = bf_hi(u.y);
    v[4] = bf_lo(u.z); v[5] = bf_hi(u.z); v[6] = bf_lo(u.w); v[7] = bf_hi(u.w);
}
DEV int xn_off(int row, int chunk) { return (row >> 5) * 40960 + (chunk >> 3) * 4096 + (row & 31) * 128 + (((chunk ^ row) & 7) << 4); }

DEV void ln_row(float (&v)[3][8], int lane) {
    float s = 0.f;
#pragma unroll
    for (int c = 0; c < 3; c++)
#pragma unroll
        for (int j = 0; j < 8; j++) s += v[c][j];
#pragma unroll
    for (int o = 16; o; o >>= 1) s += __shfl_xor_sync(~0u, s, o);
    float mean = s * (1.f / D_), q = 0.f;
#pragma unroll
    for (int c = 0; c < 3; c++)
        if (c < 2 || lane < 16)
#pragma unroll
            for (int j = 0; j < 8; j++) { float d = v[c][j] - mean; q += d * d; }
#pragma unroll
    for (int o = 16; o; o >>= 1) q += __shfl_xor_sync(~0u, q, o);
    float mb = bf_round(mean);
    float inv = 1.f / bf_round(sqrtf(bf_round(bf_round(q * (1.f / D_)) + 1e-5f)));
#pragma unroll
    for (int c = 0; c < 3; c++)
#pragma unroll
        for (int j = 0; j < 8; j++) v[c][j] = bf_round(v[c][j] - mb) * inv;
}

__host__ __device__ constexpr int col_freq(int c) {
    return c == 320 ? 320 : c < 192 ? (c >> 6) * 128 + (c & 63) : c == 192 ? 192 : c < 256 ? 448 - c : c == 256 ? 64 : 384 - c;
}
DEV float rdft(int n, int k, int sn, int N) {
    float s, c;
    sincospif((float)((n * k) & (N - 1)) * (2.f / N), &s, &c);
    return !sn ? c : k ? s : (n & 1 ? -1.f : 1.f);
}

__global__ void __launch_bounds__(512) prep_kernel(const bf16* __restrict__ x, const bf16* __restrict__ Wv, const bf16* __restrict__ Wo) {
    __shared__ float red[32], col[4][640];
    const int tid = threadIdx.x, lane = tid & 31, warp = tid >> 5, b = blockIdx.x, row = b * 16 + warp;
    TLS(0);
    pdl_launch();
    uint4 ux[3], uv[5], uo[8];
#pragma unroll
    for (int c = 0; c < 3; c++) ux[c] = c < 2 || lane < 16 ? *(const uint4*)(x + row * D_ + (c * 32 + lane) * 8) : make_uint4(0, 0, 0, 0);
#pragma unroll
    for (int i = 0; i < 5; i++) uv[i] = *(const uint4*)(Wv + (size_t)((b & 3) * 160 + i * 32 + (tid >> 4)) * 4096 + (b >> 2) * E_ + (tid & 15) * 8);
    if (tid < 320) {
#pragma unroll
        for (int r = 0; r < 8; r++) uo[r] = *(const uint4*)(Wo + (size_t)(b * 32 + tid / 80 * 8 + r) * D_ + tid % 80 * 8);
    }
    if (b < 3) ((uint4*)g_sync)[b * 512 + tid] = make_uint4(0, 0, 0, 0);
    for (int i = b * 512 + tid; i < ACC_LAYER; i += 128 * 512) ((uint4*)g_acc)[i] = make_uint4(0, 0, 0, 0);
    if (tid < 2 * YT_ROWS * D_ / 4 / 128) ((uint4*)g_yt)[b * (2 * YT_ROWS * D_ / 4 / 128) + tid] = make_uint4(0, 0, 0, 0);
    const int gid = tid < 104 ? b * 104 + tid : 1 << 20;
    if (gid < 4096) {
        const int inv = gid >> 11, ks = (gid >> 8) & 7, t = gid & 255, g = (t & 31) >> 2, q = t & 3, tile = t >> 5;
        uint32_t v[4];
#pragma unroll
        for (int j = 0; j < 4; j++) {
            float x[2];
#pragma unroll
            for (int u = 0; u < 2; u++) {
                const int m = inv ? 16 * tile + 2 * g + (j & 1) : 16 * ks + 8 * (j >> 1) + 2 * q + u;
                const int k2 = inv ? 8 * ks + 2 * q + u : 8 * tile + g, sn = inv ? j >> 1 : j & 1;
                x[u] = rdft(m, k2, sn, 128);
                if (sn && k2) x[u] = -x[u];
            }
            v[j] = pack2(x[0], x[1]);
        }
        g_f128[gid] = make_uint4(v[0], v[1], v[2], v[3]);
    } else if (gid < 5120) {
        const int id = gid - 4096, inv = id >> 9, ks = (id >> 7) & 3, t = id & 127, g = (t & 31) >> 2, q = t & 3, tile = t >> 5;
        uint32_t v[4];
#pragma unroll
        for (int j = 0; j < 4; j++) {
            float x[2];
#pragma unroll
            for (int u = 0; u < 2; u++) {
                const int a = inv ? 16 * tile + g + 8 * (j & 1) : 16 * ks + 8 * (j >> 1) + 2 * q + u;
                const int ka = inv ? 8 * ks + 2 * q + u : 8 * tile + g, sn = inv ? j >> 1 : j & 1;
                x[u] = rdft(a, ka, sn, 64);
            }
            v[j] = pack2(x[0], x[1]);
        }
        g_f64[id] = make_uint4(v[0], v[1], v[2], v[3]);
    } else if (gid < 5120 + 8192) {
        const int id = gid - 5120, inv = id >> 12, n = ((id >> 9) & 7) * 8 + ((id >> 3) & 7), k = ((id >> 6) & 7) * 8 + (id & 7);
        float s, c;
        sincospif((float)(((n >> 1) * (k >> 1)) & 31) * (1.f / 16), &s, &c);
        if (inv) s = -s;
        g_g32[id] = __float2bfloat16_rn((n & 1) == (k & 1) ? c : (k & 1) ? s : -s);
    }
    {
        float v[3][8];
#pragma unroll
        for (int c = 0; c < 3; c++) unpack8(v[c], ux[c]);
        ln_row(v, lane);
#pragma unroll
        for (int c = 0; c < 3; c++)
            if (c < 2 || lane < 16)
                *(uint4*)(g_xn + xn_off(row, c * 32 + lane)) =
                    make_uint4(pack2(v[c][0], v[c][1]), pack2(v[c][2], v[c][3]), pack2(v[c][4], v[c][5]), pack2(v[c][6], v[c][7]));
    }
    float sv = 0.f;
#pragma unroll
    for (int i = 0; i < 5; i++) {
        float w[8];
        unpack8(w, uv[i]);
#pragma unroll
        for (int j = 0; j < 8; j++) sv += w[j] * w[j];
    }
    if (tid < 320) {
        float a[8] = {0.f, 0.f, 0.f, 0.f, 0.f, 0.f, 0.f, 0.f};
#pragma unroll
        for (int r = 0; r < 8; r++) {
            float w[8];
            unpack8(w, uo[r]);
#pragma unroll
            for (int j = 0; j < 8; j++) a[j] += w[j] * w[j];
        }
#pragma unroll
        for (int j = 0; j < 8; j++) col[tid / 80][tid % 80 * 8 + j] = a[j];
    }
    __syncthreads();
    float so = (col[0][tid] + col[1][tid]) + (col[2][tid] + col[3][tid]);
    if (tid < 128) so = fmaxf(so, (col[0][512 + tid] + col[1][512 + tid]) + (col[2][512 + tid] + col[3][512 + tid]));
#pragma unroll
    for (int o = 16; o; o >>= 1) { sv += __shfl_xor_sync(~0u, sv, o); so = fmaxf(so, __shfl_xor_sync(~0u, so, o)); }
    if (lane == 0) { red[warp] = sv; red[16 + warp] = so; }
    __syncthreads();
    if (tid == 0) {
        float a = 0.f, c = 0.f;
        for (int i = 0; i < 16; i++) { a += red[i]; c = fmaxf(c, red[16 + i]); }
        g_nrm[b] = a; g_nrm[128 + b] = c;
    }
    TLE(0);
}

constexpr int FT_BYTES = 64 * NCOL * 2;
DEV uint32_t lds16(uint32_t a) { unsigned short x; asm volatile("ld.shared.u16 %0,[%1];" : "=h"(x) : "r"(a) : "memory"); return x; }
DEV void filter_tile(uint32_t sr, uint32_t si, int kb, int warp, int lane) {
#pragma unroll 3
    for (int c = warp; c < NCOL; c += 12) {
        const uint32_t o = lane * (4 * NCOL) + col_freq(c) * 2;
        *(uint2*)(g_wt + c * 8192 + kb * 256 + ((lane ^ ((kb & 3) << 2)) << 3)) =
            make_uint2(lds16(sr + o) | (lds16(si + o) << 16), lds16(sr + o + 2 * NCOL) | (lds16(si + o + 2 * NCOL) << 16));
    }
}

namespace wk {
constexpr int STAGE = 49152, NST = 4, OFF_OUT = 3 * STAGE, OFF_RED = 4 * STAGE, OFF_BAR = OFF_RED + 32768, SMEM = OFF_BAR + 128;
constexpr int NPB = 11;
__host__ __device__ constexpr int pb_start(int b) { return b == 0 ? 2 : b < NPB ? 6 * b : 64; }
#define NOB 7
#define SPLIT_Z 2
#define SPLIT_A 3
#define SPLIT_B 9
constexpr int N_P = NPB * H_, I_F = N_P, I_OB = I_F + 32, I_OT = I_OB + NOB * 5, I_SZ = I_OT + (29 - 3 * NOB) * 10;
constexpr int I_SA = I_SZ + 10 * SPLIT_Z, I_SB = I_SA + 10 * SPLIT_A;
DEV void ot_decode(int id, int& b, int& nt, int& k0, int& k1) {
    const int base = id < I_SZ ? I_OT : id < I_SA ? I_SZ : id < I_SB ? I_SA : I_SB, j = (id - base) / 10;
    const int ns = id < I_SA ? SPLIT_Z : id < I_SB ? SPLIT_A : SPLIT_B;
    nt = (id - base) % 10;
    if (id < I_SZ) { b = 3 * NOB + j; k0 = 0; k1 = 22; }
    else { b = id < I_SA ? 29 : id < I_SB ? 30 : 31; k0 = 22 * j / ns; k1 = 22 * (j + 1) / ns; }
}
enum { SY_TICKET = 0, SY_O = 32, SY_P = 128 };
}
struct Ring {
    int st; uint32_t ph;
    DEV uint32_t par() const { return (ph >> st) & 1; }
    DEV void next(int n) { ph ^= 1u << st; st = st + 1 >= n ? 0 : st + 1; }
};
struct Maps { CUtensorMap wq2, wv1, wo2, wo1, x6, x4, o6, o2; const bf16 *wr, *wi; };

template <int NSG> DEV void proj_tile(uint32_t sb, uint32_t bar, Ring& rg, int wg, int id) {
    using namespace wk;
    float acc[NSG * 16];
#pragma unroll
    for (int i = 0; i < NSG * 16; i++) acc[i] = 0.f;
    const int lane = threadIdx.x & 31, ww = (threadIdx.x >> 5) & 3;
    for (int kb = 0; kb < 10; kb++, rg.next(3)) {
        const int st = rg.st;
        if (kb) mbar_wait(bar + 8 * st, rg.par());
        const u64 da = mkdesc(sb + st * STAGE + wg * 8192, 0, 1024) | SW128, db = mkdesc(sb + st * STAGE + 24576, 0, 1024) | SW128;
        wg_fence();
#pragma unroll
        for (int ks = 0; ks < 4; ks++) {
            if (NSG == 4) wgmma_n128_ss<1, 0>(acc, da + ks * 128, db + ks * 2, 1);
            if (NSG == 6) wgmma_n192_ss<1, 0>(acc, da + ks * 128, db + ks * 2, 1);
        }
        wg_commit();
        wg_wait<0>();
        mbar_arrive_elect(bar + 8 * (NST + st));
    }
    const uint32_t out = sb + OFF_OUT + wg * 24576;
    bar_sync(5 + wg, 160);
    const uint32_t la = out + (wg < 2 ? (lane >> 4) * 1024 + ww * 256 + (lane & 15) * 16 : ww * 1024 + ((lane >> 3) & 1) * 512 + (lane >> 4) * 128 + (lane & 7) * 16);
#pragma unroll
    for (int j = 0; j < 2 * NSG; j++) {
        const float* c = acc + 8 * j;
        const uint32_t p0 = pack2(c[0], c[1]), p1 = pack2(c[2], c[3]), p2 = pack2(c[4], c[5]), p3 = pack2(c[6], c[7]);
        if (wg < 2) stsm4t(la + j * 2048, p0, p1, p2, p3);
        else stsm4(la + (j >> 1) * 4096 + (j & 1) * 256, p0, p1, p2, p3);
    }
    if ((threadIdx.x & 127) == 0) sts32(bar + 80 + 4 * wg, id);
    fence_async();
    bar_arrive(1 + wg, 160);
}

DEV uint32_t resid(uint32_t u, float a, float b) { return pack2(bf_lo(u) + bf_round(a), bf_hi(u) + bf_round(b)); }

template <bool SIDE>
DEV void worker(uint32_t sb, const Maps& maps, const bf16* __restrict__ x, bf16* __restrict__ x1, int layer, int fix, int nfix) {
    using namespace wk;
    const uint32_t bar = sb + OFF_BAR, slot = bar + 64;
    const int tid = threadIdx.x, lane = tid & 31, warp = __shfl_sync(~0u, tid >> 5, 0);
    uint32_t* sy = g_sync + layer * SYNC_LAYER;
    if (tid == 0) {
        for (int i = 0; i < NST; i++) { mbar_init(bar + 8 * i, 1); mbar_init(bar + 8 * (NST + i), 12); }
        asm volatile("fence.mbarrier_init.release.cluster;" ::: "memory");
    }
    __syncthreads();
    if (warp > 12) {
        const int wg = warp - 13;
        bar_arrive(5 + wg, 160);
        for (;;) {
            bar_sync(1 + wg, 160);
            const int id = (int)lds32(bar + 80 + 4 * wg);
            if (id < 0) break;
            const int s0 = pb_start(id >> 5), ns = pb_start((id >> 5) + 1) - s0;
            if (lane == 0) {
                for (int j = 0; j < ns; j++)
                    bulk_s2g(g_p + (size_t)(((s0 + j) * H_ + (id & 31)) * 3 + wg) * 4096, sb + OFF_OUT + wg * 24576 + j * 4096, 4096);
                bulk_commit();
                bulk_wait<0>();
                flag_add(sy + SY_P + id);
            }
            __syncwarp();
            bar_arrive(5 + wg, 160);
        }
    } else if (warp == 12) {
        if (lane == 0) {
            Ring rg = {0, 7u};
            auto acquire = [&]() { mbar_wait(bar + 8 * (NST + rg.st), rg.par()); return sb + rg.st * STAGE; };
            if (fix >= 0 && fix < N_P) {
                for (int kb = 0; kb < 3; kb++) {
                    tma3d(sb + kb * STAGE, &maps.wq2, 0, kb * 64, 2 * (fix & 31), bar + 8 * kb);
                    tma3d(sb + kb * STAGE + 16384, &maps.wv1, 0, kb * 64, 2 * (fix & 31), bar + 8 * kb);
                }
                asm volatile("prefetch.tensormap [%0];" ::"l"(&maps.x4) : "memory");
            }
            if (SIDE) flag_wait(g_started + layer, 1); else pdl_wait();
            for (;;) {
                int id = fix;
                if (id < 0) {
                    id = nfix + (int)atomicAdd(sy + SY_TICKET, 1u);
                    if (layer && id >= I_F) id += I_OB - I_F;
                    if (id >= I_SB) id = -1;
                }
                if (id >= 0) { TLI(id, 0, gtime()); TLI(id, 3, blockIdx.x + (SIDE ? 1000 : 0)); }
                uint32_t d = acquire();
                sts32(slot + 4 * rg.st, id);
                if (id < 0) { mbar_arrive(bar + 8 * rg.st); if (SIDE) pdl_launch(); break; }
                if (id < N_P) {
                    const int b = id >> 5, h = id & 31;
                    const bool six = b && b < NPB - 1;
                    for (int kb = 0; kb < 10; kb++, rg.next(3)) {
                        if (kb) d = acquire();
                        const uint32_t fb = bar + 8 * rg.st;
                        mbar_expect(fb, six ? 49152 : 40960);
                        tma3d(d + 24576, six ? &maps.x6 : &maps.x4, 0, 2 * kb, pb_start(b), fb);
                        if (fix < 0 || kb >= 3) {
                            tma3d(d, &maps.wq2, 0, kb * 64, 2 * h, fb);
                            tma3d(d + 16384, &maps.wv1, 0, kb * 64, 2 * h, fb);
                        }
                    }
                } else if (id < I_OB) {
                    for (int i = 0; i < 2; i++, rg.next(NST)) {
                        if (i) d = acquire();
                        mbar_expect(bar + 8 * rg.st, FT_BYTES);
                        bulk_g2s(d, (const char*)(i ? maps.wi : maps.wr) + (id - I_F) * FT_BYTES, FT_BYTES, bar + 8 * rg.st);
                    }
                } else if (id < I_OT) {
                    const int b = (id - I_OB) / 5, nt = (id - I_OB) % 5;
                    flag_wait(sy + SY_O + 6 * b + 5, 64);
                    for (int kb = 0; kb < 64; kb++, rg.next(NST)) {
                        if (kb) d = acquire();
                        const uint32_t fb = bar + 8 * rg.st;
                        mbar_expect(fb, 40960);
                        tma3d(d, &maps.o6, 0, 2 * kb, 6 * b, fb);
                        tma3d(d + 24576, &maps.wo2, 0, kb * 64, 2 * nt, fb);
                    }
                } else {
                    int b, nt, k0, k1;
                    ot_decode(id, b, nt, k0, k1);
                    const int pre = fix >= 0 ? k1 : k0 + 1;
                    for (int kb = k0; kb < pre; kb++) tma3d(d + (kb - k0) * STAGE + 24576, &maps.wo1, 0, 3 * kb * 64, nt, bar + 8 * (rg.st + kb - k0));
                    flag_wait(sy + SY_O + 2 * b + 1, 64);
                    for (int kb = k0; kb < k1; kb++, rg.next(NST)) {
                        if (kb > k0) d = acquire();
                        const uint32_t fb = bar + 8 * rg.st;
                        mbar_expect(fb, 49152);
                        if (kb >= pre) tma3d(d + 24576, &maps.wo1, 0, 3 * kb * 64, nt, fb);
                        for (int u = 0; u < 3; u++) tma3d(d + u * 8192, &maps.o2, 0, 2 * (3 * kb + u), 2 * b, fb);
                    }
                }
                fix = -1;
            }
        }
    } else {
        const int wg = warp >> 2, g = lane >> 2, q = lane & 3;
        Ring rg = {0, 0u};
        bool stores_done = false;
        for (;;) {
            mbar_wait(bar + 8 * rg.st, rg.par());
            const int id = (int)lds32(slot + 4 * rg.st);
            if ((id < 0 || id >= N_P) && !stores_done) {
                bar_sync(5 + wg, 160);
                if ((tid & 127) == 0) sts32(bar + 80 + 4 * wg, ~0u);
                bar_arrive(1 + wg, 160);
                stores_done = true;
                bar_sync(4, 384);
                mbar_arrive_elect(bar + 8 * (NST + 3));
            }
            if (id < 0) break;
            if (tid == 0) TLI(id, 1, gtime());
            if (id < N_P) {
                const int b = id >> 5;
                if (b == 0 || b == NPB - 1) proj_tile<4>(sb, bar, rg, wg, id);
                else proj_tile<6>(sb, bar, rg, wg, id);
            } else if (id < I_OB) {
                const int s0 = rg.st;
                rg.next(NST);
                mbar_wait(bar + 8 * rg.st, rg.par());
                filter_tile(sb + s0 * STAGE, sb + rg.st * STAGE, id - I_F, warp, lane);
                mbar_arrive_elect(bar + 8 * (NST + s0));
                mbar_arrive_elect(bar + 8 * (NST + rg.st));
                rg.next(NST);
            } else if (id < I_OT) {
                const int b = (id - I_OB) / 5, nt = (id - I_OB) % 5;
                const size_t o = (size_t)(192 * b + 16 * warp + g) * D_ + nt * 128 + 2 * q;
                float acc[64];
#pragma unroll
                for (int i = 0; i < 64; i++) acc[i] = 0.f;
                for (int kb = 0; kb < 64; kb++, rg.next(NST)) {
                    const int st = rg.st;
                    if (kb) mbar_wait(bar + 8 * st, rg.par());
                    const u64 da = mkdesc(sb + st * STAGE + wg * 8192, 128, 1024), db = mkdesc(sb + st * STAGE + 24576, 8192, 1024) | SW128;
                    wg_fence();
#pragma unroll
                    for (int ks = 0; ks < 4; ks++) wgmma_n128_ss<0, 1>(acc, da + ks * 16, db + ks * 128, 1);
                    wg_commit();
                    wg_wait<0>();
                    mbar_arrive_elect(bar + 8 * (NST + st));
                }
                uint32_t xr[32];
#pragma unroll
                for (int t = 0; t < 32; t++) xr[t] = ldg32(x + o + 8 * (t >> 1) + (t & 1) * 8 * D_);
#pragma unroll
                for (int t = 0; t < 32; t++) *(uint32_t*)(x1 + o + 8 * (t >> 1) + (t & 1) * 8 * D_) = resid(xr[t], acc[2 * t], acc[2 * t + 1]);
            } else {
                int b, nt, k0, k1;
                ot_decode(id, b, nt, k0, k1);
                const size_t o = (size_t)(64 * b + 16 * (warp & 3) + g) * D_ + nt * 64 + 2 * q;
                float acc[32];
                uint32_t xr[16];
#pragma unroll
                for (int t = 0; t < 16; t++) xr[t] = wg == 0 && id < I_SZ ? ldg32(x + o + 8 * (t >> 1) + (t & 1) * 8 * D_) : 0;
#pragma unroll
                for (int i = 0; i < 32; i++) acc[i] = 0.f;
                for (int kb = k0; kb < k1; kb++, rg.next(NST)) {
                    const int st = rg.st;
                    if (kb > k0) mbar_wait(bar + 8 * st, rg.par());
                    const u64 da = mkdesc(sb + st * STAGE + wg * 8192, 128, 1024), db = mkdesc(sb + st * STAGE + 24576 + wg * 8192, 0, 1024) | SW128;
                    wg_fence();
#pragma unroll
                    for (int ks = 0; ks < 4; ks++) wgmma_n64_ss<0, 1>(acc, da + ks * 16, db + ks * 128, 1);
                    wg_commit();
                    wg_wait<0>();
                    mbar_arrive_elect(bar + 8 * (NST + st));
                }
                const uint32_t ra = sb + OFF_RED + (tid & 127) * 16;
                if (wg) {
#pragma unroll
                    for (int t = 0; t < 8; t++)
                        sts128(ra + (wg - 1) * 16384 + t * 2048, __float_as_uint(acc[4 * t]), __float_as_uint(acc[4 * t + 1]), __float_as_uint(acc[4 * t + 2]), __float_as_uint(acc[4 * t + 3]));
                }
                bar_sync(4, 384);
                if (wg == 0) {
#pragma unroll
                    for (int t = 0; t < 8; t++) {
                        float u[4], v[4];
                        lds128f(u, ra + t * 2048); lds128f(v, ra + 16384 + t * 2048);
#pragma unroll
                        for (int i = 0; i < 4; i++) acc[4 * t + i] += u[i] + v[i];
                    }
                }
                bar_sync(4, 384);
                if (wg == 0) {
                    if (id < I_SZ) {
#pragma unroll
                        for (int t = 0; t < 16; t++) *(uint32_t*)(x1 + o + 8 * (t >> 1) + (t & 1) * 8 * D_) = resid(xr[t], acc[2 * t], acc[2 * t + 1]);
                    } else {
                        float* y = g_yt + (layer * YT_ROWS - (S_ - YT_ROWS)) * D_ + o;
#pragma unroll
                        for (int t = 0; t < 16; t++)
                            asm volatile("red.relaxed.gpu.global.add.v2.f32 [%0],{%1,%2};" ::"l"(y + 8 * (t >> 1) + (t & 1) * 8 * D_), "f"(acc[2 * t]), "f"(acc[2 * t + 1]) : "memory");
                    }
                }
            }
            if (tid == 0) TLI(id, 2, gtime());
        }
    }
}

__global__ void __launch_bounds__(512, 1) side_kernel(const __grid_constant__ Maps maps, const bf16* __restrict__ x, bf16* __restrict__ x1, int layer, int nfix) {
    extern __shared__ __align__(1024) unsigned char smem[];
    TLS(3 + 5 * layer);
    worker<true>(s2u(smem), maps, x, x1, layer, -1, nfix);
    __syncwarp();
    if (blockIdx.x == 0) pdl_wait();
    TLE(3 + 5 * layer);
}

constexpr float C5A = 0.30901699437494742f, C5B = -0.80901699437494742f, S5A = 0.95105651629515357f, S5B = 0.58778525229247313f;
template <int SGN> DEV void dft5(const float (&tr)[5], const float (&ti)[5], float (&zr)[5], float (&zi)[5]) {
    const float ar = tr[1] + tr[4], ai = ti[1] + ti[4], br = tr[2] + tr[3], bi = ti[2] + ti[3];
    const float cr = tr[1] - tr[4], ci = ti[1] - ti[4], dr = tr[2] - tr[3], di = ti[2] - ti[3];
    zr[0] = tr[0] + ar + br; zi[0] = ti[0] + ai + bi;
    const float m1r = tr[0] + C5A * ar + C5B * br, m1i = ti[0] + C5A * ai + C5B * bi;
    const float m2r = tr[0] + C5B * ar + C5A * br, m2i = ti[0] + C5B * ai + C5A * bi;
    const float n1r = SGN * (S5A * cr + S5B * dr), n1i = SGN * (S5A * ci + S5B * di);
    const float n2r = SGN * (S5B * cr - S5A * dr), n2i = SGN * (S5B * ci - S5A * di);
    zr[1] = m1r + n1i; zi[1] = m1i - n1r; zr[4] = m1r - n1i; zi[4] = m1i + n1r;
    zr[2] = m2r + n2i; zi[2] = m2i - n2r; zr[3] = m2r - n2i; zi[3] = m2i + n2r;
}
DEV void ln40(float (&v)[40]) {
    float s = 0.f;
#pragma unroll
    for (int i = 0; i < 40; i++) s += v[i];
#pragma unroll
    for (int o = 8; o; o >>= 1) s += __shfl_xor_sync(~0u, s, o);
    const float mean = s * (1.f / D_);
    float q = 0.f;
#pragma unroll
    for (int i = 0; i < 40; i++) { const float d = v[i] - mean; q += d * d; }
#pragma unroll
    for (int o = 8; o; o >>= 1) q += __shfl_xor_sync(~0u, q, o);
    const float mb = bf_round(mean);
    const float inv = 1.f / bf_round(sqrtf(bf_round(bf_round(q * (1.f / D_)) + 1e-5f)));
#pragma unroll
    for (int i = 0; i < 40; i++) v[i] = bf_round(v[i] - mb) * inv;
}
__global__ void __maxnreg__(120) rowfft_kernel(const bf16* __restrict__ x0, bf16* __restrict__ x, int layer) {
    extern __shared__ __align__(1024) unsigned char smem[];
    const uint32_t sb = s2u(smem), sx = sb + 23552, sy = sx + 20480, bar = sy + 40960;
    const int tid = threadIdx.x, lane = tid & 31, q = lane & 3, blk = 127 - blockIdx.x, k2 = tid >> 2;
    if (tid == 0) TLI(800 + blk, 0, gtime());
    float twr[5], twi[5];
#pragma unroll
    for (int r = 1; r < 5; r++) { sincospif((float)(r * k2) * (-1.f / 320), &twi[r], &twr[r]); }
    uint32_t f[8][4];
#pragma unroll
    for (int ks = 0; ks < 8; ks++) { const uint4 u = g_f128[ks * 256 + tid]; f[ks][0] = u.x; f[ks][1] = u.y; f[ks][2] = u.z; f[ks][3] = u.w; }
    const bool split = blk * 16 >= S_ - YT_ROWS;
    if (tid == 0) {
        mbar_init(bar, 1);
        asm volatile("fence.mbarrier_init.release.cluster;" ::: "memory");
        mbar_expect(bar, split ? 61440 : 20480);
        if (split) bulk_g2s(sx, x0 + (size_t)blk * 16 * D_, 20480, bar);
    }
    __syncthreads();
    pdl_wait();
    pdl_launch();
    TLS(4 + 5 * layer);
    if (tid == 0) TLI(800 + blk, 1, gtime());
    if (tid == 0 && blk == 0) g_started[layer] = 0;
    if (tid == 0) {
        if (split) bulk_g2s(sy, g_yt + (layer * YT_ROWS + blk * 16 - (S_ - YT_ROWS)) * D_, 40960, bar);
        else bulk_g2s(sx, x + (size_t)blk * 16 * D_, 20480, bar);
    }
    mbar_wait(bar, 0);
    {
        const int rho = tid >> 4, j = tid & 15;
        float v[40];
#pragma unroll
        for (int i = 0; i < 5; i++) {
            uint32_t u[4];
            lds128(u, sx + tid * 80 + i * 16);
            if (split) {
                float p[8];
                lds128f(p, sy + tid * 160 + i * 32); lds128f(p + 4, sy + tid * 160 + i * 32 + 16);
#pragma unroll
                for (int k = 0; k < 4; k++) u[k] = resid(u[k], p[2 * k], p[2 * k + 1]);
                sts128(sx + tid * 80 + i * 16, u[0], u[1], u[2], u[3]);
            }
            unpack8(v + 8 * i, make_uint4(u[0], u[1], u[2], u[3]));
        }
        ln40(v);
        const uint32_t a = sb + ((rho >> 1) & 1) * 2304 + j * 144 + (2 * (rho >> 2) + (rho & 1)) * 16;
#pragma unroll
        for (int r = 0; r < 5; r++)
            sts128(a + r * 4608, pack2(v[r], v[5 + r]), pack2(v[10 + r], v[15 + r]), pack2(v[20 + r], v[25 + r]), pack2(v[30 + r], v[35 + r]));
    }
    fence_async();
    __syncthreads();
    if (tid == 0) TLI(800 + blk, 2, gtime());
    if (tid == 0 && split) { bulk_s2g(x + (size_t)blk * 16 * D_, sx, 20480); bulk_commit(); }
    float acc[40];
    const u64 db = mkdesc(sb, 144, 2304);
    wg_fence();
    wgmma_n80_rs<0, 0>(acc, f[0], db);
#pragma unroll
    for (int ks = 1; ks < 8; ks++) wgmma_n80_rs<1, 0>(acc, f[ks], db + ks * 18);
    wg_commit();
    wg_wait<0>();
    unsigned char* zp = g_z + (blk >> 1) * 128 + ((((blk & 1) * 4 + q) ^ ((blk >> 1) & 7)) << 4);
    uint32_t o[5][4];
#pragma unroll
    for (int u = 0; u < 4; u++) {
        float tr[5], ti[5], zr[5], zi[5];
#pragma unroll
        for (int r = 0; r < 5; r++) {
            const float yr = acc[8 * r + 4 * (u >> 1) + (u & 1)], yi = k2 ? acc[8 * r + 4 * (u >> 1) + 2 + (u & 1)] : 0.f;
            tr[r] = r ? yr * twr[r] - yi * twi[r] : yr;
            ti[r] = r ? yr * twi[r] + yi * twr[r] : yi;
        }
        dft5<1>(tr, ti, zr, zi);
#pragma unroll
        for (int j = 0; j < 5; j++) o[j][u] = pack2(zr[j], j < 3 ? zi[j] : -zi[j]);
    }
#pragma unroll
    for (int j = 0; j < 5; j++)
        if (j < 3 || k2) *(uint4*)(zp + (64 * j + k2) * 8192) = make_uint4(o[j][0], o[j][1], o[j][2], o[j][3]);
    if (k2 == 0) {
#pragma unroll
        for (int u = 0; u < 4; u++) {
            float tr[5], ti[5], zr[5], zi[5];
            const float cr[5] = {1.f, -C5B, C5A, -C5A, C5B}, ci[5] = {0.f, -S5B, -S5A, -S5A, -S5B};
#pragma unroll
            for (int r = 0; r < 5; r++) { const float y = acc[8 * r + 4 * (u >> 1) + 2 + (u & 1)]; tr[r] = y * cr[r]; ti[r] = y * ci[r]; }
            dft5<1>(tr, ti, zr, zi);
            o[0][u] = pack2(zr[0], zi[0]); o[1][u] = pack2(zr[1], zi[1]); o[2][u] = pack2(zr[2], 0.f);
        }
        *(uint4*)(zp + 256 * 8192) = make_uint4(o[0][0], o[0][1], o[0][2], o[0][3]);
        *(uint4*)(zp + 192 * 8192) = make_uint4(o[1][0], o[1][1], o[1][2], o[1][3]);
        *(uint4*)(zp + 320 * 8192) = make_uint4(o[2][0], o[2][1], o[2][2], o[2][3]);
    }
    if (tid == 0) bulk_wait_read<0>();
    TLE(4 + 5 * layer);
    if (tid == 0) TLI(800 + blk, 3, gtime());
}

constexpr int CF_SMEM = 16384 + 8192 + 3 * 24576 + 64;
__global__ void __maxnreg__(88) colfft_kernel(int layer) {
    extern __shared__ __align__(1024) unsigned char smem[];
    const uint32_t sb = s2u(smem), bar = sb + 98304;
    const int tid = threadIdx.x, lane = tid & 31, q = lane & 3, wg = __shfl_sync(~0u, tid >> 7, 0), t = tid & 127, ka = t >> 2;
    asm volatile("setmaxnreg.inc.sync.aligned.u32 88;");
    const int col = blockIdx.x * 3 + wg;
    const uint32_t d0 = sb + 24576 + wg * 24576, d1 = d0 + 8192;
    if (tid == 0) {
        for (int i = 0; i < 4; i++) mbar_init(bar + 8 * i, 1);
        asm volatile("fence.mbarrier_init.release.cluster;" ::: "memory");
        mbar_expect(bar + 24, 49152);
        for (int i = 0; i < 3; i++) bulk_g2s(d0 + i * 24576 + 16384, g_wt + (col + i) * 8192, 8192, bar + 24);
        bulk_g2s(sb, g_g32, 16384, bar + 24);
        bulk_g2s(sb + 16384, g_f64 + 512, 8192, bar + 24);
    }
    uint32_t a[4][4];
#pragma unroll
    for (int ks = 0; ks < 4; ks++) { const uint4 u = g_f64[ks * 128 + t]; a[ks][0] = u.x; a[ks][1] = u.y; a[ks][2] = u.z; a[ks][3] = u.w; }
    float twr[8], twi[8];
#pragma unroll
    for (int i = 0; i < 8; i++) sincospif((float)((4 * i + q) * (ka ? ka : -32)) * (1.f / 1024), &twi[i], &twr[i]);
    __syncthreads();
    pdl_wait();
    pdl_launch();
    TLS(5 + 5 * layer);
    if (t == 0) {
        mbar_expect(bar + 8 * wg, 8192);
        bulk_g2s(d0, g_z + col * 8192, 8192, bar + 8 * wg);
    }
    float acc[32];
    mbar_wait(bar + 8 * wg, 0);
    {
        const u64 db = mkdesc(d0, 0, 1024) | SW128;
        wg_fence();
        wgmma_n64_rs<0, 1>(acc, a[0], db);
#pragma unroll
        for (int ks = 1; ks < 4; ks++) wgmma_n64_rs<1, 1>(acc, a[ks], db + ks * 128);
        wg_commit();
        wg_wait<0>();
    }
#pragma unroll
    for (int i = 0; i < 8; i++) {
        const float c0 = acc[4 * i], c1 = acc[4 * i + 1], c2 = acc[4 * i + 2], c3 = acc[4 * i + 3];
        const float pr = c0 + c3, pi = c1 - c2, nr = ka ? c0 - c3 : c2, ni = ka ? c1 + c2 : c3;
        a[i >> 1][2 * (i & 1)] = ka ? pack2(pr * twr[i] + pi * twi[i], pi * twr[i] - pr * twi[i]) : pack2(c0, c1);
        a[i >> 1][2 * (i & 1) + 1] = pack2(nr * twr[i] - ni * twi[i], ni * twr[i] + nr * twi[i]);
    }
    mbar_wait(bar + 24, 0);
    {
        const u64 db = mkdesc(sb, 128, 1024);
        wg_fence();
        wgmma_n64_rs<0, 0>(acc, a[0], db);
#pragma unroll
        for (int ks = 1; ks < 4; ks++) wgmma_n64_rs<1, 0>(acc, a[ks], db + ks * 16);
        wg_commit();
        wg_wait<0>();
    }
    constexpr float NORM = 1.f / (2048.f * 640.f);
#pragma unroll
    for (int i = 0; i < 16; i++) {
        const int k = ((i & 1 ? (ka ? -ka : 32) : ka) + 64 * q + 256 * (i >> 1)) & 2047;
        a[i >> 2][i & 3] = lds32(d0 + 16384 + 4 * (k ^ ((k >> 3) & 24)));
    }
#pragma unroll
    for (int i = 0; i < 16; i++) {
        const float zr = acc[2 * i] * NORM, zi = acc[2 * i + 1] * NORM, wr = bf_lo(a[i >> 2][i & 3]), wi = bf_hi(a[i >> 2][i & 3]);
        a[i >> 2][i & 3] = pack2(zr * wr - zi * wi, zr * wi + zi * wr);
    }
    {
        const u64 db = mkdesc(sb + 8192, 128, 1024);
        wg_fence();
        wgmma_n64_rs<0, 0>(acc, a[0], db);
#pragma unroll
        for (int ks = 1; ks < 4; ks++) wgmma_n64_rs<1, 0>(acc, a[ks], db + ks * 16);
        wg_commit();
        wg_wait<0>();
    }
    const uint32_t row = (t >> 5) * 2048 + (lane & 15) * 128;
#pragma unroll
    for (int i = 0; i < 8; i++) {
        const float c0 = acc[4 * i], c1 = acc[4 * i + 1], c2 = acc[4 * i + 2], c3 = acc[4 * i + 3];
        const float pr = c0 * twr[i] - c1 * twi[i], pi = c1 * twr[i] + c0 * twi[i];
        const float nr = c2 * twr[i] + c3 * twi[i], ni = c3 * twr[i] - c2 * twi[i];
        a[i >> 1][2 * (i & 1)] = ka ? pack2(pr + nr, pi + ni) : pack2(c0, c1);
        a[i >> 1][2 * (i & 1) + 1] = ka ? pack2(ni - pi, pr - nr) : pack2(nr, ni);
    }
#pragma unroll
    for (int i = 0; i < 4; i++) stsm4(d1 + row + (((2 * i + (lane >> 4)) ^ (lane & 7)) << 4), a[i][0], a[i][1], a[i][2], a[i][3]);
#pragma unroll
    for (int i = 0; i < 4; i++) lds128(a[i], sb + 16384 + i * 2048 + t * 16);
    fence_async();
    bar_sync(1 + wg, 128);
    {
        const u64 db = mkdesc(d1, 0, 1024) | SW128;
        wg_fence();
        wgmma_n64_rs<0, 1>(acc, a[0], db);
#pragma unroll
        for (int ks = 1; ks < 4; ks++) wgmma_n64_rs<1, 1>(acc, a[ks], db + ks * 128);
        wg_commit();
        wg_wait<0>();
    }
#pragma unroll
    for (int i = 0; i < 4; i++)
        stsm4(d0 + row + (((2 * i + (lane >> 4)) ^ (lane & 7)) << 4), pack2(acc[8 * i], acc[8 * i + 1]), pack2(acc[8 * i + 2], acc[8 * i + 3]),
              pack2(acc[8 * i + 4], acc[8 * i + 5]), pack2(acc[8 * i + 6], acc[8 * i + 7]));
    fence_async();
    bar_sync(1 + wg, 128);
    if (t == 0) {
        bulk_s2g(g_z + col * 8192, d0, 8192);
        asm volatile("cp.async.bulk.commit_group;" ::: "memory");
        bulk_wait_read<0>();
    }
    TLE(5 + 5 * layer);
}

__global__ void __maxnreg__(120) rowifft_kernel(const bf16* __restrict__ x, bf16* __restrict__ out, int last) {
    extern __shared__ __align__(1024) unsigned char smem[];
    const uint32_t sb = s2u(smem), sx = sb + 20480, sy = sx + 20480, bar = sy + 16 * 1296;
    const int tid = threadIdx.x, lane = tid & 31, q = lane & 3, blk = blockIdx.x, k2 = tid >> 2, warp = tid >> 5;
    float twr[5], twi[5];
#pragma unroll
    for (int r = 1; r < 5; r++) { sincospif((float)(r * k2) * (1.f / 320), &twi[r], &twr[r]); twr[r] *= 2.f; twi[r] *= 2.f; }
    uint32_t f[8][4];
#pragma unroll
    for (int ks = 0; ks < 8; ks++) { const uint4 u = g_f128[2048 + ks * 256 + tid]; f[ks][0] = u.x; f[ks][1] = u.y; f[ks][2] = u.z; f[ks][3] = u.w; }
    if (tid == 0) {
        mbar_init(bar, 1);
        asm volatile("fence.mbarrier_init.release.cluster;" ::: "memory");
        mbar_expect(bar, 20480);
        bulk_g2s(sx, x + (size_t)blk * 16 * D_, 20480, bar);
    }
    pdl_wait();
    pdl_launch();
    TLS(6 + 5 * last);
    const unsigned char* zp = g_z + (blk >> 1) * 128 + ((((blk & 1) * 4 + q) ^ ((blk >> 1) & 7)) << 4);
    uint4 z[6];
#pragma unroll
    for (int j = 0; j < 5; j++) z[j] = *(const uint4*)(zp + (64 * j + k2) * 8192);
    z[5] = k2 ? make_uint4(0, 0, 0, 0) : *(const uint4*)(zp + 320 * 8192);
    float acc[40];
#pragma unroll
    for (int u = 0; u < 4; u++) {
        float yr[6], yi[6], tr[5], ti[5], zr[5], zi[5];
#pragma unroll
        for (int j = 0; j < 6; j++) { const uint32_t v = u == 0 ? z[j].x : u == 1 ? z[j].y : u == 2 ? z[j].z : z[j].w; yr[j] = bf_lo(v); yi[j] = bf_hi(v); }
#pragma unroll
        for (int j = 0; j < 5; j++) { tr[j] = yr[j]; ti[j] = j < 3 ? yi[j] : -yi[j]; }
        dft5<-1>(tr, ti, zr, zi);
        const float c1[5] = {1.f, C5A, C5B, C5B, C5A}, s1[5] = {0.f, S5A, S5B, -S5B, -S5A};
        const float c2[5] = {1.f, C5B, C5A, C5A, C5B}, s2[5] = {0.f, S5B, -S5A, S5A, -S5B};
        const float c3[5] = {1.f, -C5B, C5A, -C5A, C5B}, s3[5] = {0.f, S5B, S5A, S5A, S5B};
        const float c4[5] = {1.f, -C5A, C5B, -C5B, C5A}, s4[5] = {0.f, S5A, -S5B, -S5B, S5A};
#pragma unroll
        for (int r = 0; r < 5; r++) {
            float er = r ? zr[r] * twr[r] - zi[r] * twi[r] : 2.f * zr[0], ei = r ? zr[r] * twi[r] + zi[r] * twr[r] : 2.f * zi[0];
            if (k2 == 0) {
                er = yr[0] + 2.f * (yr[1] * c1[r] - yi[1] * s1[r] + yr[2] * c2[r] - yi[2] * s2[r]);
                ei = (r & 1 ? -yr[5] : yr[5]) + 2.f * (yr[4] * c3[r] - yi[4] * s3[r] + yr[3] * c4[r] - yi[3] * s4[r]);
            }
            acc[8 * r + 4 * (u >> 1) + (u & 1)] = er;
            acc[8 * r + 4 * (u >> 1) + 2 + (u & 1)] = ei;
        }
    }
#pragma unroll
    for (int r = 0; r < 5; r++)
        stsm4(sb + (2 * warp + ((lane >> 3) & 1)) * 1280 + (2 * r + (lane >> 4)) * 128 + (lane & 7) * 16, pack2(acc[8 * r], acc[8 * r + 1]),
              pack2(acc[8 * r + 2], acc[8 * r + 3]), pack2(acc[8 * r + 4], acc[8 * r + 5]), pack2(acc[8 * r + 6], acc[8 * r + 7]));
    fence_async();
    __syncthreads();
    const u64 db = mkdesc(sb, 1280, 128);
    wg_fence();
    wgmma_n80_rs<0, 1>(acc, f[0], db);
#pragma unroll
    for (int ks = 1; ks < 8; ks++) wgmma_n80_rs<1, 1>(acc, f[ks], db + ks * 160);
    wg_commit();
    wg_wait<0>();
#pragma unroll
    for (int u = 0; u < 4; u++) {
        float e[10];
#pragma unroll
        for (int r = 0; r < 5; r++) { e[r] = acc[8 * r + 4 * (u >> 1) + (u & 1)]; e[5 + r] = acc[8 * r + 4 * (u >> 1) + 2 + (u & 1)]; }
#pragma unroll
        for (int i = 0; i < 5; i++) sts32(sy + (4 * q + u) * 1296 + k2 * 20 + i * 4, pack2(e[2 * i], e[2 * i + 1]));
    }
    __syncthreads();
    const int rho = tid >> 4, j = tid & 15;
    float v[40];
    mbar_wait(bar, 0);
#pragma unroll
    for (int i = 0; i < 5; i++) {
        uint32_t y[4], u[4];
        lds128(y, sy + rho * 1296 + j * 80 + i * 16);
        lds128(u, sx + tid * 80 + i * 16);
#pragma unroll
        for (int k = 0; k < 4; k++) u[k] = pack2(bf_lo(u[k]) + bf_lo(y[k]), bf_hi(u[k]) + bf_hi(y[k]));
        sts128(sx + tid * 80 + i * 16, u[0], u[1], u[2], u[3]);
        unpack8(v + 8 * i, make_uint4(u[0], u[1], u[2], u[3]));
    }
    if (!last) {
        ln40(v);
#pragma unroll
        for (int i = 0; i < 5; i++) {
            const int c = j * 5 + i;
            sts128(sb + (c >> 3) * 2048 + rho * 128 + (((c ^ rho) & 7) << 4), pack2(v[8 * i], v[8 * i + 1]), pack2(v[8 * i + 2], v[8 * i + 3]),
                   pack2(v[8 * i + 4], v[8 * i + 5]), pack2(v[8 * i + 6], v[8 * i + 7]));
        }
    }
    fence_async();
    __syncthreads();
    if (lane == 0) {
        if (warp == 7) bulk_s2g(out + (size_t)blk * 16 * D_, sx, 20480);
        else if (!last && warp < 5) {
            unsigned char* p = g_xn + (blk >> 1) * 40960 + warp * 8192 + (blk & 1) * 2048;
            bulk_s2g(p, sb + warp * 4096, 2048);
            bulk_s2g(p + 4096, sb + warp * 4096 + 2048, 2048);
        }
        bulk_commit();
        bulk_wait_read<0>();
    }
    TLE(6 + 5 * last);
}

namespace rec {
#define NS 3
constexpr int OFF_X = 0;
constexpr int OFF_WO = 81920;
constexpr int OFF_WS = OFF_WO + 65536;
constexpr int OFF_XCH = OFF_WS + NS * 4096;
constexpr int OFF_MEMB = OFF_XCH + 12288;
constexpr int OFF_VX = OFF_MEMB + 10240;
constexpr int OFF_VM = OFF_VX + 16384;
constexpr int OFF_Q = OFF_VM + 4096;
constexpr int OFF_K = OFF_Q + 10240;
constexpr int OFF_OST = OFF_WO + 49152;
constexpr int OFF_PX = OFF_OST + 8192;
constexpr int OFF_PT = OFF_PX + 2560;
constexpr int OFF_PS = OFF_K + 10240;
constexpr int OFF_OB = OFF_PS + 1280;
constexpr int OFF_MX = OFF_OB + 2048;
constexpr int OFF_BAR = OFF_MX + 64;
constexpr int OFF_PROF = OFF_BAR + 256;
constexpr int SMEM = OFF_PROF + 4096 > wk::SMEM ? OFF_PROF + 4096 : wk::SMEM;
enum { B_XT = 0, B_VM = 2, B_VX = 4, B_XD = 6, B_X1 = 8, B_GO = 10, B_PXF = 12, B_PXE = 13, B_FIN = 14, B_ST = 15, B_MEM = 16   };
enum { NB_W2 = 0, NB_XCH = 1, NB_QK = 2, NB_WIN = 3, NB_ATT = 4, NB_X = 5, NB_PRO = 6, NB_W1 = 7, NB_PAIR = 8  , NB_KF = 12, NB_LD = 13, NB_KX = 15 };
#define TPOS 1
#define LATE 1
#define STAG 585
#define NOX 0
#define NW1 4
#define NW1B 0
template <int N> struct IC { static constexpr int value = N; };
template <int N, int I = 0, class F> DEV void static_for(F&& f) { if constexpr (I < N) { f(IC<I>{}); static_for<N, I + 1>(f); } }
constexpr float SM_SCALE = 0.08838834764831845f * 1.4426950408889634f;
}

__global__ void __launch_bounds__(512, 1) rec_kernel(const __grid_constant__ Maps maps, const bf16* __restrict__ x, bf16* __restrict__ x1, const bf16* __restrict__ mem0, const bf16* __restrict__ Wq, const bf16* __restrict__ Wk,
                                                     const bf16* __restrict__ Wv, const bf16* __restrict__ Wo, int layer, int delay, int delay2) {
    using namespace rec;
    extern __shared__ __align__(1024) unsigned char smem[];
    const uint32_t sb = s2u(smem);
    pdl_launch();
    if (blockIdx.x < 3 * H_) {
    const int tid = threadIdx.x, lane = tid & 31, warp = __shfl_sync(~0u, tid >> 5, 0);
    const int g = lane >> 2, q = lane & 3;
    const int h = blockIdx.x / 3;
    const uint32_t bar = sb + OFF_BAR;
    STAMP(2 * layer);
    TLS(2 + 5 * layer);
    if (tid == 0) TLI(690 + blockIdx.x, 0, gtime());
    if (tid == 0) {
        for (int i = 0; i < 2; i++) {
            mbar_init(bar + 8 * (B_XT + i), 1); mbar_init(bar + 8 * (B_VX + i), 1);
            mbar_init(bar + 8 * (B_XD + i), 8); mbar_init(bar + 8 * (B_X1 + i), 1); mbar_init(bar + 8 * (B_VM + i), 1);
        }
        mbar_init(bar + 8 * B_PXF, 1); mbar_init(bar + 8 * B_PXE, 2); mbar_init(bar + 8 * B_ST, 2); mbar_init(bar + 8 * B_GO, 1);
        for (int i = 0; i < 5; i++) mbar_init(bar + 8 * (B_MEM + i), 4);
        mbar_init(bar + 8 * B_FIN, 48);
        asm volatile("fence.mbarrier_init.release.cluster;" ::: "memory");
    }
    asm volatile("barrier.cluster.arrive.aligned; barrier.cluster.wait.aligned;" ::: "memory");
    const bool never = delay < 0;

    if (warp < 8) {
        asm volatile("setmaxnreg.inc.sync.aligned.u32 184;");
        const uint32_t rank = cta_rank();
        const int wg = warp >> 2;
        uint32_t fa[20 - NS][4], fb[20][4];
        const uint32_t l16 = opaque(sb + lane * 16);
        uint32_t dst = opaque(rank < 2 ? sb + OFF_Q + wg * 10240 + (warp & 3) * 256 + (lane & 15) * 16 + (lane >> 4) * 1024
                                       : sb + OFF_VM + warp * 256 + lane * 4);
        int dstep = rank < 2 ? 5120 : 2048;
        uint32_t& sfd = dst;
        const uint32_t ws = OFF_WS + warp * 512, xo = OFF_XCH + warp * 512, xi = OFF_XCH + (warp ^ 4) * 512, mb = OFF_MEMB + wg * 512;
        {
            static_assert(NS <= 4 && OFF_WS + 32768 <= OFF_VX, "staging space");
            const int t = tid & 127;
            const bf16* src = (rank == 2 ? Wv + wg * 64 : (wg ? Wk : Wq) + rank * 64) + h * E_ + (size_t)(512 + (t >> 3)) * 4096 + (t & 7) * 8;
            constexpr int SA = OFF_WS, SB = OFF_VX;
            const uint32_t sdst = sb + (wg ? SB : SA) + (t >> 3) * 128 + (((t & 7) ^ ((t >> 3) & 7)) << 4);
            const uint32_t ra = sb + wg * 4096 + ((lane >> 4) * 8 + (lane & 7)) * 128 + (((2 * (warp & 3) + ((lane >> 3) & 1)) ^ (lane & 7)) << 4);
            auto issue = [&](int rd) {
#pragma unroll 1
                for (int i = 0; i < 8; i++, src += 16 * 4096) cp16(sdst + (~rd & 1) * 16384 + i * 2048, src);
                src -= 256 * 4096;
                cp_commit();
            };
            issue(4); issue(3);
            float acc[16];
            const u64 da = mkdesc(sb + SA, 0, 1024) | SW128, db = mkdesc(sb + OFF_X + wg * 40960, 0, 1024) | SW128;
            mbar_spin(bar + 8 * (B_XT + wg), 0);
#pragma unroll
            for (int rd = 4; rd >= 0; rd--) {
                if (rd) cp_wait<1>(); else cp_wait<0>();
                fence_async();
                bar_sync(NB_XCH, 256);
                wg_fence();
#pragma unroll
                for (int ks = 0; ks < 8; ks++) {
                    const u64 a = da + (~rd & 1) * 1024 + ks * 128, b = db + (2 * rd + (ks >> 2)) * 256 + (ks & 3) * 2;
                    if (rd == 4 && ks == 0) wgmma_n32_ss<0>(acc, a, b); else wgmma_n32_ss<1>(acc, a, b);
                }
                wg_commit();
                wg_wait<0>();
#pragma unroll
                for (int i = 0; i < 4; i++) {
                    const int n = rd * 4 + i, o = (~rd & 1) * 16384 + (i >> 1) * 8192 + (i & 1) * 2048;
                    if (n < NS) {
                        uint32_t f[4];
                        ldsm4t(f, ra + SA + o);
                        sts128(l16 + ws + n * 4096, f[0], f[1], f[2], f[3]);
                    } else ldsm4t(fa[n - NS], ra + SA + o);
                    ldsm4t(fb[n], ra + SB + o);
                }
                if (rd > 1) { bar_sync(NB_XCH, 256); issue(rd - 2); }
            }
            fence_async();
            bar_sync(NB_PRO, 416);
            uint32_t pk[8];
#pragma unroll
            for (int i = 0; i < 8; i++) pk[i] = pack2(acc[2 * i], acc[2 * i + 1]);
            if (rank < 2) {
                stsm4t(dst - wg * 5120 + 1024, pk[0], pk[1], pk[2], pk[3]);
                stsm4t(dst - wg * 5120 + 3072, pk[4], pk[5], pk[6], pk[7]);
            } else {
                const uint32_t la = l16 + (l16 & 256) + OFF_VX + wg * 8192 + (warp & 3) * 1024;
                stsm4(la, pk[0], pk[2], pk[1], pk[3]);
                stsm4(la + 256, pk[4], pk[6], pk[5], pk[7]);
            }
        }
        uint32_t xlo = (uint32_t)mkdesc(sb + OFF_X + wg * 64, 0, 0);
        const uint32_t xtog = xlo ^ (uint32_t)mkdesc(sb + OFF_X + 40960 + wg * 64, 0, 0);
        uint32_t p8 = 0;
        bar_sync(NB_LD, 288);
        for (int s = -1;; s++) {
            uint32_t t[NS ? NS : 1][4];
            {
                float acc[16];
                auto xproj = [&](auto I0, auto I1) {
                    const u64 desc = (u64)xlo | (64ull << 32) | SW128;
                    wg_fence();
#pragma unroll
                    for (int i = I0.value; i < I1.value; i++) {
                        const u64 db = desc + (i >> 1) * 256 + (i & 1) * 2;
                        if (i == 0) wgmma_n32_rs<0>(acc, fb[i], db);
                        else if (!NOX) wgmma_n32_rs<1>(acc, fb[i], db);
                    }
                    wg_commit();
                    if (TPOS == 0 ? I0.value == 0 : I1.value == 20) {
#pragma unroll
                        for (int i = 0; i < NS; i++) lds128(t[i], l16 + ws + i * 4096);
                    }
                    wg_wait<0>();
                };
                if (s >= 0 && rank < 2) { fence_async(); bar_arrive(NB_W1, 512); bar_sync(NB_X, 384); }
                bar_sync_if<NB_W1, 480>(s >= 0 && rank == 2);
                if (s == NSEG - 1) break;
                xproj(IC<0>{}, IC<NW1>{});
                if (warp == 4 && s >= 0) PROFT(15);
                bar_sync_if<NB_W2, 384>(s >= 0 && rank < 2);
                if (NW1B > 0) xproj(IC<NW1>{}, IC<NW1 + NW1B>{});
                bar_sync_if<NB_WIN, 384>(s >= 0 && rank == 2);
                xproj(IC<NW1 + NW1B>{}, IC<20>{});
                if (warp == 4 && s >= 0) PROFT(12);
                sts128f_if(l16 + xo, acc + 8, !wg); sts128f_if(l16 + xo + 4096, acc + 12, !wg);
                sts128f_if(l16 + xo, acc, wg); sts128f_if(l16 + xo + 4096, acc + 4, wg);
                bar_sync(NB_PAIR + (warp & 3), 64);
                lds128f_if(acc + 8, l16 + xi, !wg); lds128f_if(acc + 12, l16 + xi + 4096, !wg);
                lds128f_if(acc, l16 + xi, wg); lds128f_if(acc + 4, l16 + xi + 4096, wg);
                float u[8];
#pragma unroll
                for (int i = 0; i < 8; i++) u[i] = acc[i] + acc[8 + i];
                if (rank < 2) {
                    stsm4t(dst + (wg ? 3072 : 11264), pack2(u[0], u[1]), pack2(u[2], u[3]), pack2(u[4], u[5]), pack2(u[6], u[7]));
                } else {
                    stsm4(l16 + (l16 & 256) + OFF_VX + 4096 + (warp & 3) * 1024 + wg * 256 + p8 * 1024,
                          pack2(u[0], u[1]), pack2(u[4], u[5]), pack2(u[2], u[3]), pack2(u[6], u[7]));
                    bar_arrive(NB_KF, 288);
                }
                bar_arrive(NB_KX, 384);
                xlo ^= xtog;
                if (warp == 4 && s >= 0) PROFT(3);
            }
            float da[4] = {0.f, 0.f, 0.f, 0.f}, db[4] = {0.f, 0.f, 0.f, 0.f}, ea[4] = {0.f, 0.f, 0.f, 0.f}, eb[4] = {0.f, 0.f, 0.f, 0.f};
            uint32_t b[10][4];
            const uint32_t mp = p8 >> 3;
            while (!mbar_try(bar + 8 * B_MEM, mp)) {}
            lds128(b[0], l16 + mb); lds128(b[1], l16 + mb + 1024);
            bool rdy;
            const uint32_t xb0 = mapa(bar + 8 * B_VM + p8, 0), xb1 = mapa(bar + 8 * B_VM + p8, 1);
            SFENCE();
            float is;
#pragma unroll
            for (int j = 0; j < 10; j++) {
#pragma unroll
                for (int x = 0; x < 2; x++) {
                    const int i = 2 * j + x;
                    const uint32_t* f = i < NS ? t[i] : fa[i - NS];
                    mma16(NS > 2 && x && j ? ea : da, f[0], f[1], f[2], f[3], b[j][2 * x], b[j][2 * x + 1]);
                    mma16(NS > 2 && x && j ? eb : db, fb[i][0], fb[i][1], fb[i][2], fb[i][3], b[j][2 * x], b[j][2 * x + 1]);
                    SFENCE();
                    if (x == 0 && j < 8 && !(j & 1)) rdy = mbar_try(bar + 8 * (B_MEM + 1 + (j >> 1)), mp, 1);
                    if (x == LATE && j < 8 && (j & 1) == 1 - LATE) {
                        if (__builtin_expect(!rdy, 0)) while (!mbar_try(bar + 8 * (B_MEM + 1 + (j >> 1)), mp)) {}
                        lds128(b[(j | 1) + 1], l16 + mb + ((j | 1) + 1) * 1024);
                        lds128(b[(j | 1) + 2], l16 + mb + ((j | 1) + 2) * 1024);
                    }
                    if (x == 0 && j == 8) is = lds32f(sb + OFF_MX + 16);
                }
                if (j == 0 && warp == 4) PROFT(16);
            }
            if (warp == 4) PROFT(20);
            if (NS > 2) {
#pragma unroll
                for (int i = 0; i < 4; i++) { da[i] += ea[i]; db[i] += eb[i]; }
            }
            sts128f_if(l16 + xo + 8192, db, !wg); sts128f_if(l16 + xo + 8192, da, wg);
            bar_sync(NB_PAIR + (warp & 3), 64);
            lds128f_if(db, l16 + xi + 8192, !wg); lds128f_if(da, l16 + xi + 8192, wg);
            const uint32_t p0 = pack2((da[0] + db[0]) * is, (da[1] + db[1]) * is), p1 = pack2((da[2] + db[2]) * is, (da[3] + db[3]) * is);
            stsm2t_if(dst, p0, p1, rank < 2);
            bar_arrive_if<NB_QK, 384>(rank < 2);
            if (rank == 2) {
                st_async1(mapa(dst, 0), p0, xb0); st_async1(mapa(dst, 1), p0, xb1);
                st_async1(mapa(dst + 128, 0), p1, xb0); st_async1(mapa(dst + 128, 1), p1, xb1);
                sts32(dst, p0); sts32(dst + 128, p1);
                bar_arrive(NB_QK, 384);
            }
            if (warp == 4) PROFT(17);
            dst += dstep; dstep = -dstep; p8 ^= 8;
        }
    } else if (warp < 12) {
        asm volatile("setmaxnreg.dec.sync.aligned.u32 96;");
        const uint32_t rank = cta_rank();
        const int w = warp - 8;
        uint32_t amax = 0;
        {
            const int t = tid & 127, nr = rank == 2 ? 4 : 3;
            for (int r = 0; r < nr; r++) {
                const bf16* src = Wo + (size_t)(h * E_) * D_ + (r < 3 ? 192 * r + 64 * rank : 576);
#pragma unroll 1
                for (int i = 0; i < 8; i++) {
                    const int e = i * 16 + (t >> 3);
                    cp16(sb + OFF_WO + r * 16384 + e * 128 + (((t & 7) ^ (e & 6)) << 4), src + e * D_ + (t & 7) * 8);
                }
            }
            cp_commit();
            cp_wait<0>();
            bar_sync(NB_ATT, 128);
            for (int r = 0; r < nr; r++) {
                uint32_t u[8][4];
                const uint32_t p = sb + OFF_WO + r * 16384 + 2 * q * 128 + (((2 * w + (g & 1)) ^ (2 * q)) << 4) + (g >> 1) * 4;
#pragma unroll
                for (int ks = 0; ks < 8; ks++)
#pragma unroll
                    for (int j = 0; j < 4; j++) u[ks][j] = lds32(p + (16 * ks + (j & 1) * 8 + (j >> 1)) * 128);
                bar_sync(NB_ATT, 128);
#pragma unroll
                for (int ks = 0; ks < 8; ks++)
                    sts128(sb + OFF_WO + (r * 4 + w) * 4096 + ks * 512 + lane * 16, prmt(u[ks][0], u[ks][2], 0x5410), prmt(u[ks][0], u[ks][2], 0x7632),
                           prmt(u[ks][1], u[ks][3], 0x5410), prmt(u[ks][1], u[ks][3], 0x7632));
            }
        }
        {
            uint32_t m0[5][4];
#pragma unroll
            for (int it = 0; it < 5; it++)
#pragma unroll
                for (int j = 0; j < 4; j++) m0[it][j] = ldg32(mem0 + g * D_ + (it * 4 + w) * 32 + 2 * q + 8 * j);
            bar_sync(NB_PRO, 416);
#pragma unroll
            for (int it = 0; it < 5; it++) {
                sts128(sb + OFF_MEMB + (it * 4 + w) * 512 + lane * 16, m0[it][0], m0[it][1], m0[it][2], m0[it][3]);
                amax = absmax2(amax, absmax2(absmax2(m0[it][0], m0[it][1]), absmax2(m0[it][2], m0[it][3])));
            }
            if (tid == 256) { sts32(sb + OFF_MX + 16, 0x3f800000u); sts128(sb + OFF_MX + 48, 0x3f803f80u, 0x3f803f80u, 0x3f803f80u, 0x3f803f80u); }
            __syncwarp();
            if (lane < 5) mbar_arrive(bar + 8 * (B_MEM + lane));
            __syncwarp();
        }
        if (w == 0) TLI(690 + blockIdx.x, 3, gtime());
        pdl_wait();
        float cw;
        {
            const float4 a = ((const float4*)g_nrm)[lane], c = ((const float4*)g_nrm)[32 + lane];
            float sm = sqrt_approx((a.x + a.y) + (a.z + a.w)) * sqrt_approx((c.x + c.y) + (c.z + c.w)), mxv = sm;
#pragma unroll 1
            for (int o = 16; o; o >>= 1) { sm += __shfl_xor_sync(~0u, sm, o); mxv = fmaxf(mxv, __shfl_xor_sync(~0u, mxv, o)); }
            cw = 26.5f * fmaxf(sm, 8.f * mxv);
        }
        if (w == 0) {
            mbar_expect_elect(bar + 8 * B_X1, 1280);
            mbar_expect_elect(bar + 8 * B_VM, rank < 2 ? 2048 : 0);
            mbar_expect_elect(bar + 8 * B_VX, rank < 2 ? 8192 : 0);
        }
        {
            const int kind = rank;
            const uint32_t l16 = opaque(sb + lane * 16), lw = opaque(sb + lane * 16 + w * 512);
            const uint32_t pa = opaque(sb + OFF_PS + rank * 512 + lane * 4 + w * 128);
            uint32_t lq = opaque(sb + OFF_Q + (lane & 7) * 16 + ((lane >> 3) & 1) * 256 + (lane >> 4) * 128);
            const uint32_t lv = opaque(sb + OFF_VX + w * 2048 + (lane & 7) * 16 + ((lane >> 3) & 1) * 512 + (lane >> 4) * 128);
            const uint32_t lo = opaque(sb + OFF_WO + w * 4096 + lane * 16);
            uint32_t& sfd = lq;
            const char* rp = (const char*)(g_acc + layer * ACC_LAYER) + (4 * rank + w) * 4096 + opaque((q >> 1) * 1024 + ((q & 1) * 8 + g) * 8);
            const char* lp = (const char*)(g_acc + layer * ACC_LAYER) + opaque(w * 8192 + (lane >> 3) * 1024 + (lane & 7) * 16);
            const uint32_t arm = bar + 8 * (w == 0 ? B_X1 + 1 : w == 1 ? B_VX + 1 : w == 2 ? B_XT : B_VM + 1);
            const uint32_t armb = w == 0 ? 1280 : (w == 1 ? 4096 : w == 2 ? 40960 : 0) + (rank == 2 ? 0 : w == 3 ? 2048 : 4096);
            float isig = 1.f;
            for (int s = 0; s < NSEG - 1; s++) {
                const uint32_t pb = s & 1, ph = (s >> 1) & 1, x1 = bar + 8 * (B_X1 + pb);
                uint32_t kf[8];
                bar_sync(NB_KX, 384);
                ldsm4(kf, lw + OFF_K + 1024 + w * 512 + pb * 5120); ldsm4(kf + 4, lw + OFF_K + 1536 + w * 512 + pb * 5120);
                sts32(sb + OFF_MX + w * 4, __reduce_max_sync(~0u, max(amax & 0x7fff0000u, (amax << 16) & 0x7fff0000u)));
                const uint32_t va = lv + pb * 8192, vma = lw + OFF_VM + pb * 2048;
                uint32_t wf[8][4], vf[2][2][4], vm[4], one[4];
                mbar_spin(bar + 8 * (B_VX + pb), ph);
#pragma unroll
                for (int t = 0; t < 2; t++)
#pragma unroll
                    for (int j = 0; j < 2; j++) ldsm4(vf[t][j], va + t * 1024 + j * 256);
                lds128(one, sb + OFF_MX + 48);
                auto scores = [&](auto MM) {
                    constexpr int mm = MM.value;
                    uint32_t qf[8], mf[8];
                    const uint32_t qa = lq + pb * 5120, ka = l16 + OFF_K + pb * 5120;
                    const uint32_t pa0 = mapa(pa, rank ^ 1), pa1 = mapa(pa, 2), pa2 = mapa(pa, rank);
                    const uint32_t xb0 = mapa(x1, rank ^ 1), xb1 = mapa(x1, 2), xb2 = mapa(x1, rank);
                    const uint32_t pm = 640 - rank * 384;
                    SFENCE();
                    if (w == 0) PROFT(2);
                    bar_sync(NB_QK, 384);
                    ldsm4(qf, qa); ldsm4(qf + 4, qa + 512);
                    if (mm) { ldsm4(mf, ka); ldsm4(mf + 4, ka + 512); }
                    SFENCE();
                    float c[4][4];
#pragma unroll
                    for (int i = 0; i < 4; i++) c[i][0] = c[i][1] = c[i][2] = c[i][3] = 0.f;
#pragma unroll
                    for (int i = 0; i < (mm ? 8 : 4); i++) {
                        const int hf = mm ? i >> 2 : i >> 1;
                        const uint32_t* f = (mm && (i & 2) ? mf : kf) + 4 * hf + 2 * (i & 1);
                        mma16(c[i & 3], qf[4 * hf], qf[4 * hf + 1], qf[4 * hf + 2], qf[4 * hf + 3], f[0], f[1]);
                    }
                    SFENCE();
                    bar_arrive(NB_W1, 512);
                    const uint32_t y = mm ? pack2(c[0][0] + c[1][2], c[0][1] + c[1][3])
                                          : pack2((c[0][0] + c[1][2]) + (c[2][0] + c[3][2]), (c[0][1] + c[1][3]) + (c[2][1] + c[3][3]));
                    st_async1(pa0, y, xb0); st_async1(pa1, y, xb1);
                    if (mm) {
                        const uint32_t z = pack2(c[2][0] + c[3][2], c[2][1] + c[3][3]);
                        st_async1(pa0 + pm, z, xb0); st_async1(pa1 + pm, z, xb1); st_async1(pa2 + pm, z, xb2);
                    }
                    st_async1(pa2, y, xb2);
                    if (w == 0) PROFT(5);
                };
                if (kind == 2) bar_sync(NB_QK, 384);
                else if (w == 3) scores(IC<1>{});
                else scores(IC<0>{});
                float m4[4];
                lds128f(m4, sb + OFF_MX);
                bar_arrive_if<NB_W1, 480>(kind == 2);
                mbar_spin(x1, ph);
                if (w == 0) PROFT(6);
                float sc[10];
                {
                    uint32_t u[4], v[4], m[2];
                    ldsm4(u, l16 + OFF_PS); ldsm4(v, l16 + OFF_PS + 512); ldsm2(m, l16 + OFF_PS + 1024);
                    SFENCE();
                    m4[0] = fmaxf(fmaxf(m4[0], m4[1]), fmaxf(m4[2], m4[3])) * isig;
                    SFENCE();
#pragma unroll
                    for (int i = 0; i < 4; i++) { sc[2 * i] = bf_lo(u[i]) + bf_lo(v[i]); sc[2 * i + 1] = bf_hi(u[i]) + bf_hi(v[i]); }
                    sc[8] = bf_lo(m[0]) + bf_lo(m[1]); sc[9] = bf_hi(m[0]) + bf_hi(m[1]);
                }
                float mx = fmaxf(fmaxf(fmaxf(fmaxf(sc[0], sc[1]), fmaxf(sc[2], sc[3])), fmaxf(fmaxf(sc[4], sc[5]), fmaxf(sc[6], sc[7]))), fmaxf(sc[8], sc[9]));
                auto fetch = [&](int i) { lds128(wf[i], lo + i * 512); };
                {
                    float m1 = __shfl_xor_sync(~0u, mx, 1), m2 = __shfl_xor_sync(~0u, mx, 2), m3 = __shfl_xor_sync(~0u, mx, 3);
                    mbar_spin(bar + 8 * (B_VM + pb), ph);
                    ldsm4(vm, vma);
                    mx = fmaxf(fmaxf(mx, m1), fmaxf(m2, m3)) * SM_SCALE;
                }
#pragma unroll
                for (int i = 0; i < 10; i++) sc[i] = fmaf(sc[i], SM_SCALE, -mx);
                float o0[4] = {0.f, 0.f, 0.f, 0.f}, o1[4] = {0.f, 0.f, 0.f, 0.f}, rs[4] = {0.f, 0.f, 0.f, 0.f};
                sc[8] = ex2(sc[8]); fetch(0); fetch(1); sc[9] = ex2(sc[9]);
                SFENCE();
                fetch(2); sc[0] = ex2(sc[0]); fetch(3); fetch(4); sc[1] = ex2(sc[1]); fetch(5); fetch(6); sc[2] = ex2(sc[2]);
                SFENCE();
                {
                    const uint32_t p = pack2(sc[8], sc[9]);
                    sc[3] = ex2(sc[3]); fetch(7);
                    mma8(o0, vm[0], vm[1], p);
                    mma8(o1, vm[2], vm[3], p);
                    sc[4] = ex2(sc[4]);
                    mma8(rs, one[0], one[1], p);
                    sc[5] = ex2(sc[5]);
                }
                SFENCE();
                {
                    const uint32_t p0 = pack2(sc[0], sc[1]), p1 = pack2(sc[2], sc[3]);
                    sc[6] = ex2(sc[6]);
                    mma16(o0, vf[0][0][0], vf[0][0][1], vf[0][0][2], vf[0][0][3], p0, p1);
                    SFENCE();
                    sc[7] = ex2(sc[7]);
                    mma16(o1, vf[1][0][0], vf[1][0][1], vf[1][0][2], vf[1][0][3], p0, p1);
                    SFENCE();
                    mma16(rs, one[0], one[1], one[2], one[3], p0, p1);
                    SFENCE();
                }
                {
                    const uint32_t p0 = pack2(sc[4], sc[5]), p1 = pack2(sc[6], sc[7]);
                    mma16(o0, vf[0][1][0], vf[0][1][1], vf[0][1][2], vf[0][1][3], p0, p1);
                    mma16(o1, vf[1][1][0], vf[1][1][1], vf[1][1][2], vf[1][1][3], p0, p1);
                    SFENCE();
                    mma16(rs, one[0], one[1], one[2], one[3], p0, p1);
                }
                const uint32_t e = max((__float_as_uint(cw * fmaxf(m4[0], 1.f)) >> 23) & 255u, 31u);
                SFENCE();
                stsm4t(lw + OFF_OB, pack2(o0[0], o0[1]), pack2(o0[2], o0[3]), pack2(o1[0], o1[1]), pack2(o1[2], o1[3]));
                if (w == 0) PROFT(13);
                bar_sync(NB_ATT, 128);
                uint32_t ob[16];
#pragma unroll
                for (int j = 0; j < 4; j++) ldsm4(ob + 4 * j, l16 + OFF_OB + j * 512);
                SFENCE();
                const float sig = __uint_as_float((278u - e) << 23);
                isig = __uint_as_float((e - 30u) << 23);
                const float sg0 = rcp(rs[0]) * sig, sg1 = rcp(rs[1]) * sig;
                SFENCE();
                auto tile = [&](uint32_t next, const char* p, auto LAST) {
                    float c[4][4];
#pragma unroll
                    for (int i = 0; i < 4; i++) c[i][0] = c[i][1] = c[i][2] = c[i][3] = 0.f;
#pragma unroll
                    for (int ks = 0; ks < 8; ks++) {
                        mma16(c[ks & 3], wf[ks][0], wf[ks][1], wf[ks][2], wf[ks][3], ob[2 * ks], ob[2 * ks + 1]);
                        if ((ks & 3) == 0) SFENCE();
                        if ((ks & 3) == 3 && !LAST.value) {
                            SFENCE();
#pragma unroll
                            for (int i = ks; i >= ks - 3; i--) { lds128(wf[i], next + i * 512); if (i == ks - 2) SFENCE(); }
                            if (ks == 3) SFENCE();
                        }
                    }
                    SFENCE();
                    if (LAST.value) { bar_arrive_if<NB_WIN, 256>(kind < 2); bar_arrive_if<NB_WIN, 384>(kind == 2); }
                    uint32_t v[4];
#pragma unroll
                    for (int i = 0; i < 4; i++)
                        v[i] = (__float_as_uint(fmaf((c[0][i] + c[1][i]) + (c[2][i] + c[3][i]), i & 1 ? sg1 : sg0, 12582912.f)) << 6) + (i < 2);
                    red_add64((u64*)p, v[0], v[2]);
                    red_add64((u64*)(p + 2048), v[1], v[3]);
                };
                tile(lo + 16384, rp, IC<0>{});
                if (w == 0) PROFT(7);
                tile(lo + 32768, rp + 49152, IC<0>{});
                if (kind == 2) tile(lo + 49152, rp + 98304, IC<0>{});
                tile(0, rp + (kind == 2 ? 28 * 4096 : 98304), IC<1>{});
                if (w == 0) PROFT(8);
                sts32(sb + OFF_MX + 16, __float_as_uint(isig));
                mbar_expect_elect(arm ^ (8 * pb), armb - (w == 2 && s == NSEG - 2 ? 40960 : 0) - (s == 0 && w == (rank < 2 ? 2 : 1) ? 4096 : 0));
                u64 y[20];
                uint32_t b[20];
                bool done[5] = {false, false, false, false, false};
                float z = isig;
                mbar_spin(bar + 8 * B_GO, pb);
                if (w == 0) PROFT(9);
                do {
#pragma unroll
                    for (int i = 0; i < 10; i++) {
                        if (STAG && (i == 2 || i == 5 || i == 8)) {
#pragma unroll
                            for (int k = 0; k < (i == 2 ? STAG / 100 : i == 5 ? STAG / 10 % 10 : STAG % 10); k++) asm volatile("ex2.approx.ftz.f32 %0,%0;" : "+f"(z));
                            asm volatile("{.reg .pred p; setp.ne.u32 p,%1,0; @p mov.b32 %0,%2;}" : "+r"(sfd) : "r"((uint32_t)never), "f"(z));
                            SFENCE();
                        }
                        ld_acc0(y[2 * i], y[2 * i + 1], lp + (i >> 1) * 32768 + (i & 1) * 4096);
                        if (STAG && (i == 1 || i == 4 || i == 7)) SFENCE();
                    }
                    uint32_t ok = 32u, late = 32u;
                    static_for<5>([&](auto IT) {
                        constexpr int it = IT.value;
                        if (it == 1) late = and3((uint32_t)y[4], (uint32_t)y[6], (uint32_t)y[8]);
                        else if (it == 2) late &= and3((uint32_t)y[10], (uint32_t)y[12], (uint32_t)y[14]);
                        else if (it == 3) ok &= late;
                        else ok = and3(ok, (uint32_t)y[4 * it], (uint32_t)y[4 * it + 2]);
                        if (it != 3) SFENCE();
                        if (it == 1 || it == 2) ok = and3(ok, (uint32_t)y[4 * it], (uint32_t)y[4 * it + 2]);
                        ok = and3(ok, (uint32_t)y[4 * it + 1], (uint32_t)y[4 * it + 3]);
                        const bool all = __all_sync(~0u, ok);
#pragma unroll
                        for (int j = 0; j < 4; j++) {
                            const u64 v = y[4 * it + j];
                            b[4 * it + j] = pack2((float)(int)(uint32_t)v, (float)(int)(uint32_t)(v >> 32));
                        }
                        sts128(lw + OFF_MEMB + it * 2048, b[4 * it], b[4 * it + 1], b[4 * it + 2], b[4 * it + 3]);
                        mbar_arrive_elect_if(bar + 8 * (B_MEM + it), all && !done[it]);
                        done[it] = all;
                        SFENCE();
                        if (it == 0 && w == 0) PROFT(10);
                    });
                } while (!done[4]);
                if (w == 0) PROFT(11);
                amax = b[0];
#pragma unroll
                for (int i = 1; i < 19; i += 2) amax = absmax2(amax, absmax2(b[i], b[i + 1]));
                amax = absmax2(amax, b[19]);
                const int adv = (s & 7) == 7 ? 163840 - 896 : 128;
                rp += adv; lp += adv;
            }
        }
        asm volatile("prefetch.tensormap [%0];" ::"l"(w & 1 ? &maps.wo1 : &maps.o2) : "memory");
        bar_sync(NB_KX, 384);
        bar_sync(NB_QK, 384);
        if (rank < 2) { bar_arrive(NB_W1, 512); bar_arrive(NB_WIN, 256); } else bar_arrive(NB_W1, 480);
    } else {
        asm volatile("setmaxnreg.dec.sync.aligned.u32 %0;" ::"n"(48));
        const uint32_t rank = cta_rank();
        const int w = warp - 12;
        pdl_wait();
        if (blockIdx.x == 2 && w == 3) asm volatile("st.release.gpu.global.u32 [%0],1;" ::"l"(g_started + layer) : "memory");
        uint32_t* sy = g_sync + layer * SYNC_LAYER;
        if (w == 1) TLI(690 + blockIdx.x, 1, gtime());
        if (w == 1) {
            mbar_expect_elect(bar + 8 * B_XT, 40960);
            mbar_expect_elect(bar + 8 * (B_XT + 1), 40960);
            if (rank < 2) bulk_g2s_all3_elect(sb + OFF_X + rank * 40960, g_xn + rank * 40960, 40960, bar + 8 * (B_XT + rank));
            bar_sync(NB_PRO, 416);
            if (rank == 2) mbar_spin(bar + 8 * B_ST, 0);
            else mbar_arrive_remote_elect(mapa(bar + 8 * B_ST, 2));
            TLI(690 + blockIdx.x, 2, gtime());
            bar_arrive(NB_LD, 288);
        }
        uint32_t* hp = sy + 1024;
        auto hint = [&](uint32_t t) {
            asm volatile("{.reg .pred p; elect.sync _|p, 0xffffffff; @p red.relaxed.gpu.global.max.u32 [%0+4],%1; @p red.relaxed.gpu.global.add.u32 [%0],1;}"
                         ::"l"(hp), "r"(t) : "memory");
        };
        if (rank == 2) {
            if (w == 0) {
                for (int s = -1; s < NSEG - 1; s++) {
                    const uint32_t pb = s & 1, nby = s < 1 ? 8192 : 4096, va = sb + OFF_VX + (pb ^ 1) * 8192 + 8192 - nby, vb = bar + 8 * (B_VX + (pb ^ 1));
                    bar_sync(NB_KF, 288);
                    fence_async();
                    bulk_s2s_elect(mapa(va, 0), va, nby, mapa(vb, 0));
                    bulk_s2s_elect(mapa(va, 1), va, nby, mapa(vb, 1));
                    if (s >= 0) mbar_spin(bar + 8 * (B_XD + pb), (s >> 1) & 1);
                    bar_sync(NB_W1, 480);
                }
            } else if (w == 1) {
                const unsigned char *pn = g_p + (H_ + h) * 12288, *px = g_xn + 2 * 40960;
                const uint32_t* pf = sy + wk::SY_P + h;
                bar_sync(NB_W1, 480);
                for (int s = 0, nb = 1; s < NSEG - 1; s++, pn += H_ * 12288, px += 40960) {
                    const uint32_t pb = s & 1, xt = bar + 8 * (B_XT + pb), qa = sb + OFF_Q + (pb ^ 1) * 5120 + 1024;
                    mbar_spin(bar + 8 * (B_X1 + pb), (s >> 1) & 1);
                    if (s + 2 < NSEG) bulk_g2s_all3_elect(sb + OFF_X + pb * 40960, px, 40960, xt);
                    if (s == nb) {
                        while (__any_sync(~0u, ld_acquire(pf) < 3)) {}
                        pf += H_;
                        nb += s == 1 ? 4 : 6;
                    }
                    if (s) {
                        bulk_g2s_all3_elect(sb + OFF_VX + (pb ^ 1) * 8192, pn + 8192, 4096, bar + 8 * (B_VX + (pb ^ 1)));
                        bulk_g2s_elect(mapa(qa, 0), pn, 4096, mapa(xt, 0));
                        bulk_g2s_elect(mapa(qa, 1), pn + 4096, 4096, mapa(xt, 1));
                    }
                    mbar_spin(xt, ((s + 2) >> 1) & 1);
                    bar_sync(NB_W1, 480);
                }
                mbar_spin(bar + 8 * (B_VX + 1), 1);
            } else if (w == 2) {
                const char* pf = lane < 5 ? (const char*)(g_acc + layer * ACC_LAYER) + (5 * h + lane) * 1024 : (const char*)hp;
                const int pfa = lane < 5 ? 163840 : 1024;
                if (lane < 6) for (int i = 0; i < 8; i++) prefetch_l2(pf + i * 128);
                __syncwarp();
                const uint32_t go = mapa(bar + 8 * B_GO, min(lane, 2));
                for (int s = 0; s < NSEG - 1; s++, hp += 32) {
                    bar_sync(NB_W1, 480);
                    sts32(sb + OFF_MX + 32, 0);
                    uint32_t t = gtime32(), t0 = clk(), c, tm;
                    hint(t);
                    if (h == 0) TLI(940 + s, 0, t);
                    if (lane < 6 && s < NSEG - 8) prefetch_l2(pf + ((s >> 3) + 1) * pfa + (s & 7) * 128);
                    __syncwarp();
                    while (clk() - t0 < (uint32_t)delay2) {}
                    do asm volatile("ld.relaxed.gpu.global.v2.u32 {%0,%1},[%2];" : "=r"(c), "=r"(tm) : "l"(hp) : "memory"); while (__any_sync(~0u, c != 3 * H_));
                    const uint32_t wait = min(tm - t, 10000u) * 7 / 4 + delay;
                    while (clk() - t0 < wait) {}
                    if (lane < 3) mbar_arrive_remote(go);
                    __syncwarp();
                }
                bar_sync(NB_W1, 480);
            }
        } else {
            if (w < 2) sts32(sb + OFF_PT + w * 768 + 640 + lane * 4, 0u);
            const uint32_t px = opaque(sb + OFF_PX + (w & 1) * 1280 + lane * 8);
            const uint32_t pt = opaque(sb + OFF_PT + (w & 1) * 768 + lane * 4);
            uint32_t os = opaque(sb + OFF_OST + (lane >> 4) * 1024 + w * 256 + (lane & 15) * 16);
            uint32_t& sfd = os;
            const int lim = opaque(8 * w + g + 8 - 2 * q);
            unsigned char* op = g_o + h * 8192 + rank * 2048;
            uint32_t* oc = sy + wk::SY_O;
            auto report = [&]() {
                bulk_wait<0>();
                __syncwarp();
                asm volatile("{.reg .pred p; elect.sync _|p, 0xffffffff; @p red.relaxed.gpu.global.add.u32 [%0],1;}" ::"l"(oc) : "memory");
                oc++;
            };
            auto store_o = [&](int n) {
                bulk_s2g_elect(op, sb + OFF_OST + (n & 1) * 4096, 2048);
                bulk_s2g_elect(op + 4096, sb + OFF_OST + (n & 1) * 4096 + 2048, 2048);
                bulk_commit();
                op += H_ * 8192;
            };
            for (int s = 0; s < NSEG; s++) {
                const uint32_t pb = s & 1, ph = (s >> 1) & 1;
                if ((w >> 1) != rank) { if (s >= 1) mbar_spin(bar + 8 * B_PXE, pb ^ 1); }
                else if (w & 1) mbar_spin(bar + 8 * (B_XT + (pb ^ 1)), ((s + 1) >> 1) & 1);
                else mbar_expect_elect(bar + 8 * B_PXF, rank ? 2560 : 1536);
                const u64 dq = mkdesc(sb + OFF_Q + pb * 5120 + 1024, 128, 512), dk = mkdesc(sb + OFF_K + pb * 5120, 128, 1024);
                SFENCE();
                bar_sync(NB_W1, 512);
                float c[20];
                wg_fence();
                wgmma_n40_ss<0>(c, dq, dk);
#pragma unroll
                for (int ks = 1; ks < 4; ks++) wgmma_n40_ss<1>(c, dq + ks * 16, dk + ks * 16);
                wg_commit();
                bar_arrive(NB_X, 384);
                if (w == 2 * rank) { hint(gtime32()); hp += 32; }
                wg_wait<0>();
                if ((w >> 1) != rank) {
                    const uint32_t pa = mapa(px, rank ^ 1), pf = mapa(bar + 8 * B_PXF, rank ^ 1);
#pragma unroll
                    for (int nt = 0; nt < 5; nt++)
                        if (nt < 3 || rank == 0) st_async2(pa + nt * 256, __float_as_uint(c[4 * nt]), __float_as_uint(c[4 * nt + 1]), pf);
                    if ((w & 1) && s) store_o(s - 1);
                    mbar_spin(bar + 8 * (w & 1 ? B_VX : B_VM) + 8 * pb, ph);
                } else {
                    mbar_spin(bar + 8 * B_PXF, pb);
                    float u[10];
#pragma unroll
                    for (int nt = 0; nt < 5; nt++) lds64f(u[2 * nt], u[2 * nt + 1], px + nt * 256);
#pragma unroll
                    for (int i = 0; i < 10; i++) u[i] = 8 * (i >> 1) + (i & 1) <= lim ? u[i] + c[4 * (i >> 1) + (i & 1)] : -INFINITY;
                    float mx = fmaxf(fmaxf(fmaxf(fmaxf(u[0], u[1]), fmaxf(u[2], u[3])), fmaxf(fmaxf(u[4], u[5]), fmaxf(u[6], u[7]))), fmaxf(u[8], u[9]));
                    const float m1 = __shfl_xor_sync(~0u, mx, 1), m2 = __shfl_xor_sync(~0u, mx, 2), m3 = __shfl_xor_sync(~0u, mx, 3);
                    mx = fmaxf(fmaxf(mx, m1), fmaxf(m2, m3)) * SM_SCALE;
#pragma unroll
                    for (int i = 0; i < 10; i++) u[i] = ex2(fmaf(u[i], SM_SCALE, -mx));
                    float sum = (((u[0] + u[1]) + (u[2] + u[3])) + ((u[4] + u[5]) + (u[6] + u[7]))) + (u[8] + u[9]);
                    const float s1 = __shfl_xor_sync(~0u, sum, 1), s2 = __shfl_xor_sync(~0u, sum, 2), s3 = __shfl_xor_sync(~0u, sum, 3);
                    sum = rcp((sum + s1) + (s2 + s3));
#pragma unroll
                    for (int nt = 0; nt < 5; nt++) sts32(pt + (nt ? nt - 1 : 4) * 128, pack2(u[2 * nt] * sum, u[2 * nt + 1] * sum));
                }
                float acc[2][8];
                const u64 dv = mkdesc(sb + OFF_VX + pb * 8192, 128, 512), dp = mkdesc(sb + OFF_PT, 128, 768);
                const u64 dm = mkdesc(sb + OFF_VM + pb * 2048, 0, 128);
                fence_async();
                bar_sync(NB_WIN, 256);
                wg_fence();
#pragma unroll
                for (int m = 0; m < 2; m++) {
                    wgmma_n16_ss<0>(acc[m], dv + m * 256, dp);
                    wgmma_n16_ss<1>(acc[m], dv + m * 256 + 16, dp + 16);
                    wgmma_n16_ss<1>(acc[m], dm + m * 64, dp + 32);
                }
                wg_commit();
                bar_arrive_if<NB_W2, 384>(s < NSEG - 1);
                wg_wait<0>();
#pragma unroll
                for (int m = 0; m < 2; m++)
                    stsm4t(os + pb * 4096 + m * 2048, pack2(acc[m][0], acc[m][1]), pack2(acc[m][2], acc[m][3]), pack2(acc[m][4], acc[m][5]), pack2(acc[m][6], acc[m][7]));
                fence_async();
                mbar_arrive_remote_elect(mapa(bar + 8 * (B_XD + pb), 2));
                if ((w >> 1) == rank) mbar_arrive_remote_elect(mapa(bar + 8 * B_PXE, rank ^ 1));
                else if ((w & 1) && s) report();
            }
            bar_sync(NB_W2, 128);
            if (w == 3 - 2 * rank) {
                store_o(NSEG - 1);
                report();
            }
        }
    }
    __syncwarp();
    if (lane < 3) mbar_arrive_remote(mapa(bar + 8 * B_FIN, lane));
    mbar_wait(bar + 8 * B_FIN, 0);
    TLE(2 + 5 * layer);
    fence_async();
    if (warp < 8) asm volatile("setmaxnreg.dec.sync.aligned.u32 128;"); else asm volatile("setmaxnreg.inc.sync.aligned.u32 128;");
    }
    const int b = blockIdx.x;
    worker<false>(sb, maps, x, x1, layer, b >= 3 * H_ ? b - 3 * H_ : b < 10 * SPLIT_B ? wk::I_SB + b : -1, gridDim.x - 3 * H_);
}

int g_delay = 5001350, g_layers = 2;

void make_map(CUtensorMap* m, CUtensorMapDataType dt, const void* p, const cuuint64_t* dim, const cuuint64_t* str, const cuuint32_t* box, CUtensorMapSwizzle sw) {
    typedef CUresult (*Fn)(CUtensorMap*, CUtensorMapDataType, cuuint32_t, void*, const cuuint64_t*, const cuuint64_t*, const cuuint32_t*,
                           const cuuint32_t*, CUtensorMapInterleave, CUtensorMapSwizzle, CUtensorMapL2promotion, CUtensorMapFloatOOBfill);
    static Fn fn = nullptr;
    if (!fn) {
        cudaDriverEntryPointQueryResult qr;
        cudaGetDriverEntryPoint("cuTensorMapEncodeTiled", (void**)&fn, cudaEnableDefault, &qr);
    }
    const cuuint32_t es[3] = {1, 1, 1};
    fn(m, dt, 3, (void*)p, dim, str, box, es, CU_TENSOR_MAP_INTERLEAVE_NONE, sw, CU_TENSOR_MAP_L2_PROMOTION_L2_128B, CU_TENSOR_MAP_FLOAT_OOB_FILL_NONE);
}
void map_weight(CUtensorMap* m, const bf16* p, int rows, int cols, int ng, int br = 64) {
    const cuuint64_t dim[3] = {64, (cuuint64_t)rows, (cuuint64_t)cols / 64}, str[2] = {(cuuint64_t)cols * 2, 128};
    const cuuint32_t box[3] = {64, (cuuint32_t)br, (cuuint32_t)ng};
    make_map(m, CU_TENSOR_MAP_DATA_TYPE_BFLOAT16, p, dim, str, box, CU_TENSOR_MAP_SWIZZLE_128B);
}
void map_pieces(CUtensorMap* m, const void* p, int np, int ns) {
    const cuuint64_t dim[3] = {256, (cuuint64_t)np * 2, NSEG}, str[2] = {2048, (cuuint64_t)np * 4096};
    const cuuint32_t box[3] = {256, 2, (cuuint32_t)ns};
    make_map(m, CU_TENSOR_MAP_DATA_TYPE_UINT64, p, dim, str, box, CU_TENSOR_MAP_SWIZZLE_NONE);
}

template <class... P, class... A> void launch(void (*k)(P...), int grid, int block, int smem, int cluster, bool pdl, A... args) {
    cudaLaunchConfig_t c = {};
    c.gridDim = dim3(grid); c.blockDim = dim3(block); c.dynamicSmemBytes = smem; c.stream = cudaStreamPerThread;
    cudaLaunchAttribute at[2];
    int n = 0;
    if (cluster > 1) { at[n].id = cudaLaunchAttributeClusterDimension; at[n].val.clusterDim.x = cluster; at[n].val.clusterDim.y = 1; at[n].val.clusterDim.z = 1; n++; }
    if (pdl) { at[n].id = cudaLaunchAttributeProgrammaticStreamSerialization; at[n].val.programmaticStreamSerializationAllowed = 1; n++; }
    c.attrs = at; c.numAttrs = n;
    cudaLaunchKernelEx(&c, k, args...);
}

int max_clusters() {
    cudaLaunchConfig_t c = {};
    c.gridDim = dim3(3 * H_); c.blockDim = dim3(512); c.dynamicSmemBytes = rec::SMEM;
    cudaLaunchAttribute at[1];
    at[0].id = cudaLaunchAttributeClusterDimension; at[0].val.clusterDim.x = 3; at[0].val.clusterDim.y = 1; at[0].val.clusterDim.z = 1;
    c.attrs = at; c.numAttrs = 1;
    int n = 0;
    cudaOccupancyMaxActiveClusters(&n, rec_kernel, &c);
    return n;
}

}

extern "C" void kernel_launch(void* const* d_in, const int* in_sizes, int n_in, void* d_out, int out_size) {
    const bf16* x = (const bf16*)d_in[0];
    const bf16* mem0 = (const bf16*)d_in[1];
    const bf16* Wq = (const bf16*)d_in[2];
    const bf16* Wk = (const bf16*)d_in[3];
    const bf16* Wv = (const bf16*)d_in[4];
    const bf16* Wo = (const bf16*)d_in[5];
    const bf16* wr = (const bf16*)d_in[8];
    const bf16* wi = (const bf16*)d_in[9];
    cudaFuncSetAttribute(rec_kernel, cudaFuncAttributeMaxDynamicSharedMemorySize, rec::SMEM);
    cudaFuncSetAttribute(side_kernel, cudaFuncAttributeMaxDynamicSharedMemorySize, wk::SMEM);
    cudaFuncSetAttribute(colfft_kernel, cudaFuncAttributeMaxDynamicSharedMemorySize, CF_SMEM);
    Maps maps;
    void *pxn, *po;
    cudaGetSymbolAddress(&pxn, g_xn);
    cudaGetSymbolAddress(&po, g_o);
    map_weight(&maps.wq2, Wq, D_, 4096, 2); map_weight(&maps.wv1, Wv, D_, 4096, 1);
    map_weight(&maps.wo2, Wo, 4096, D_, 2); map_weight(&maps.wo1, Wo, 4096, D_, 1, 192);
    map_pieces(&maps.x6, pxn, 10, 6); map_pieces(&maps.x4, pxn, 10, 4);
    map_pieces(&maps.o6, po, 64, 6); map_pieces(&maps.o2, po, 64, 2);
    bf16 *x1, *x2;
    cudaGetSymbolAddress((void**)&x1, g_x1);
    cudaGetSymbolAddress((void**)&x2, g_x2);
    constexpr int ONE_PER_SM = 116 * 1024;
    cudaFuncSetAttribute(rowfft_kernel, cudaFuncAttributeMaxDynamicSharedMemorySize, ONE_PER_SM);
    cudaFuncSetAttribute(rowifft_kernel, cudaFuncAttributeMaxDynamicSharedMemorySize, ONE_PER_SM);
    static int ncl = 0, nsm = 0;
    if (!ncl) { ncl = max_clusters(); cudaDeviceGetAttribute(&nsm, cudaDevAttrMultiProcessorCount, 0); }
    maps.wr = wr; maps.wi = wi;
    launch(prep_kernel, 128, 512, 0, 1, false, x, Wv, Wo);
    for (int layer = 0; layer < g_layers; layer++) {
        const bf16* xin = layer ? x2 : x;
        launch(rec_kernel, 3 * ncl, 512, rec::SMEM, 3, true, maps, xin, x1, mem0, Wq, Wk, Wv, Wo, layer, g_delay % 10000, g_delay / 10000);
        launch(side_kernel, max(nsm - 3 * ncl, 1), 512, wk::SMEM, 1, true, maps, xin, x1, layer, 3 * (ncl - H_));
        launch(rowfft_kernel, 128, 256, ONE_PER_SM, 1, true, xin, x1, layer);
        launch(colfft_kernel, 107, 384, CF_SMEM, 1, true, layer);
        launch(rowifft_kernel, 128, 256, ONE_PER_SM, 1, true, (const bf16*)x1, layer ? (bf16*)d_out : x2, layer);
    }
}
```
